```python
import torch

def _softmax(x, axis=-1):
    return torch.softmax(x, dim=axis)

def _gelu(x):
    return torch.nn.functional.gelu(x, approximate='tanh')

def _silu(x):
    return torch.nn.functional.silu(x)

def _sigmoid(x):
    return torch.sigmoid(x)

def _layernorm(x, axis=-1, eps=1e-05):
    m = x.mean(dim=axis, keepdim=True)
    v = x.var(dim=axis, keepdim=True, unbiased=False)
    return (x - m) / torch.sqrt(v + eps)

def _scatter_add(tgt, idx, src, axis=0):
    return tgt.clone().index_add_(axis, idx, src)

def _segment_sum(src, seg, n):
    out = torch.zeros((n,) + src.shape[1:], dtype=src.dtype)
    return out.index_add_(0, seg, src)

def _pad(x, pw):
    flat = tuple((v for pair in reversed(pw) for v in pair))
    return torch.nn.functional.pad(x, flat)
kernel_name = 'adaLN_cond__gqa_block_cached__geglu_ffn__decode'

def setup_inputs():

    _w = lambda a: (lambda t: t.to(torch.bfloat16) if t.is_floating_point() else t)(torch.as_tensor(a))

    def _A_setup():
        B, Sq, D = (2, 1, 512)
        Hq, Hkv, Sk, Dh = (32, 8, 32768, 128)
        assert Hq % Hkv == 0, (Hq, Hkv)
        return {'x': _w((lambda *s: torch.randn(*s, dtype=torch.bfloat16) * 0.1)(B, Sq, D)), 'k_cache': _w((lambda *s: torch.randn(*s, dtype=torch.bfloat16) * 0.8)(B, Hkv, Sk, Dh)), 'v_cache': _w((lambda *s: torch.randn(*s, dtype=torch.bfloat16) * 0.8)(B, Hkv, Sk, Dh)), 'wq': _w((lambda *s: torch.randn(*s, dtype=torch.bfloat16) * 0.8)(D, Hq * Dh) * D ** (-0.5)), 'wo': _w((lambda *s: torch.randn(*s, dtype=torch.bfloat16) * 0.8)(Hq * Dh, D) * (Hq * Dh) ** (-0.5))}
    _A_in = _A_setup()

    def _B_setup():
        B, S, D, F = (2, 1, 512, 1792)
        return {'x': _w((lambda *s: torch.randn(*s, dtype=torch.bfloat16) * 0.1)(B, S, D)), 'w_gate': _w((lambda *s: torch.randn(*s, dtype=torch.bfloat16) * 0.1)(D, F)), 'w_up': _w((lambda *s: torch.randn(*s, dtype=torch.bfloat16) * 0.1)(D, F)), 'w_down': _w((lambda *s: torch.randn(*s, dtype=torch.bfloat16) * 0.1)(F, D))}
    _B_in = _B_setup()
    return {'A_x': _A_in['x'], 'A_k_cache': _A_in['k_cache'], 'A_v_cache': _A_in['v_cache'], 'A_wq': _A_in['wq'], 'A_wo': _A_in['wo'], 'B_x': _B_in['x'], 'B_w_gate': _B_in['w_gate'], 'B_w_up': _B_in['w_up'], 'B_w_down': _B_in['w_down'], 'c': _w((lambda *s: torch.randn(*s, dtype=torch.bfloat16) * 0.4)(2, 512) * 8.0), 'w_mod': _w((lambda *s: torch.randn(*s, dtype=torch.bfloat16) * 0.4)(512, 6 * 512) * 512 ** (-0.5) * 8.0)}

def reference(A_x, A_k_cache, A_v_cache, A_wq, A_wo, B_x, B_w_gate, B_w_up, B_w_down, c, w_mod):

    def _A_ref(x, k_cache, v_cache, wq, wo):
        B, Sq, D = x.shape
        Hq, Dh = (32, 128)
        Hkv = k_cache.shape[1]
        rep = Hq // Hkv
        q = (lambda x, *d: x.permute(*d))((x @ wq).reshape(B, Sq, Hq, Dh), 0, 2, 1, 3)
        k = (lambda x, n, axis: torch.repeat_interleave(x, n, dim=axis))(k_cache, rep, axis=1)
        v = (lambda x, n, axis: torch.repeat_interleave(x, n, dim=axis))(v_cache, rep, axis=1)
        scores = torch.einsum('bhqd,bhkd->bhqk', q, k) * Dh ** (-0.5)
        p = _softmax(scores, axis=-1)
        o = torch.einsum('bhqk,bhkd->bhqd', p, v)
        return (lambda x, *d: x.permute(*d))(o, 0, 2, 1, 3).reshape(B, Sq, Hq * Dh) @ wo

    def _B_ref(x, w_gate, w_up, w_down):
        return _gelu(x @ w_gate) * (x @ w_up) @ w_down
    x = A_x
    mod = (_silu(c) @ w_mod).reshape(c.shape[0], 6, 1, -1)
    sa, ca, ga, sb, cb, gb = (mod[:, 0].clone(), mod[:, 1].clone(), mod[:, 2].clone(), mod[:, 3].clone(), mod[:, 4].clone(), mod[:, 5].clone())
    h = _layernorm(x, axis=-1) * (1 + ca) + sa
    x = x + ga * _A_ref(h, A_k_cache, A_v_cache, A_wq, A_wo)
    h = _layernorm(x, axis=-1) * (1 + cb) + sb
    x = x + gb * _B_ref(h, B_w_gate, B_w_up, B_w_down)
    return x
```

```cpp
#include <cuda_runtime.h>
#include <cuda.h>
#include <cuda_bf16.h>
#include <stdint.h>

namespace {

constexpr int D_MODEL = 512;
constexpr int N_HEADS = 32;
constexpr int N_KV = 8;
constexpr int SK = 32768;
constexpr int DH = 128;
constexpr int D_FF = 1792;
constexpr int N_MOD = 6 * D_MODEL;

constexpr int NCTA = 128;
constexpr int NFFN = D_FF / 16;
constexpr int NTHREADS = 320;
constexpr int NST = 12;
constexpr int TILE = 16384;
constexpr int INFLIGHT = 4;
constexpr int KV_TILES = 64;
constexpr int IDX_KV0 = 3;
constexpr int IDX_WO = IDX_KV0 + 2 * KV_TILES;
constexpr int IDX_WG = IDX_WO + 2;
constexpr int IDX_WU = IDX_WG + 1;
constexpr int IDX_WD = IDX_WU + 1;
constexpr int SPIN_LIMIT = 1 << 20;

constexpr float LOG2E = 1.4426950408889634f;
constexpr float QK_SCALE = 0.08838834764831845f;

constexpr int SM_RING = 0;
constexpr int SM_MRG = SM_RING + NST * TILE;
constexpr int SM_ML = SM_MRG + 8 * 4 * 136 * 4;
constexpr int SM_RED = SM_ML + 8 * 4 * 8;
constexpr int SM_RED2 = SM_RED + 8 * 64 * 4;
constexpr int SM_QS = SM_RED2 + 8 * 64 * 4;
constexpr int SM_OS = SM_QS + 512 * 2;
constexpr int SM_SBCB = SM_OS + 2 * 16 * 4;
constexpr int SM_STAT = SM_SBCB + 2 * 512 * 4;
constexpr int SM_BAR = SM_STAT + 8 * 2 * 8;
constexpr int SM_END = SM_BAR + (2 * NST + 2) * 8;
constexpr int SMEM_BYTES = SM_END + 1024;

struct Params {
    const __nv_bfloat16* x;
    const __nv_bfloat16* c;
    const __nv_bfloat16* w_mod;
    __nv_bfloat16* out;
};

__device__ unsigned g_epoch;
__device__ uint2 g_mod[2][N_MOD / 2];
__device__ uint2 g_q[2][N_HEADS * DH / 2];
__device__ uint4 g_part_o[NCTA][4][64];
__device__ uint4 g_part_ml[NCTA][4][2];
__device__ uint4 g_inbox_b[NCTA][NCTA][4];
__device__ uint2 g_x1[D_MODEL];
__device__ uint4 g_inbox_c[NCTA][NFFN][4];
#define TSTAMP(i) do { } while (0)

__device__ __forceinline__ uint32_t smem_u32(const void* p) { return (uint32_t)__cvta_generic_to_shared(p); }

__device__ __forceinline__ void mbar_init(uint32_t bar, uint32_t cnt) {
    asm volatile("mbarrier.init.shared::cta.b64 [%0], %1;" ::"r"(bar), "r"(cnt) : "memory");
}
__device__ __forceinline__ void mbar_expect_tx(uint32_t bar, uint32_t bytes) {
    asm volatile("mbarrier.arrive.expect_tx.shared::cta.b64 _, [%0], %1;" ::"r"(bar), "r"(bytes) : "memory");
}
__device__ __forceinline__ void mbar_arrive(uint32_t bar) {
    asm volatile("mbarrier.arrive.shared::cta.b64 _, [%0];" ::"r"(bar) : "memory");
}
__device__ __forceinline__ bool mbar_try(uint32_t bar, uint32_t parity) {
    uint32_t ok;
    asm volatile(
        "{\n\t.reg .pred p;\n\t"
        "mbarrier.try_wait.parity.shared::cta.b64 p, [%1], %2;\n\t"
        "selp.u32 %0, 1, 0, p;\n\t}"
        : "=r"(ok) : "r"(bar), "r"(parity) : "memory");
    return ok != 0;
}
__device__ __forceinline__ void mbar_wait(uint32_t bar, uint32_t parity) {
    if (mbar_try(bar, parity)) return;
    for (int i = 0; i < SPIN_LIMIT; i++)
        if (mbar_try(bar, parity)) return;
}
__device__ __forceinline__ void cons_sync() { asm volatile("bar.sync 1, 256;" ::: "memory"); }

__device__ __forceinline__ void tma_2d(uint32_t dst, const CUtensorMap* m, int c0, int c1, uint32_t bar) {
    asm volatile("cp.async.bulk.tensor.2d.shared::cluster.global.mbarrier::complete_tx::bytes [%0], [%1, {%3, %4}], [%2];"
                 ::"r"(dst), "l"(m), "r"(bar), "r"(c0), "r"(c1) : "memory");
}
__device__ __forceinline__ void tma_3d(uint32_t dst, const CUtensorMap* m, int c0, int c1, int c2, uint32_t bar) {
    asm volatile("cp.async.bulk.tensor.3d.shared::cluster.global.mbarrier::complete_tx::bytes [%0], [%1, {%3, %4, %5}], [%2];"
                 ::"r"(dst), "l"(m), "r"(bar), "r"(c0), "r"(c1), "r"(c2) : "memory");
}
__device__ __forceinline__ void prefetch_tmap(const CUtensorMap* m) {
    asm volatile("prefetch.tensormap [%0];" ::"l"(m) : "memory");
}

__device__ __forceinline__ void ldsm4(uint32_t addr, uint32_t (&r)[4]) {
    asm volatile("ldmatrix.sync.aligned.m8n8.x4.shared.b16 {%0,%1,%2,%3}, [%4];"
                 : "=r"(r[0]), "=r"(r[1]), "=r"(r[2]), "=r"(r[3]) : "r"(addr) : "memory");
}
__device__ __forceinline__ void ldsm4t(uint32_t addr, uint32_t (&r)[4]) {
    asm volatile("ldmatrix.sync.aligned.m8n8.x4.trans.shared.b16 {%0,%1,%2,%3}, [%4];"
                 : "=r"(r[0]), "=r"(r[1]), "=r"(r[2]), "=r"(r[3]) : "r"(addr) : "memory");
}
__device__ __forceinline__ void mma16816(float (&c)[4], const uint32_t (&a)[4], uint32_t b0, uint32_t b1) {
    asm volatile("mma.sync.aligned.m16n8k16.row.col.f32.bf16.bf16.f32 {%0,%1,%2,%3}, {%4,%5,%6,%7}, {%8,%9}, {%0,%1,%2,%3};"
                 : "+f"(c[0]), "+f"(c[1]), "+f"(c[2]), "+f"(c[3])
                 : "r"(a[0]), "r"(a[1]), "r"(a[2]), "r"(a[3]), "r"(b0), "r"(b1));
}
__device__ __forceinline__ uint32_t movmatrix_t(uint32_t a) {
    uint32_t d;
    asm volatile("movmatrix.sync.aligned.m8n8.trans.b16 %0, %1;" : "=r"(d) : "r"(a));
    return d;
}
__device__ __forceinline__ uint32_t pack_bf16(float a, float b) {
    uint32_t r;
    asm("cvt.rn.bf16x2.f32 %0, %1, %2;" : "=r"(r) : "f"(b), "f"(a));
    return r;
}
__device__ __forceinline__ float bf_lo(uint32_t v) { return __uint_as_float(v << 16); }
__device__ __forceinline__ float bf_hi(uint32_t v) { return __uint_as_float(v & 0xffff0000u); }
__device__ __forceinline__ float bf16r(float a) { return bf_lo(pack_bf16(a, 0.f)); }
__device__ __forceinline__ uint32_t max_bf16x2(uint32_t a, uint32_t b) {
    uint32_t r;
    asm("max.bf16x2 %0, %1, %2;" : "=r"(r) : "r"(a), "r"(b));
    return r;
}
__device__ __forceinline__ float ex2(float x) {
    float r;
    asm("ex2.approx.ftz.f32 %0, %1;" : "=f"(r) : "f"(x));
    return r;
}

__device__ __forceinline__ void st_ll2(uint2* p, uint32_t v, uint32_t tag) {
    asm volatile("st.relaxed.gpu.global.v2.u32 [%0], {%1, %2};" ::"l"(p), "r"(v), "r"(tag) : "memory");
}
__device__ __forceinline__ void st_ll4(uint4* p, uint32_t v0, uint32_t v1, uint32_t tag) {
    asm volatile("st.relaxed.gpu.global.v4.u32 [%0], {%1, %2, %3, %2};" ::"l"(p), "r"(v0), "r"(tag), "r"(v1) : "memory");
}
__device__ __forceinline__ uint2 ld_ll2(const uint2* p) {
    uint2 v;
    asm volatile("ld.relaxed.gpu.global.v2.u32 {%0, %1}, [%2];" : "=r"(v.x), "=r"(v.y) : "l"(p) : "memory");
    return v;
}
__device__ __forceinline__ uint4 ld_ll4(const uint4* p) {
    uint4 v;
    asm volatile("ld.relaxed.gpu.global.v4.u32 {%0, %1, %2, %3}, [%4];"
                 : "=r"(v.x), "=r"(v.y), "=r"(v.z), "=r"(v.w) : "l"(p) : "memory");
    return v;
}

__device__ __forceinline__ float silu_bf(float v) { return bf16r(v / (1.0f + expf(-v))); }
__device__ __forceinline__ float gelu_tanh(float v) {
    const float k0 = 0.7978845608028654f, k1 = 0.044715f;
    return 0.5f * v * (1.0f + tanhf(k0 * (v + k1 * v * v * v)));
}
__device__ __forceinline__ float ln_mod(float xv, float mean_bf, float sq_bf, float cmul, float sadd) {
    float d = bf16r(xv - mean_bf);
    float n = bf16r(d / sq_bf);
    float t = bf16r(n * bf16r(1.0f + cmul));
    return t + sadd;
}

__global__ void __launch_bounds__(NTHREADS, 1)
fused_block_kernel(const __grid_constant__ CUtensorMap tm_k, const __grid_constant__ CUtensorMap tm_v,
                   const __grid_constant__ CUtensorMap tm_wq, const __grid_constant__ CUtensorMap tm_wmod,
                   const __grid_constant__ CUtensorMap tm_wo, const __grid_constant__ CUtensorMap tm_wg,
                   const __grid_constant__ CUtensorMap tm_wu, const __grid_constant__ CUtensorMap tm_wd,
                   const Params p) {
    extern __shared__ unsigned char smem_raw[];
    const uint32_t sbase = (smem_u32(smem_raw) + 1023u) & ~1023u;
    unsigned char* sgen = smem_raw + (sbase - smem_u32(smem_raw));
    const int tid = threadIdx.x, warp = tid >> 5, lane = tid & 31;
    const int cta = blockIdx.x;
    const uint32_t bar_full = sbase + SM_BAR, bar_empty = bar_full + NST * 8;
    const uint32_t bar_sbcb = bar_empty + NST * 8, bar_tail = bar_sbcb + 8;

    if (warp == 8) {
        if (lane == 0) {
            for (int i = 0; i < NST; i++) { mbar_init(bar_full + 8 * i, 1); mbar_init(bar_empty + 8 * i, 4); }
            mbar_init(bar_sbcb, 32);
            mbar_init(bar_tail, 1);
            asm volatile("fence.mbarrier_init.release.cluster;" ::: "memory");
        }
        __syncwarp();
        asm volatile("bar.arrive 2, 320;" ::: "memory");
        if (lane == 0) {
            prefetch_tmap(&tm_wq); prefetch_tmap(&tm_wmod); prefetch_tmap(&tm_k); prefetch_tmap(&tm_v);
            const int pair = cta >> 3, j = cta & 7;
            const int key0 = pair * SK + j * 64;
            const int n_tiles = cta < NFFN ? IDX_WD + 1 : IDX_WG;
            int slot = 0; uint32_t ph = 1;
            int wslot = 0; uint32_t wph = 0;
            for (int idx = 0; idx < n_tiles; idx++) {
                if (idx >= NST) mbar_wait(bar_empty + 8 * slot, ph);
                if (idx >= INFLIGHT) {
                    mbar_wait(bar_full + 8 * wslot, wph);
                    if (++wslot == NST) { wslot = 0; wph ^= 1; }
                }
                const uint32_t fb = bar_full + 8 * slot, dst = sbase + SM_RING + slot * TILE;
                mbar_expect_tx(fb, TILE);
                if (idx >= IDX_KV0 && idx < IDX_WO) {
                    const int i = (idx - IDX_KV0) >> 1;
                    tma_3d(dst, ((idx - IDX_KV0) & 1) ? &tm_v : &tm_k, 0, key0 + i * 512, 0, fb);
                } else if (idx < 2) {
                    tma_2d(dst, &tm_wq, cta * 32, idx * 256, fb);
                } else if (idx == 2) {
                    tma_2d(dst, &tm_wmod, 1024 + cta * 16, 0, fb);
                    tma_2d(dst + 8192, &tm_wmod, 1024 + cta * 16, 256, fb);
                    prefetch_tmap(&tm_wo); prefetch_tmap(&tm_wg); prefetch_tmap(&tm_wu); prefetch_tmap(&tm_wd);
                } else if (idx < IDX_WG) {
                    if (idx == IDX_WO) mbar_arrive(bar_tail);
                    tma_3d(dst, &tm_wo, 0, cta * 32 + (idx - IDX_WO) * 16, 0, fb);
                } else if (idx < IDX_WD) {
                    const CUtensorMap* m = idx == IDX_WG ? &tm_wg : &tm_wu;
                    tma_2d(dst, m, cta * 16, 0, fb);
                    tma_2d(dst + 8192, m, cta * 16, 256, fb);
                } else {
                    tma_3d(dst, &tm_wd, 0, cta * 16, 0, fb);
                }
                if (++slot == NST) { slot = 0; ph ^= 1; }
            }
        }
    } else if (warp == 9) {
        const uint32_t tag = *(volatile unsigned*)&g_epoch + 1;
        const int col = cta * 4 + (lane & 3);
        const float x0 = __bfloat162float(p.x[col]), x1in = __bfloat162float(p.x[D_MODEL + col]);
        asm volatile("bar.sync 2, 320;" ::: "memory");
        uint32_t* sbcb = (uint32_t*)(sgen + SM_SBCB);
        float ga0, ga1, gb0, gb1;
        {
            int it = 0;
            for (int b = 0; b < 2; b++) {
                for (int half = 0; half < 2; half++) {
                    uint4 v[4];
                    while (true) {
                        bool ok = true;
#pragma unroll
                        for (int i = 0; i < 4; i++)
                            v[i] = ld_ll4((const uint4*)&g_mod[b][768 + half * 256] + i * 32 + lane);
#pragma unroll
                        for (int i = 0; i < 4; i++) ok = ok && v[i].y == tag && v[i].w == tag;
                        if (__all_sync(0xffffffffu, ok) || ++it > SPIN_LIMIT) break;
                        __nanosleep(200);
                    }
#pragma unroll
                    for (int i = 0; i < 4; i++) {
                        const int w = (i * 32 + lane) * 2;
                        sbcb[b * 512 + half * 256 + w] = v[i].x;
                        sbcb[b * 512 + half * 256 + w + 1] = v[i].z;
                    }
                }
            }
            uint2 a0, a1, b0, b1;
            while (true) {
                a0 = ld_ll2(&g_mod[0][512 + (col >> 1)]); a1 = ld_ll2(&g_mod[1][512 + (col >> 1)]);
                b0 = ld_ll2(&g_mod[0][1280 + (col >> 1)]); b1 = ld_ll2(&g_mod[1][1280 + (col >> 1)]);
                bool ok = a0.y == tag && a1.y == tag && b0.y == tag && b1.y == tag;
                if (__all_sync(0xffffffffu, ok) || ++it > SPIN_LIMIT) break;
                __nanosleep(200);
            }
            const bool hi = col & 1;
            ga0 = hi ? bf_hi(a0.x) : bf_lo(a0.x); ga1 = hi ? bf_hi(a1.x) : bf_lo(a1.x);
            gb0 = hi ? bf_hi(b0.x) : bf_lo(b0.x); gb1 = hi ? bf_hi(b1.x) : bf_lo(b1.x);
            mbar_arrive(bar_sbcb);
        }
        mbar_wait(bar_tail, 0);
        float xm0, xm1;
        {
            float s0, s1;
            for (int it = 0;; it++) {
                uint4 v[16];
#pragma unroll
                for (int i = 0; i < 16; i++) v[i] = ld_ll4(&g_inbox_b[cta][0][0] + i * 32 + lane);
                bool ok = true;
                s0 = 0.f; s1 = 0.f;
#pragma unroll
                for (int i = 0; i < 16; i++) {
                    ok = ok && v[i].y == tag && v[i].w == tag;
                    s0 += __uint_as_float(v[i].x); s1 += __uint_as_float(v[i].z);
                }
                if (__all_sync(0xffffffffu, ok) || it > SPIN_LIMIT) break;
            }
#pragma unroll
            for (int o = 4; o < 32; o <<= 1) { s0 += __shfl_xor_sync(0xffffffffu, s0, o); s1 += __shfl_xor_sync(0xffffffffu, s1, o); }
            xm0 = bf16r(x0 + bf16r(ga0 * bf16r(s0)));
            xm1 = bf16r(x1in + bf16r(ga1 * bf16r(s1)));
            if (lane < 4) st_ll2(&g_x1[col], pack_bf16(xm0, xm1), tag);
        }
        TSTAMP(10);
        {
            float s0, s1;
            for (int it = 0;; it++) {
                uint4 v[14];
#pragma unroll
                for (int i = 0; i < 14; i++) v[i] = ld_ll4(&g_inbox_c[cta][0][0] + i * 32 + lane);
                bool ok = true;
                s0 = 0.f; s1 = 0.f;
#pragma unroll
                for (int i = 0; i < 14; i++) {
                    ok = ok && v[i].y == tag && v[i].w == tag;
                    s0 += __uint_as_float(v[i].x); s1 += __uint_as_float(v[i].z);
                }
                if (__all_sync(0xffffffffu, ok) || it > SPIN_LIMIT) break;
            }
#pragma unroll
            for (int o = 4; o < 32; o <<= 1) { s0 += __shfl_xor_sync(0xffffffffu, s0, o); s1 += __shfl_xor_sync(0xffffffffu, s1, o); }
            if (lane < 4) {
                p.out[col] = __float2bfloat16_rn(xm0 + bf16r(gb0 * bf16r(s0)));
                p.out[D_MODEL + col] = __float2bfloat16_rn(xm1 + bf16r(gb1 * bf16r(s1)));
            }
            if (cta == 0 && lane == 0) *(volatile unsigned*)&g_epoch = tag;
        }
        TSTAMP(13);
    } else {
        const int g = lane >> 2, t = lane & 3;
        const int bb = g & 1;
        if (warp == 0) TSTAMP(0);
        const uint4 w0 = __ldg((const uint4*)(p.w_mod + (size_t)tid * N_MOD + cta * 8));
        const uint4 w1 = __ldg((const uint4*)(p.w_mod + (size_t)(tid + 256) * N_MOD + cta * 8));
        const float c00 = __bfloat162float(p.c[tid]), c01 = __bfloat162float(p.c[tid + 256]);
        const float c10 = __bfloat162float(p.c[D_MODEL + tid]), c11 = __bfloat162float(p.c[D_MODEL + tid + 256]);
        const uint32_t tag = *(volatile unsigned*)&g_epoch + 1;
        uint4 xs[4];
        {
            const int l16 = (g >> 1) * 4 + t;
            const uint4* xp = (const uint4*)(p.x + bb * D_MODEL + l16 * 32);
#pragma unroll
            for (int i = 0; i < 4; i++) xs[i] = __ldg(xp + i);
        }
        uint32_t xf[8], cf[8];
#pragma unroll
        for (int s = 0; s < 4; s++) {
            const int k = 64 * warp + 16 * s + 2 * t;
            xf[2 * s] = __ldg((const uint32_t*)(p.x + bb * D_MODEL + k));
            xf[2 * s + 1] = __ldg((const uint32_t*)(p.x + bb * D_MODEL + k + 8));
            cf[2 * s] = __ldg((const uint32_t*)(p.c + bb * D_MODEL + k));
            cf[2 * s + 1] = __ldg((const uint32_t*)(p.c + bb * D_MODEL + k + 8));
        }
        float* red = (float*)(sgen + SM_RED);
        float* red2 = (float*)(sgen + SM_RED2);
        {
            const float s00 = silu_bf(c00), s01 = silu_bf(c01), s10 = silu_bf(c10), s11 = silu_bf(c11);
            const uint32_t a[4] = {w0.x, w0.y, w0.z, w0.w}, b[4] = {w1.x, w1.y, w1.z, w1.w};
            float v[16];
#pragma unroll
            for (int i = 0; i < 4; i++) {
                v[2 * i] = s00 * bf_lo(a[i]) + s01 * bf_lo(b[i]);
                v[2 * i + 1] = s00 * bf_hi(a[i]) + s01 * bf_hi(b[i]);
                v[8 + 2 * i] = s10 * bf_lo(a[i]) + s11 * bf_lo(b[i]);
                v[8 + 2 * i + 1] = s10 * bf_hi(a[i]) + s11 * bf_hi(b[i]);
            }
#pragma unroll
            for (int n = 8, o = 16; n >= 1; n >>= 1, o >>= 1) {
                const bool up = lane & o;
#pragma unroll
                for (int i = 0; i < n; i++) {
                    const float send = up ? v[i] : v[i + n], keep = up ? v[i + n] : v[i];
                    v[i] = keep + __shfl_xor_sync(0xffffffffu, send, o);
                }
            }
            v[0] += __shfl_xor_sync(0xffffffffu, v[0], 1);
            if (!(lane & 1)) red[warp * 16 + (lane >> 1)] = v[0];
            asm volatile("bar.sync 2, 320;" ::: "memory");
            if (warp == 0) {
                float s = 0.f;
#pragma unroll
                for (int w = 0; w < 8; w++) s += red[w * 16 + (lane & 15)];
                const float nx = __shfl_down_sync(0xffffffffu, s, 1);
                if (lane < 16 && !(lane & 1))
                    st_ll2(&g_mod[lane >> 3][cta * 4 + ((lane & 7) >> 1)], pack_bf16(s, nx), tag);
                TSTAMP(1);
            }
        }
        float mean_bf, sq_bf;
        {
            float xv[32];
#pragma unroll
            for (int i = 0; i < 4; i++) {
                const uint32_t u[4] = {xs[i].x, xs[i].y, xs[i].z, xs[i].w};
#pragma unroll
                for (int k = 0; k < 4; k++) { xv[8 * i + 2 * k] = bf_lo(u[k]); xv[8 * i + 2 * k + 1] = bf_hi(u[k]); }
            }
            float s = 0.f;
#pragma unroll
            for (int i = 0; i < 32; i++) s += xv[i];
            s += __shfl_xor_sync(0xffffffffu, s, 1); s += __shfl_xor_sync(0xffffffffu, s, 2);
            s += __shfl_xor_sync(0xffffffffu, s, 8); s += __shfl_xor_sync(0xffffffffu, s, 16);
            const float mean = s * (1.0f / D_MODEL);
            float q = 0.f;
#pragma unroll
            for (int i = 0; i < 32; i++) { const float d = xv[i] - mean; q += d * d; }
            q += __shfl_xor_sync(0xffffffffu, q, 1); q += __shfl_xor_sync(0xffffffffu, q, 2);
            q += __shfl_xor_sync(0xffffffffu, q, 8); q += __shfl_xor_sync(0xffffffffu, q, 16);
            mean_bf = bf16r(mean);
            sq_bf = bf16r(sqrtf(bf16r(bf16r(q * (1.0f / D_MODEL)) + 1e-5f)));
        }
        {
            uint32_t hb[8];
            {
                uint2 sa[8], ca[8];
                for (int it = 0;; it++) {
                    bool ok = true;
#pragma unroll
                    for (int i = 0; i < 8; i++) {
                        const int w = 32 * warp + 8 * (i >> 1) + 4 * (i & 1) + t;
                        sa[i] = ld_ll2(&g_mod[bb][w]);
                        ca[i] = ld_ll2(&g_mod[bb][256 + w]);
                    }
#pragma unroll
                    for (int i = 0; i < 8; i++) ok = ok && sa[i].y == tag && ca[i].y == tag;
                    if (__all_sync(0xffffffffu, ok) || it > SPIN_LIMIT) break;
                }
#pragma unroll
                for (int i = 0; i < 8; i++)
                    hb[i] = pack_bf16(ln_mod(bf_lo(xf[i]), mean_bf, sq_bf, bf_lo(ca[i].x), bf_lo(sa[i].x)),
                                      ln_mod(bf_hi(xf[i]), mean_bf, sq_bf, bf_hi(ca[i].x), bf_hi(sa[i].x)));
            }
            if (warp == 0) TSTAMP(2);
            float cq[2][4] = {};
            const int ts = warp >> 2;
            mbar_wait(bar_full + 8 * ts, 0);
            const uint32_t tb = sbase + SM_RING + ts * TILE;
#pragma unroll
            for (int s = 0; s < 4; s++) {
                const int row = 64 * (warp & 3) + 16 * s + (lane & 7) + (lane >> 4) * 8;
#pragma unroll
                for (int mt = 0; mt < 2; mt++) {
                    const int ch = 2 * mt + ((lane >> 3) & 1);
                    uint32_t a[4];
                    ldsm4t(tb + row * 64 + ((ch ^ ((row >> 1) & 3)) << 4), a);
                    mma16816(cq[mt], a, hb[2 * s], hb[2 * s + 1]);
                }
            }
            if (t < 2) {
                const float v0 = t == 0 ? cq[0][0] : cq[1][0], v1 = t == 0 ? cq[0][1] : cq[1][1];
                const float v2 = t == 0 ? cq[0][2] : cq[1][2], v3 = t == 0 ? cq[0][3] : cq[1][3];
                *(float2*)&red2[warp * 64 + (16 * t + g) * 2] = make_float2(v0, v1);
                *(float2*)&red2[warp * 64 + (16 * t + g + 8) * 2] = make_float2(v2, v3);
            }
            cons_sync();
            if (warp < 4 && lane == 0) { mbar_arrive(bar_empty + 0); mbar_arrive(bar_empty + 8); }
            if (warp == 0) {
                const int b = lane >> 4, cp = lane & 15;
                float q0 = 0.f, q1 = 0.f;
#pragma unroll
                for (int w = 0; w < 8; w++) {
                    const float4 v = *(const float4*)&red2[w * 64 + cp * 4];
                    q0 += b ? v.y : v.x; q1 += b ? v.w : v.z;
                }
                st_ll2(&g_q[b][cta * 16 + cp], pack_bf16(q0, q1), tag);
                TSTAMP(3);
            }
        }
        {
            float cm[4] = {};
            mbar_wait(bar_full + 8 * 2, 0);
            const uint32_t tb = sbase + SM_RING + 2 * TILE;
#pragma unroll
            for (int s = 0; s < 4; s++) {
                const int row = 64 * warp + 16 * s + (lane & 7) + (lane >> 4) * 8;
                const int ch = (lane >> 3) & 1;
                uint32_t a[4];
                ldsm4t(tb + row * 32 + ((ch ^ ((row >> 2) & 1)) << 4), a);
                const uint32_t b0 = pack_bf16(silu_bf(bf_lo(cf[2 * s])), silu_bf(bf_hi(cf[2 * s])));
                const uint32_t b1 = pack_bf16(silu_bf(bf_lo(cf[2 * s + 1])), silu_bf(bf_hi(cf[2 * s + 1])));
                mma16816(cm, a, b0, b1);
            }
            if (t == 0) {
                *(float2*)&red[warp * 64 + g * 2] = make_float2(cm[0], cm[1]);
                *(float2*)&red[warp * 64 + (g + 8) * 2] = make_float2(cm[2], cm[3]);
            }
            cons_sync();
            if (warp < 4 && lane == 0) mbar_arrive(bar_empty + 16);
            if (warp == 1 && lane < 16) {
                const int b = lane >> 3, cp = lane & 7;
                float q0 = 0.f, q1 = 0.f;
#pragma unroll
                for (int w = 0; w < 8; w++) {
                    const float4 v = *(const float4*)&red[w * 64 + cp * 4];
                    q0 += b ? v.y : v.x; q1 += b ? v.w : v.z;
                }
                st_ll2(&g_mod[b][512 + cta * 8 + cp], pack_bf16(q0, q1), tag);
            }
        }
        const int pair = cta >> 3;
        uint32_t qf[16];
        {
            uint2* qs = (uint2*)(sgen + SM_QS);
            if (tid < 128) {
                const uint4* src = (const uint4*)&g_q[pair >> 3][(pair & 7) * 256] + tid;
                uint4 v;
                for (int it = 0;; it++) {
                    v = ld_ll4(src);
                    if ((v.y == tag && v.w == tag) || it > SPIN_LIMIT) break;
                }
                qs[tid] = make_uint2(v.x, v.z);
            }
            cons_sync();
            const uint32_t* q32 = (const uint32_t*)(sgen + SM_QS);
#pragma unroll
            for (int s = 0; s < 8; s++) {
                qf[2 * s] = q32[(g & 3) * 64 + 8 * s + t];
                qf[2 * s + 1] = q32[(g & 3) * 64 + 8 * s + 4 + t];
            }
        }
        if (warp == 0) TSTAMP(4);

        float o[8][4];
#pragma unroll
        for (int i = 0; i < 8; i++) { o[i][0] = o[i][1] = o[i][2] = o[i][3] = 0.f; }
        uint32_t mrun = 0xff80ff80u;
        float l0 = 0.f, l1 = 0.f;
        {
            const int grp = warp >> 2, wi = warp & 3;
            const int krow = 16 * wi + (lane & 7) + ((lane >> 3) & 1) * 8;
            const uint32_t koff = krow * 128 + ((((lane >> 4) & 1) ^ (lane & 7)) << 4);
            const int vrow = 16 * wi + (lane & 7) + (lane >> 4) * 8;
            const uint32_t voff = vrow * 128 + ((((lane >> 3) & 1) ^ (lane & 7)) << 4);
            int ks = IDX_KV0 + 2 * grp, vs = ks + 1;
            uint32_t kph = 0, vph = 0;
            for (int i = grp; i < KV_TILES; i += 2) {
                mbar_wait(bar_full + 8 * ks, kph);
                const uint32_t kb = sbase + SM_RING + ks * TILE + koff;
                float sa[4] = {0.f, 0.f, 0.f, 0.f}, sb[4] = {0.f, 0.f, 0.f, 0.f};
#pragma unroll
                for (int s = 0; s < 8; s += 2) {
                    uint32_t a0[4], a1[4];
                    ldsm4((kb ^ ((s & 3) << 5)) + (s >> 2) * 8192, a0);
                    ldsm4((kb ^ (((s + 1) & 3) << 5)) + (s >> 2) * 8192, a1);
                    mma16816(sa, a0, qf[2 * s], qf[2 * s + 1]);
                    mma16816(sb, a1, qf[2 * s + 2], qf[2 * s + 3]);
                }
                __syncwarp();
                if (lane == 0) mbar_arrive(bar_empty + 8 * ks);
                uint32_t r01 = pack_bf16(sa[0] + sb[0], sa[1] + sb[1]);
                uint32_t r23 = pack_bf16(sa[2] + sb[2], sa[3] + sb[3]);
                r01 = pack_bf16(bf_lo(r01) * QK_SCALE, bf_hi(r01) * QK_SCALE);
                r23 = pack_bf16(bf_lo(r23) * QK_SCALE, bf_hi(r23) * QK_SCALE);
                uint32_t mx = max_bf16x2(r01, r23);
                mx = max_bf16x2(mx, __shfl_xor_sync(0xffffffffu, mx, 4));
                mx = max_bf16x2(mx, __shfl_xor_sync(0xffffffffu, mx, 8));
                mx = max_bf16x2(mx, __shfl_xor_sync(0xffffffffu, mx, 16));
                const uint32_t mnew = max_bf16x2(mrun, mx);
                const float m0 = bf_lo(mnew), m1 = bf_hi(mnew);
                if (__any_sync(0xffffffffu, mnew != mrun)) {
                    const float al0 = ex2((bf_lo(mrun) - m0) * LOG2E), al1 = ex2((bf_hi(mrun) - m1) * LOG2E);
                    l0 *= al0; l1 *= al1;
#pragma unroll
                    for (int d = 0; d < 8; d++) { o[d][0] *= al0; o[d][1] *= al1; o[d][2] *= al0; o[d][3] *= al1; }
                    mrun = mnew;
                }
                const float p0 = ex2((bf_lo(r01) - m0) * LOG2E), p1 = ex2((bf_hi(r01) - m1) * LOG2E);
                const float p2 = ex2((bf_lo(r23) - m0) * LOG2E), p3 = ex2((bf_hi(r23) - m1) * LOG2E);
                l0 += p0 + p2; l1 += p1 + p3;
                const uint32_t pb0 = movmatrix_t(pack_bf16(p0, p1)), pb1 = movmatrix_t(pack_bf16(p2, p3));
                mbar_wait(bar_full + 8 * vs, vph);
                const uint32_t vb = sbase + SM_RING + vs * TILE + voff;
#pragma unroll
                for (int d = 0; d < 8; d++) {
                    uint32_t a[4];
                    ldsm4t((vb ^ ((d & 3) << 5)) + (d >> 2) * 8192, a);
                    mma16816(o[d], a, pb0, pb1);
                }
                __syncwarp();
                if (lane == 0) mbar_arrive(bar_empty + 8 * vs);
                ks += 4; if (ks >= NST) { ks -= NST; kph ^= 1; }
                vs += 4; if (vs >= NST) { vs -= NST; vph ^= 1; }
            }
        }
        if (warp == 7) TSTAMP(5);
        {
            float* mrg = (float*)(sgen + SM_MRG);
            float2* ml = (float2*)(sgen + SM_ML);
#pragma unroll
            for (int o_ = 4; o_ < 32; o_ <<= 1) { l0 += __shfl_xor_sync(0xffffffffu, l0, o_); l1 += __shfl_xor_sync(0xffffffffu, l1, o_); }
            if (t < 2) {
                if (g == 0) { ml[warp * 4 + 2 * t] = make_float2(bf_lo(mrun), l0); ml[warp * 4 + 2 * t + 1] = make_float2(bf_hi(mrun), l1); }
                float* m0p = mrg + (warp * 4 + 2 * t) * 136 + g;
#pragma unroll
                for (int d = 0; d < 8; d++) {
                    m0p[16 * d] = o[d][0]; m0p[136 + 16 * d] = o[d][1];
                    m0p[16 * d + 8] = o[d][2]; m0p[136 + 16 * d + 8] = o[d][3];
                }
            }
            cons_sync();
            const int hh = tid >> 6, dp = tid & 63;
            float mm[8], M = -INFINITY;
#pragma unroll
            for (int w = 0; w < 8; w++) { mm[w] = ml[w * 4 + hh].x; M = fmaxf(M, mm[w]); }
            float L = 0.f, o0 = 0.f, o1 = 0.f;
#pragma unroll
            for (int w = 0; w < 8; w++) {
                const float wt = ex2((mm[w] - M) * LOG2E);
                const float2 v = *(const float2*)&mrg[(w * 4 + hh) * 136 + 2 * dp];
                L += wt * ml[w * 4 + hh].y; o0 += wt * v.x; o1 += wt * v.y;
            }
            st_ll4(&g_part_o[cta][hh][dp], __float_as_uint(o0), __float_as_uint(o1), tag);
            if (dp < 2) st_ll4(&g_part_ml[cta][hh][dp], __float_as_uint(M), __float_as_uint(L), tag);
        }
        if (warp == 0) TSTAMP(6);
        uint32_t ob[4];
        {
            const int hq = cta >> 2, kvh = hq >> 2, hh = hq & 3, ds = cta & 3;
            const int b = tid >> 7, dpl = (tid >> 3) & 15, j = tid & 7;
            const int pc = (b * 8 + kvh) * 8 + j;
            uint4 vo, vm;
            for (int it = 0;; it++) {
                vo = ld_ll4(&g_part_o[pc][hh][ds * 16 + dpl]);
                vm = ld_ll4(&g_part_ml[pc][hh][0]);
                const bool ok = vo.y == tag && vo.w == tag && vm.y == tag && vm.w == tag;
                if (__all_sync(0xffffffffu, ok) || it > SPIN_LIMIT) break;
            }
            const float m = __uint_as_float(vm.x);
            float M = m;
            M = fmaxf(M, __shfl_xor_sync(0xffffffffu, M, 1));
            M = fmaxf(M, __shfl_xor_sync(0xffffffffu, M, 2));
            M = fmaxf(M, __shfl_xor_sync(0xffffffffu, M, 4));
            const float wt = ex2((m - M) * LOG2E);
            float L = wt * __uint_as_float(vm.z), o0 = wt * __uint_as_float(vo.x), o1 = wt * __uint_as_float(vo.z);
#pragma unroll
            for (int o_ = 1; o_ < 8; o_ <<= 1) {
                L += __shfl_xor_sync(0xffffffffu, L, o_);
                o0 += __shfl_xor_sync(0xffffffffu, o0, o_);
                o1 += __shfl_xor_sync(0xffffffffu, o1, o_);
            }
            uint32_t* os = (uint32_t*)(sgen + SM_OS);
            if (j == 0) os[b * 16 + dpl] = pack_bf16(o0 / L, o1 / L);
            cons_sync();
#pragma unroll
            for (int s = 0; s < 2; s++) { ob[2 * s] = os[bb * 16 + 8 * s + t]; ob[2 * s + 1] = os[bb * 16 + 8 * s + 4 + t]; }
        }
        if (warp == 0) TSTAMP(7);
        {
            float y[4][4] = {};
            const uint32_t aoff = warp * 2048 + ((lane & 7) + (lane >> 4) * 8) * 128 + ((((lane >> 3) & 1) ^ (lane & 7)) << 4);
#pragma unroll
            for (int s = 0; s < 2; s++) {
                const int idx = IDX_WO + s;
                mbar_wait(bar_full + 8 * (idx % NST), (idx / NST) & 1);
                const uint32_t tb = sbase + SM_RING + (idx % NST) * TILE + aoff;
#pragma unroll
                for (int mt = 0; mt < 4; mt++) {
                    uint32_t a[4];
                    ldsm4t(tb ^ (mt << 5), a);
                    mma16816(y[mt], a, ob[2 * s], ob[2 * s + 1]);
                }
            }
            float v[4];
#pragma unroll
            for (int i = 0; i < 4; i++) v[i] = t == 0 ? y[0][i] : t == 1 ? y[1][i] : t == 2 ? y[2][i] : y[3][i];
            const int col = 64 * warp + 16 * t + g;
            st_ll4(&g_inbox_b[col >> 2][cta][col & 3], __float_as_uint(v[0]), __float_as_uint(v[1]), tag);
            st_ll4(&g_inbox_b[(col + 8) >> 2][cta][col & 3], __float_as_uint(v[2]), __float_as_uint(v[3]), tag);
        }
        if (warp == 0) TSTAMP(8);
        if (cta < NFFN) {
            uint32_t hb[8];
            {
                float xv[16];
                {
                    uint4 v[8];
                    for (int it = 0;; it++) {
                        bool ok = true;
#pragma unroll
                        for (int i = 0; i < 8; i++)
                            v[i] = ld_ll4((const uint4*)&g_x1[64 * warp + 16 * (i >> 1) + 8 * (i & 1) + 2 * t]);
#pragma unroll
                        for (int i = 0; i < 8; i++) ok = ok && v[i].y == tag && v[i].w == tag;
                        if (__all_sync(0xffffffffu, ok) || it > SPIN_LIMIT) break;
                    }
#pragma unroll
                    for (int i = 0; i < 8; i++) {
                        xv[2 * i] = bb ? bf_hi(v[i].x) : bf_lo(v[i].x);
                        xv[2 * i + 1] = bb ? bf_hi(v[i].z) : bf_lo(v[i].z);
                    }
                }
                if (warp == 0) TSTAMP(9);
                float mean = 0.f;
#pragma unroll
                for (int i = 0; i < 16; i++) mean += xv[i];
                mean *= (1.0f / 16);
                float m2 = 0.f;
#pragma unroll
                for (int i = 0; i < 16; i++) { const float d = xv[i] - mean; m2 += d * d; }
#pragma unroll
                for (int o_ = 1, n = 16; o_ < 4; o_ <<= 1, n <<= 1) {
                    const float mo = __shfl_xor_sync(0xffffffffu, mean, o_), qo = __shfl_xor_sync(0xffffffffu, m2, o_);
                    const float d = mo - mean;
                    m2 += qo + d * d * (0.5f * n);
                    mean = 0.5f * (mean + mo);
                }
                float2* stat = (float2*)(sgen + SM_STAT);
                if (t == 0 && g < 2) stat[warp * 2 + g] = make_float2(mean, m2);
                cons_sync();
                float mu = 0.f;
                float2 st[8];
#pragma unroll
                for (int w = 0; w < 8; w++) { st[w] = stat[w * 2 + bb]; mu += st[w].x; }
                mu *= 0.125f;
                float q = 0.f;
#pragma unroll
                for (int w = 0; w < 8; w++) { const float d = st[w].x - mu; q += st[w].y + 64.f * d * d; }
                const float mean_b = bf16r(mu);
                const float sq_b = bf16r(sqrtf(bf16r(bf16r(q * (1.0f / D_MODEL)) + 1e-5f)));
                mbar_wait(bar_sbcb, 0);
                const uint32_t* sbcb = (const uint32_t*)(sgen + SM_SBCB) + bb * 512;
#pragma unroll
                for (int i = 0; i < 8; i++) {
                    const int w = 32 * warp + 8 * (i >> 1) + 4 * (i & 1) + t;
                    const uint32_t sbw = sbcb[w], cbw = sbcb[256 + w];
                    hb[i] = pack_bf16(ln_mod(xv[2 * i], mean_b, sq_b, bf_lo(cbw), bf_lo(sbw)),
                                      ln_mod(xv[2 * i + 1], mean_b, sq_b, bf_hi(cbw), bf_hi(sbw)));
                }
            }
            {
                float cg[4] = {}, cu[4] = {};
                mbar_wait(bar_full + 8 * (IDX_WG % NST), (IDX_WG / NST) & 1);
                mbar_wait(bar_full + 8 * (IDX_WU % NST), (IDX_WU / NST) & 1);
                const uint32_t tg = sbase + SM_RING + (IDX_WG % NST) * TILE, tu = sbase + SM_RING + (IDX_WU % NST) * TILE;
#pragma unroll
                for (int s = 0; s < 4; s++) {
                    const int row = 64 * warp + 16 * s + (lane & 7) + (lane >> 4) * 8;
                    const uint32_t off = row * 32 + ((((lane >> 3) & 1) ^ ((row >> 2) & 1)) << 4);
                    uint32_t a[4], b[4];
                    ldsm4t(tg + off, a);
                    ldsm4t(tu + off, b);
                    mma16816(cg, a, hb[2 * s], hb[2 * s + 1]);
                    mma16816(cu, b, hb[2 * s], hb[2 * s + 1]);
                }
                if (t < 2) {
                    const float v0 = t ? cu[0] : cg[0], v1 = t ? cu[1] : cg[1], v2 = t ? cu[2] : cg[2], v3 = t ? cu[3] : cg[3];
                    *(float2*)&red[warp * 64 + t * 32 + g * 2] = make_float2(v0, v1);
                    *(float2*)&red[warp * 64 + t * 32 + (g + 8) * 2] = make_float2(v2, v3);
                }
                cons_sync();
            }
            {
                float gs = 0.f, us = 0.f;
#pragma unroll
                for (int w = 0; w < 8; w++) { gs += red[w * 64 + lane]; us += red[w * 64 + 32 + lane]; }
                const float act = bf16r(bf16r(gelu_tanh(bf16r(gs))) * bf16r(us));
                const float a0 = __shfl_sync(0xffffffffu, act, 4 * t + bb), a1 = __shfl_sync(0xffffffffu, act, 4 * t + 2 + bb);
                const float a2 = __shfl_sync(0xffffffffu, act, 4 * t + 16 + bb), a3 = __shfl_sync(0xffffffffu, act, 4 * t + 18 + bb);
                const uint32_t b0 = pack_bf16(a0, a1), b1 = pack_bf16(a2, a3);
                float y[4][4] = {};
                mbar_wait(bar_full + 8 * (IDX_WD % NST), (IDX_WD / NST) & 1);
                const uint32_t tb = sbase + SM_RING + (IDX_WD % NST) * TILE + warp * 2048 +
                                    ((lane & 7) + (lane >> 4) * 8) * 128 + ((((lane >> 3) & 1) ^ (lane & 7)) << 4);
#pragma unroll
                for (int mt = 0; mt < 4; mt++) {
                    uint32_t a[4];
                    ldsm4t(tb ^ (mt << 5), a);
                    mma16816(y[mt], a, b0, b1);
                }
                float v[4];
#pragma unroll
                for (int i = 0; i < 4; i++) v[i] = t == 0 ? y[0][i] : t == 1 ? y[1][i] : t == 2 ? y[2][i] : y[3][i];
                const int col = 64 * warp + 16 * t + g;
                st_ll4(&g_inbox_c[col >> 2][cta][col & 3], __float_as_uint(v[0]), __float_as_uint(v[1]), tag);
                st_ll4(&g_inbox_c[(col + 8) >> 2][cta][col & 3], __float_as_uint(v[2]), __float_as_uint(v[3]), tag);
            }
            if (warp == 0) TSTAMP(12);
        }
    }
}

typedef CUresult (*EncodeFn)(CUtensorMap*, CUtensorMapDataType, cuuint32_t, void*, const cuuint64_t*, const cuuint64_t*,
                             const cuuint32_t*, const cuuint32_t*, CUtensorMapInterleave, CUtensorMapSwizzle,
                             CUtensorMapL2promotion, CUtensorMapFloatOOBfill);

struct Maps { CUtensorMap k, v, wq, wmod, wo, wg, wu, wd; };

void encode(EncodeFn fn, CUtensorMap* m, const void* ptr, int rank, const cuuint64_t* dims, const cuuint64_t* strides,
            const cuuint32_t* box, CUtensorMapSwizzle sw) {
    const cuuint32_t es[3] = {1, 1, 1};
    fn(m, CU_TENSOR_MAP_DATA_TYPE_BFLOAT16, rank, const_cast<void*>(ptr), dims, strides, box, es,
       CU_TENSOR_MAP_INTERLEAVE_NONE, sw, CU_TENSOR_MAP_L2_PROMOTION_L2_256B, CU_TENSOR_MAP_FLOAT_OOB_FILL_NONE);
}

}

extern "C" void kernel_launch(void* const* d_in, const int* in_sizes, int n_in, void* d_out, int out_size) {
    (void)in_sizes; (void)n_in; (void)out_size;
    static EncodeFn enc = nullptr;
    if (!enc) {
        void* fn = nullptr;
        cudaDriverEntryPointQueryResult qr;
        cudaGetDriverEntryPoint("cuTensorMapEncodeTiled", &fn, cudaEnableDefault, &qr);
        enc = (EncodeFn)fn;
        cudaFuncSetAttribute(fused_block_kernel, cudaFuncAttributeMaxDynamicSharedMemorySize, SMEM_BYTES);
    }
    Maps m;
    {
        const cuuint64_t dims[3] = {64, (cuuint64_t)16 * SK, 2}, str[2] = {256, 128};
        const cuuint32_t box[3] = {64, 64, 2};
        encode(enc, &m.k, d_in[1], 3, dims, str, box, CU_TENSOR_MAP_SWIZZLE_128B);
        encode(enc, &m.v, d_in[2], 3, dims, str, box, CU_TENSOR_MAP_SWIZZLE_128B);
    }
    {
        const cuuint64_t dims[2] = {4096, 512}, str[1] = {8192};
        const cuuint32_t box[2] = {32, 256};
        encode(enc, &m.wq, d_in[3], 2, dims, str, box, CU_TENSOR_MAP_SWIZZLE_64B);
    }
    {
        const cuuint64_t dims[2] = {N_MOD, 512}, str[1] = {N_MOD * 2};
        const cuuint32_t box[2] = {16, 256};
        encode(enc, &m.wmod, d_in[10], 2, dims, str, box, CU_TENSOR_MAP_SWIZZLE_32B);
    }
    {
        const cuuint64_t dims_o[3] = {64, 4096, 8}, dims_d[3] = {64, D_FF, 8}, str[2] = {1024, 128};
        const cuuint32_t box[3] = {64, 16, 8};
        encode(enc, &m.wo, d_in[4], 3, dims_o, str, box, CU_TENSOR_MAP_SWIZZLE_128B);
        encode(enc, &m.wd, d_in[8], 3, dims_d, str, box, CU_TENSOR_MAP_SWIZZLE_128B);
    }
    {
        const cuuint64_t dims[2] = {D_FF, 512}, str[1] = {D_FF * 2};
        const cuuint32_t box[2] = {16, 256};
        encode(enc, &m.wg, d_in[6], 2, dims, str, box, CU_TENSOR_MAP_SWIZZLE_32B);
        encode(enc, &m.wu, d_in[7], 2, dims, str, box, CU_TENSOR_MAP_SWIZZLE_32B);
    }
    Params p;
    p.x = (const __nv_bfloat16*)d_in[0];
    p.c = (const __nv_bfloat16*)d_in[9];
    p.w_mod = (const __nv_bfloat16*)d_in[10];
    p.out = (__nv_bfloat16*)d_out;
    fused_block_kernel<<<NCTA, NTHREADS, SMEM_BYTES, cudaStreamPerThread>>>(m.k, m.v, m.wq, m.wmod, m.wo, m.wg, m.wu, m.wd, p);
}
```

```cpp
#include <cuda_runtime.h>
#include <cuda.h>
#include <cuda_bf16.h>
#include <stdint.h>

namespace {

constexpr int D_MODEL = 512;
constexpr int N_HEADS = 32;
constexpr int SK = 32768;
constexpr int DH = 128;
constexpr int D_FF = 1792;
constexpr int N_MOD = 6 * D_MODEL;

constexpr int NCTA = 128;
constexpr int NFFN = D_FF / 16;
constexpr int NTHREADS = 288;
constexpr int NST = 12;
constexpr int TILE = 16384;
#define INFL_PRO 2
#define INFL_MAIN 3
#define INFL_TAIL 2
#define PRO_TILES 8
constexpr int KV_TILES = 64;
constexpr int WO_AT = 61;
constexpr int IDX_KV0 = 3;
constexpr int IDX_WO = IDX_KV0 + 2 * WO_AT;
constexpr int IDX_WG = IDX_KV0 + 2 * KV_TILES + 2;
constexpr int IDX_WU = IDX_WG + 1;
constexpr int IDX_WD = IDX_WU + 1;
static_assert(IDX_WD - IDX_WO < NST, "wo must stay resident until the end");
constexpr int SPIN_LIMIT = 1 << 20;

constexpr float LOG2E = 1.4426950408889634f;
constexpr float QK_SCALE = 0.08838834764831845f;

constexpr int SM_RING = 0;
constexpr int SM_MRG = SM_RING + NST * TILE;
constexpr int SM_ML = SM_MRG + 8 * 4 * 136 * 4;
constexpr int SM_RED = SM_ML + 8 * 4 * 8;
constexpr int SM_RED2 = SM_RED + 8 * 64 * 4;
constexpr int SM_QS = SM_RED2 + 8 * 64 * 4;
constexpr int SM_OS = SM_QS + 512 * 2;
constexpr int SM_SC = SM_OS + 2 * 16 * 4;
constexpr int SM_HS = SM_SC + 2 * 512 * 2;
constexpr int SM_STAT = SM_HS + 8 * 2 * 32 * 4;
constexpr int SM_BAR = SM_STAT + 8 * 2 * 8;
constexpr int SM_END = SM_BAR + (2 * NST + 1) * 8;
constexpr int SMEM_BYTES = SM_END + 1024;

struct Params {
    const __nv_bfloat16* x;
    const __nv_bfloat16* c;
    const __nv_bfloat16* w_mod;
    __nv_bfloat16* out;
};

__device__ unsigned g_epoch;
__device__ uint2 g_mod[2][N_MOD / 2];
__device__ uint2 g_q[2][N_HEADS * DH / 2];
__device__ uint4 g_part_o[NCTA][4][64];
__device__ uint4 g_part_ml[NCTA][4][2];
__device__ uint4 g_inbox_b[NCTA][NCTA][4];
__device__ uint2 g_x1[D_MODEL];
__device__ uint4 g_inbox_c[NCTA][NFFN][4];
#define TSTAMP(i) do { } while (0)

__device__ __forceinline__ uint32_t smem_u32(const void* p) { return (uint32_t)__cvta_generic_to_shared(p); }

__device__ __forceinline__ void mbar_init(uint32_t bar, uint32_t cnt) {
    asm volatile("mbarrier.init.shared::cta.b64 [%0], %1;" ::"r"(bar), "r"(cnt) : "memory");
}
__device__ __forceinline__ void mbar_expect_tx(uint32_t bar, uint32_t bytes) {
    asm volatile("mbarrier.arrive.expect_tx.shared::cta.b64 _, [%0], %1;" ::"r"(bar), "r"(bytes) : "memory");
}
__device__ __forceinline__ void mbar_arrive(uint32_t bar) {
    asm volatile("mbarrier.arrive.shared::cta.b64 _, [%0];" ::"r"(bar) : "memory");
}
__device__ __forceinline__ bool mbar_try(uint32_t bar, uint32_t parity) {
    uint32_t ok;
    asm volatile(
        "{\n\t.reg .pred p;\n\t"
        "mbarrier.try_wait.parity.shared::cta.b64 p, [%1], %2;\n\t"
        "selp.u32 %0, 1, 0, p;\n\t}"
        : "=r"(ok) : "r"(bar), "r"(parity) : "memory");
    return ok != 0;
}
__device__ __forceinline__ void mbar_wait(uint32_t bar, uint32_t parity) {
    if (mbar_try(bar, parity)) return;
    for (int i = 0; i < SPIN_LIMIT; i++)
        if (mbar_try(bar, parity)) return;
}
__device__ __forceinline__ void cons_sync() { asm volatile("bar.sync 1, 256;" ::: "memory"); }

__device__ __forceinline__ void tma_2d(uint32_t dst, const CUtensorMap* m, int c0, int c1, uint32_t bar) {
    asm volatile("cp.async.bulk.tensor.2d.shared::cluster.global.mbarrier::complete_tx::bytes [%0], [%1, {%3, %4}], [%2];"
                 ::"r"(dst), "l"(m), "r"(bar), "r"(c0), "r"(c1) : "memory");
}
__device__ __forceinline__ void tma_3d(uint32_t dst, const CUtensorMap* m, int c0, int c1, int c2, uint32_t bar) {
    asm volatile("cp.async.bulk.tensor.3d.shared::cluster.global.mbarrier::complete_tx::bytes [%0], [%1, {%3, %4, %5}], [%2];"
                 ::"r"(dst), "l"(m), "r"(bar), "r"(c0), "r"(c1), "r"(c2) : "memory");
}
__device__ __forceinline__ void prefetch_tmap(const CUtensorMap* m) {
    asm volatile("prefetch.tensormap [%0];" ::"l"(m) : "memory");
}

__device__ __forceinline__ void ldsm4(uint32_t addr, uint32_t (&r)[4]) {
    asm volatile("ldmatrix.sync.aligned.m8n8.x4.shared.b16 {%0,%1,%2,%3}, [%4];"
                 : "=r"(r[0]), "=r"(r[1]), "=r"(r[2]), "=r"(r[3]) : "r"(addr) : "memory");
}
__device__ __forceinline__ void ldsm4t(uint32_t addr, uint32_t (&r)[4]) {
    asm volatile("ldmatrix.sync.aligned.m8n8.x4.trans.shared.b16 {%0,%1,%2,%3}, [%4];"
                 : "=r"(r[0]), "=r"(r[1]), "=r"(r[2]), "=r"(r[3]) : "r"(addr) : "memory");
}
__device__ __forceinline__ void mma16816(float (&c)[4], const uint32_t (&a)[4], uint32_t b0, uint32_t b1) {
    asm volatile("mma.sync.aligned.m16n8k16.row.col.f32.bf16.bf16.f32 {%0,%1,%2,%3}, {%4,%5,%6,%7}, {%8,%9}, {%0,%1,%2,%3};"
                 : "+f"(c[0]), "+f"(c[1]), "+f"(c[2]), "+f"(c[3])
                 : "r"(a[0]), "r"(a[1]), "r"(a[2]), "r"(a[3]), "r"(b0), "r"(b1));
}
__device__ __forceinline__ uint32_t movmatrix_t(uint32_t a) {
    uint32_t d;
    asm volatile("movmatrix.sync.aligned.m8n8.trans.b16 %0, %1;" : "=r"(d) : "r"(a));
    return d;
}
__device__ __forceinline__ uint32_t pack_bf16(float a, float b) {
    uint32_t r;
    asm("cvt.rn.bf16x2.f32 %0, %1, %2;" : "=r"(r) : "f"(b), "f"(a));
    return r;
}
__device__ __forceinline__ float bf_lo(uint32_t v) { return __uint_as_float(v << 16); }
__device__ __forceinline__ float bf_hi(uint32_t v) { return __uint_as_float(v & 0xffff0000u); }
__device__ __forceinline__ float bf16r(float a) { return bf_lo(pack_bf16(a, 0.f)); }
__device__ __forceinline__ uint32_t max_bf16x2(uint32_t a, uint32_t b) {
    uint32_t r;
    asm("max.bf16x2 %0, %1, %2;" : "=r"(r) : "r"(a), "r"(b));
    return r;
}
__device__ __forceinline__ float ex2(float x) {
    float r;
    asm("ex2.approx.ftz.f32 %0, %1;" : "=f"(r) : "f"(x));
    return r;
}

__device__ __forceinline__ void st_ll2(uint2* p, uint32_t v, uint32_t tag) {
    asm volatile("st.relaxed.gpu.global.v2.u32 [%0], {%1, %2};" ::"l"(p), "r"(v), "r"(tag) : "memory");
}
__device__ __forceinline__ void st_ll4(uint4* p, uint32_t v0, uint32_t v1, uint32_t tag) {
    asm volatile("st.relaxed.gpu.global.v4.u32 [%0], {%1, %2, %3, %2};" ::"l"(p), "r"(v0), "r"(tag), "r"(v1) : "memory");
}
__device__ __forceinline__ uint2 ld_ll2(const uint2* p) {
    uint2 v;
    asm volatile("ld.relaxed.gpu.global.v2.u32 {%0, %1}, [%2];" : "=r"(v.x), "=r"(v.y) : "l"(p) : "memory");
    return v;
}
__device__ __forceinline__ uint4 ld_ll4(const uint4* p) {
    uint4 v;
    asm volatile("ld.relaxed.gpu.global.v4.u32 {%0, %1, %2, %3}, [%4];"
                 : "=r"(v.x), "=r"(v.y), "=r"(v.z), "=r"(v.w) : "l"(p) : "memory");
    return v;
}

__device__ __forceinline__ float silu_bf(float v) { return bf16r(v / (1.0f + expf(-v))); }

__device__ __forceinline__ float2 half_warp_sums(const float (&v)[4], float pivot) {
    float s1 = 0.f, s2 = 0.f;
#pragma unroll
    for (int i = 0; i < 4; i++) { const float d = v[i] - pivot; s1 += d; s2 += d * d; }
#pragma unroll
    for (int o = 1; o < 16; o <<= 1) { s1 += __shfl_xor_sync(0xffffffffu, s1, o); s2 += __shfl_xor_sync(0xffffffffu, s2, o); }
    return make_float2(s1, s2);
}
__device__ __forceinline__ void ln_stats(const float2* stat, int b, float pivot, float& mean_bf, float& rstd) {
    float s1 = 0.f, s2 = 0.f;
#pragma unroll
    for (int w = 0; w < 8; w++) { const float2 v = stat[w * 2 + b]; s1 += v.x; s2 += v.y; }
    const float dm = s1 * (1.0f / D_MODEL);
    const float var = fmaxf(s2 * (1.0f / D_MODEL) - dm * dm, 0.f);
    mean_bf = bf16r(pivot + dm);
    rstd = 1.0f / bf16r(sqrtf(bf16r(bf16r(var) + 1e-5f)));
}
__device__ __forceinline__ float ln_norm(float xv, float mean_bf, float rstd) { return bf16r(bf16r(xv - mean_bf) * rstd); }
__device__ __forceinline__ float ln_mod(float n, float cmul, float sadd) { return bf16r(n * bf16r(1.0f + cmul)) + sadd; }

__global__ void __launch_bounds__(NTHREADS, 1)
fused_block_kernel(const __grid_constant__ CUtensorMap tm_k, const __grid_constant__ CUtensorMap tm_v,
                   const __grid_constant__ CUtensorMap tm_wq, const __grid_constant__ CUtensorMap tm_wmod,
                   const __grid_constant__ CUtensorMap tm_wo, const __grid_constant__ CUtensorMap tm_wg,
                   const __grid_constant__ CUtensorMap tm_wu, const __grid_constant__ CUtensorMap tm_wd,
                   const Params p) {
    extern __shared__ unsigned char smem_raw[];
    const uint32_t sbase = (smem_u32(smem_raw) + 1023u) & ~1023u;
    unsigned char* sgen = smem_raw + (sbase - smem_u32(smem_raw));
    const int tid = threadIdx.x, warp = tid >> 5, lane = tid & 31;
    const int cta = blockIdx.x;
    const uint32_t bar_full = sbase + SM_BAR, bar_empty = bar_full + NST * 8;
    const uint32_t bar_p0 = bar_empty + NST * 8;

    if (warp == 8) {
        if (lane == 0) {
            prefetch_tmap(&tm_wq);
            for (int i = 0; i < NST; i++) { mbar_init(bar_full + 8 * i, 1); mbar_init(bar_empty + 8 * i, 4); }
            mbar_init(bar_p0, 8);
            asm volatile("fence.mbarrier_init.release.cluster;" ::: "memory");
        }
        __syncwarp();
        asm volatile("bar.arrive 2, 288;" ::: "memory");
        if (lane == 0) {
            const int pair = cta >> 3, j = cta & 7;
            const int key0 = pair * SK + j * 64;
            const int n_tiles = cta < NFFN ? IDX_WD + 1 : IDX_WG;
            int slot = 0; uint32_t ph = 1;
            int landed = 0, wslot = 0; uint32_t wph = 0;
            for (int idx = 0; idx < n_tiles; idx++) {
                if (idx >= NST) mbar_wait(bar_empty + 8 * slot, ph);
                const int window = idx < PRO_TILES ? INFL_PRO : idx >= IDX_WG ? INFL_TAIL : INFL_MAIN;
                while (landed + window <= idx) {
                    mbar_wait(bar_full + 8 * wslot, wph);
                    if (++wslot == NST) { wslot = 0; wph ^= 1; }
                    landed++;
                }
                const uint32_t fb = bar_full + 8 * slot, dst = sbase + SM_RING + slot * TILE;
                if (idx == 2) {
                    prefetch_tmap(&tm_wmod); prefetch_tmap(&tm_k); prefetch_tmap(&tm_v);
                    mbar_wait(bar_p0, 0);
                }
                mbar_expect_tx(fb, TILE);
                if (idx < 2) {
                    tma_2d(dst, &tm_wq, cta * 32, idx * 256, fb);
                } else if (idx == 2) {
                    tma_2d(dst, &tm_wmod, 1024 + cta * 16, 0, fb);
                    tma_2d(dst + 8192, &tm_wmod, 1024 + cta * 16, 256, fb);
                } else if (idx < IDX_WO) {
                    const int i = (idx - IDX_KV0) >> 1;
                    tma_3d(dst, ((idx - IDX_KV0) & 1) ? &tm_v : &tm_k, 0, key0 + i * 512, 0, fb);
                    if (idx == 16) { prefetch_tmap(&tm_wo); prefetch_tmap(&tm_wg); prefetch_tmap(&tm_wu); prefetch_tmap(&tm_wd); }
                } else if (idx < IDX_WO + 2) {
                    tma_3d(dst, &tm_wo, 0, cta * 32 + (idx - IDX_WO) * 16, 0, fb);
                } else if (idx < IDX_WG) {
                    const int i = (idx - IDX_KV0 - 2) >> 1;
                    tma_3d(dst, ((idx - IDX_KV0) & 1) ? &tm_v : &tm_k, 0, key0 + i * 512, 0, fb);
                } else if (idx < IDX_WD) {
                    const CUtensorMap* m = idx == IDX_WG ? &tm_wg : &tm_wu;
                    tma_2d(dst, m, cta * 16, 0, fb);
                    tma_2d(dst + 8192, m, cta * 16, 256, fb);
                } else {
                    tma_3d(dst, &tm_wd, 0, cta * 16, 0, fb);
                }
                if (++slot == NST) { slot = 0; ph ^= 1; }
            }
        }
    } else {
        const int g = lane >> 2, t = lane & 3;
        const int bb = g & 1;
        const int eb = lane >> 4;
        const int ec = 64 * warp + 4 * (lane & 15);
        if (warp == 0) TSTAMP(0);
        const uint4 w0 = __ldg((const uint4*)(p.w_mod + (size_t)tid * N_MOD + cta * 8));
        const uint4 w1 = __ldg((const uint4*)(p.w_mod + (size_t)(tid + 256) * N_MOD + cta * 8));
        const float c00 = __bfloat162float(p.c[tid]), c01 = __bfloat162float(p.c[tid + 256]);
        const float c10 = __bfloat162float(p.c[D_MODEL + tid]), c11 = __bfloat162float(p.c[D_MODEL + tid + 256]);
        const uint2 xe = __ldg((const uint2*)(p.x + eb * D_MODEL + ec));
        const float xpivot = __bfloat162float(p.x[eb * D_MODEL]);
        const uint32_t tag = *(volatile unsigned*)&g_epoch + 1;
        const int ocol = cta * 4 + (lane & 3);
        const float xo0 = __bfloat162float(p.x[ocol]), xo1 = __bfloat162float(p.x[D_MODEL + ocol]);

        float* red = (float*)(sgen + SM_RED);
        float* red2 = (float*)(sgen + SM_RED2);
        float2* stat = (float2*)(sgen + SM_STAT);
        uint32_t* hs = (uint32_t*)(sgen + SM_HS) + warp * 64;
        float xn[4];
        {
            float xv[4] = {bf_lo(xe.x), bf_hi(xe.x), bf_lo(xe.y), bf_hi(xe.y)};
            const float2 ps = half_warp_sums(xv, xpivot);
            if ((lane & 15) == 0) stat[warp * 2 + eb] = ps;
            const float s00 = silu_bf(c00), s01 = silu_bf(c01), s10 = silu_bf(c10), s11 = silu_bf(c11);
            __nv_bfloat16* sc = (__nv_bfloat16*)(sgen + SM_SC);
            sc[tid] = __float2bfloat16_rn(s00); sc[tid + 256] = __float2bfloat16_rn(s01);
            sc[512 + tid] = __float2bfloat16_rn(s10); sc[512 + tid + 256] = __float2bfloat16_rn(s11);
            const uint32_t a[4] = {w0.x, w0.y, w0.z, w0.w}, b[4] = {w1.x, w1.y, w1.z, w1.w};
            float v[16];
#pragma unroll
            for (int i = 0; i < 4; i++) {
                v[2 * i] = s00 * bf_lo(a[i]) + s01 * bf_lo(b[i]);
                v[2 * i + 1] = s00 * bf_hi(a[i]) + s01 * bf_hi(b[i]);
                v[8 + 2 * i] = s10 * bf_lo(a[i]) + s11 * bf_lo(b[i]);
                v[8 + 2 * i + 1] = s10 * bf_hi(a[i]) + s11 * bf_hi(b[i]);
            }
#define XRED(N, O)                                                                       \
            {                                                                            \
                const bool up = lane & (O);                                              \
                _Pragma("unroll") for (int i = 0; i < (N); i++) {                        \
                    const float send = up ? v[i] : v[i + (N)], keep = up ? v[i + (N)] : v[i]; \
                    v[i] = keep + __shfl_xor_sync(0xffffffffu, send, (O));               \
                }                                                                        \
            }
            XRED(8, 16) XRED(4, 8) XRED(2, 4) XRED(1, 2)
#undef XRED
            v[0] += __shfl_xor_sync(0xffffffffu, v[0], 1);
            if (!(lane & 1)) red[warp * 16 + (lane >> 1)] = v[0];
            if (warp == 0) TSTAMP(14);
            asm volatile("bar.sync 2, 288;" ::: "memory");
            if (lane == 0) mbar_arrive(bar_p0);
            if (warp == 0) {
                float s = 0.f;
#pragma unroll
                for (int w = 0; w < 8; w++) s += red[w * 16 + (lane & 15)];
                const float nx = __shfl_down_sync(0xffffffffu, s, 1);
                if (lane < 16 && !(lane & 1))
                    st_ll2(&g_mod[lane >> 3][cta * 4 + ((lane & 7) >> 1)], pack_bf16(s, nx), tag);
                TSTAMP(1);
            }
            float mean_bf, rstd;
            ln_stats(stat, eb, xpivot, mean_bf, rstd);
#pragma unroll
            for (int i = 0; i < 4; i++) xn[i] = ln_norm(xv[i], mean_bf, rstd);
        }
        {
            uint4 sa, ca;
            for (int it = 0;; it++) {
                sa = ld_ll4((const uint4*)&g_mod[eb][ec >> 1]);
                ca = ld_ll4((const uint4*)&g_mod[eb][256 + (ec >> 1)]);
                const bool ok = sa.y == tag && sa.w == tag && ca.y == tag && ca.w == tag;
                if (__all_sync(0xffffffffu, ok) || it > SPIN_LIMIT) break;
            }
            *(uint2*)&hs[eb * 32 + 2 * (lane & 15)] =
                make_uint2(pack_bf16(ln_mod(xn[0], bf_lo(ca.x), bf_lo(sa.x)), ln_mod(xn[1], bf_hi(ca.x), bf_hi(sa.x))),
                           pack_bf16(ln_mod(xn[2], bf_lo(ca.z), bf_lo(sa.z)), ln_mod(xn[3], bf_hi(ca.z), bf_hi(sa.z))));
            __syncwarp();
            uint32_t hb[8];
#pragma unroll
            for (int i = 0; i < 8; i++) hb[i] = hs[bb * 32 + 8 * (i >> 1) + 4 * (i & 1) + t];
            if (warp == 0) TSTAMP(2);
            float cq[2][4] = {};
            const int ts = warp >> 2;
            mbar_wait(bar_full + 8 * ts, 0);
            const uint32_t tb = sbase + SM_RING + ts * TILE;
#pragma unroll
            for (int s = 0; s < 4; s++) {
                const int row = 64 * (warp & 3) + 16 * s + (lane & 7) + (lane >> 4) * 8;
#pragma unroll
                for (int mt = 0; mt < 2; mt++) {
                    const int ch = 2 * mt + ((lane >> 3) & 1);
                    uint32_t a[4];
                    ldsm4t(tb + row * 64 + ((ch ^ ((row >> 1) & 3)) << 4), a);
                    mma16816(cq[mt], a, hb[2 * s], hb[2 * s + 1]);
                }
            }
            if (t < 2) {
                const float v0 = t == 0 ? cq[0][0] : cq[1][0], v1 = t == 0 ? cq[0][1] : cq[1][1];
                const float v2 = t == 0 ? cq[0][2] : cq[1][2], v3 = t == 0 ? cq[0][3] : cq[1][3];
                *(float2*)&red2[warp * 64 + (16 * t + g) * 2] = make_float2(v0, v1);
                *(float2*)&red2[warp * 64 + (16 * t + g + 8) * 2] = make_float2(v2, v3);
            }
            cons_sync();
            if (warp < 4 && lane == 0) { mbar_arrive(bar_empty + 0); mbar_arrive(bar_empty + 8); }
            if (warp == 0) {
                const int b = lane >> 4, cp = lane & 15;
                float q0 = 0.f, q1 = 0.f;
#pragma unroll
                for (int w = 0; w < 8; w++) {
                    const float4 v = *(const float4*)&red2[w * 64 + cp * 4];
                    q0 += b ? v.y : v.x; q1 += b ? v.w : v.z;
                }
                st_ll2(&g_q[b][cta * 16 + cp], pack_bf16(q0, q1), tag);
                TSTAMP(3);
            }
        }
        {
            float cm[4] = {};
            const uint32_t* sc32 = (const uint32_t*)(sgen + SM_SC) + bb * 256 + 32 * warp + t;
            mbar_wait(bar_full + 8 * 2, 0);
            const uint32_t tb = sbase + SM_RING + 2 * TILE;
#pragma unroll
            for (int s = 0; s < 4; s++) {
                const int row = 64 * warp + 16 * s + (lane & 7) + (lane >> 4) * 8;
                const int ch = (lane >> 3) & 1;
                uint32_t a[4];
                ldsm4t(tb + row * 32 + ((ch ^ ((row >> 2) & 1)) << 4), a);
                mma16816(cm, a, sc32[8 * s], sc32[8 * s + 4]);
            }
            if (t == 0) {
                *(float2*)&red[warp * 64 + g * 2] = make_float2(cm[0], cm[1]);
                *(float2*)&red[warp * 64 + (g + 8) * 2] = make_float2(cm[2], cm[3]);
            }
            cons_sync();
            if (warp < 4 && lane == 0) mbar_arrive(bar_empty + 16);
            if (warp == 1 && lane < 16) {
                const int b = lane >> 3, cp = lane & 7;
                float q0 = 0.f, q1 = 0.f;
#pragma unroll
                for (int w = 0; w < 8; w++) {
                    const float4 v = *(const float4*)&red[w * 64 + cp * 4];
                    q0 += b ? v.y : v.x; q1 += b ? v.w : v.z;
                }
                st_ll2(&g_mod[b][512 + cta * 8 + cp], pack_bf16(q0, q1), tag);
            }
        }
        const int pair = cta >> 3;
        uint32_t qf[16];
        {
            uint2* qs = (uint2*)(sgen + SM_QS);
            if (tid < 128) {
                const uint4* src = (const uint4*)&g_q[pair >> 3][(pair & 7) * 256] + tid;
                uint4 v;
                for (int it = 0;; it++) {
                    v = ld_ll4(src);
                    if ((v.y == tag && v.w == tag) || it > SPIN_LIMIT) break;
                }
                qs[tid] = make_uint2(v.x, v.z);
            }
            cons_sync();
            const uint32_t* q32 = (const uint32_t*)(sgen + SM_QS);
#pragma unroll
            for (int s = 0; s < 8; s++) {
                qf[2 * s] = q32[(g & 3) * 64 + 8 * s + t];
                qf[2 * s + 1] = q32[(g & 3) * 64 + 8 * s + 4 + t];
            }
        }
        if (warp == 0) TSTAMP(4);

        float o[8][4];
#pragma unroll
        for (int i = 0; i < 8; i++) { o[i][0] = o[i][1] = o[i][2] = o[i][3] = 0.f; }
        uint32_t mrun = 0xff80ff80u;
        float ls[4] = {0.f, 0.f, 0.f, 0.f};
        uint4 m_sb, m_cb; uint2 m_ga0, m_ga1, m_gb0, m_gb1;
        {
            const int grp = warp >> 2, wi = warp & 3;
            const int krow = 16 * wi + (lane & 7) + ((lane >> 3) & 1) * 8;
            const uint32_t koff = krow * 128 + ((((lane >> 4) & 1) ^ (lane & 7)) << 4);
            const int vrow = 16 * wi + (lane & 7) + (lane >> 4) * 8;
            const uint32_t voff = vrow * 128 + ((((lane >> 3) & 1) ^ (lane & 7)) << 4);
            const uint32_t ones[4] = {0x3f803f80u, 0x3f803f80u, 0x3f803f80u, 0x3f803f80u};
            int ks = IDX_KV0 + 2 * grp, vs = ks + 1;
            uint32_t kph = 0, vph = 0;
            for (int i = grp; i < KV_TILES; i += 2) {
                if (i == 56 + grp) {
                    m_sb = ld_ll4((const uint4*)&g_mod[eb][768 + (ec >> 1)]);
                    m_cb = ld_ll4((const uint4*)&g_mod[eb][1024 + (ec >> 1)]);
                    m_ga0 = ld_ll2(&g_mod[0][512 + (ocol >> 1)]); m_ga1 = ld_ll2(&g_mod[1][512 + (ocol >> 1)]);
                    m_gb0 = ld_ll2(&g_mod[0][1280 + (ocol >> 1)]); m_gb1 = ld_ll2(&g_mod[1][1280 + (ocol >> 1)]);
                }
                mbar_wait(bar_full + 8 * ks, kph);
                const uint32_t kb = sbase + SM_RING + ks * TILE + koff;
                float sa[4] = {0.f, 0.f, 0.f, 0.f}, sb[4] = {0.f, 0.f, 0.f, 0.f};
#pragma unroll
                for (int s = 0; s < 8; s += 2) {
                    uint32_t a0[4], a1[4];
                    ldsm4((kb ^ ((s & 3) << 5)) + (s >> 2) * 8192, a0);
                    ldsm4((kb ^ (((s + 1) & 3) << 5)) + (s >> 2) * 8192, a1);
                    mma16816(sa, a0, qf[2 * s], qf[2 * s + 1]);
                    mma16816(sb, a1, qf[2 * s + 2], qf[2 * s + 3]);
                }
                __syncwarp();
                if (lane == 0) mbar_arrive(bar_empty + 8 * ks);
                uint32_t r01 = pack_bf16(sa[0] + sb[0], sa[1] + sb[1]);
                uint32_t r23 = pack_bf16(sa[2] + sb[2], sa[3] + sb[3]);
                r01 = pack_bf16(bf_lo(r01) * QK_SCALE, bf_hi(r01) * QK_SCALE);
                r23 = pack_bf16(bf_lo(r23) * QK_SCALE, bf_hi(r23) * QK_SCALE);
                uint32_t mx = max_bf16x2(r01, r23);
                mx = max_bf16x2(mx, __shfl_xor_sync(0xffffffffu, mx, 4));
                mx = max_bf16x2(mx, __shfl_xor_sync(0xffffffffu, mx, 8));
                mx = max_bf16x2(mx, __shfl_xor_sync(0xffffffffu, mx, 16));
                const uint32_t mnew = max_bf16x2(mrun, mx);
                const float m0 = bf_lo(mnew), m1 = bf_hi(mnew);
                if (__any_sync(0xffffffffu, mnew != mrun)) {
                    const float al0 = ex2((bf_lo(mrun) - m0) * LOG2E), al1 = ex2((bf_hi(mrun) - m1) * LOG2E);
                    ls[0] *= al0; ls[1] *= al1;
#pragma unroll
                    for (int d = 0; d < 8; d++) { o[d][0] *= al0; o[d][1] *= al1; o[d][2] *= al0; o[d][3] *= al1; }
                    mrun = mnew;
                }
                const float p0 = ex2((bf_lo(r01) - m0) * LOG2E), p1 = ex2((bf_hi(r01) - m1) * LOG2E);
                const float p2 = ex2((bf_lo(r23) - m0) * LOG2E), p3 = ex2((bf_hi(r23) - m1) * LOG2E);
                const uint32_t pb0 = movmatrix_t(pack_bf16(p0, p1)), pb1 = movmatrix_t(pack_bf16(p2, p3));
                mma16816(ls, ones, pb0, pb1);
                mbar_wait(bar_full + 8 * vs, vph);
                const uint32_t vb = sbase + SM_RING + vs * TILE + voff;
#pragma unroll
                for (int d = 0; d < 8; d++) {
                    uint32_t a[4];
                    ldsm4t((vb ^ ((d & 3) << 5)) + (d >> 2) * 8192, a);
                    mma16816(o[d], a, pb0, pb1);
                }
                __syncwarp();
                if (lane == 0) mbar_arrive(bar_empty + 8 * vs);
                const int adv = (i < WO_AT && i + 2 >= WO_AT) ? 6 : 4;
                ks += adv; if (ks >= NST) { ks -= NST; kph ^= 1; }
                vs += adv; if (vs >= NST) { vs -= NST; vph ^= 1; }
            }
        }
        if (warp == 7) TSTAMP(5);
        {
            float* mrg = (float*)(sgen + SM_MRG);
            float2* ml = (float2*)(sgen + SM_ML);
            if (t < 2) {
                if (g == 0) { ml[warp * 4 + 2 * t] = make_float2(bf_lo(mrun), ls[0]); ml[warp * 4 + 2 * t + 1] = make_float2(bf_hi(mrun), ls[1]); }
                float* m0p = mrg + (warp * 4 + 2 * t) * 136 + g;
#pragma unroll
                for (int d = 0; d < 8; d++) {
                    m0p[16 * d] = o[d][0]; m0p[136 + 16 * d] = o[d][1];
                    m0p[16 * d + 8] = o[d][2]; m0p[136 + 16 * d + 8] = o[d][3];
                }
            }
            cons_sync();
            const int hh = tid >> 6, dp = tid & 63;
            float2 mw[8];
            float M = -INFINITY;
#pragma unroll
            for (int w = 0; w < 8; w++) { mw[w] = ml[w * 4 + hh]; M = fmaxf(M, mw[w].x); }
            float L = 0.f, o0 = 0.f, o1 = 0.f;
#pragma unroll
            for (int w = 0; w < 8; w++) {
                const float wt = ex2((mw[w].x - M) * LOG2E);
                const float2 v = *(const float2*)&mrg[(w * 4 + hh) * 136 + 2 * dp];
                L += wt * mw[w].y; o0 += wt * v.x; o1 += wt * v.y;
            }
            st_ll4(&g_part_o[cta][hh][dp], __float_as_uint(o0), __float_as_uint(o1), tag);
            if (dp < 2) st_ll4(&g_part_ml[cta][hh][dp], __float_as_uint(M), __float_as_uint(L), tag);
        }
        if (warp == 0) TSTAMP(6);
        const uint32_t aoff = warp * 2048 + ((lane & 7) + (lane >> 4) * 8) * 128 + ((((lane >> 3) & 1) ^ (lane & 7)) << 4);
        uint32_t wf[8][4];
#pragma unroll
        for (int s = 0; s < 2; s++) {
            constexpr int i0 = IDX_WO;
            const int idx = i0 + s;
            mbar_wait(bar_full + 8 * (idx % NST), (idx / NST) & 1);
            const uint32_t tb = sbase + SM_RING + (idx % NST) * TILE + aoff;
#pragma unroll
            for (int mt = 0; mt < 4; mt++) ldsm4t(tb ^ (mt << 5), wf[s * 4 + mt]);
        }
        {
            const int hq = cta >> 2, kvh = hq >> 2, hh = hq & 3, ds = cta & 3;
            const int b = tid >> 7, dpl = (tid >> 3) & 15, j = tid & 7;
            const int pc = (b * 8 + kvh) * 8 + j;
            uint4 vo, vm;
            for (int it = 0;; it++) {
                vo = ld_ll4(&g_part_o[pc][hh][ds * 16 + dpl]);
                vm = ld_ll4(&g_part_ml[pc][hh][0]);
                const bool ok = vo.y == tag && vo.w == tag && vm.y == tag && vm.w == tag;
                if (__all_sync(0xffffffffu, ok) || it > SPIN_LIMIT) break;
            }
            const float m = __uint_as_float(vm.x);
            float M = m;
            M = fmaxf(M, __shfl_xor_sync(0xffffffffu, M, 1));
            M = fmaxf(M, __shfl_xor_sync(0xffffffffu, M, 2));
            M = fmaxf(M, __shfl_xor_sync(0xffffffffu, M, 4));
            const float wt = ex2((m - M) * LOG2E);
            float L = wt * __uint_as_float(vm.z), o0 = wt * __uint_as_float(vo.x), o1 = wt * __uint_as_float(vo.z);
#pragma unroll
            for (int o_ = 1; o_ < 8; o_ <<= 1) {
                L += __shfl_xor_sync(0xffffffffu, L, o_);
                o0 += __shfl_xor_sync(0xffffffffu, o0, o_);
                o1 += __shfl_xor_sync(0xffffffffu, o1, o_);
            }
            uint32_t* os = (uint32_t*)(sgen + SM_OS);
            const float rl = 1.0f / L;
            if (j == 0) os[b * 16 + dpl] = pack_bf16(o0 * rl, o1 * rl);
            cons_sync();
            if (warp == 0) TSTAMP(7);
            float y[4][4] = {};
#pragma unroll
            for (int s = 0; s < 2; s++) {
                const uint32_t b0 = os[bb * 16 + 8 * s + t], b1 = os[bb * 16 + 8 * s + 4 + t];
#pragma unroll
                for (int mt = 0; mt < 4; mt++) mma16816(y[mt], wf[s * 4 + mt], b0, b1);
            }
            float v[4];
#pragma unroll
            for (int i = 0; i < 4; i++) v[i] = t == 0 ? y[0][i] : t == 1 ? y[1][i] : t == 2 ? y[2][i] : y[3][i];
            const int col = 64 * warp + 16 * t + g;
            st_ll4(&g_inbox_b[col >> 2][cta][col & 3], __float_as_uint(v[0]), __float_as_uint(v[1]), tag);
            st_ll4(&g_inbox_b[(col + 8) >> 2][cta][col & 3], __float_as_uint(v[2]), __float_as_uint(v[3]), tag);
        }
        if (warp == 0) TSTAMP(8);
        for (int it = 0;; it++) {
            const bool ok = m_sb.y == tag && m_sb.w == tag && m_cb.y == tag && m_cb.w == tag &&
                            m_ga0.y == tag && m_ga1.y == tag && m_gb0.y == tag && m_gb1.y == tag;
            if (__all_sync(0xffffffffu, ok) || it > SPIN_LIMIT) break;
            m_sb = ld_ll4((const uint4*)&g_mod[eb][768 + (ec >> 1)]);
            m_cb = ld_ll4((const uint4*)&g_mod[eb][1024 + (ec >> 1)]);
            m_ga0 = ld_ll2(&g_mod[0][512 + (ocol >> 1)]); m_ga1 = ld_ll2(&g_mod[1][512 + (ocol >> 1)]);
            m_gb0 = ld_ll2(&g_mod[0][1280 + (ocol >> 1)]); m_gb1 = ld_ll2(&g_mod[1][1280 + (ocol >> 1)]);
        }
        float xm0 = 0.f, xm1 = 0.f;
        {
            float s0, s1;
            for (int it = 0;; it++) {
                const uint4 v0 = ld_ll4(&g_inbox_b[cta][0][0] + tid), v1 = ld_ll4(&g_inbox_b[cta][0][0] + 256 + tid);
                s0 = __uint_as_float(v0.x) + __uint_as_float(v1.x);
                s1 = __uint_as_float(v0.z) + __uint_as_float(v1.z);
                const bool ok = v0.y == tag && v0.w == tag && v1.y == tag && v1.w == tag;
                if (__all_sync(0xffffffffu, ok) || it > SPIN_LIMIT) break;
            }
#pragma unroll
            for (int o_ = 4; o_ < 32; o_ <<= 1) { s0 += __shfl_xor_sync(0xffffffffu, s0, o_); s1 += __shfl_xor_sync(0xffffffffu, s1, o_); }
            if (lane < 4) *(float2*)&red2[warp * 8 + lane * 2] = make_float2(s0, s1);
            cons_sync();
            if (warp == 0) {
                float a0 = 0.f, a1 = 0.f;
#pragma unroll
                for (int w = 0; w < 8; w++) { const float2 v = *(const float2*)&red2[w * 8 + (lane & 3) * 2]; a0 += v.x; a1 += v.y; }
                const bool hi = ocol & 1;
                const float ga0 = hi ? bf_hi(m_ga0.x) : bf_lo(m_ga0.x), ga1 = hi ? bf_hi(m_ga1.x) : bf_lo(m_ga1.x);
                xm0 = bf16r(xo0 + bf16r(ga0 * bf16r(a0)));
                xm1 = bf16r(xo1 + bf16r(ga1 * bf16r(a1)));
                if (lane < 4) st_ll2(&g_x1[ocol], pack_bf16(xm0, xm1), tag);
                TSTAMP(10);
            }
        }
        if (cta < NFFN) {
            uint32_t gf[4][4], uf[4][4];
            mbar_wait(bar_full + 8 * (IDX_WG % NST), (IDX_WG / NST) & 1);
            mbar_wait(bar_full + 8 * (IDX_WU % NST), (IDX_WU / NST) & 1);
            {
                const uint32_t tg = sbase + SM_RING + (IDX_WG % NST) * TILE, tu = sbase + SM_RING + (IDX_WU % NST) * TILE;
#pragma unroll
                for (int s = 0; s < 4; s++) {
                    const int row = 64 * warp + 16 * s + (lane & 7) + (lane >> 4) * 8;
                    const uint32_t off = row * 32 + ((((lane >> 3) & 1) ^ ((row >> 2) & 1)) << 4);
                    ldsm4t(tg + off, gf[s]);
                    ldsm4t(tu + off, uf[s]);
                }
            }
            if (warp == 0) TSTAMP(11);
            uint32_t hb[8];
            {
                uint4 v0, v1; uint2 pv;
                for (int it = 0;; it++) {
                    v0 = ld_ll4((const uint4*)&g_x1[ec]); v1 = ld_ll4((const uint4*)&g_x1[ec + 2]); pv = ld_ll2(&g_x1[0]);
                    const bool ok = v0.y == tag && v0.w == tag && v1.y == tag && v1.w == tag && pv.y == tag;
                    if (__all_sync(0xffffffffu, ok) || it > SPIN_LIMIT) break;
                }
                if (warp == 0) TSTAMP(9);
                const float xv[4] = {eb ? bf_hi(v0.x) : bf_lo(v0.x), eb ? bf_hi(v0.z) : bf_lo(v0.z),
                                     eb ? bf_hi(v1.x) : bf_lo(v1.x), eb ? bf_hi(v1.z) : bf_lo(v1.z)};
                const float pivot = eb ? bf_hi(pv.x) : bf_lo(pv.x);
                const float2 ps = half_warp_sums(xv, pivot);
                if ((lane & 15) == 0) stat[warp * 2 + eb] = ps;
                cons_sync();
                float mean_bf, rstd;
                ln_stats(stat, eb, pivot, mean_bf, rstd);
                *(uint2*)&hs[eb * 32 + 2 * (lane & 15)] = make_uint2(
                    pack_bf16(ln_mod(ln_norm(xv[0], mean_bf, rstd), bf_lo(m_cb.x), bf_lo(m_sb.x)),
                              ln_mod(ln_norm(xv[1], mean_bf, rstd), bf_hi(m_cb.x), bf_hi(m_sb.x))),
                    pack_bf16(ln_mod(ln_norm(xv[2], mean_bf, rstd), bf_lo(m_cb.z), bf_lo(m_sb.z)),
                              ln_mod(ln_norm(xv[3], mean_bf, rstd), bf_hi(m_cb.z), bf_hi(m_sb.z))));
                __syncwarp();
#pragma unroll
                for (int i = 0; i < 8; i++) hb[i] = hs[bb * 32 + 8 * (i >> 1) + 4 * (i & 1) + t];
            }
            {
                float cg[2][4] = {}, cu[2][4] = {};
#pragma unroll
                for (int s = 0; s < 4; s++) {
                    mma16816(cg[s & 1], gf[s], hb[2 * s], hb[2 * s + 1]);
                    mma16816(cu[s & 1], uf[s], hb[2 * s], hb[2 * s + 1]);
                }
                if (t < 2) {
                    float v[4];
#pragma unroll
                    for (int i = 0; i < 4; i++) v[i] = t ? cu[0][i] + cu[1][i] : cg[0][i] + cg[1][i];
                    *(float2*)&red[warp * 64 + t * 32 + g * 2] = make_float2(v[0], v[1]);
                    *(float2*)&red[warp * 64 + t * 32 + (g + 8) * 2] = make_float2(v[2], v[3]);
                }
            }
            uint32_t df[4][4];
            mbar_wait(bar_full + 8 * (IDX_WD % NST), (IDX_WD / NST) & 1);
#pragma unroll
            for (int mt = 0; mt < 4; mt++) ldsm4t((sbase + SM_RING + (IDX_WD % NST) * TILE + aoff) ^ (mt << 5), df[mt]);
            cons_sync();
            {
                float gs = 0.f, us = 0.f;
#pragma unroll
                for (int w = 0; w < 8; w++) { gs += red[w * 64 + lane]; us += red[w * 64 + 32 + lane]; }
                gs = bf16r(gs);
                const float u2 = gs * (1.0f + 0.044715f * gs * gs) * (2.0f * 0.7978845608028654f * LOG2E);
                const float ge = bf16r(__fdividef(gs, 1.0f + ex2(-u2)));
                const float act = bf16r(ge * bf16r(us));
                const float a0 = __shfl_sync(0xffffffffu, act, 4 * t + bb), a1 = __shfl_sync(0xffffffffu, act, 4 * t + 2 + bb);
                const float a2 = __shfl_sync(0xffffffffu, act, 4 * t + 16 + bb), a3 = __shfl_sync(0xffffffffu, act, 4 * t + 18 + bb);
                const uint32_t b0 = pack_bf16(a0, a1), b1 = pack_bf16(a2, a3);
                float y[4][4] = {};
#pragma unroll
                for (int mt = 0; mt < 4; mt++) mma16816(y[mt], df[mt], b0, b1);
                float v[4];
#pragma unroll
                for (int i = 0; i < 4; i++) v[i] = t == 0 ? y[0][i] : t == 1 ? y[1][i] : t == 2 ? y[2][i] : y[3][i];
                const int col = 64 * warp + 16 * t + g;
                st_ll4(&g_inbox_c[col >> 2][cta][col & 3], __float_as_uint(v[0]), __float_as_uint(v[1]), tag);
                st_ll4(&g_inbox_c[(col + 8) >> 2][cta][col & 3], __float_as_uint(v[2]), __float_as_uint(v[3]), tag);
            }
            if (warp == 0) TSTAMP(12);
        }
        {
            float s0, s1;
            for (int it = 0;; it++) {
                const uint4 v0 = ld_ll4(&g_inbox_c[cta][0][0] + tid);
                uint4 v1 = make_uint4(0u, tag, 0u, tag);
                if (tid < NFFN * 4 - 256) v1 = ld_ll4(&g_inbox_c[cta][0][0] + 256 + tid);
                s0 = __uint_as_float(v0.x) + __uint_as_float(v1.x);
                s1 = __uint_as_float(v0.z) + __uint_as_float(v1.z);
                const bool ok = v0.y == tag && v0.w == tag && v1.y == tag && v1.w == tag;
                if (__all_sync(0xffffffffu, ok) || it > SPIN_LIMIT) break;
            }
#pragma unroll
            for (int o_ = 4; o_ < 32; o_ <<= 1) { s0 += __shfl_xor_sync(0xffffffffu, s0, o_); s1 += __shfl_xor_sync(0xffffffffu, s1, o_); }
            if (lane < 4) *(float2*)&red2[64 + warp * 8 + lane * 2] = make_float2(s0, s1);
            cons_sync();
            if (warp == 0) {
                float a0 = 0.f, a1 = 0.f;
#pragma unroll
                for (int w = 0; w < 8; w++) { const float2 v = *(const float2*)&red2[64 + w * 8 + (lane & 3) * 2]; a0 += v.x; a1 += v.y; }
                const bool hi = ocol & 1;
                const float gb0 = hi ? bf_hi(m_gb0.x) : bf_lo(m_gb0.x), gb1 = hi ? bf_hi(m_gb1.x) : bf_lo(m_gb1.x);
                if (lane < 4) {
                    p.out[ocol] = __float2bfloat16_rn(xm0 + bf16r(gb0 * bf16r(a0)));
                    p.out[D_MODEL + ocol] = __float2bfloat16_rn(xm1 + bf16r(gb1 * bf16r(a1)));
                }
                if (cta == 0 && lane == 0) *(volatile unsigned*)&g_epoch = tag;
                TSTAMP(13);
            }
        }
    }
}

typedef CUresult (*EncodeFn)(CUtensorMap*, CUtensorMapDataType, cuuint32_t, void*, const cuuint64_t*, const cuuint64_t*,
                             const cuuint32_t*, const cuuint32_t*, CUtensorMapInterleave, CUtensorMapSwizzle,
                             CUtensorMapL2promotion, CUtensorMapFloatOOBfill);

struct Maps { CUtensorMap k, v, wq, wmod, wo, wg, wu, wd; };

void encode(EncodeFn fn, CUtensorMap* m, const void* ptr, int rank, const cuuint64_t* dims, const cuuint64_t* strides,
            const cuuint32_t* box, CUtensorMapSwizzle sw) {
    const cuuint32_t es[3] = {1, 1, 1};
    fn(m, CU_TENSOR_MAP_DATA_TYPE_BFLOAT16, rank, const_cast<void*>(ptr), dims, strides, box, es,
       CU_TENSOR_MAP_INTERLEAVE_NONE, sw, CU_TENSOR_MAP_L2_PROMOTION_L2_256B, CU_TENSOR_MAP_FLOAT_OOB_FILL_NONE);
}

}

extern "C" void kernel_launch(void* const* d_in, const int* in_sizes, int n_in, void* d_out, int out_size) {
    (void)in_sizes; (void)n_in; (void)out_size;
    static EncodeFn enc = nullptr;
    if (!enc) {
        void* fn = nullptr;
        cudaDriverEntryPointQueryResult qr;
        cudaGetDriverEntryPoint("cuTensorMapEncodeTiled", &fn, cudaEnableDefault, &qr);
        enc = (EncodeFn)fn;
        cudaFuncSetAttribute(fused_block_kernel, cudaFuncAttributeMaxDynamicSharedMemorySize, SMEM_BYTES);
    }
    Maps m;
    {
        const cuuint64_t dims[3] = {64, (cuuint64_t)16 * SK, 2}, str[2] = {256, 128};
        const cuuint32_t box[3] = {64, 64, 2};
        encode(enc, &m.k, d_in[1], 3, dims, str, box, CU_TENSOR_MAP_SWIZZLE_128B);
        encode(enc, &m.v, d_in[2], 3, dims, str, box, CU_TENSOR_MAP_SWIZZLE_128B);
    }
    {
        const cuuint64_t dims[2] = {4096, 512}, str[1] = {8192};
        const cuuint32_t box[2] = {32, 256};
        encode(enc, &m.wq, d_in[3], 2, dims, str, box, CU_TENSOR_MAP_SWIZZLE_64B);
    }
    {
        const cuuint64_t dims[2] = {N_MOD, 512}, str[1] = {N_MOD * 2};
        const cuuint32_t box[2] = {16, 256};
        encode(enc, &m.wmod, d_in[10], 2, dims, str, box, CU_TENSOR_MAP_SWIZZLE_32B);
    }
    {
        const cuuint64_t dims_o[3] = {64, 4096, 8}, dims_d[3] = {64, D_FF, 8}, str[2] = {1024, 128};
        const cuuint32_t box[3] = {64, 16, 8};
        encode(enc, &m.wo, d_in[4], 3, dims_o, str, box, CU_TENSOR_MAP_SWIZZLE_128B);
        encode(enc, &m.wd, d_in[8], 3, dims_d, str, box, CU_TENSOR_MAP_SWIZZLE_128B);
    }
    {
        const cuuint64_t dims[2] = {D_FF, 512}, str[1] = {D_FF * 2};
        const cuuint32_t box[2] = {16, 256};
        encode(enc, &m.wg, d_in[6], 2, dims, str, box, CU_TENSOR_MAP_SWIZZLE_32B);
        encode(enc, &m.wu, d_in[7], 2, dims, str, box, CU_TENSOR_MAP_SWIZZLE_32B);
    }
    Params p;
    p.x = (const __nv_bfloat16*)d_in[0];
    p.c = (const __nv_bfloat16*)d_in[9];
    p.w_mod = (const __nv_bfloat16*)d_in[10];
    p.out = (__nv_bfloat16*)d_out;
    fused_block_kernel<<<NCTA, NTHREADS, SMEM_BYTES, cudaStreamPerThread>>>(m.k, m.v, m.wq, m.wmod, m.wo, m.wg, m.wu, m.wd, p);
}
```

```cpp
#include <cuda_runtime.h>
#include <cuda.h>
#include <cuda_bf16.h>
#include <stdint.h>

namespace {

constexpr int D_MODEL = 512;
constexpr int N_HEADS = 32;
constexpr int SK = 32768;
constexpr int DH = 128;
constexpr int D_FF = 1792;
constexpr int N_MOD = 6 * D_MODEL;

constexpr int NCTA = 128;
constexpr int NFFN = D_FF / 16;
constexpr int NTHREADS = 288;
constexpr int NST = 12;
constexpr int TILE = 16384;
#define INFL_PRO 2
#define INFL_MAIN 3
#define INFL_TAIL 2
#define PRO_TILES 8
constexpr int KV_TILES = 64;
constexpr int WO_AT = 61;
constexpr int IDX_KV0 = 3;
constexpr int IDX_WO = IDX_KV0 + 2 * WO_AT;
constexpr int IDX_WG = IDX_KV0 + 2 * KV_TILES + 2;
constexpr int IDX_WU = IDX_WG + 1;
constexpr int IDX_WD = IDX_WU + 1;
static_assert(IDX_WD - IDX_WO < NST, "wo must stay resident until the end");
constexpr int SPIN_LIMIT = 1 << 20;

constexpr float LOG2E = 1.4426950408889634f;
constexpr float QK_SCALE = 0.08838834764831845f;

constexpr int SM_RING = 0;
constexpr int SM_MRG = SM_RING + NST * TILE;
constexpr int SM_ML = SM_MRG + 8 * 4 * 136 * 4;
constexpr int SM_RED = SM_ML + 8 * 4 * 8;
constexpr int SM_RED2 = SM_RED + 8 * 64 * 4;
constexpr int SM_QS = SM_RED2 + 8 * 64 * 4;
constexpr int SM_OS = SM_QS + 512 * 2;
constexpr int SM_SC = SM_OS + 2 * 16 * 4;
constexpr int SM_HS = SM_SC + 2 * 512 * 2;
constexpr int SM_STAT = SM_HS + 8 * 2 * 32 * 4;
constexpr int SM_BAR = SM_STAT + 8 * 2 * 8;
constexpr int SM_END = SM_BAR + (2 * NST + 1) * 8;
constexpr int SMEM_BYTES = SM_END + 1024;

struct Params {
    const __nv_bfloat16* x;
    const __nv_bfloat16* c;
    const __nv_bfloat16* w_mod;
    __nv_bfloat16* out;
};

__device__ unsigned g_epoch;
__device__ uint2 g_mod[2][N_MOD / 2];
__device__ uint2 g_q[2][N_HEADS * DH / 2];
__device__ uint4 g_part_o[NCTA][4][64];
__device__ uint4 g_part_ml[NCTA][4][2];
__device__ uint4 g_inbox[NCTA][NCTA][4];
constexpr uint32_t F_PART = 1, F_WO = 1, F_DOWN = 2, F_X1 = 3;
#define TSTAMP(i) do { } while (0)

__device__ __forceinline__ uint32_t smem_u32(const void* p) { return (uint32_t)__cvta_generic_to_shared(p); }

__device__ __forceinline__ void mbar_init(uint32_t bar, uint32_t cnt) {
    asm volatile("mbarrier.init.shared::cta.b64 [%0], %1;" ::"r"(bar), "r"(cnt) : "memory");
}
__device__ __forceinline__ void mbar_expect_tx(uint32_t bar, uint32_t bytes) {
    asm volatile("mbarrier.arrive.expect_tx.shared::cta.b64 _, [%0], %1;" ::"r"(bar), "r"(bytes) : "memory");
}
__device__ __forceinline__ void mbar_arrive(uint32_t bar) {
    asm volatile("mbarrier.arrive.shared::cta.b64 _, [%0];" ::"r"(bar) : "memory");
}
__device__ __forceinline__ bool mbar_try(uint32_t bar, uint32_t parity) {
    uint32_t ok;
    asm volatile(
        "{\n\t.reg .pred p;\n\t"
        "mbarrier.try_wait.parity.shared::cta.b64 p, [%1], %2;\n\t"
        "selp.u32 %0, 1, 0, p;\n\t}"
        : "=r"(ok) : "r"(bar), "r"(parity) : "memory");
    return ok != 0;
}
__device__ __forceinline__ void mbar_wait(uint32_t bar, uint32_t parity) {
    if (mbar_try(bar, parity)) return;
    for (int i = 0; i < SPIN_LIMIT; i++)
        if (mbar_try(bar, parity)) return;
}
__device__ __forceinline__ void cons_sync() { asm volatile("bar.sync 1, 256;" ::: "memory"); }

__device__ __forceinline__ void tma_2d(uint32_t dst, const CUtensorMap* m, int c0, int c1, uint32_t bar) {
    asm volatile("cp.async.bulk.tensor.2d.shared::cluster.global.mbarrier::complete_tx::bytes [%0], [%1, {%3, %4}], [%2];"
                 ::"r"(dst), "l"(m), "r"(bar), "r"(c0), "r"(c1) : "memory");
}
__device__ __forceinline__ void tma_3d(uint32_t dst, const CUtensorMap* m, int c0, int c1, int c2, uint32_t bar) {
    asm volatile("cp.async.bulk.tensor.3d.shared::cluster.global.mbarrier::complete_tx::bytes [%0], [%1, {%3, %4, %5}], [%2];"
                 ::"r"(dst), "l"(m), "r"(bar), "r"(c0), "r"(c1), "r"(c2) : "memory");
}
__device__ __forceinline__ void tma_3d_hint(uint32_t dst, const CUtensorMap* m, int c0, int c1, int c2, uint32_t bar, uint64_t pol) {
    asm volatile("cp.async.bulk.tensor.3d.shared::cluster.global.mbarrier::complete_tx::bytes.L2::cache_hint [%0], [%1, {%3, %4, %5}], [%2], %6;"
                 ::"r"(dst), "l"(m), "r"(bar), "r"(c0), "r"(c1), "r"(c2), "l"(pol) : "memory");
}
__device__ __forceinline__ void prefetch_tmap(const CUtensorMap* m) {
    asm volatile("prefetch.tensormap [%0];" ::"l"(m) : "memory");
}

__device__ __forceinline__ void ldsm4(uint32_t addr, uint32_t (&r)[4]) {
    asm volatile("ldmatrix.sync.aligned.m8n8.x4.shared.b16 {%0,%1,%2,%3}, [%4];"
                 : "=r"(r[0]), "=r"(r[1]), "=r"(r[2]), "=r"(r[3]) : "r"(addr) : "memory");
}
__device__ __forceinline__ void ldsm4t(uint32_t addr, uint32_t (&r)[4]) {
    asm volatile("ldmatrix.sync.aligned.m8n8.x4.trans.shared.b16 {%0,%1,%2,%3}, [%4];"
                 : "=r"(r[0]), "=r"(r[1]), "=r"(r[2]), "=r"(r[3]) : "r"(addr) : "memory");
}
__device__ __forceinline__ void mma16816(float (&c)[4], const uint32_t (&a)[4], uint32_t b0, uint32_t b1) {
    asm volatile("mma.sync.aligned.m16n8k16.row.col.f32.bf16.bf16.f32 {%0,%1,%2,%3}, {%4,%5,%6,%7}, {%8,%9}, {%0,%1,%2,%3};"
                 : "+f"(c[0]), "+f"(c[1]), "+f"(c[2]), "+f"(c[3])
                 : "r"(a[0]), "r"(a[1]), "r"(a[2]), "r"(a[3]), "r"(b0), "r"(b1));
}
__device__ __forceinline__ uint32_t movmatrix_t(uint32_t a) {
    uint32_t d;
    asm volatile("movmatrix.sync.aligned.m8n8.trans.b16 %0, %1;" : "=r"(d) : "r"(a));
    return d;
}
__device__ __forceinline__ uint32_t pack_bf16(float a, float b) {
    uint32_t r;
    asm("cvt.rn.bf16x2.f32 %0, %1, %2;" : "=r"(r) : "f"(b), "f"(a));
    return r;
}
__device__ __forceinline__ float bf_lo(uint32_t v) { return __uint_as_float(v << 16); }
__device__ __forceinline__ float bf_hi(uint32_t v) { return __uint_as_float(v & 0xffff0000u); }
__device__ __forceinline__ float bf16r(float a) { return bf_lo(pack_bf16(a, 0.f)); }
__device__ __forceinline__ uint32_t max_bf16x2(uint32_t a, uint32_t b) {
    uint32_t r;
    asm("max.bf16x2 %0, %1, %2;" : "=r"(r) : "r"(a), "r"(b));
    return r;
}
__device__ __forceinline__ float ex2(float x) {
    float r;
    asm("ex2.approx.ftz.f32 %0, %1;" : "=f"(r) : "f"(x));
    return r;
}

__device__ __forceinline__ void st_ll2(uint2* p, uint32_t v, uint32_t tag) {
    asm volatile("st.relaxed.gpu.global.v2.u32 [%0], {%1, %2};" ::"l"(p), "r"(v), "r"(tag) : "memory");
}
__device__ __forceinline__ void st_ll4(uint4* p, uint32_t v0, uint32_t v1, uint32_t tag) {
    asm volatile("st.relaxed.gpu.global.v4.u32 [%0], {%1, %2, %3, %2};" ::"l"(p), "r"(v0), "r"(tag), "r"(v1) : "memory");
}
__device__ __forceinline__ uint2 ld_ll2(const uint2* p) {
    uint2 v;
    asm volatile("ld.relaxed.gpu.global.v2.u32 {%0, %1}, [%2];" : "=r"(v.x), "=r"(v.y) : "l"(p) : "memory");
    return v;
}
__device__ __forceinline__ uint4 ld_ll4(const uint4* p) {
    uint4 v;
    asm volatile("ld.relaxed.gpu.global.v4.u32 {%0, %1, %2, %3}, [%4];"
                 : "=r"(v.x), "=r"(v.y), "=r"(v.z), "=r"(v.w) : "l"(p) : "memory");
    return v;
}

__device__ __forceinline__ float silu_bf(float v) { return bf16r(v / (1.0f + expf(-v))); }

__device__ __forceinline__ float2 half_warp_sums(const float (&v)[4], float pivot) {
    float s1 = 0.f, s2 = 0.f;
#pragma unroll
    for (int i = 0; i < 4; i++) { const float d = v[i] - pivot; s1 += d; s2 += d * d; }
#pragma unroll
    for (int o = 1; o < 16; o <<= 1) { s1 += __shfl_xor_sync(0xffffffffu, s1, o); s2 += __shfl_xor_sync(0xffffffffu, s2, o); }
    return make_float2(s1, s2);
}
__device__ __forceinline__ void ln_stats(const float2* stat, int b, float pivot, float& mean_bf, float& rstd) {
    float s1 = 0.f, s2 = 0.f;
#pragma unroll
    for (int w = 0; w < 8; w++) { const float2 v = stat[w * 2 + b]; s1 += v.x; s2 += v.y; }
    const float dm = s1 * (1.0f / D_MODEL);
    const float var = fmaxf(s2 * (1.0f / D_MODEL) - dm * dm, 0.f);
    mean_bf = bf16r(pivot + dm);
    rstd = 1.0f / bf16r(sqrtf(bf16r(bf16r(var) + 1e-5f)));
}
__device__ __forceinline__ float ln_norm(float xv, float mean_bf, float rstd) { return bf16r(bf16r(xv - mean_bf) * rstd); }
__device__ __forceinline__ float ln_mod(float n, float cmul, float sadd) { return bf16r(n * bf16r(1.0f + cmul)) + sadd; }

__global__ void __launch_bounds__(NTHREADS, 1)
fused_block_kernel(const __grid_constant__ CUtensorMap tm_k, const __grid_constant__ CUtensorMap tm_v,
                   const __grid_constant__ CUtensorMap tm_wq, const __grid_constant__ CUtensorMap tm_wmod,
                   const __grid_constant__ CUtensorMap tm_wo, const __grid_constant__ CUtensorMap tm_wg,
                   const __grid_constant__ CUtensorMap tm_wu, const __grid_constant__ CUtensorMap tm_wd,
                   const Params p) {
    extern __shared__ unsigned char smem_raw[];
    const uint32_t sbase = (smem_u32(smem_raw) + 1023u) & ~1023u;
    unsigned char* sgen = smem_raw + (sbase - smem_u32(smem_raw));
    const int tid = threadIdx.x, warp = tid >> 5, lane = tid & 31;
    const int cta = blockIdx.x;
    const uint32_t bar_full = sbase + SM_BAR, bar_empty = bar_full + NST * 8;
    const uint32_t bar_p0 = bar_empty + NST * 8;

    if (warp == 8) {
        if (lane == 0) {
            prefetch_tmap(&tm_wq);
            for (int i = 0; i < NST; i++) { mbar_init(bar_full + 8 * i, 1); mbar_init(bar_empty + 8 * i, 4); }
            mbar_init(bar_p0, 8);
            asm volatile("fence.mbarrier_init.release.cluster;" ::: "memory");
        }
        __syncwarp();
        asm volatile("bar.arrive 2, 288;" ::: "memory");
        if (lane == 0) {
            const int pair = cta >> 3, j = cta & 7;
            const int key0 = pair * SK + j * 64;
            const int n_tiles = cta < NFFN ? IDX_WD + 1 : IDX_WG;
            uint64_t pol;
            asm volatile("createpolicy.fractional.L2::evict_first.b64 %0, 1.0;" : "=l"(pol));
            int slot = 0; uint32_t ph = 1;
            int landed = 0, wslot = 0; uint32_t wph = 0;
            for (int idx = 0; idx < n_tiles; idx++) {
                if (idx >= NST) mbar_wait(bar_empty + 8 * slot, ph);
                const int window = idx < PRO_TILES ? INFL_PRO : idx >= IDX_WG ? INFL_TAIL : INFL_MAIN;
                while (landed + window <= idx) {
                    mbar_wait(bar_full + 8 * wslot, wph);
                    if (++wslot == NST) { wslot = 0; wph ^= 1; }
                    landed++;
                }
                const uint32_t fb = bar_full + 8 * slot, dst = sbase + SM_RING + slot * TILE;
                if (idx == 2) {
                    prefetch_tmap(&tm_wmod); prefetch_tmap(&tm_k); prefetch_tmap(&tm_v);
                    mbar_wait(bar_p0, 0);
                }
                mbar_expect_tx(fb, TILE);
                if (idx < 2) {
                    tma_2d(dst, &tm_wq, cta * 32, idx * 256, fb);
                } else if (idx == 2) {
                    tma_2d(dst, &tm_wmod, 1024 + cta * 16, 0, fb);
                    tma_2d(dst + 8192, &tm_wmod, 1024 + cta * 16, 256, fb);
                } else if (idx < IDX_WO) {
                    const int i = (idx - IDX_KV0) >> 1;
                    tma_3d_hint(dst, ((idx - IDX_KV0) & 1) ? &tm_v : &tm_k, 0, key0 + i * 512, 0, fb, pol);
                    if (idx == 16) { prefetch_tmap(&tm_wo); prefetch_tmap(&tm_wg); prefetch_tmap(&tm_wu); prefetch_tmap(&tm_wd); }
                } else if (idx < IDX_WO + 2) {
                    tma_3d(dst, &tm_wo, 0, cta * 32 + (idx - IDX_WO) * 16, 0, fb);
                } else if (idx < IDX_WG) {
                    const int i = (idx - IDX_KV0 - 2) >> 1;
                    tma_3d_hint(dst, ((idx - IDX_KV0) & 1) ? &tm_v : &tm_k, 0, key0 + i * 512, 0, fb, pol);
                } else if (idx < IDX_WD) {
                    const CUtensorMap* m = idx == IDX_WG ? &tm_wg : &tm_wu;
                    tma_2d(dst, m, cta * 16, 0, fb);
                    tma_2d(dst + 8192, m, cta * 16, 256, fb);
                } else {
                    tma_3d(dst, &tm_wd, 0, cta * 16, 0, fb);
                }
                if (++slot == NST) { slot = 0; ph ^= 1; }
            }
        }
    } else {
        const int g = lane >> 2, t = lane & 3;
        const int bb = g & 1;
        const int eb = lane >> 4;
        const int ec = 64 * warp + 4 * (lane & 15);
        if (warp == 0) TSTAMP(0);
        const uint4 w0 = __ldg((const uint4*)(p.w_mod + (size_t)tid * N_MOD + cta * 8));
        const uint4 w1 = __ldg((const uint4*)(p.w_mod + (size_t)(tid + 256) * N_MOD + cta * 8));
        const float c00 = __bfloat162float(p.c[tid]), c01 = __bfloat162float(p.c[tid + 256]);
        const float c10 = __bfloat162float(p.c[D_MODEL + tid]), c11 = __bfloat162float(p.c[D_MODEL + tid + 256]);
        const uint2 xe = __ldg((const uint2*)(p.x + eb * D_MODEL + ec));
        const float xpivot = __bfloat162float(p.x[eb * D_MODEL]);
        const uint32_t tag = *(volatile unsigned*)&g_epoch + 1;
        const int ocol = cta * 4 + (lane & 3);
        const float xo0 = __bfloat162float(p.x[ocol]), xo1 = __bfloat162float(p.x[D_MODEL + ocol]);

        st_ll4(&g_inbox[cta][0][0] + tid, 0u, 0u, 0u);
        st_ll4(&g_inbox[cta][0][0] + 256 + tid, 0u, 0u, 0u);
        st_ll4(&g_part_o[cta][0][0] + tid, 0u, 0u, 0u);
        if (tid < 8) st_ll4(&g_part_ml[cta][0][0] + tid, 0u, 0u, 0u);

        float* red = (float*)(sgen + SM_RED);
        float* red2 = (float*)(sgen + SM_RED2);
        float2* stat = (float2*)(sgen + SM_STAT);
        uint32_t* hs = (uint32_t*)(sgen + SM_HS) + warp * 64;
        float xn[4];
        {
            float xv[4] = {bf_lo(xe.x), bf_hi(xe.x), bf_lo(xe.y), bf_hi(xe.y)};
            const float2 ps = half_warp_sums(xv, xpivot);
            if ((lane & 15) == 0) stat[warp * 2 + eb] = ps;
            const float s00 = silu_bf(c00), s01 = silu_bf(c01), s10 = silu_bf(c10), s11 = silu_bf(c11);
            __nv_bfloat16* sc = (__nv_bfloat16*)(sgen + SM_SC);
            sc[tid] = __float2bfloat16_rn(s00); sc[tid + 256] = __float2bfloat16_rn(s01);
            sc[512 + tid] = __float2bfloat16_rn(s10); sc[512 + tid + 256] = __float2bfloat16_rn(s11);
            const uint32_t a[4] = {w0.x, w0.y, w0.z, w0.w}, b[4] = {w1.x, w1.y, w1.z, w1.w};
            float v[16];
#pragma unroll
            for (int i = 0; i < 4; i++) {
                v[2 * i] = s00 * bf_lo(a[i]) + s01 * bf_lo(b[i]);
                v[2 * i + 1] = s00 * bf_hi(a[i]) + s01 * bf_hi(b[i]);
                v[8 + 2 * i] = s10 * bf_lo(a[i]) + s11 * bf_lo(b[i]);
                v[8 + 2 * i + 1] = s10 * bf_hi(a[i]) + s11 * bf_hi(b[i]);
            }
#define XRED(N, O)                                                                       \
            {                                                                            \
                const bool up = lane & (O);                                              \
                _Pragma("unroll") for (int i = 0; i < (N); i++) {                        \
                    const float send = up ? v[i] : v[i + (N)], keep = up ? v[i + (N)] : v[i]; \
                    v[i] = keep + __shfl_xor_sync(0xffffffffu, send, (O));               \
                }                                                                        \
            }
            XRED(8, 16) XRED(4, 8) XRED(2, 4) XRED(1, 2)
#undef XRED
            v[0] += __shfl_xor_sync(0xffffffffu, v[0], 1);
            if (!(lane & 1)) red[warp * 16 + (lane >> 1)] = v[0];
            if (warp == 0) TSTAMP(14);
            asm volatile("fence.acq_rel.gpu;" ::: "memory");
            asm volatile("bar.sync 2, 288;" ::: "memory");
            if (lane == 0) mbar_arrive(bar_p0);
            if (warp == 0) {
                float s = 0.f;
#pragma unroll
                for (int w = 0; w < 8; w++) s += red[w * 16 + (lane & 15)];
                const float nx = __shfl_down_sync(0xffffffffu, s, 1);
                if (lane < 16 && !(lane & 1))
                    st_ll2(&g_mod[lane >> 3][cta * 4 + ((lane & 7) >> 1)], pack_bf16(s, nx), tag);
                TSTAMP(1);
            }
            float mean_bf, rstd;
            ln_stats(stat, eb, xpivot, mean_bf, rstd);
#pragma unroll
            for (int i = 0; i < 4; i++) xn[i] = ln_norm(xv[i], mean_bf, rstd);
        }
        {
            uint4 sa, ca;
            for (int it = 0;; it++) {
                sa = ld_ll4((const uint4*)&g_mod[eb][ec >> 1]);
                ca = ld_ll4((const uint4*)&g_mod[eb][256 + (ec >> 1)]);
                const bool ok = sa.y == tag && sa.w == tag && ca.y == tag && ca.w == tag;
                if (__all_sync(0xffffffffu, ok) || it > SPIN_LIMIT) break;
            }
            *(uint2*)&hs[eb * 32 + 2 * (lane & 15)] =
                make_uint2(pack_bf16(ln_mod(xn[0], bf_lo(ca.x), bf_lo(sa.x)), ln_mod(xn[1], bf_hi(ca.x), bf_hi(sa.x))),
                           pack_bf16(ln_mod(xn[2], bf_lo(ca.z), bf_lo(sa.z)), ln_mod(xn[3], bf_hi(ca.z), bf_hi(sa.z))));
            __syncwarp();
            uint32_t hb[8];
#pragma unroll
            for (int i = 0; i < 8; i++) hb[i] = hs[bb * 32 + 8 * (i >> 1) + 4 * (i & 1) + t];
            if (warp == 0) TSTAMP(2);
            float cq[2][4] = {};
            const int ts = warp >> 2;
            mbar_wait(bar_full + 8 * ts, 0);
            const uint32_t tb = sbase + SM_RING + ts * TILE;
#pragma unroll
            for (int s = 0; s < 4; s++) {
                const int row = 64 * (warp & 3) + 16 * s + (lane & 7) + (lane >> 4) * 8;
#pragma unroll
                for (int mt = 0; mt < 2; mt++) {
                    const int ch = 2 * mt + ((lane >> 3) & 1);
                    uint32_t a[4];
                    ldsm4t(tb + row * 64 + ((ch ^ ((row >> 1) & 3)) << 4), a);
                    mma16816(cq[mt], a, hb[2 * s], hb[2 * s + 1]);
                }
            }
            if (t < 2) {
                const float v0 = t == 0 ? cq[0][0] : cq[1][0], v1 = t == 0 ? cq[0][1] : cq[1][1];
                const float v2 = t == 0 ? cq[0][2] : cq[1][2], v3 = t == 0 ? cq[0][3] : cq[1][3];
                *(float2*)&red2[warp * 64 + (16 * t + g) * 2] = make_float2(v0, v1);
                *(float2*)&red2[warp * 64 + (16 * t + g + 8) * 2] = make_float2(v2, v3);
            }
            cons_sync();
            if (warp < 4 && lane == 0) { mbar_arrive(bar_empty + 0); mbar_arrive(bar_empty + 8); }
            if (warp == 0) {
                const int b = lane >> 4, cp = lane & 15;
                float q0 = 0.f, q1 = 0.f;
#pragma unroll
                for (int w = 0; w < 8; w++) {
                    const float4 v = *(const float4*)&red2[w * 64 + cp * 4];
                    q0 += b ? v.y : v.x; q1 += b ? v.w : v.z;
                }
                st_ll2(&g_q[b][cta * 16 + cp], pack_bf16(q0, q1), tag);
                TSTAMP(3);
            }
        }
        {
            float cm[4] = {};
            const uint32_t* sc32 = (const uint32_t*)(sgen + SM_SC) + bb * 256 + 32 * warp + t;
            mbar_wait(bar_full + 8 * 2, 0);
            const uint32_t tb = sbase + SM_RING + 2 * TILE;
#pragma unroll
            for (int s = 0; s < 4; s++) {
                const int row = 64 * warp + 16 * s + (lane & 7) + (lane >> 4) * 8;
                const int ch = (lane >> 3) & 1;
                uint32_t a[4];
                ldsm4t(tb + row * 32 + ((ch ^ ((row >> 2) & 1)) << 4), a);
                mma16816(cm, a, sc32[8 * s], sc32[8 * s + 4]);
            }
            if (t == 0) {
                *(float2*)&red[warp * 64 + g * 2] = make_float2(cm[0], cm[1]);
                *(float2*)&red[warp * 64 + (g + 8) * 2] = make_float2(cm[2], cm[3]);
            }
            cons_sync();
            if (warp < 4 && lane == 0) mbar_arrive(bar_empty + 16);
            if (warp == 1 && lane < 16) {
                const int b = lane >> 3, cp = lane & 7;
                float q0 = 0.f, q1 = 0.f;
#pragma unroll
                for (int w = 0; w < 8; w++) {
                    const float4 v = *(const float4*)&red[w * 64 + cp * 4];
                    q0 += b ? v.y : v.x; q1 += b ? v.w : v.z;
                }
                st_ll2(&g_mod[b][512 + cta * 8 + cp], pack_bf16(q0, q1), tag);
            }
        }
        const int pair = cta >> 3;
        uint32_t qf[16];
        {
            uint2* qs = (uint2*)(sgen + SM_QS);
            if (tid < 128) {
                const uint4* src = (const uint4*)&g_q[pair >> 3][(pair & 7) * 256] + tid;
                uint4 v;
                for (int it = 0;; it++) {
                    v = ld_ll4(src);
                    if ((v.y == tag && v.w == tag) || it > SPIN_LIMIT) break;
                }
                qs[tid] = make_uint2(v.x, v.z);
            }
            cons_sync();
            const uint32_t* q32 = (const uint32_t*)(sgen + SM_QS);
#pragma unroll
            for (int s = 0; s < 8; s++) {
                qf[2 * s] = q32[(g & 3) * 64 + 8 * s + t];
                qf[2 * s + 1] = q32[(g & 3) * 64 + 8 * s + 4 + t];
            }
        }
        asm volatile("fence.acq_rel.gpu;" ::: "memory");
        if (warp == 0) TSTAMP(4);

        float o[8][4];
#pragma unroll
        for (int i = 0; i < 8; i++) { o[i][0] = o[i][1] = o[i][2] = o[i][3] = 0.f; }
        uint32_t mrun = 0xff80ff80u;
        float ls[4] = {0.f, 0.f, 0.f, 0.f};
        uint4 m_sb, m_cb; uint2 m_ga0, m_ga1, m_gb0, m_gb1;
        {
            const int grp = warp >> 2, wi = warp & 3;
            const int krow = 16 * wi + (lane & 7) + ((lane >> 3) & 1) * 8;
            const uint32_t koff = krow * 128 + ((((lane >> 4) & 1) ^ (lane & 7)) << 4);
            const int vrow = 16 * wi + (lane & 7) + (lane >> 4) * 8;
            const uint32_t voff = vrow * 128 + ((((lane >> 3) & 1) ^ (lane & 7)) << 4);
            const uint32_t ones[4] = {0x3f803f80u, 0x3f803f80u, 0x3f803f80u, 0x3f803f80u};
            int ks = IDX_KV0 + 2 * grp, vs = ks + 1;
            uint32_t kph = 0, vph = 0;
            for (int i = grp; i < KV_TILES; i += 2) {
                if (i == 56 + grp) {
                    m_sb = ld_ll4((const uint4*)&g_mod[eb][768 + (ec >> 1)]);
                    m_cb = ld_ll4((const uint4*)&g_mod[eb][1024 + (ec >> 1)]);
                    m_ga0 = ld_ll2(&g_mod[0][512 + (ocol >> 1)]); m_ga1 = ld_ll2(&g_mod[1][512 + (ocol >> 1)]);
                    m_gb0 = ld_ll2(&g_mod[0][1280 + (ocol >> 1)]); m_gb1 = ld_ll2(&g_mod[1][1280 + (ocol >> 1)]);
                }
                mbar_wait(bar_full + 8 * ks, kph);
                const uint32_t kb = sbase + SM_RING + ks * TILE + koff;
                float sa[4] = {0.f, 0.f, 0.f, 0.f}, sb[4] = {0.f, 0.f, 0.f, 0.f};
#pragma unroll
                for (int s = 0; s < 8; s += 2) {
                    uint32_t a0[4], a1[4];
                    ldsm4((kb ^ ((s & 3) << 5)) + (s >> 2) * 8192, a0);
                    ldsm4((kb ^ (((s + 1) & 3) << 5)) + (s >> 2) * 8192, a1);
                    mma16816(sa, a0, qf[2 * s], qf[2 * s + 1]);
                    mma16816(sb, a1, qf[2 * s + 2], qf[2 * s + 3]);
                }
                __syncwarp();
                if (lane == 0) mbar_arrive(bar_empty + 8 * ks);
                uint32_t r01 = pack_bf16(sa[0] + sb[0], sa[1] + sb[1]);
                uint32_t r23 = pack_bf16(sa[2] + sb[2], sa[3] + sb[3]);
                r01 = pack_bf16(bf_lo(r01) * QK_SCALE, bf_hi(r01) * QK_SCALE);
                r23 = pack_bf16(bf_lo(r23) * QK_SCALE, bf_hi(r23) * QK_SCALE);
                uint32_t mx = max_bf16x2(r01, r23);
                mx = max_bf16x2(mx, __shfl_xor_sync(0xffffffffu, mx, 4));
                mx = max_bf16x2(mx, __shfl_xor_sync(0xffffffffu, mx, 8));
                mx = max_bf16x2(mx, __shfl_xor_sync(0xffffffffu, mx, 16));
                const uint32_t mnew = max_bf16x2(mrun, mx);
                const float m0 = bf_lo(mnew), m1 = bf_hi(mnew);
                if (__any_sync(0xffffffffu, mnew != mrun)) {
                    const float al0 = ex2((bf_lo(mrun) - m0) * LOG2E), al1 = ex2((bf_hi(mrun) - m1) * LOG2E);
                    ls[0] *= al0; ls[1] *= al1;
#pragma unroll
                    for (int d = 0; d < 8; d++) { o[d][0] *= al0; o[d][1] *= al1; o[d][2] *= al0; o[d][3] *= al1; }
                    mrun = mnew;
                }
                const float p0 = ex2((bf_lo(r01) - m0) * LOG2E), p1 = ex2((bf_hi(r01) - m1) * LOG2E);
                const float p2 = ex2((bf_lo(r23) - m0) * LOG2E), p3 = ex2((bf_hi(r23) - m1) * LOG2E);
                const uint32_t pb0 = movmatrix_t(pack_bf16(p0, p1)), pb1 = movmatrix_t(pack_bf16(p2, p3));
                mma16816(ls, ones, pb0, pb1);
                mbar_wait(bar_full + 8 * vs, vph);
                const uint32_t vb = sbase + SM_RING + vs * TILE + voff;
#pragma unroll
                for (int d = 0; d < 8; d++) {
                    uint32_t a[4];
                    ldsm4t((vb ^ ((d & 3) << 5)) + (d >> 2) * 8192, a);
                    mma16816(o[d], a, pb0, pb1);
                }
                __syncwarp();
                if (lane == 0) mbar_arrive(bar_empty + 8 * vs);
                const int adv = (i < WO_AT && i + 2 >= WO_AT) ? 6 : 4;
                ks += adv; if (ks >= NST) { ks -= NST; kph ^= 1; }
                vs += adv; if (vs >= NST) { vs -= NST; vph ^= 1; }
            }
        }
        if (warp == 7) TSTAMP(5);
        {
            float* mrg = (float*)(sgen + SM_MRG);
            float2* ml = (float2*)(sgen + SM_ML);
            if (t < 2) {
                if (g == 0) { ml[warp * 4 + 2 * t] = make_float2(bf_lo(mrun), ls[0]); ml[warp * 4 + 2 * t + 1] = make_float2(bf_hi(mrun), ls[1]); }
                float* m0p = mrg + (warp * 4 + 2 * t) * 136 + g;
#pragma unroll
                for (int d = 0; d < 8; d++) {
                    m0p[16 * d] = o[d][0]; m0p[136 + 16 * d] = o[d][1];
                    m0p[16 * d + 8] = o[d][2]; m0p[136 + 16 * d + 8] = o[d][3];
                }
            }
            cons_sync();
            const int hh = tid >> 6, dp = tid & 63;
            float2 mw[8];
            float M = -INFINITY;
#pragma unroll
            for (int w = 0; w < 8; w++) { mw[w] = ml[w * 4 + hh]; M = fmaxf(M, mw[w].x); }
            float L = 0.f, o0 = 0.f, o1 = 0.f;
#pragma unroll
            for (int w = 0; w < 8; w++) {
                const float wt = ex2((mw[w].x - M) * LOG2E);
                const float2 v = *(const float2*)&mrg[(w * 4 + hh) * 136 + 2 * dp];
                L += wt * mw[w].y; o0 += wt * v.x; o1 += wt * v.y;
            }
            st_ll4(&g_part_o[cta][hh][dp], __float_as_uint(o0), __float_as_uint(o1), F_PART);
            if (dp < 2) st_ll4(&g_part_ml[cta][hh][dp], __float_as_uint(M), __float_as_uint(L), F_PART);
        }
        if (warp == 0) TSTAMP(6);
        const uint32_t aoff = warp * 2048 + ((lane & 7) + (lane >> 4) * 8) * 128 + ((((lane >> 3) & 1) ^ (lane & 7)) << 4);
        uint32_t wf[8][4];
#pragma unroll
        for (int s = 0; s < 2; s++) {
            constexpr int i0 = IDX_WO;
            const int idx = i0 + s;
            mbar_wait(bar_full + 8 * (idx % NST), (idx / NST) & 1);
            const uint32_t tb = sbase + SM_RING + (idx % NST) * TILE + aoff;
#pragma unroll
            for (int mt = 0; mt < 4; mt++) ldsm4t(tb ^ (mt << 5), wf[s * 4 + mt]);
        }
        {
            const int hq = cta >> 2, kvh = hq >> 2, hh = hq & 3, ds = cta & 3;
            const int b = tid >> 7, dpl = (tid >> 3) & 15, j = tid & 7;
            const int pc = (b * 8 + kvh) * 8 + j;
            uint4 vo, vm;
            for (int it = 0;; it++) {
                vo = ld_ll4(&g_part_o[pc][hh][ds * 16 + dpl]);
                vm = ld_ll4(&g_part_ml[pc][hh][0]);
                const bool ok = vo.y == F_PART && vo.w == F_PART && vm.y == F_PART && vm.w == F_PART;
                if (__all_sync(0xffffffffu, ok) || it > SPIN_LIMIT) break;
            }
            const float m = __uint_as_float(vm.x);
            float M = m;
            M = fmaxf(M, __shfl_xor_sync(0xffffffffu, M, 1));
            M = fmaxf(M, __shfl_xor_sync(0xffffffffu, M, 2));
            M = fmaxf(M, __shfl_xor_sync(0xffffffffu, M, 4));
            const float wt = ex2((m - M) * LOG2E);
            float L = wt * __uint_as_float(vm.z), o0 = wt * __uint_as_float(vo.x), o1 = wt * __uint_as_float(vo.z);
#pragma unroll
            for (int o_ = 1; o_ < 8; o_ <<= 1) {
                L += __shfl_xor_sync(0xffffffffu, L, o_);
                o0 += __shfl_xor_sync(0xffffffffu, o0, o_);
                o1 += __shfl_xor_sync(0xffffffffu, o1, o_);
            }
            uint32_t* os = (uint32_t*)(sgen + SM_OS);
            const float rl = 1.0f / L;
            if (j == 0) os[b * 16 + dpl] = pack_bf16(o0 * rl, o1 * rl);
            cons_sync();
            if (warp == 0) TSTAMP(7);
            float y[4][4] = {};
#pragma unroll
            for (int s = 0; s < 2; s++) {
                const uint32_t b0 = os[bb * 16 + 8 * s + t], b1 = os[bb * 16 + 8 * s + 4 + t];
#pragma unroll
                for (int mt = 0; mt < 4; mt++) mma16816(y[mt], wf[s * 4 + mt], b0, b1);
            }
            float v[4];
#pragma unroll
            for (int i = 0; i < 4; i++) v[i] = t == 0 ? y[0][i] : t == 1 ? y[1][i] : t == 2 ? y[2][i] : y[3][i];
            const int col = 64 * warp + 16 * t + g;
            st_ll4(&g_inbox[col >> 2][cta][col & 3], __float_as_uint(v[0]), __float_as_uint(v[1]), F_WO);
            st_ll4(&g_inbox[(col + 8) >> 2][cta][col & 3], __float_as_uint(v[2]), __float_as_uint(v[3]), F_WO);
        }
        if (warp == 0) TSTAMP(8);
        for (int it = 0;; it++) {
            const bool ok = m_sb.y == tag && m_sb.w == tag && m_cb.y == tag && m_cb.w == tag &&
                            m_ga0.y == tag && m_ga1.y == tag && m_gb0.y == tag && m_gb1.y == tag;
            if (__all_sync(0xffffffffu, ok) || it > SPIN_LIMIT) break;
            m_sb = ld_ll4((const uint4*)&g_mod[eb][768 + (ec >> 1)]);
            m_cb = ld_ll4((const uint4*)&g_mod[eb][1024 + (ec >> 1)]);
            m_ga0 = ld_ll2(&g_mod[0][512 + (ocol >> 1)]); m_ga1 = ld_ll2(&g_mod[1][512 + (ocol >> 1)]);
            m_gb0 = ld_ll2(&g_mod[0][1280 + (ocol >> 1)]); m_gb1 = ld_ll2(&g_mod[1][1280 + (ocol >> 1)]);
        }
        float xm0 = 0.f, xm1 = 0.f;
        {
            float s0, s1;
            for (int it = 0;; it++) {
                const uint4 v0 = ld_ll4(&g_inbox[cta][0][0] + tid), v1 = ld_ll4(&g_inbox[cta][0][0] + 256 + tid);
                s0 = __uint_as_float(v0.x) + __uint_as_float(v1.x);
                s1 = __uint_as_float(v0.z) + __uint_as_float(v1.z);
                const bool ok = v0.y == F_WO && v0.w == F_WO && v1.y == F_WO && v1.w == F_WO;
                if (__all_sync(0xffffffffu, ok) || it > SPIN_LIMIT) break;
            }
#pragma unroll
            for (int o_ = 4; o_ < 32; o_ <<= 1) { s0 += __shfl_xor_sync(0xffffffffu, s0, o_); s1 += __shfl_xor_sync(0xffffffffu, s1, o_); }
            if (lane < 4) *(float2*)&red2[warp * 8 + lane * 2] = make_float2(s0, s1);
            cons_sync();
            if (warp == 0) {
                float a0 = 0.f, a1 = 0.f;
#pragma unroll
                for (int w = 0; w < 8; w++) { const float2 v = *(const float2*)&red2[w * 8 + (lane & 3) * 2]; a0 += v.x; a1 += v.y; }
                const bool hi = ocol & 1;
                const float ga0 = hi ? bf_hi(m_ga0.x) : bf_lo(m_ga0.x), ga1 = hi ? bf_hi(m_ga1.x) : bf_lo(m_ga1.x);
                xm0 = bf16r(xo0 + bf16r(ga0 * bf16r(a0)));
                xm1 = bf16r(xo1 + bf16r(ga1 * bf16r(a1)));
                if (lane < 4) st_ll2((uint2*)&g_inbox[cta][NCTA - 1][0] + lane, pack_bf16(xm0, xm1), F_X1);
                TSTAMP(10);
            }
        }
        if (cta < NFFN) {
            uint32_t gf[4][4], uf[4][4];
            mbar_wait(bar_full + 8 * (IDX_WG % NST), (IDX_WG / NST) & 1);
            mbar_wait(bar_full + 8 * (IDX_WU % NST), (IDX_WU / NST) & 1);
            {
                const uint32_t tg = sbase + SM_RING + (IDX_WG % NST) * TILE, tu = sbase + SM_RING + (IDX_WU % NST) * TILE;
#pragma unroll
                for (int s = 0; s < 4; s++) {
                    const int row = 64 * warp + 16 * s + (lane & 7) + (lane >> 4) * 8;
                    const uint32_t off = row * 32 + ((((lane >> 3) & 1) ^ ((row >> 2) & 1)) << 4);
                    ldsm4t(tg + off, gf[s]);
                    ldsm4t(tu + off, uf[s]);
                }
            }
            if (warp == 0) TSTAMP(11);
            uint32_t hb[8];
            {
                uint4 v0, v1; uint2 pv;
                for (int it = 0;; it++) {
                    v0 = ld_ll4(&g_inbox[ec >> 2][NCTA - 1][0]); v1 = ld_ll4(&g_inbox[ec >> 2][NCTA - 1][1]);
                    pv = ld_ll2((const uint2*)&g_inbox[0][NCTA - 1][0]);
                    const bool ok = v0.y == F_X1 && v0.w == F_X1 && v1.y == F_X1 && v1.w == F_X1 && pv.y == F_X1;
                    if (__all_sync(0xffffffffu, ok) || it > SPIN_LIMIT) break;
                }
                if (warp == 0) TSTAMP(9);
                const float xv[4] = {eb ? bf_hi(v0.x) : bf_lo(v0.x), eb ? bf_hi(v0.z) : bf_lo(v0.z),
                                     eb ? bf_hi(v1.x) : bf_lo(v1.x), eb ? bf_hi(v1.z) : bf_lo(v1.z)};
                const float pivot = eb ? bf_hi(pv.x) : bf_lo(pv.x);
                const float2 ps = half_warp_sums(xv, pivot);
                if ((lane & 15) == 0) stat[warp * 2 + eb] = ps;
                cons_sync();
                float mean_bf, rstd;
                ln_stats(stat, eb, pivot, mean_bf, rstd);
                *(uint2*)&hs[eb * 32 + 2 * (lane & 15)] = make_uint2(
                    pack_bf16(ln_mod(ln_norm(xv[0], mean_bf, rstd), bf_lo(m_cb.x), bf_lo(m_sb.x)),
                              ln_mod(ln_norm(xv[1], mean_bf, rstd), bf_hi(m_cb.x), bf_hi(m_sb.x))),
                    pack_bf16(ln_mod(ln_norm(xv[2], mean_bf, rstd), bf_lo(m_cb.z), bf_lo(m_sb.z)),
                              ln_mod(ln_norm(xv[3], mean_bf, rstd), bf_hi(m_cb.z), bf_hi(m_sb.z))));
                __syncwarp();
#pragma unroll
                for (int i = 0; i < 8; i++) hb[i] = hs[bb * 32 + 8 * (i >> 1) + 4 * (i & 1) + t];
            }
            {
                float cg[2][4] = {}, cu[2][4] = {};
#pragma unroll
                for (int s = 0; s < 4; s++) {
                    mma16816(cg[s & 1], gf[s], hb[2 * s], hb[2 * s + 1]);
                    mma16816(cu[s & 1], uf[s], hb[2 * s], hb[2 * s + 1]);
                }
                if (t < 2) {
                    float v[4];
#pragma unroll
                    for (int i = 0; i < 4; i++) v[i] = t ? cu[0][i] + cu[1][i] : cg[0][i] + cg[1][i];
                    *(float2*)&red[warp * 64 + t * 32 + g * 2] = make_float2(v[0], v[1]);
                    *(float2*)&red[warp * 64 + t * 32 + (g + 8) * 2] = make_float2(v[2], v[3]);
                }
            }
            uint32_t df[4][4];
            mbar_wait(bar_full + 8 * (IDX_WD % NST), (IDX_WD / NST) & 1);
#pragma unroll
            for (int mt = 0; mt < 4; mt++) ldsm4t((sbase + SM_RING + (IDX_WD % NST) * TILE + aoff) ^ (mt << 5), df[mt]);
            cons_sync();
            {
                float gs = 0.f, us = 0.f;
#pragma unroll
                for (int w = 0; w < 8; w++) { gs += red[w * 64 + lane]; us += red[w * 64 + 32 + lane]; }
                gs = bf16r(gs);
                const float u2 = gs * (1.0f + 0.044715f * gs * gs) * (2.0f * 0.7978845608028654f * LOG2E);
                const float ge = bf16r(__fdividef(gs, 1.0f + ex2(-u2)));
                const float act = bf16r(ge * bf16r(us));
                const float a0 = __shfl_sync(0xffffffffu, act, 4 * t + bb), a1 = __shfl_sync(0xffffffffu, act, 4 * t + 2 + bb);
                const float a2 = __shfl_sync(0xffffffffu, act, 4 * t + 16 + bb), a3 = __shfl_sync(0xffffffffu, act, 4 * t + 18 + bb);
                const uint32_t b0 = pack_bf16(a0, a1), b1 = pack_bf16(a2, a3);
                float y[4][4] = {};
#pragma unroll
                for (int mt = 0; mt < 4; mt++) mma16816(y[mt], df[mt], b0, b1);
                float v[4];
#pragma unroll
                for (int i = 0; i < 4; i++) v[i] = t == 0 ? y[0][i] : t == 1 ? y[1][i] : t == 2 ? y[2][i] : y[3][i];
                const int col = 64 * warp + 16 * t + g;
                st_ll4(&g_inbox[col >> 2][cta][col & 3], __float_as_uint(v[0]), __float_as_uint(v[1]), F_DOWN);
                st_ll4(&g_inbox[(col + 8) >> 2][cta][col & 3], __float_as_uint(v[2]), __float_as_uint(v[3]), F_DOWN);
            }
            if (warp == 0) TSTAMP(12);
        }
        {
            float s0, s1;
            for (int it = 0;; it++) {
                const uint4 v0 = ld_ll4(&g_inbox[cta][0][0] + tid);
                uint4 v1 = make_uint4(0u, F_DOWN, 0u, F_DOWN);
                if (tid < NFFN * 4 - 256) v1 = ld_ll4(&g_inbox[cta][0][0] + 256 + tid);
                s0 = __uint_as_float(v0.x) + __uint_as_float(v1.x);
                s1 = __uint_as_float(v0.z) + __uint_as_float(v1.z);
                const bool ok = v0.y == F_DOWN && v0.w == F_DOWN && v1.y == F_DOWN && v1.w == F_DOWN;
                if (__all_sync(0xffffffffu, ok) || it > SPIN_LIMIT) break;
            }
#pragma unroll
            for (int o_ = 4; o_ < 32; o_ <<= 1) { s0 += __shfl_xor_sync(0xffffffffu, s0, o_); s1 += __shfl_xor_sync(0xffffffffu, s1, o_); }
            if (lane < 4) *(float2*)&red2[64 + warp * 8 + lane * 2] = make_float2(s0, s1);
            cons_sync();
            if (warp == 0) {
                float a0 = 0.f, a1 = 0.f;
#pragma unroll
                for (int w = 0; w < 8; w++) { const float2 v = *(const float2*)&red2[64 + w * 8 + (lane & 3) * 2]; a0 += v.x; a1 += v.y; }
                const bool hi = ocol & 1;
                const float gb0 = hi ? bf_hi(m_gb0.x) : bf_lo(m_gb0.x), gb1 = hi ? bf_hi(m_gb1.x) : bf_lo(m_gb1.x);
                if (lane < 4) {
                    p.out[ocol] = __float2bfloat16_rn(xm0 + bf16r(gb0 * bf16r(a0)));
                    p.out[D_MODEL + ocol] = __float2bfloat16_rn(xm1 + bf16r(gb1 * bf16r(a1)));
                }
                if (cta == 0 && lane == 0) *(volatile unsigned*)&g_epoch = tag;
                TSTAMP(13);
            }
        }
    }
}

typedef CUresult (*EncodeFn)(CUtensorMap*, CUtensorMapDataType, cuuint32_t, void*, const cuuint64_t*, const cuuint64_t*,
                             const cuuint32_t*, const cuuint32_t*, CUtensorMapInterleave, CUtensorMapSwizzle,
                             CUtensorMapL2promotion, CUtensorMapFloatOOBfill);

struct Maps { CUtensorMap k, v, wq, wmod, wo, wg, wu, wd; };

void encode(EncodeFn fn, CUtensorMap* m, const void* ptr, int rank, const cuuint64_t* dims, const cuuint64_t* strides,
            const cuuint32_t* box, CUtensorMapSwizzle sw) {
    const cuuint32_t es[3] = {1, 1, 1};
    fn(m, CU_TENSOR_MAP_DATA_TYPE_BFLOAT16, rank, const_cast<void*>(ptr), dims, strides, box, es,
       CU_TENSOR_MAP_INTERLEAVE_NONE, sw, CU_TENSOR_MAP_L2_PROMOTION_L2_256B, CU_TENSOR_MAP_FLOAT_OOB_FILL_NONE);
}

}

extern "C" void kernel_launch(void* const* d_in, const int* in_sizes, int n_in, void* d_out, int out_size) {
    (void)in_sizes; (void)n_in; (void)out_size;
    static EncodeFn enc = nullptr;
    if (!enc) {
        void* fn = nullptr;
        cudaDriverEntryPointQueryResult qr;
        cudaGetDriverEntryPoint("cuTensorMapEncodeTiled", &fn, cudaEnableDefault, &qr);
        enc = (EncodeFn)fn;
        cudaFuncSetAttribute(fused_block_kernel, cudaFuncAttributeMaxDynamicSharedMemorySize, SMEM_BYTES);
    }
    Maps m;
    {
        const cuuint64_t dims[3] = {64, (cuuint64_t)16 * SK, 2}, str[2] = {256, 128};
        const cuuint32_t box[3] = {64, 64, 2};
        encode(enc, &m.k, d_in[1], 3, dims, str, box, CU_TENSOR_MAP_SWIZZLE_128B);
        encode(enc, &m.v, d_in[2], 3, dims, str, box, CU_TENSOR_MAP_SWIZZLE_128B);
    }
    {
        const cuuint64_t dims[2] = {4096, 512}, str[1] = {8192};
        const cuuint32_t box[2] = {32, 256};
        encode(enc, &m.wq, d_in[3], 2, dims, str, box, CU_TENSOR_MAP_SWIZZLE_64B);
    }
    {
        const cuuint64_t dims[2] = {N_MOD, 512}, str[1] = {N_MOD * 2};
        const cuuint32_t box[2] = {16, 256};
        encode(enc, &m.wmod, d_in[10], 2, dims, str, box, CU_TENSOR_MAP_SWIZZLE_32B);
    }
    {
        const cuuint64_t dims_o[3] = {64, 4096, 8}, dims_d[3] = {64, D_FF, 8}, str[2] = {1024, 128};
        const cuuint32_t box[3] = {64, 16, 8};
        encode(enc, &m.wo, d_in[4], 3, dims_o, str, box, CU_TENSOR_MAP_SWIZZLE_128B);
        encode(enc, &m.wd, d_in[8], 3, dims_d, str, box, CU_TENSOR_MAP_SWIZZLE_128B);
    }
    {
        const cuuint64_t dims[2] = {D_FF, 512}, str[1] = {D_FF * 2};
        const cuuint32_t box[2] = {16, 256};
        encode(enc, &m.wg, d_in[6], 2, dims, str, box, CU_TENSOR_MAP_SWIZZLE_32B);
        encode(enc, &m.wu, d_in[7], 2, dims, str, box, CU_TENSOR_MAP_SWIZZLE_32B);
    }
    Params p;
    p.x = (const __nv_bfloat16*)d_in[0];
    p.c = (const __nv_bfloat16*)d_in[9];
    p.w_mod = (const __nv_bfloat16*)d_in[10];
    p.out = (__nv_bfloat16*)d_out;
    fused_block_kernel<<<NCTA, NTHREADS, SMEM_BYTES, cudaStreamPerThread>>>(m.k, m.v, m.wq, m.wmod, m.wo, m.wg, m.wu, m.wd, p);
}
```

```cpp
#include <cuda_runtime.h>
#include <cuda.h>
#include <cuda_bf16.h>
#include <stdint.h>

namespace {

constexpr int D_MODEL = 512;
constexpr int N_HEADS = 32;
constexpr int SK = 32768;
constexpr int DH = 128;
constexpr int D_FF = 1792;
constexpr int N_MOD = 6 * D_MODEL;

constexpr int NCTA = 128;
constexpr int NFFN = D_FF / 16;
constexpr int NTHREADS = 320;
constexpr int NST = 12;
constexpr int TILE = 16384;
#define INFL_PRO 2
#define INFL_MAIN 3
#define INFL_TAIL 2
#define PACE_HI 96
#define PACE_LO 96
#define PACE_SLEEP 200
#define WO_TRIG 0
#define FF_TRIG 0
#define PF_WO 0
#define PF_FF 0
#define PRO_TILES 8
constexpr int KV_TILES = 64;
#define MOD_AT 8
#define WO_AT 64
#define FF_AT 64
static_assert(MOD_AT % 2 == 0 && MOD_AT < WO_AT && WO_AT <= FF_AT && FF_AT <= KV_TILES, "schedule");
__host__ __device__ constexpr int kv_idx(int i) {
    return 2 + 2 * i + (i >= MOD_AT ? 1 : 0) + (i >= WO_AT ? 2 : 0) + (i >= FF_AT ? 3 : 0);
}
constexpr int IDX_MOD = 2 + 2 * MOD_AT;
constexpr int IDX_WO = 3 + 2 * WO_AT;
constexpr int IDX_WG = 5 + 2 * FF_AT;
constexpr int IDX_WU = IDX_WG + 1;
constexpr int IDX_WD = IDX_WU + 1;
constexpr int N_TILES = 2 + 2 * KV_TILES + 1 + 2 + 3;
static_assert(N_TILES - 1 - IDX_WO < NST, "wo and the FFN weights must stay resident until the end");
constexpr int SPIN_LIMIT = 1 << 20;

constexpr float LOG2E = 1.4426950408889634f;
constexpr float QK_SCALE = 0.08838834764831845f;

constexpr int SM_RING = 0;
constexpr int SM_MRG = SM_RING + NST * TILE;
constexpr int SM_ML = SM_MRG + 8 * 4 * 136 * 4;
constexpr int SM_RED = SM_ML + 8 * 4 * 8;
constexpr int SM_RED2 = SM_RED + 8 * 64 * 4;
constexpr int SM_QS = SM_RED2 + 8 * 64 * 4;
constexpr int SM_OS = SM_QS + 512 * 2;
constexpr int SM_SC = SM_OS + 2 * 16 * 4;
constexpr int SM_HS = SM_SC + 2 * 512 * 2;
constexpr int SM_STAT = SM_HS + 8 * 2 * 32 * 4;
constexpr int SM_PACE = SM_STAT + 8 * 2 * 8;
constexpr int SM_BAR = SM_PACE + 8;
constexpr int SM_END = SM_BAR + (2 * NST + 3) * 8;
constexpr int SMEM_BYTES = SM_END + 1024;

struct Scratch {
    uint4 inbox[NCTA][NCTA][4];
    uint4 part_o[NCTA][4][64];
    uint4 part_ml[NCTA][4][2];
    uint2 mod[2][N_MOD / 2];
    uint2 q[2][N_HEADS * DH / 2];
    unsigned epoch;
    unsigned pad_[31];
    unsigned cleared;
    unsigned pad2_[31];
    unsigned progress;
};
__device__ Scratch g_scratch;
constexpr uint32_t F_PART = 1, F_WO = 1, F_DOWN = 2, F_X1 = 3;

struct Params {
    const __nv_bfloat16* x;
    const __nv_bfloat16* c;
    const __nv_bfloat16* w_mod;
    __nv_bfloat16* out;
    Scratch* sc;
};

#define TSTAMP(i) do { } while (0)

__device__ __forceinline__ uint32_t smem_u32(const void* p) { return (uint32_t)__cvta_generic_to_shared(p); }

__device__ __forceinline__ void mbar_init(uint32_t bar, uint32_t cnt) {
    asm volatile("mbarrier.init.shared::cta.b64 [%0], %1;" ::"r"(bar), "r"(cnt) : "memory");
}
__device__ __forceinline__ void mbar_expect_tx(uint32_t bar, uint32_t bytes) {
    asm volatile("mbarrier.arrive.expect_tx.shared::cta.b64 _, [%0], %1;" ::"r"(bar), "r"(bytes) : "memory");
}
__device__ __forceinline__ void mbar_arrive(uint32_t bar) {
    asm volatile("mbarrier.arrive.shared::cta.b64 _, [%0];" ::"r"(bar) : "memory");
}
__device__ __forceinline__ bool mbar_try(uint32_t bar, uint32_t parity) {
    uint32_t ok;
    asm volatile(
        "{\n\t.reg .pred p;\n\t"
        "mbarrier.try_wait.parity.shared::cta.b64 p, [%1], %2;\n\t"
        "selp.u32 %0, 1, 0, p;\n\t}"
        : "=r"(ok) : "r"(bar), "r"(parity) : "memory");
    return ok != 0;
}
__device__ __forceinline__ void mbar_wait(uint32_t bar, uint32_t parity) {
    if (mbar_try(bar, parity)) return;
    for (int i = 0; i < SPIN_LIMIT; i++)
        if (mbar_try(bar, parity)) return;
}
__device__ __forceinline__ void cons_sync() { asm volatile("bar.sync 1, 256;" ::: "memory"); }

__device__ __forceinline__ void tma_2d(uint32_t dst, const CUtensorMap* m, int c0, int c1, uint32_t bar) {
    asm volatile("cp.async.bulk.tensor.2d.shared::cluster.global.mbarrier::complete_tx::bytes [%0], [%1, {%3, %4}], [%2];"
                 ::"r"(dst), "l"(m), "r"(bar), "r"(c0), "r"(c1) : "memory");
}
__device__ __forceinline__ void tma_3d(uint32_t dst, const CUtensorMap* m, int c0, int c1, int c2, uint32_t bar) {
    asm volatile("cp.async.bulk.tensor.3d.shared::cluster.global.mbarrier::complete_tx::bytes [%0], [%1, {%3, %4, %5}], [%2];"
                 ::"r"(dst), "l"(m), "r"(bar), "r"(c0), "r"(c1), "r"(c2) : "memory");
}
__device__ __forceinline__ void tma_3d_hint(uint32_t dst, const CUtensorMap* m, int c0, int c1, int c2, uint32_t bar, uint64_t pol) {
    asm volatile("cp.async.bulk.tensor.3d.shared::cluster.global.mbarrier::complete_tx::bytes.L2::cache_hint [%0], [%1, {%3, %4, %5}], [%2], %6;"
                 ::"r"(dst), "l"(m), "r"(bar), "r"(c0), "r"(c1), "r"(c2), "l"(pol) : "memory");
}
__device__ __forceinline__ void l2pf_2d(const CUtensorMap* m, int c0, int c1) {
    asm volatile("cp.async.bulk.prefetch.tensor.2d.L2.global.tile [%0, {%1, %2}];" ::"l"(m), "r"(c0), "r"(c1) : "memory");
}
__device__ __forceinline__ void l2pf_3d(const CUtensorMap* m, int c0, int c1, int c2) {
    asm volatile("cp.async.bulk.prefetch.tensor.3d.L2.global.tile [%0, {%1, %2, %3}];" ::"l"(m), "r"(c0), "r"(c1), "r"(c2) : "memory");
}
__device__ __forceinline__ void prefetch_tmap(const CUtensorMap* m) {
    asm volatile("prefetch.tensormap [%0];" ::"l"(m) : "memory");
}

__device__ __forceinline__ void ldsm4(uint32_t addr, uint32_t (&r)[4]) {
    asm volatile("ldmatrix.sync.aligned.m8n8.x4.shared.b16 {%0,%1,%2,%3}, [%4];"
                 : "=r"(r[0]), "=r"(r[1]), "=r"(r[2]), "=r"(r[3]) : "r"(addr) : "memory");
}
__device__ __forceinline__ void ldsm4t(uint32_t addr, uint32_t (&r)[4]) {
    asm volatile("ldmatrix.sync.aligned.m8n8.x4.trans.shared.b16 {%0,%1,%2,%3}, [%4];"
                 : "=r"(r[0]), "=r"(r[1]), "=r"(r[2]), "=r"(r[3]) : "r"(addr) : "memory");
}
__device__ __forceinline__ void mma16816(float (&c)[4], const uint32_t (&a)[4], uint32_t b0, uint32_t b1) {
    asm volatile("mma.sync.aligned.m16n8k16.row.col.f32.bf16.bf16.f32 {%0,%1,%2,%3}, {%4,%5,%6,%7}, {%8,%9}, {%0,%1,%2,%3};"
                 : "+f"(c[0]), "+f"(c[1]), "+f"(c[2]), "+f"(c[3])
                 : "r"(a[0]), "r"(a[1]), "r"(a[2]), "r"(a[3]), "r"(b0), "r"(b1));
}
__device__ __forceinline__ uint32_t movmatrix_t(uint32_t a) {
    uint32_t d;
    asm volatile("movmatrix.sync.aligned.m8n8.trans.b16 %0, %1;" : "=r"(d) : "r"(a));
    return d;
}
__device__ __forceinline__ uint32_t pack_bf16(float a, float b) {
    uint32_t r;
    asm("cvt.rn.bf16x2.f32 %0, %1, %2;" : "=r"(r) : "f"(b), "f"(a));
    return r;
}
__device__ __forceinline__ float bf_lo(uint32_t v) { return __uint_as_float(v << 16); }
__device__ __forceinline__ float bf_hi(uint32_t v) { return __uint_as_float(v & 0xffff0000u); }
__device__ __forceinline__ float bf16r(float a) { return bf_lo(pack_bf16(a, 0.f)); }
__device__ __forceinline__ uint32_t max_bf16x2(uint32_t a, uint32_t b) {
    uint32_t r;
    asm("max.bf16x2 %0, %1, %2;" : "=r"(r) : "r"(a), "r"(b));
    return r;
}
__device__ __forceinline__ float ex2(float x) {
    float r;
    asm("ex2.approx.ftz.f32 %0, %1;" : "=f"(r) : "f"(x));
    return r;
}

__device__ __forceinline__ void st_ll2(uint2* p, uint32_t v, uint32_t tag) {
    asm volatile("st.relaxed.gpu.global.v2.u32 [%0], {%1, %2};" ::"l"(p), "r"(v), "r"(tag) : "memory");
}
__device__ __forceinline__ void st_ll4(uint4* p, uint32_t v0, uint32_t v1, uint32_t tag) {
    asm volatile("st.relaxed.gpu.global.v4.u32 [%0], {%1, %2, %3, %2};" ::"l"(p), "r"(v0), "r"(tag), "r"(v1) : "memory");
}
__device__ __forceinline__ uint2 ld_ll2(const uint2* p) {
    uint2 v;
    asm volatile("ld.relaxed.gpu.global.v2.u32 {%0, %1}, [%2];" : "=r"(v.x), "=r"(v.y) : "l"(p) : "memory");
    return v;
}
__device__ __forceinline__ uint4 ld_ll4(const uint4* p) {
    uint4 v;
    asm volatile("ld.relaxed.gpu.global.v4.u32 {%0, %1, %2, %3}, [%4];"
                 : "=r"(v.x), "=r"(v.y), "=r"(v.z), "=r"(v.w) : "l"(p) : "memory");
    return v;
}

#define POLL_GAP 160
#define POLL2(A, B, LOAD, OK, USE)                                               \
    {                                                                            \
        LOAD(A);                                                                 \
        { const uint32_t c0_ = clock32(); while (clock32() - c0_ < POLL_GAP) {} } \
        for (int it_ = 0;; it_++) {                                              \
            LOAD(B);                                                             \
            if (__all_sync(0xffffffffu, OK(A))) { USE(A); break; }               \
            LOAD(A);                                                             \
            if (__all_sync(0xffffffffu, OK(B)) || it_ > SPIN_LIMIT) { USE(B); break; } \
        }                                                                        \
    }
__device__ __forceinline__ uint32_t clock32() {
    uint32_t c;
    asm volatile("mov.u32 %0, %clock;" : "=r"(c));
    return c;
}
__device__ __forceinline__ float rcp_approx(float x) {
    float r;
    asm("rcp.approx.ftz.f32 %0, %1;" : "=f"(r) : "f"(x));
    return r;
}
__device__ __forceinline__ float sqrt_approx(float x) {
    float r;
    asm("sqrt.approx.f32 %0, %1;" : "=f"(r) : "f"(x));
    return r;
}

__device__ __forceinline__ float silu_bf(float v) { return bf16r(v / (1.0f + expf(-v))); }

__device__ __forceinline__ float2 half_warp_sums(const float (&v)[4], float pivot) {
    float s1 = 0.f, s2 = 0.f;
#pragma unroll
    for (int i = 0; i < 4; i++) { const float d = v[i] - pivot; s1 += d; s2 += d * d; }
#pragma unroll
    for (int o = 1; o < 16; o <<= 1) { s1 += __shfl_xor_sync(0xffffffffu, s1, o); s2 += __shfl_xor_sync(0xffffffffu, s2, o); }
    return make_float2(s1, s2);
}
__device__ __forceinline__ void ln_stats(const float2* stat, int b, float pivot, float& mean_bf, float& rstd) {
    float s1 = 0.f, s2 = 0.f;
#pragma unroll
    for (int w = 0; w < 8; w++) { const float2 v = stat[w * 2 + b]; s1 += v.x; s2 += v.y; }
    const float dm = s1 * (1.0f / D_MODEL);
    const float var = fmaxf(s2 * (1.0f / D_MODEL) - dm * dm, 0.f);
    mean_bf = bf16r(pivot + dm);
    rstd = rcp_approx(bf16r(sqrt_approx(bf16r(bf16r(var) + 1e-5f))));
}
__device__ __forceinline__ float ln_norm(float xv, float mean_bf, float rstd) { return bf16r(bf16r(xv - mean_bf) * rstd); }
__device__ __forceinline__ float ln_mod(float n, float cmul, float sadd) { return bf16r(n * bf16r(1.0f + cmul)) + sadd; }

__global__ void __launch_bounds__(NTHREADS, 1)
fused_block_kernel(const Params p, const __grid_constant__ CUtensorMap tm_k, const __grid_constant__ CUtensorMap tm_v,
                   const __grid_constant__ CUtensorMap tm_wq, const __grid_constant__ CUtensorMap tm_wmod,
                   const __grid_constant__ CUtensorMap tm_wo, const __grid_constant__ CUtensorMap tm_wg,
                   const __grid_constant__ CUtensorMap tm_wu, const __grid_constant__ CUtensorMap tm_wd) {
    extern __shared__ unsigned char smem_raw[];
    const uint32_t sbase = (smem_u32(smem_raw) + 1023u) & ~1023u;
    unsigned char* sgen = smem_raw + (sbase - smem_u32(smem_raw));
    const int tid = threadIdx.x, warp = tid >> 5, lane = tid & 31;
    const int cta = blockIdx.x;
    const uint32_t bar_full = sbase + SM_BAR, bar_empty = bar_full + NST * 8;
    const uint32_t bar_clear = bar_empty + NST * 8;
    const uint32_t bar_go_wo = bar_clear + 8, bar_go_ff = bar_clear + 16;

    if (warp == 8) {
        if (lane == 0) {
            prefetch_tmap(&tm_wq);
            for (int i = 0; i < NST; i++) { mbar_init(bar_full + 8 * i, 1); mbar_init(bar_empty + 8 * i, 4); }
            mbar_init(bar_clear, 1);
            mbar_init(bar_go_wo, 1);
            mbar_init(bar_go_ff, 1);
            ((volatile uint32_t*)(sgen + SM_PACE))[0] = 0;
            ((volatile uint32_t*)(sgen + SM_PACE))[1] = INFL_MAIN;
            asm volatile("fence.mbarrier_init.release.cluster;" ::: "memory");
        }
        __syncwarp();
        asm volatile("bar.arrive 2, 320;" ::: "memory");
        asm volatile("bar.arrive 3, 64;" ::: "memory");
        if (lane == 0) {
            const int pair = cta >> 3, j = cta & 7;
            const int key0 = pair * SK + j * 64;
            uint64_t pol;
            asm volatile("createpolicy.fractional.L2::evict_first.b64 %0, 1.0;" : "=l"(pol));
            int slot = 0; uint32_t ph = 1;
            int landed = 0, wslot = 0; uint32_t wph = 0;
            int kv = 0;
            for (int idx = 0; idx < N_TILES; idx++) {
                if (idx >= NST) mbar_wait(bar_empty + 8 * slot, ph);
                if (idx == kv_idx(KV_TILES - 1) + 2) {
                    if (PF_WO == 1) { l2pf_3d(&tm_wo, 0, cta * 32, 0); l2pf_3d(&tm_wo, 0, cta * 32 + 16, 0); }
                }
                if ((PF_FF == 1 && idx == kv_idx(KV_TILES - 1) + 2) || (PF_FF == 2 && idx == IDX_WG)) {
                    if (cta < NFFN) {
                        l2pf_2d(&tm_wg, cta * 16, 0); l2pf_2d(&tm_wg, cta * 16, 256);
                        l2pf_2d(&tm_wu, cta * 16, 0); l2pf_2d(&tm_wu, cta * 16, 256);
                        l2pf_3d(&tm_wd, 0, cta * 16, 0);
                    }
                }
                const int window = idx < PRO_TILES ? INFL_PRO : idx >= kv_idx(KV_TILES - 1) + 2 ? INFL_TAIL
                                                               : (int)((volatile uint32_t*)(sgen + SM_PACE))[1];
                while (landed + window <= idx) {
                    mbar_wait(bar_full + 8 * wslot, wph);
                    if (++wslot == NST) { wslot = 0; wph ^= 1; }
                    landed++;
                }
                if (WO_TRIG != 0 && idx == IDX_WO) mbar_wait(bar_go_wo, 0);
                if (FF_TRIG != 0 && idx == IDX_WG) mbar_wait(bar_go_ff, 0);
                const uint32_t fb = bar_full + 8 * slot, dst = sbase + SM_RING + slot * TILE;
                if (idx == 0) { prefetch_tmap(&tm_k); prefetch_tmap(&tm_v); prefetch_tmap(&tm_wmod); }
                if (idx == 12) { prefetch_tmap(&tm_wo); prefetch_tmap(&tm_wg); prefetch_tmap(&tm_wu); prefetch_tmap(&tm_wd); }
                if (idx >= IDX_WG && idx <= IDX_WD && cta >= NFFN) {
                    mbar_arrive(fb);
                } else {
                    mbar_expect_tx(fb, TILE);
                    if (idx < 2) {
                        tma_2d(dst, &tm_wq, cta * 32, idx * 256, fb);
                    } else if (idx == IDX_MOD) {
                        tma_2d(dst, &tm_wmod, 1024 + cta * 16, 0, fb);
                        tma_2d(dst + 8192, &tm_wmod, 1024 + cta * 16, 256, fb);
                    } else if (idx == IDX_WO || idx == IDX_WO + 1) {
                        tma_3d(dst, &tm_wo, 0, cta * 32 + (idx - IDX_WO) * 16, 0, fb);
                    } else if (idx == IDX_WG || idx == IDX_WU) {
                        const CUtensorMap* m = idx == IDX_WG ? &tm_wg : &tm_wu;
                        tma_2d(dst, m, cta * 16, 0, fb);
                        tma_2d(dst + 8192, m, cta * 16, 256, fb);
                    } else if (idx == IDX_WD) {
                        tma_3d(dst, &tm_wd, 0, cta * 16, 0, fb);
                    } else {
                        tma_3d_hint(dst, (kv & 1) ? &tm_v : &tm_k, 0, key0 + (kv >> 1) * 512, 0, fb, pol);
                        kv++;
                    }
                }
                ((volatile uint32_t*)(sgen + SM_PACE))[0] = idx + 1;
                if (++slot == NST) { slot = 0; ph ^= 1; }
            }
        }
    } else if (warp == 9) {
        Scratch* const sc = p.sc;
        const uint32_t tag = *(volatile unsigned*)&sc->epoch + 1;
        if (lane < 2) {
            st_ll4((uint4*)&sc->mod[lane][cta * 4], 0u, 0u, 0u);
            st_ll4((uint4*)&sc->mod[lane][cta * 4] + 1, 0u, 0u, 0u);
        }
        if (lane < 8) st_ll4((uint4*)&sc->mod[lane >> 2][512 + cta * 8] + (lane & 3), 0u, 0u, 0u);
        if (lane < 16) st_ll4((uint4*)&sc->q[lane >> 3][cta * 16] + (lane & 7), 0u, 0u, 0u);
        __syncwarp();
        asm volatile("bar.arrive 2, 320;" ::: "memory");
        asm volatile("bar.sync 3, 64;" ::: "memory");
#pragma unroll 4
        for (int i = 0; i < 16; i++) st_ll4(&sc->inbox[cta][0][0] + i * 32 + lane, 0u, 0u, 0u);
#pragma unroll 4
        for (int i = 0; i < 8; i++) st_ll4(&sc->part_o[cta][0][0] + i * 32 + lane, 0u, 0u, 0u);
        if (lane < 8) st_ll4(&sc->part_ml[cta][0][0] + lane, 0u, 0u, 0u);
        if (cta == 0 && lane == 0) asm volatile("st.relaxed.gpu.global.u32 [%0], %1;" ::"l"(&sc->progress), "r"(0u) : "memory");
        asm volatile("fence.acq_rel.gpu;" ::: "memory");
        __syncwarp();
        if (lane == 0) {
            asm volatile("fence.acq_rel.gpu;" ::: "memory");
            asm volatile("red.relaxed.gpu.global.add.u32 [%0], %1;" ::"l"(&sc->cleared), "r"(1u) : "memory");
            const uint32_t target = tag * NCTA;
            for (int it = 0; it < SPIN_LIMIT; it++) {
                uint32_t v;
                asm volatile("ld.relaxed.gpu.global.u32 %0, [%1];" : "=r"(v) : "l"(&sc->cleared) : "memory");
                if ((int32_t)(v - target) >= 0) break;
                __nanosleep(500);
            }
            asm volatile("fence.acq_rel.gpu;" ::: "memory");
            mbar_arrive(bar_clear);
            volatile uint32_t* pace = (volatile uint32_t*)(sgen + SM_PACE);
            uint32_t posted = 0;
            for (int it = 0; it < SPIN_LIMIT; it++) {
                const uint32_t own = pace[0];
                if (own >= kv_idx(KV_TILES - 1) + 2) break;
                if (own > posted) {
                    asm volatile("red.relaxed.gpu.global.add.u32 [%0], %1;" ::"l"(&sc->progress), "r"(own - posted) : "memory");
                    posted = own;
                }
                uint32_t v;
                asm volatile("ld.relaxed.gpu.global.u32 %0, [%1];" : "=r"(v) : "l"(&sc->progress) : "memory");
                const int diff = (int)v - (int)own * NCTA;
                pace[1] = diff > PACE_HI ? INFL_MAIN + 1 : diff < -PACE_LO ? INFL_MAIN - 1 : INFL_MAIN;
                __nanosleep(PACE_SLEEP);
            }
        }
    } else {
        const int g = lane >> 2, t = lane & 3;
        const int bb = g & 1;
        const int eb = lane >> 4;
        const int ec = 64 * warp + 4 * (lane & 15);
        if (warp == 0) TSTAMP(0);
        Scratch* const sc = p.sc;
        const uint4 w0 = __ldg((const uint4*)(p.w_mod + (size_t)tid * N_MOD + cta * 8));
        const uint4 w1 = __ldg((const uint4*)(p.w_mod + (size_t)(tid + 256) * N_MOD + cta * 8));
        const float c00 = __bfloat162float(p.c[tid]), c01 = __bfloat162float(p.c[tid + 256]);
        const float c10 = __bfloat162float(p.c[D_MODEL + tid]), c11 = __bfloat162float(p.c[D_MODEL + tid + 256]);
        const uint2 xe = __ldg((const uint2*)(p.x + eb * D_MODEL + ec));
        const float xpivot = __bfloat162float(p.x[eb * D_MODEL]);
        const uint32_t tag = *(volatile unsigned*)&sc->epoch + 1;
        const int ocol = cta * 4 + (lane & 3);
        const float xo0 = __bfloat162float(p.x[ocol]), xo1 = __bfloat162float(p.x[D_MODEL + ocol]);

        float* red = (float*)(sgen + SM_RED);
        float* red2 = (float*)(sgen + SM_RED2);
        float2* stat = (float2*)(sgen + SM_STAT);
        uint32_t* hs = (uint32_t*)(sgen + SM_HS) + warp * 64;
        float xn[4];
        {
            float xv[4] = {bf_lo(xe.x), bf_hi(xe.x), bf_lo(xe.y), bf_hi(xe.y)};
            const float2 ps = half_warp_sums(xv, xpivot);
            if ((lane & 15) == 0) stat[warp * 2 + eb] = ps;
            const float s00 = silu_bf(c00), s01 = silu_bf(c01), s10 = silu_bf(c10), s11 = silu_bf(c11);
            __nv_bfloat16* scs = (__nv_bfloat16*)(sgen + SM_SC);
            scs[tid] = __float2bfloat16_rn(s00); scs[tid + 256] = __float2bfloat16_rn(s01);
            scs[512 + tid] = __float2bfloat16_rn(s10); scs[512 + tid + 256] = __float2bfloat16_rn(s11);
            const uint32_t a[4] = {w0.x, w0.y, w0.z, w0.w}, b[4] = {w1.x, w1.y, w1.z, w1.w};
            float v[16];
#pragma unroll
            for (int i = 0; i < 4; i++) {
                v[2 * i] = s00 * bf_lo(a[i]) + s01 * bf_lo(b[i]);
                v[2 * i + 1] = s00 * bf_hi(a[i]) + s01 * bf_hi(b[i]);
                v[8 + 2 * i] = s10 * bf_lo(a[i]) + s11 * bf_lo(b[i]);
                v[8 + 2 * i + 1] = s10 * bf_hi(a[i]) + s11 * bf_hi(b[i]);
            }
#define XRED(N, O)                                                                       \
            {                                                                            \
                const bool up = lane & (O);                                              \
                _Pragma("unroll") for (int i = 0; i < (N); i++) {                        \
                    const float send = up ? v[i] : v[i + (N)], keep = up ? v[i + (N)] : v[i]; \
                    v[i] = keep + __shfl_xor_sync(0xffffffffu, send, (O));               \
                }                                                                        \
            }
            XRED(8, 16) XRED(4, 8) XRED(2, 4) XRED(1, 2)
#undef XRED
            v[0] += __shfl_xor_sync(0xffffffffu, v[0], 1);
            if (!(lane & 1)) red[warp * 16 + (lane >> 1)] = v[0];
            if (warp == 0) TSTAMP(14);
            asm volatile("bar.sync 2, 320;" ::: "memory");
            if (warp == 0) TSTAMP(23);
            if (warp == 0) {
                float s = 0.f;
#pragma unroll
                for (int w = 0; w < 8; w++) s += red[w * 16 + (lane & 15)];
                const float nx = __shfl_down_sync(0xffffffffu, s, 1);
                if (lane < 16 && !(lane & 1))
                    st_ll2(&sc->mod[lane >> 3][cta * 4 + ((lane & 7) >> 1)], pack_bf16(s, nx), tag);
                TSTAMP(1);
            }
            float mean_bf, rstd;
            ln_stats(stat, eb, xpivot, mean_bf, rstd);
#pragma unroll
            for (int i = 0; i < 4; i++) xn[i] = ln_norm(xv[i], mean_bf, rstd);
        }
        {
            uint4 sa, ca;
            for (int it = 0;; it++) {
                sa = ld_ll4((const uint4*)&sc->mod[eb][ec >> 1]);
                ca = ld_ll4((const uint4*)&sc->mod[eb][256 + (ec >> 1)]);
                const bool ok = sa.y == tag && sa.w == tag && ca.y == tag && ca.w == tag;
                if (__all_sync(0xffffffffu, ok) || it > SPIN_LIMIT) break;
            }
            *(uint2*)&hs[eb * 32 + 2 * (lane & 15)] =
                make_uint2(pack_bf16(ln_mod(xn[0], bf_lo(ca.x), bf_lo(sa.x)), ln_mod(xn[1], bf_hi(ca.x), bf_hi(sa.x))),
                           pack_bf16(ln_mod(xn[2], bf_lo(ca.z), bf_lo(sa.z)), ln_mod(xn[3], bf_hi(ca.z), bf_hi(sa.z))));
            __syncwarp();
            uint32_t hb[8];
#pragma unroll
            for (int i = 0; i < 8; i++) hb[i] = hs[bb * 32 + 8 * (i >> 1) + 4 * (i & 1) + t];
            if (warp == 0) TSTAMP(2);
            float cq[2][4] = {};
            const int ts = warp >> 2;
            mbar_wait(bar_full + 8 * ts, 0);
            const uint32_t tb = sbase + SM_RING + ts * TILE;
#pragma unroll
            for (int s = 0; s < 4; s++) {
                const int row = 64 * (warp & 3) + 16 * s + (lane & 7) + (lane >> 4) * 8;
#pragma unroll
                for (int mt = 0; mt < 2; mt++) {
                    const int ch = 2 * mt + ((lane >> 3) & 1);
                    uint32_t a[4];
                    ldsm4t(tb + row * 64 + ((ch ^ ((row >> 1) & 3)) << 4), a);
                    mma16816(cq[mt], a, hb[2 * s], hb[2 * s + 1]);
                }
            }
            if (t < 2) {
                const float v0 = t == 0 ? cq[0][0] : cq[1][0], v1 = t == 0 ? cq[0][1] : cq[1][1];
                const float v2 = t == 0 ? cq[0][2] : cq[1][2], v3 = t == 0 ? cq[0][3] : cq[1][3];
                *(float2*)&red2[warp * 64 + (16 * t + g) * 2] = make_float2(v0, v1);
                *(float2*)&red2[warp * 64 + (16 * t + g + 8) * 2] = make_float2(v2, v3);
            }
            cons_sync();
            if (warp < 4 && lane == 0) { mbar_arrive(bar_empty + 0); mbar_arrive(bar_empty + 8); }
            if (warp == 0) {
                const int b = lane >> 4, cp = lane & 15;
                float q0 = 0.f, q1 = 0.f;
#pragma unroll
                for (int w = 0; w < 8; w++) {
                    const float4 v = *(const float4*)&red2[w * 64 + cp * 4];
                    q0 += b ? v.y : v.x; q1 += b ? v.w : v.z;
                }
                st_ll2(&sc->q[b][cta * 16 + cp], pack_bf16(q0, q1), tag);
                TSTAMP(3);
            }
        }
        const int pair = cta >> 3;
        uint32_t qf[16];
        {
            uint2* qs = (uint2*)(sgen + SM_QS);
            if (tid < 128) {
                const uint4* src = (const uint4*)&sc->q[pair >> 3][(pair & 7) * 256] + tid;
                uint4 v;
                for (int it = 0;; it++) {
                    v = ld_ll4(src);
                    if ((v.y == tag && v.w == tag) || it > SPIN_LIMIT) break;
                }
                qs[tid] = make_uint2(v.x, v.z);
            }
            cons_sync();
            const uint32_t* q32 = (const uint32_t*)(sgen + SM_QS);
#pragma unroll
            for (int s = 0; s < 8; s++) {
                qf[2 * s] = q32[(g & 3) * 64 + 8 * s + t];
                qf[2 * s + 1] = q32[(g & 3) * 64 + 8 * s + 4 + t];
            }
        }
        if (warp == 0) TSTAMP(4);

        float o[8][4];
#pragma unroll
        for (int i = 0; i < 8; i++) { o[i][0] = o[i][1] = o[i][2] = o[i][3] = 0.f; }
        uint32_t mrun = 0xff80ff80u;
        float ls[4] = {0.f, 0.f, 0.f, 0.f};
        uint4 m_sb, m_cb; uint2 m_ga0, m_ga1, m_gb0, m_gb1;
        {
            const int grp = warp >> 2, wi = warp & 3;
            const int krow = 16 * wi + (lane & 7) + ((lane >> 3) & 1) * 8;
            const uint32_t koff = krow * 128 + ((((lane >> 4) & 1) ^ (lane & 7)) << 4);
            const int vrow = 16 * wi + (lane & 7) + (lane >> 4) * 8;
            const uint32_t voff = vrow * 128 + ((((lane >> 3) & 1) ^ (lane & 7)) << 4);
            const uint32_t ones[4] = {0x3f803f80u, 0x3f803f80u, 0x3f803f80u, 0x3f803f80u};
            for (int i = grp; i < KV_TILES; i += 2) {
                if (i == MOD_AT + grp) {
                    float cm[4] = {};
                    const uint32_t* sc32 = (const uint32_t*)(sgen + SM_SC) + bb * 256 + 32 * warp + t;
                    mbar_wait(bar_full + 8 * (IDX_MOD % NST), (IDX_MOD / NST) & 1);
                    const uint32_t tb = sbase + SM_RING + (IDX_MOD % NST) * TILE;
#pragma unroll
                    for (int s = 0; s < 4; s++) {
                        const int row = 64 * warp + 16 * s + (lane & 7) + (lane >> 4) * 8;
                        const int ch = (lane >> 3) & 1;
                        uint32_t a[4];
                        ldsm4t(tb + row * 32 + ((ch ^ ((row >> 2) & 1)) << 4), a);
                        mma16816(cm, a, sc32[8 * s], sc32[8 * s + 4]);
                    }
                    if (t == 0) {
                        *(float2*)&red[warp * 64 + g * 2] = make_float2(cm[0], cm[1]);
                        *(float2*)&red[warp * 64 + (g + 8) * 2] = make_float2(cm[2], cm[3]);
                    }
                    cons_sync();
                    if (warp < 4 && lane == 0) mbar_arrive(bar_empty + 8 * (IDX_MOD % NST));
                    if (warp == 1 && lane < 16) {
                        const int b = lane >> 3, cp = lane & 7;
                        float q0 = 0.f, q1 = 0.f;
#pragma unroll
                        for (int w = 0; w < 8; w++) {
                            const float4 v = *(const float4*)&red[w * 64 + cp * 4];
                            q0 += b ? v.y : v.x; q1 += b ? v.w : v.z;
                        }
                        st_ll2(&sc->mod[b][512 + cta * 8 + cp], pack_bf16(q0, q1), tag);
                    }
                }
                if (i == 56 + grp) {
                    m_sb = ld_ll4((const uint4*)&sc->mod[eb][768 + (ec >> 1)]);
                    m_cb = ld_ll4((const uint4*)&sc->mod[eb][1024 + (ec >> 1)]);
                    m_ga0 = ld_ll2(&sc->mod[0][512 + (ocol >> 1)]); m_ga1 = ld_ll2(&sc->mod[1][512 + (ocol >> 1)]);
                    m_gb0 = ld_ll2(&sc->mod[0][1280 + (ocol >> 1)]); m_gb1 = ld_ll2(&sc->mod[1][1280 + (ocol >> 1)]);
                }
                if (i == 60 + grp) {
                    for (int it = 0;; it++) {
                        const bool ok = m_sb.y == tag && m_sb.w == tag && m_cb.y == tag && m_cb.w == tag &&
                                        m_ga0.y == tag && m_ga1.y == tag && m_gb0.y == tag && m_gb1.y == tag;
                        if (__all_sync(0xffffffffu, ok) || it > SPIN_LIMIT) break;
                        m_sb = ld_ll4((const uint4*)&sc->mod[eb][768 + (ec >> 1)]);
                        m_cb = ld_ll4((const uint4*)&sc->mod[eb][1024 + (ec >> 1)]);
                        m_ga0 = ld_ll2(&sc->mod[0][512 + (ocol >> 1)]); m_ga1 = ld_ll2(&sc->mod[1][512 + (ocol >> 1)]);
                        m_gb0 = ld_ll2(&sc->mod[0][1280 + (ocol >> 1)]); m_gb1 = ld_ll2(&sc->mod[1][1280 + (ocol >> 1)]);
                    }
                    mbar_wait(bar_clear, 0);
                }
                const int ki = kv_idx(i), ks = ki % NST, vs = (ki + 1) % NST;
                const uint32_t kph = (ki / NST) & 1, vph = ((ki + 1) / NST) & 1;
                mbar_wait(bar_full + 8 * ks, kph);
                const uint32_t kb = sbase + SM_RING + ks * TILE + koff;
                float sa[4] = {0.f, 0.f, 0.f, 0.f}, sb[4] = {0.f, 0.f, 0.f, 0.f};
#pragma unroll
                for (int s = 0; s < 8; s += 2) {
                    uint32_t a0[4], a1[4];
                    ldsm4((kb ^ ((s & 3) << 5)) + (s >> 2) * 8192, a0);
                    ldsm4((kb ^ (((s + 1) & 3) << 5)) + (s >> 2) * 8192, a1);
                    mma16816(sa, a0, qf[2 * s], qf[2 * s + 1]);
                    mma16816(sb, a1, qf[2 * s + 2], qf[2 * s + 3]);
                }
                __syncwarp();
                if (lane == 0) mbar_arrive(bar_empty + 8 * ks);
                uint32_t r01 = pack_bf16(sa[0] + sb[0], sa[1] + sb[1]);
                uint32_t r23 = pack_bf16(sa[2] + sb[2], sa[3] + sb[3]);
                r01 = pack_bf16(bf_lo(r01) * QK_SCALE, bf_hi(r01) * QK_SCALE);
                r23 = pack_bf16(bf_lo(r23) * QK_SCALE, bf_hi(r23) * QK_SCALE);
                uint32_t mx = max_bf16x2(r01, r23);
                mx = max_bf16x2(mx, __shfl_xor_sync(0xffffffffu, mx, 4));
                mx = max_bf16x2(mx, __shfl_xor_sync(0xffffffffu, mx, 8));
                mx = max_bf16x2(mx, __shfl_xor_sync(0xffffffffu, mx, 16));
                const uint32_t mnew = max_bf16x2(mrun, mx);
                const float m0 = bf_lo(mnew), m1 = bf_hi(mnew);
                if (__any_sync(0xffffffffu, mnew != mrun)) {
                    const float al0 = ex2((bf_lo(mrun) - m0) * LOG2E), al1 = ex2((bf_hi(mrun) - m1) * LOG2E);
                    ls[0] *= al0; ls[1] *= al1;
#pragma unroll
                    for (int d = 0; d < 8; d++) { o[d][0] *= al0; o[d][1] *= al1; o[d][2] *= al0; o[d][3] *= al1; }
                    mrun = mnew;
                }
                const float p0 = ex2((bf_lo(r01) - m0) * LOG2E), p1 = ex2((bf_hi(r01) - m1) * LOG2E);
                const float p2 = ex2((bf_lo(r23) - m0) * LOG2E), p3 = ex2((bf_hi(r23) - m1) * LOG2E);
                const uint32_t pb0 = movmatrix_t(pack_bf16(p0, p1)), pb1 = movmatrix_t(pack_bf16(p2, p3));
                mma16816(ls, ones, pb0, pb1);
                mbar_wait(bar_full + 8 * vs, vph);
                const uint32_t vb = sbase + SM_RING + vs * TILE + voff;
#pragma unroll
                for (int d = 0; d < 8; d++) {
                    uint32_t a[4];
                    ldsm4t((vb ^ ((d & 3) << 5)) + (d >> 2) * 8192, a);
                    mma16816(o[d], a, pb0, pb1);
                }
                __syncwarp();
                if (lane == 0) mbar_arrive(bar_empty + 8 * vs);
            }
        }
        if (warp == 7) TSTAMP(5);
        if (WO_TRIG == 1 && warp == 7 && lane == 0) mbar_arrive(bar_go_wo);
        if (FF_TRIG == 1 && warp == 7 && lane == 0) mbar_arrive(bar_go_ff);
        {
            float* mrg = (float*)(sgen + SM_MRG);
            float2* ml = (float2*)(sgen + SM_ML);
            {
                const int hp = (t & 1) * 2, up = t >> 1;
                if (g == 0 && up == 0) { ml[warp * 4 + hp] = make_float2(bf_lo(mrun), ls[0]); ml[warp * 4 + hp + 1] = make_float2(bf_hi(mrun), ls[1]); }
                float* m0p = mrg + (warp * 4 + hp) * 136 + up * 72 + g;
#pragma unroll
                for (int d = 0; d < 4; d++) {
                    m0p[16 * d] = up ? o[d + 4][0] : o[d][0]; m0p[136 + 16 * d] = up ? o[d + 4][1] : o[d][1];
                    m0p[16 * d + 8] = up ? o[d + 4][2] : o[d][2]; m0p[136 + 16 * d + 8] = up ? o[d + 4][3] : o[d][3];
                }
            }
            cons_sync();
            const int hh = tid >> 6, dp = tid & 63;
            float2 mw[8];
            float M = -INFINITY;
#pragma unroll
            for (int w = 0; w < 8; w++) { mw[w] = ml[w * 4 + hh]; M = fmaxf(M, mw[w].x); }
            float L = 0.f, o0 = 0.f, o1 = 0.f;
#pragma unroll
            for (int w = 0; w < 8; w++) {
                const float wt = ex2((mw[w].x - M) * LOG2E);
                const float2 v = *(const float2*)&mrg[(w * 4 + hh) * 136 + 2 * dp + (dp >= 32 ? 8 : 0)];
                L += wt * mw[w].y; o0 += wt * v.x; o1 += wt * v.y;
            }
            st_ll4(&sc->part_o[cta][hh][dp], __float_as_uint(o0), __float_as_uint(o1), F_PART);
            if (dp < 2) st_ll4(&sc->part_ml[cta][hh][dp], __float_as_uint(M), __float_as_uint(L), F_PART);
        }
        if (WO_TRIG == 2 && tid == 0) mbar_arrive(bar_go_wo);
        if (warp == 0) TSTAMP(6);
        const uint32_t aoff = warp * 2048 + ((lane & 7) + (lane >> 4) * 8) * 128 + ((((lane >> 3) & 1) ^ (lane & 7)) << 4);
        uint32_t wf[8][4];
        if (WO_AT < KV_TILES) {
#pragma unroll
            for (int s = 0; s < 2; s++) {
                constexpr int i0 = IDX_WO;
                const int idx = i0 + s;
                mbar_wait(bar_full + 8 * (idx % NST), (idx / NST) & 1);
                const uint32_t tb = sbase + SM_RING + (idx % NST) * TILE + aoff;
#pragma unroll
                for (int mt = 0; mt < 4; mt++) ldsm4t(tb ^ (mt << 5), wf[s * 4 + mt]);
            }
        }
        {
            const int hq = cta >> 2, kvh = hq >> 2, hh = hq & 3, ds = cta & 3;
            const int b = tid >> 7, dpl = (tid >> 3) & 15, j = tid & 7;
            const int pc = (b * 8 + kvh) * 8 + j;
            struct SetA { uint4 o, m[8]; } pa, pb;
            const uint4* po = &sc->part_o[pc][hh][ds * 16 + dpl];
            const uint4* pm = &sc->part_ml[pc - j][hh][0];
#define LOAD_A(S) { S.o = ld_ll4(po); _Pragma("unroll") for (int jj = 0; jj < 8; jj++) S.m[jj] = ld_ll4(pm + jj * 8); }
#define OK_A(S) (S.o.y == F_PART && S.o.w == F_PART && S.m[0].y == F_PART && S.m[0].w == F_PART && S.m[1].y == F_PART && S.m[1].w == F_PART && \
                 S.m[2].y == F_PART && S.m[2].w == F_PART && S.m[3].y == F_PART && S.m[3].w == F_PART && S.m[4].y == F_PART && S.m[4].w == F_PART && \
                 S.m[5].y == F_PART && S.m[5].w == F_PART && S.m[6].y == F_PART && S.m[6].w == F_PART && S.m[7].y == F_PART && S.m[7].w == F_PART)
            float L, o0, o1;
#define USE_A(S) {                                                                                   \
                float M = __uint_as_float(S.m[0].x);                                                 \
                _Pragma("unroll") for (int jj = 1; jj < 8; jj++) M = fmaxf(M, __uint_as_float(S.m[jj].x)); \
                float wt = 0.f; L = 0.f;                                                             \
                _Pragma("unroll") for (int jj = 0; jj < 8; jj++) {                                   \
                    const float w_ = ex2((__uint_as_float(S.m[jj].x) - M) * LOG2E);                  \
                    L += w_ * __uint_as_float(S.m[jj].z);                                            \
                    wt = jj == j ? w_ : wt;                                                          \
                }                                                                                    \
                o0 = wt * __uint_as_float(S.o.x); o1 = wt * __uint_as_float(S.o.z); }
            POLL2(pa, pb, LOAD_A, OK_A, USE_A)
#pragma unroll
            for (int o_ = 1; o_ < 8; o_ <<= 1) {
                o0 += __shfl_xor_sync(0xffffffffu, o0, o_);
                o1 += __shfl_xor_sync(0xffffffffu, o1, o_);
            }
            uint32_t* os = (uint32_t*)(sgen + SM_OS);
            const float rl = rcp_approx(L);
            if (j == 0) os[b * 16 + dpl] = pack_bf16(o0 * rl, o1 * rl);
            if (WO_AT == KV_TILES) {
#pragma unroll
            for (int s = 0; s < 2; s++) {
                constexpr int i0 = IDX_WO;
                const int idx = i0 + s;
                mbar_wait(bar_full + 8 * (idx % NST), (idx / NST) & 1);
                const uint32_t tb = sbase + SM_RING + (idx % NST) * TILE + aoff;
#pragma unroll
                for (int mt = 0; mt < 4; mt++) ldsm4t(tb ^ (mt << 5), wf[s * 4 + mt]);
            }
            }
            cons_sync();
            if (FF_TRIG == 2 && tid == 0) mbar_arrive(bar_go_ff);
            if (warp == 0) TSTAMP(7);
            float y[4][4] = {};
#pragma unroll
            for (int s = 0; s < 2; s++) {
                const uint32_t b0 = os[bb * 16 + 8 * s + t], b1 = os[bb * 16 + 8 * s + 4 + t];
#pragma unroll
                for (int mt = 0; mt < 4; mt++) mma16816(y[mt], wf[s * 4 + mt], b0, b1);
            }
            float v[4];
#pragma unroll
            for (int i = 0; i < 4; i++) v[i] = t == 0 ? y[0][i] : t == 1 ? y[1][i] : t == 2 ? y[2][i] : y[3][i];
            const int col = 64 * warp + 16 * t + g;
            st_ll4(&sc->inbox[col >> 2][cta][col & 3], __float_as_uint(v[0]), __float_as_uint(v[1]), F_WO);
            st_ll4(&sc->inbox[(col + 8) >> 2][cta][col & 3], __float_as_uint(v[2]), __float_as_uint(v[3]), F_WO);
        }
        if (FF_TRIG == 3 && tid == 0) mbar_arrive(bar_go_ff);
        if (warp == 0) TSTAMP(8);
        float xm0 = 0.f, xm1 = 0.f;
        {
            struct SetB { uint4 a, b; } pa, pb;
            const uint4* pin = &sc->inbox[cta][0][0] + tid;
#define LOAD_B(S) { S.a = ld_ll4(pin); S.b = ld_ll4(pin + 256); }
#define OK_B(S) (S.a.y == F_WO && S.a.w == F_WO && S.b.y == F_WO && S.b.w == F_WO)
            float s0, s1;
#define USE_B(S) { s0 = __uint_as_float(S.a.x) + __uint_as_float(S.b.x); s1 = __uint_as_float(S.a.z) + __uint_as_float(S.b.z); }
            POLL2(pa, pb, LOAD_B, OK_B, USE_B)
#pragma unroll
            for (int o_ = 4; o_ < 32; o_ <<= 1) { s0 += __shfl_xor_sync(0xffffffffu, s0, o_); s1 += __shfl_xor_sync(0xffffffffu, s1, o_); }
            if (lane < 4) *(float2*)&red2[warp * 8 + lane * 2] = make_float2(s0, s1);
            cons_sync();
            if (warp == 0) {
                float a0 = 0.f, a1 = 0.f;
#pragma unroll
                for (int w = 0; w < 8; w++) { const float2 v = *(const float2*)&red2[w * 8 + (lane & 3) * 2]; a0 += v.x; a1 += v.y; }
                const bool hi = ocol & 1;
                const float ga0 = hi ? bf_hi(m_ga0.x) : bf_lo(m_ga0.x), ga1 = hi ? bf_hi(m_ga1.x) : bf_lo(m_ga1.x);
                xm0 = bf16r(xo0 + bf16r(ga0 * bf16r(a0)));
                xm1 = bf16r(xo1 + bf16r(ga1 * bf16r(a1)));
                if (lane < 4) st_ll2((uint2*)&sc->inbox[cta][NCTA - 1][0] + lane, pack_bf16(xm0, xm1), F_X1);
                TSTAMP(10);
            }
        }
        if (cta < NFFN) {
            uint32_t gf[4][4], uf[4][4];
            mbar_wait(bar_full + 8 * (IDX_WG % NST), (IDX_WG / NST) & 1);
            mbar_wait(bar_full + 8 * (IDX_WU % NST), (IDX_WU / NST) & 1);
            {
                const uint32_t tg = sbase + SM_RING + (IDX_WG % NST) * TILE, tu = sbase + SM_RING + (IDX_WU % NST) * TILE;
#pragma unroll
                for (int s = 0; s < 4; s++) {
                    const int row = 64 * warp + 16 * s + (lane & 7) + (lane >> 4) * 8;
                    const uint32_t off = row * 32 + ((((lane >> 3) & 1) ^ ((row >> 2) & 1)) << 4);
                    ldsm4t(tg + off, gf[s]);
                    ldsm4t(tu + off, uf[s]);
                }
            }
            if (warp == 0) TSTAMP(11);
            uint32_t hb[8];
            {
                struct SetX { uint4 a, b; uint2 p; } pa, pb;
                const uint4* px = &sc->inbox[ec >> 2][NCTA - 1][0];
                const uint2* pp = (const uint2*)&sc->inbox[0][NCTA - 1][0];
#define LOAD_X(S) { S.a = ld_ll4(px); S.b = ld_ll4(px + 1); S.p = ld_ll2(pp); }
#define OK_X(S) (S.a.y == F_X1 && S.a.w == F_X1 && S.b.y == F_X1 && S.b.w == F_X1 && S.p.y == F_X1)
                float xv[4], pivot;
#define USE_X(S) { xv[0] = eb ? bf_hi(S.a.x) : bf_lo(S.a.x); xv[1] = eb ? bf_hi(S.a.z) : bf_lo(S.a.z);   \
                   xv[2] = eb ? bf_hi(S.b.x) : bf_lo(S.b.x); xv[3] = eb ? bf_hi(S.b.z) : bf_lo(S.b.z);   \
                   pivot = eb ? bf_hi(S.p.x) : bf_lo(S.p.x); }
                POLL2(pa, pb, LOAD_X, OK_X, USE_X)
                if (warp == 0) TSTAMP(9);
                const float2 ps = half_warp_sums(xv, pivot);
                if ((lane & 15) == 0) stat[warp * 2 + eb] = ps;
                cons_sync();
                float mean_bf, rstd;
                ln_stats(stat, eb, pivot, mean_bf, rstd);
                *(uint2*)&hs[eb * 32 + 2 * (lane & 15)] = make_uint2(
                    pack_bf16(ln_mod(ln_norm(xv[0], mean_bf, rstd), bf_lo(m_cb.x), bf_lo(m_sb.x)),
                              ln_mod(ln_norm(xv[1], mean_bf, rstd), bf_hi(m_cb.x), bf_hi(m_sb.x))),
                    pack_bf16(ln_mod(ln_norm(xv[2], mean_bf, rstd), bf_lo(m_cb.z), bf_lo(m_sb.z)),
                              ln_mod(ln_norm(xv[3], mean_bf, rstd), bf_hi(m_cb.z), bf_hi(m_sb.z))));
                __syncwarp();
#pragma unroll
                for (int i = 0; i < 8; i++) hb[i] = hs[bb * 32 + 8 * (i >> 1) + 4 * (i & 1) + t];
            }
            {
                float cg[2][4] = {}, cu[2][4] = {};
#pragma unroll
                for (int s = 0; s < 4; s++) {
                    mma16816(cg[s & 1], gf[s], hb[2 * s], hb[2 * s + 1]);
                    mma16816(cu[s & 1], uf[s], hb[2 * s], hb[2 * s + 1]);
                }
                if (t < 2) {
                    float v[4];
#pragma unroll
                    for (int i = 0; i < 4; i++) v[i] = t ? cu[0][i] + cu[1][i] : cg[0][i] + cg[1][i];
                    *(float2*)&red[warp * 64 + t * 32 + g * 2] = make_float2(v[0], v[1]);
                    *(float2*)&red[warp * 64 + t * 32 + (g + 8) * 2] = make_float2(v[2], v[3]);
                }
            }
            uint32_t df[4][4];
            mbar_wait(bar_full + 8 * (IDX_WD % NST), (IDX_WD / NST) & 1);
#pragma unroll
            for (int mt = 0; mt < 4; mt++) ldsm4t((sbase + SM_RING + (IDX_WD % NST) * TILE + aoff) ^ (mt << 5), df[mt]);
            cons_sync();
            {
                float gs = 0.f, us = 0.f;
#pragma unroll
                for (int w = 0; w < 8; w++) { gs += red[w * 64 + lane]; us += red[w * 64 + 32 + lane]; }
                gs = bf16r(gs);
                const float u2 = gs * (1.0f + 0.044715f * gs * gs) * (2.0f * 0.7978845608028654f * LOG2E);
                const float ge = bf16r(__fdividef(gs, 1.0f + ex2(-u2)));
                const float act = bf16r(ge * bf16r(us));
                const float a0 = __shfl_sync(0xffffffffu, act, 4 * t + bb), a1 = __shfl_sync(0xffffffffu, act, 4 * t + 2 + bb);
                const float a2 = __shfl_sync(0xffffffffu, act, 4 * t + 16 + bb), a3 = __shfl_sync(0xffffffffu, act, 4 * t + 18 + bb);
                const uint32_t b0 = pack_bf16(a0, a1), b1 = pack_bf16(a2, a3);
                float y[4][4] = {};
#pragma unroll
                for (int mt = 0; mt < 4; mt++) mma16816(y[mt], df[mt], b0, b1);
                float v[4];
#pragma unroll
                for (int i = 0; i < 4; i++) v[i] = t == 0 ? y[0][i] : t == 1 ? y[1][i] : t == 2 ? y[2][i] : y[3][i];
                const int col = 64 * warp + 16 * t + g;
                st_ll4(&sc->inbox[col >> 2][cta][col & 3], __float_as_uint(v[0]), __float_as_uint(v[1]), F_DOWN);
                st_ll4(&sc->inbox[(col + 8) >> 2][cta][col & 3], __float_as_uint(v[2]), __float_as_uint(v[3]), F_DOWN);
            }
            if (warp == 0) TSTAMP(12);
        }
        {
            struct SetB { uint4 a, b; } pa, pb;
            const uint4* pin = &sc->inbox[cta][0][0] + tid;
            const bool two = tid < NFFN * 4 - 256;
            pa.b = pb.b = make_uint4(0u, F_DOWN, 0u, F_DOWN);
#define LOAD_C(S) { S.a = ld_ll4(pin); if (two) S.b = ld_ll4(pin + 256); }
#define OK_C(S) (S.a.y == F_DOWN && S.a.w == F_DOWN && S.b.y == F_DOWN && S.b.w == F_DOWN)
            float s0, s1;
            POLL2(pa, pb, LOAD_C, OK_C, USE_B)
#pragma unroll
            for (int o_ = 4; o_ < 32; o_ <<= 1) { s0 += __shfl_xor_sync(0xffffffffu, s0, o_); s1 += __shfl_xor_sync(0xffffffffu, s1, o_); }
            if (lane < 4) *(float2*)&red2[64 + warp * 8 + lane * 2] = make_float2(s0, s1);
            cons_sync();
            if (warp == 0) {
                float a0 = 0.f, a1 = 0.f;
#pragma unroll
                for (int w = 0; w < 8; w++) { const float2 v = *(const float2*)&red2[64 + w * 8 + (lane & 3) * 2]; a0 += v.x; a1 += v.y; }
                const bool hi = ocol & 1;
                const float gb0 = hi ? bf_hi(m_gb0.x) : bf_lo(m_gb0.x), gb1 = hi ? bf_hi(m_gb1.x) : bf_lo(m_gb1.x);
                if (lane < 4) {
                    p.out[ocol] = __float2bfloat16_rn(xm0 + bf16r(gb0 * bf16r(a0)));
                    p.out[D_MODEL + ocol] = __float2bfloat16_rn(xm1 + bf16r(gb1 * bf16r(a1)));
                }
                if (cta == 0 && lane == 0) *(volatile unsigned*)&sc->epoch = tag;
                TSTAMP(13);
            }
        }
    }
}

typedef CUresult (*EncodeFn)(CUtensorMap*, CUtensorMapDataType, cuuint32_t, void*, const cuuint64_t*, const cuuint64_t*,
                             const cuuint32_t*, const cuuint32_t*, CUtensorMapInterleave, CUtensorMapSwizzle,
                             CUtensorMapL2promotion, CUtensorMapFloatOOBfill);

struct Maps { CUtensorMap k, v, wq, wmod, wo, wg, wu, wd; };

void encode(EncodeFn fn, CUtensorMap* m, const void* ptr, int rank, const cuuint64_t* dims, const cuuint64_t* strides,
            const cuuint32_t* box, CUtensorMapSwizzle sw) {
    const cuuint32_t es[3] = {1, 1, 1};
    fn(m, CU_TENSOR_MAP_DATA_TYPE_BFLOAT16, rank, const_cast<void*>(ptr), dims, strides, box, es,
       CU_TENSOR_MAP_INTERLEAVE_NONE, sw, CU_TENSOR_MAP_L2_PROMOTION_L2_256B, CU_TENSOR_MAP_FLOAT_OOB_FILL_NONE);
}

}

extern "C" void kernel_launch(void* const* d_in, const int* in_sizes, int n_in, void* d_out, int out_size) {
    (void)in_sizes; (void)n_in; (void)out_size;
    static EncodeFn enc = nullptr;
    static Scratch* scratch = nullptr;
    if (!enc) {
        cudaGetSymbolAddress((void**)&scratch, g_scratch);
        void* fn = nullptr;
        cudaDriverEntryPointQueryResult qr;
        cudaGetDriverEntryPoint("cuTensorMapEncodeTiled", &fn, cudaEnableDefault, &qr);
        enc = (EncodeFn)fn;
        cudaFuncSetAttribute(fused_block_kernel, cudaFuncAttributeMaxDynamicSharedMemorySize, SMEM_BYTES);
    }
    Maps m;
    {
        const cuuint64_t dims[3] = {64, (cuuint64_t)16 * SK, 2}, str[2] = {256, 128};
        const cuuint32_t box[3] = {64, 64, 2};
        encode(enc, &m.k, d_in[1], 3, dims, str, box, CU_TENSOR_MAP_SWIZZLE_128B);
        encode(enc, &m.v, d_in[2], 3, dims, str, box, CU_TENSOR_MAP_SWIZZLE_128B);
    }
    {
        const cuuint64_t dims[2] = {4096, 512}, str[1] = {8192};
        const cuuint32_t box[2] = {32, 256};
        encode(enc, &m.wq, d_in[3], 2, dims, str, box, CU_TENSOR_MAP_SWIZZLE_64B);
    }
    {
        const cuuint64_t dims[2] = {N_MOD, 512}, str[1] = {N_MOD * 2};
        const cuuint32_t box[2] = {16, 256};
        encode(enc, &m.wmod, d_in[10], 2, dims, str, box, CU_TENSOR_MAP_SWIZZLE_32B);
    }
    {
        const cuuint64_t dims_o[3] = {64, 4096, 8}, dims_d[3] = {64, D_FF, 8}, str[2] = {1024, 128};
        const cuuint32_t box[3] = {64, 16, 8};
        encode(enc, &m.wo, d_in[4], 3, dims_o, str, box, CU_TENSOR_MAP_SWIZZLE_128B);
        encode(enc, &m.wd, d_in[8], 3, dims_d, str, box, CU_TENSOR_MAP_SWIZZLE_128B);
    }
    {
        const cuuint64_t dims[2] = {D_FF, 512}, str[1] = {D_FF * 2};
        const cuuint32_t box[2] = {16, 256};
        encode(enc, &m.wg, d_in[6], 2, dims, str, box, CU_TENSOR_MAP_SWIZZLE_32B);
        encode(enc, &m.wu, d_in[7], 2, dims, str, box, CU_TENSOR_MAP_SWIZZLE_32B);
    }
    Params p;
    p.x = (const __nv_bfloat16*)d_in[0];
    p.c = (const __nv_bfloat16*)d_in[9];
    p.w_mod = (const __nv_bfloat16*)d_in[10];
    p.out = (__nv_bfloat16*)d_out;
    p.sc = scratch;
    fused_block_kernel<<<NCTA, NTHREADS, SMEM_BYTES, cudaStreamPerThread>>>(p, m.k, m.v, m.wq, m.wmod, m.wo, m.wg, m.wu, m.wd);
}
```

```cpp
#include <cuda_runtime.h>
#include <cuda.h>
#include <cuda_bf16.h>
#include <stdint.h>

namespace {

constexpr int D_MODEL = 512;
constexpr int N_HEADS = 32;
constexpr int SK = 32768;
constexpr int DH = 128;
constexpr int D_FF = 1792;
constexpr int N_MOD = 6 * D_MODEL;

constexpr int NCTA = 128;
constexpr int NFFN = D_FF / 16;
constexpr int NTHREADS = 320;
constexpr int NST = 12;
constexpr int TILE = 16384;
#define INFL_PRO 2
#define INFL_MAIN 3
#define INFL_TAIL 2
#define PACE_HI 96
#define PACE_LO 96
#define PACE_SLEEP 200
#define WO_TRIG 0
#define FF_TRIG 0
#define PF_WO 0
#define PF_FF 0
#define PRO_TILES 8
constexpr int KV_TILES = 64;
#define MOD_AT 8
#define WO_AT 64
#define FF_AT 64
static_assert(MOD_AT % 2 == 0 && MOD_AT < WO_AT && WO_AT <= FF_AT && FF_AT <= KV_TILES, "schedule");
__host__ __device__ constexpr int kv_idx(int i) {
    return 2 + 2 * i + (i >= MOD_AT ? 1 : 0) + (i >= WO_AT ? 2 : 0) + (i >= FF_AT ? 3 : 0);
}
constexpr int IDX_MOD = 2 + 2 * MOD_AT;
constexpr int IDX_WO = 3 + 2 * WO_AT;
constexpr int IDX_WG = 5 + 2 * FF_AT;
constexpr int IDX_WU = IDX_WG + 1;
constexpr int IDX_WD = IDX_WU + 1;
constexpr int N_TILES = 2 + 2 * KV_TILES + 1 + 2 + 3;
static_assert(N_TILES - 1 - IDX_WO < NST, "wo and the FFN weights must stay resident until the end");
constexpr int SPIN_LIMIT = 1 << 20;

constexpr float LOG2E = 1.4426950408889634f;
constexpr float QK_SCALE = 0.08838834764831845f;

constexpr int SM_RING = 0;
constexpr int SM_MRG = SM_RING + NST * TILE;
constexpr int SM_ML = SM_MRG + 8 * 4 * 136 * 4;
constexpr int SM_RED = SM_ML + 8 * 4 * 8;
constexpr int SM_RED2 = SM_RED + 8 * 64 * 4;
constexpr int SM_QS = SM_RED2 + 8 * 64 * 4;
constexpr int SM_OS = SM_QS + 512 * 2;
constexpr int SM_SC = SM_OS + 2 * 16 * 4;
constexpr int SM_HS = SM_SC + 2 * 512 * 2;
constexpr int SM_STAT = SM_HS + 8 * 2 * 32 * 4;
constexpr int SM_PACE = SM_STAT + 8 * 2 * 8;
constexpr int SM_BAR = SM_PACE + 8;
constexpr int SM_END = SM_BAR + (2 * NST + 3) * 8;
constexpr int SMEM_BYTES = SM_END + 1024;

struct Scratch {
    uint4 inbox[NCTA][NCTA][2];
    uint2 x1[NCTA][4];
    uint2 part_o[NCTA][4][64];
    uint2 part_ml[NCTA][4];
    uint2 mod[2][N_MOD / 2];
    uint2 q[2][N_HEADS * DH / 2];
    unsigned epoch;
    unsigned pad_[31];
    unsigned cleared;
    unsigned pad2_[31];
    unsigned progress;
};
__device__ Scratch g_scratch;
constexpr uint32_t F_PART = 1, F_WO = 1, F_DOWN = 2, F_X1 = 1;
__device__ __forceinline__ uint32_t tagf(float v, uint32_t f) { return (__float_as_uint(v) & ~3u) | f; }
__device__ __forceinline__ float untag(uint32_t v) { return __uint_as_float(v & ~3u); }

struct Params {
    const __nv_bfloat16* x;
    const __nv_bfloat16* c;
    const __nv_bfloat16* w_mod;
    __nv_bfloat16* out;
    Scratch* sc;
};

#define TSTAMP(i) do { } while (0)

__device__ __forceinline__ uint32_t smem_u32(const void* p) { return (uint32_t)__cvta_generic_to_shared(p); }

__device__ __forceinline__ void mbar_init(uint32_t bar, uint32_t cnt) {
    asm volatile("mbarrier.init.shared::cta.b64 [%0], %1;" ::"r"(bar), "r"(cnt) : "memory");
}
__device__ __forceinline__ void mbar_expect_tx(uint32_t bar, uint32_t bytes) {
    asm volatile("mbarrier.arrive.expect_tx.shared::cta.b64 _, [%0], %1;" ::"r"(bar), "r"(bytes) : "memory");
}
__device__ __forceinline__ void mbar_arrive(uint32_t bar) {
    asm volatile("mbarrier.arrive.shared::cta.b64 _, [%0];" ::"r"(bar) : "memory");
}
__device__ __forceinline__ bool mbar_try(uint32_t bar, uint32_t parity) {
    uint32_t ok;
    asm volatile(
        "{\n\t.reg .pred p;\n\t"
        "mbarrier.try_wait.parity.shared::cta.b64 p, [%1], %2;\n\t"
        "selp.u32 %0, 1, 0, p;\n\t}"
        : "=r"(ok) : "r"(bar), "r"(parity) : "memory");
    return ok != 0;
}
__device__ __forceinline__ void mbar_wait(uint32_t bar, uint32_t parity) {
    if (mbar_try(bar, parity)) return;
    for (int i = 0; i < SPIN_LIMIT; i++)
        if (mbar_try(bar, parity)) return;
}
__device__ __forceinline__ void cons_sync() { asm volatile("bar.sync 1, 256;" ::: "memory"); }

__device__ __forceinline__ void tma_2d(uint32_t dst, const CUtensorMap* m, int c0, int c1, uint32_t bar) {
    asm volatile("cp.async.bulk.tensor.2d.shared::cluster.global.mbarrier::complete_tx::bytes [%0], [%1, {%3, %4}], [%2];"
                 ::"r"(dst), "l"(m), "r"(bar), "r"(c0), "r"(c1) : "memory");
}
__device__ __forceinline__ void tma_3d(uint32_t dst, const CUtensorMap* m, int c0, int c1, int c2, uint32_t bar) {
    asm volatile("cp.async.bulk.tensor.3d.shared::cluster.global.mbarrier::complete_tx::bytes [%0], [%1, {%3, %4, %5}], [%2];"
                 ::"r"(dst), "l"(m), "r"(bar), "r"(c0), "r"(c1), "r"(c2) : "memory");
}
__device__ __forceinline__ void tma_3d_hint(uint32_t dst, const CUtensorMap* m, int c0, int c1, int c2, uint32_t bar, uint64_t pol) {
    asm volatile("cp.async.bulk.tensor.3d.shared::cluster.global.mbarrier::complete_tx::bytes.L2::cache_hint [%0], [%1, {%3, %4, %5}], [%2], %6;"
                 ::"r"(dst), "l"(m), "r"(bar), "r"(c0), "r"(c1), "r"(c2), "l"(pol) : "memory");
}
__device__ __forceinline__ void l2pf_2d(const CUtensorMap* m, int c0, int c1) {
    asm volatile("cp.async.bulk.prefetch.tensor.2d.L2.global.tile [%0, {%1, %2}];" ::"l"(m), "r"(c0), "r"(c1) : "memory");
}
__device__ __forceinline__ void l2pf_3d(const CUtensorMap* m, int c0, int c1, int c2) {
    asm volatile("cp.async.bulk.prefetch.tensor.3d.L2.global.tile [%0, {%1, %2, %3}];" ::"l"(m), "r"(c0), "r"(c1), "r"(c2) : "memory");
}
__device__ __forceinline__ void prefetch_tmap(const CUtensorMap* m) {
    asm volatile("prefetch.tensormap [%0];" ::"l"(m) : "memory");
}

__device__ __forceinline__ void ldsm4(uint32_t addr, uint32_t (&r)[4]) {
    asm volatile("ldmatrix.sync.aligned.m8n8.x4.shared.b16 {%0,%1,%2,%3}, [%4];"
                 : "=r"(r[0]), "=r"(r[1]), "=r"(r[2]), "=r"(r[3]) : "r"(addr) : "memory");
}
__device__ __forceinline__ void ldsm4t(uint32_t addr, uint32_t (&r)[4]) {
    asm volatile("ldmatrix.sync.aligned.m8n8.x4.trans.shared.b16 {%0,%1,%2,%3}, [%4];"
                 : "=r"(r[0]), "=r"(r[1]), "=r"(r[2]), "=r"(r[3]) : "r"(addr) : "memory");
}
__device__ __forceinline__ void mma16816(float (&c)[4], const uint32_t (&a)[4], uint32_t b0, uint32_t b1) {
    asm volatile("mma.sync.aligned.m16n8k16.row.col.f32.bf16.bf16.f32 {%0,%1,%2,%3}, {%4,%5,%6,%7}, {%8,%9}, {%0,%1,%2,%3};"
                 : "+f"(c[0]), "+f"(c[1]), "+f"(c[2]), "+f"(c[3])
                 : "r"(a[0]), "r"(a[1]), "r"(a[2]), "r"(a[3]), "r"(b0), "r"(b1));
}
__device__ __forceinline__ uint32_t movmatrix_t(uint32_t a) {
    uint32_t d;
    asm volatile("movmatrix.sync.aligned.m8n8.trans.b16 %0, %1;" : "=r"(d) : "r"(a));
    return d;
}
__device__ __forceinline__ uint32_t pack_bf16(float a, float b) {
    uint32_t r;
    asm("cvt.rn.bf16x2.f32 %0, %1, %2;" : "=r"(r) : "f"(b), "f"(a));
    return r;
}
__device__ __forceinline__ float bf_lo(uint32_t v) { return __uint_as_float(v << 16); }
__device__ __forceinline__ float bf_hi(uint32_t v) { return __uint_as_float(v & 0xffff0000u); }
__device__ __forceinline__ float bf16r(float a) { return bf_lo(pack_bf16(a, 0.f)); }
__device__ __forceinline__ uint32_t max_bf16x2(uint32_t a, uint32_t b) {
    uint32_t r;
    asm("max.bf16x2 %0, %1, %2;" : "=r"(r) : "r"(a), "r"(b));
    return r;
}
__device__ __forceinline__ float ex2(float x) {
    float r;
    asm("ex2.approx.ftz.f32 %0, %1;" : "=f"(r) : "f"(x));
    return r;
}

__device__ __forceinline__ void st_ll2(uint2* p, uint32_t v, uint32_t tag) {
    asm volatile("st.relaxed.gpu.global.v2.u32 [%0], {%1, %2};" ::"l"(p), "r"(v), "r"(tag) : "memory");
}
__device__ __forceinline__ void st_ll4(uint4* p, uint32_t v0, uint32_t v1, uint32_t tag) {
    asm volatile("st.relaxed.gpu.global.v4.u32 [%0], {%1, %2, %3, %2};" ::"l"(p), "r"(v0), "r"(tag), "r"(v1) : "memory");
}
__device__ __forceinline__ void st_v4(uint4* p, uint32_t a, uint32_t b, uint32_t c, uint32_t d) {
    asm volatile("st.relaxed.gpu.global.v4.u32 [%0], {%1, %2, %3, %4};" ::"l"(p), "r"(a), "r"(b), "r"(c), "r"(d) : "memory");
}
__device__ __forceinline__ uint2 ld_ll2(const uint2* p) {
    uint2 v;
    asm volatile("ld.relaxed.gpu.global.v2.u32 {%0, %1}, [%2];" : "=r"(v.x), "=r"(v.y) : "l"(p) : "memory");
    return v;
}
__device__ __forceinline__ uint4 ld_ll4(const uint4* p) {
    uint4 v;
    asm volatile("ld.relaxed.gpu.global.v4.u32 {%0, %1, %2, %3}, [%4];"
                 : "=r"(v.x), "=r"(v.y), "=r"(v.z), "=r"(v.w) : "l"(p) : "memory");
    return v;
}

#define DELAY_B1 300
#define DELAY_B2 0
#define DELAY_C 300
__device__ __forceinline__ uint32_t clock32() {
    uint32_t c;
    asm volatile("mov.u32 %0, %clock;" : "=r"(c));
    return c;
}
__device__ __forceinline__ void spin_cycles(uint32_t n) {
    if (n > 0) { const uint32_t c0 = clock32(); while (clock32() - c0 < n) {} }
}
__device__ __forceinline__ float rcp_approx(float x) {
    float r;
    asm("rcp.approx.ftz.f32 %0, %1;" : "=f"(r) : "f"(x));
    return r;
}
__device__ __forceinline__ float sqrt_approx(float x) {
    float r;
    asm("sqrt.approx.f32 %0, %1;" : "=f"(r) : "f"(x));
    return r;
}

__device__ __forceinline__ float silu_bf(float v) { return bf16r(v / (1.0f + expf(-v))); }

__device__ __forceinline__ float2 half_warp_sums(const float (&v)[4], float pivot) {
    float s1 = 0.f, s2 = 0.f;
#pragma unroll
    for (int i = 0; i < 4; i++) { const float d = v[i] - pivot; s1 += d; s2 += d * d; }
#pragma unroll
    for (int o = 1; o < 16; o <<= 1) { s1 += __shfl_xor_sync(0xffffffffu, s1, o); s2 += __shfl_xor_sync(0xffffffffu, s2, o); }
    return make_float2(s1, s2);
}
__device__ __forceinline__ void ln_stats(const float2* stat, int b, float pivot, float& mean_bf, float& rstd) {
    float s1 = 0.f, s2 = 0.f;
#pragma unroll
    for (int w = 0; w < 8; w++) { const float2 v = stat[w * 2 + b]; s1 += v.x; s2 += v.y; }
    const float dm = s1 * (1.0f / D_MODEL);
    const float var = fmaxf(s2 * (1.0f / D_MODEL) - dm * dm, 0.f);
    mean_bf = bf16r(pivot + dm);
    rstd = rcp_approx(bf16r(sqrt_approx(bf16r(bf16r(var) + 1e-5f))));
}
__device__ __forceinline__ float ln_norm(float xv, float mean_bf, float rstd) { return bf16r(bf16r(xv - mean_bf) * rstd); }
__device__ __forceinline__ float ln_mod(float n, float cmul, float sadd) { return bf16r(n * bf16r(1.0f + cmul)) + sadd; }

__global__ void __launch_bounds__(NTHREADS, 1)
fused_block_kernel(const Params p, const __grid_constant__ CUtensorMap tm_k, const __grid_constant__ CUtensorMap tm_v,
                   const __grid_constant__ CUtensorMap tm_wq, const __grid_constant__ CUtensorMap tm_wmod,
                   const __grid_constant__ CUtensorMap tm_wo, const __grid_constant__ CUtensorMap tm_wg,
                   const __grid_constant__ CUtensorMap tm_wu, const __grid_constant__ CUtensorMap tm_wd) {
    extern __shared__ unsigned char smem_raw[];
    const uint32_t sbase = (smem_u32(smem_raw) + 1023u) & ~1023u;
    unsigned char* sgen = smem_raw + (sbase - smem_u32(smem_raw));
    const int tid = threadIdx.x, warp = tid >> 5, lane = tid & 31;
    const int cta = blockIdx.x;
    const uint32_t bar_full = sbase + SM_BAR, bar_empty = bar_full + NST * 8;
    const uint32_t bar_clear = bar_empty + NST * 8;
    const uint32_t bar_go_wo = bar_clear + 8, bar_go_ff = bar_clear + 16;

    if (warp == 8) {
        if (lane == 0) {
            prefetch_tmap(&tm_wq);
            for (int i = 0; i < NST; i++) { mbar_init(bar_full + 8 * i, 1); mbar_init(bar_empty + 8 * i, 4); }
            mbar_init(bar_clear, 1);
            mbar_init(bar_go_wo, 1);
            mbar_init(bar_go_ff, 1);
            ((volatile uint32_t*)(sgen + SM_PACE))[0] = 0;
            ((volatile uint32_t*)(sgen + SM_PACE))[1] = INFL_MAIN;
            asm volatile("fence.mbarrier_init.release.cluster;" ::: "memory");
        }
        __syncwarp();
        asm volatile("bar.arrive 2, 320;" ::: "memory");
        asm volatile("bar.arrive 3, 64;" ::: "memory");
        if (lane == 0) {
            const int pair = cta >> 3, j = cta & 7;
            const int key0 = pair * SK + j * 64;
            uint64_t pol;
            asm volatile("createpolicy.fractional.L2::evict_first.b64 %0, 1.0;" : "=l"(pol));
            int slot = 0; uint32_t ph = 1;
            int landed = 0, wslot = 0; uint32_t wph = 0;
            int kv = 0;
            for (int idx = 0; idx < N_TILES; idx++) {
                if (idx >= NST) mbar_wait(bar_empty + 8 * slot, ph);
                if (idx == kv_idx(KV_TILES - 1) + 2) {
                    if (PF_WO == 1) { l2pf_3d(&tm_wo, 0, cta * 32, 0); l2pf_3d(&tm_wo, 0, cta * 32 + 16, 0); }
                }
                if ((PF_FF == 1 && idx == kv_idx(KV_TILES - 1) + 2) || (PF_FF == 2 && idx == IDX_WG)) {
                    if (cta < NFFN) {
                        l2pf_2d(&tm_wg, cta * 16, 0); l2pf_2d(&tm_wg, cta * 16, 256);
                        l2pf_2d(&tm_wu, cta * 16, 0); l2pf_2d(&tm_wu, cta * 16, 256);
                        l2pf_3d(&tm_wd, 0, cta * 16, 0);
                    }
                }
                const int window = idx < PRO_TILES ? INFL_PRO : idx >= kv_idx(KV_TILES - 1) + 2 ? INFL_TAIL
                                                               : (int)((volatile uint32_t*)(sgen + SM_PACE))[1];
                while (landed + window <= idx) {
                    mbar_wait(bar_full + 8 * wslot, wph);
                    if (++wslot == NST) { wslot = 0; wph ^= 1; }
                    landed++;
                }
                if (WO_TRIG != 0 && idx == IDX_WO) mbar_wait(bar_go_wo, 0);
                if (FF_TRIG != 0 && idx == IDX_WG) mbar_wait(bar_go_ff, 0);
                const uint32_t fb = bar_full + 8 * slot, dst = sbase + SM_RING + slot * TILE;
                if (idx == 0) { prefetch_tmap(&tm_k); prefetch_tmap(&tm_v); prefetch_tmap(&tm_wmod); }
                if (idx == 12) { prefetch_tmap(&tm_wo); prefetch_tmap(&tm_wg); prefetch_tmap(&tm_wu); prefetch_tmap(&tm_wd); }
                if (idx >= IDX_WG && idx <= IDX_WD && cta >= NFFN) {
                    mbar_arrive(fb);
                } else {
                    mbar_expect_tx(fb, TILE);
                    if (idx < 2) {
                        tma_2d(dst, &tm_wq, cta * 32, idx * 256, fb);
                    } else if (idx == IDX_MOD) {
                        tma_2d(dst, &tm_wmod, 1024 + cta * 16, 0, fb);
                        tma_2d(dst + 8192, &tm_wmod, 1024 + cta * 16, 256, fb);
                    } else if (idx == IDX_WO || idx == IDX_WO + 1) {
                        tma_3d(dst, &tm_wo, 0, cta * 32 + (idx - IDX_WO) * 16, 0, fb);
                    } else if (idx == IDX_WG || idx == IDX_WU) {
                        const CUtensorMap* m = idx == IDX_WG ? &tm_wg : &tm_wu;
                        tma_2d(dst, m, cta * 16, 0, fb);
                        tma_2d(dst + 8192, m, cta * 16, 256, fb);
                    } else if (idx == IDX_WD) {
                        tma_3d(dst, &tm_wd, 0, cta * 16, 0, fb);
                    } else {
                        tma_3d_hint(dst, (kv & 1) ? &tm_v : &tm_k, 0, key0 + (kv >> 1) * 512, 0, fb, pol);
                        kv++;
                    }
                }
                ((volatile uint32_t*)(sgen + SM_PACE))[0] = idx + 1;
                if (++slot == NST) { slot = 0; ph ^= 1; }
            }
        }
    } else if (warp == 9) {
        Scratch* const sc = p.sc;
        const uint32_t tag = *(volatile unsigned*)&sc->epoch + 1;
        if (lane < 2) {
            st_ll4((uint4*)&sc->mod[lane][cta * 4], 0u, 0u, 0u);
            st_ll4((uint4*)&sc->mod[lane][cta * 4] + 1, 0u, 0u, 0u);
        }
        if (lane < 8) st_ll4((uint4*)&sc->mod[lane >> 2][512 + cta * 8] + (lane & 3), 0u, 0u, 0u);
        if (lane < 16) st_ll4((uint4*)&sc->q[lane >> 3][cta * 16] + (lane & 7), 0u, 0u, 0u);
        __syncwarp();
        asm volatile("bar.arrive 2, 320;" ::: "memory");
        asm volatile("bar.sync 3, 64;" ::: "memory");
#pragma unroll 4
        for (int i = 0; i < 8; i++) st_v4(&sc->inbox[cta][0][0] + i * 32 + lane, 0u, 0u, 0u, 0u);
#pragma unroll 4
        for (int i = 0; i < 4; i++) st_v4((uint4*)&sc->part_o[cta][0][0] + i * 32 + lane, 0u, 0u, 0u, 0u);
        if (lane < 2) st_v4((uint4*)&sc->part_ml[cta][0] + lane, 0u, 0u, 0u, 0u);
        if (lane < 2) st_v4((uint4*)&sc->x1[cta][0] + lane, 0u, 0u, 0u, 0u);
        if (cta == 0 && lane == 0) asm volatile("st.relaxed.gpu.global.u32 [%0], %1;" ::"l"(&sc->progress), "r"(0u) : "memory");
        asm volatile("fence.acq_rel.gpu;" ::: "memory");
        __syncwarp();
        if (lane == 0) {
            asm volatile("fence.acq_rel.gpu;" ::: "memory");
            asm volatile("red.relaxed.gpu.global.add.u32 [%0], %1;" ::"l"(&sc->cleared), "r"(1u) : "memory");
            const uint32_t target = tag * NCTA;
            for (int it = 0; it < SPIN_LIMIT; it++) {
                uint32_t v;
                asm volatile("ld.relaxed.gpu.global.u32 %0, [%1];" : "=r"(v) : "l"(&sc->cleared) : "memory");
                if ((int32_t)(v - target) >= 0) break;
                __nanosleep(500);
            }
            asm volatile("fence.acq_rel.gpu;" ::: "memory");
            mbar_arrive(bar_clear);
            volatile uint32_t* pace = (volatile uint32_t*)(sgen + SM_PACE);
            uint32_t posted = 0;
            for (int it = 0; it < SPIN_LIMIT; it++) {
                const uint32_t own = pace[0];
                if (own >= kv_idx(KV_TILES - 1) + 2) break;
                if (own > posted) {
                    asm volatile("red.relaxed.gpu.global.add.u32 [%0], %1;" ::"l"(&sc->progress), "r"(own - posted) : "memory");
                    posted = own;
                }
                uint32_t v;
                asm volatile("ld.relaxed.gpu.global.u32 %0, [%1];" : "=r"(v) : "l"(&sc->progress) : "memory");
                const int diff = (int)v - (int)own * NCTA;
                pace[1] = diff > PACE_HI ? INFL_MAIN + 1 : diff < -PACE_LO ? INFL_MAIN - 1 : INFL_MAIN;
                __nanosleep(PACE_SLEEP);
            }
        }
    } else {
        const int g = lane >> 2, t = lane & 3;
        const int bb = g & 1;
        const int eb = lane >> 4;
        const int ec = 64 * warp + 4 * (lane & 15);
        if (warp == 0) TSTAMP(0);
        Scratch* const sc = p.sc;
        const uint4 w0 = __ldg((const uint4*)(p.w_mod + (size_t)tid * N_MOD + cta * 8));
        const uint4 w1 = __ldg((const uint4*)(p.w_mod + (size_t)(tid + 256) * N_MOD + cta * 8));
        const float c00 = __bfloat162float(p.c[tid]), c01 = __bfloat162float(p.c[tid + 256]);
        const float c10 = __bfloat162float(p.c[D_MODEL + tid]), c11 = __bfloat162float(p.c[D_MODEL + tid + 256]);
        const uint2 xe = __ldg((const uint2*)(p.x + eb * D_MODEL + ec));
        const float xpivot = __bfloat162float(p.x[eb * D_MODEL]);
        const uint32_t tag = *(volatile unsigned*)&sc->epoch + 1;
        const int ocol = cta * 4 + (lane & 3);
        const float xo0 = __bfloat162float(p.x[ocol]), xo1 = __bfloat162float(p.x[D_MODEL + ocol]);

        float* red = (float*)(sgen + SM_RED);
        float* red2 = (float*)(sgen + SM_RED2);
        float2* stat = (float2*)(sgen + SM_STAT);
        uint32_t* hs = (uint32_t*)(sgen + SM_HS) + warp * 64;
        float xn[4];
        {
            float xv[4] = {bf_lo(xe.x), bf_hi(xe.x), bf_lo(xe.y), bf_hi(xe.y)};
            const float2 ps = half_warp_sums(xv, xpivot);
            if ((lane & 15) == 0) stat[warp * 2 + eb] = ps;
            const float s00 = silu_bf(c00), s01 = silu_bf(c01), s10 = silu_bf(c10), s11 = silu_bf(c11);
            __nv_bfloat16* scs = (__nv_bfloat16*)(sgen + SM_SC);
            scs[tid] = __float2bfloat16_rn(s00); scs[tid + 256] = __float2bfloat16_rn(s01);
            scs[512 + tid] = __float2bfloat16_rn(s10); scs[512 + tid + 256] = __float2bfloat16_rn(s11);
            const uint32_t a[4] = {w0.x, w0.y, w0.z, w0.w}, b[4] = {w1.x, w1.y, w1.z, w1.w};
            float v[16];
#pragma unroll
            for (int i = 0; i < 4; i++) {
                v[2 * i] = s00 * bf_lo(a[i]) + s01 * bf_lo(b[i]);
                v[2 * i + 1] = s00 * bf_hi(a[i]) + s01 * bf_hi(b[i]);
                v[8 + 2 * i] = s10 * bf_lo(a[i]) + s11 * bf_lo(b[i]);
                v[8 + 2 * i + 1] = s10 * bf_hi(a[i]) + s11 * bf_hi(b[i]);
            }
#define XRED(N, O)                                                                       \
            {                                                                            \
                const bool up = lane & (O);                                              \
                _Pragma("unroll") for (int i = 0; i < (N); i++) {                        \
                    const float send = up ? v[i] : v[i + (N)], keep = up ? v[i + (N)] : v[i]; \
                    v[i] = keep + __shfl_xor_sync(0xffffffffu, send, (O));               \
                }                                                                        \
            }
            XRED(8, 16) XRED(4, 8) XRED(2, 4) XRED(1, 2)
#undef XRED
            v[0] += __shfl_xor_sync(0xffffffffu, v[0], 1);
            if (!(lane & 1)) red[warp * 16 + (lane >> 1)] = v[0];
            if (warp == 0) TSTAMP(14);
            asm volatile("bar.sync 2, 320;" ::: "memory");
            if (warp == 0) TSTAMP(23);
            if (warp == 0) {
                float s = 0.f;
#pragma unroll
                for (int w = 0; w < 8; w++) s += red[w * 16 + (lane & 15)];
                const float nx = __shfl_down_sync(0xffffffffu, s, 1);
                if (lane < 16 && !(lane & 1))
                    st_ll2(&sc->mod[lane >> 3][cta * 4 + ((lane & 7) >> 1)], pack_bf16(s, nx), tag);
                TSTAMP(1);
            }
            float mean_bf, rstd;
            ln_stats(stat, eb, xpivot, mean_bf, rstd);
#pragma unroll
            for (int i = 0; i < 4; i++) xn[i] = ln_norm(xv[i], mean_bf, rstd);
        }
        {
            uint4 sa, ca;
            for (int it = 0;; it++) {
                sa = ld_ll4((const uint4*)&sc->mod[eb][ec >> 1]);
                ca = ld_ll4((const uint4*)&sc->mod[eb][256 + (ec >> 1)]);
                const bool ok = sa.y == tag && sa.w == tag && ca.y == tag && ca.w == tag;
                if (__all_sync(0xffffffffu, ok) || it > SPIN_LIMIT) break;
            }
            *(uint2*)&hs[eb * 32 + 2 * (lane & 15)] =
                make_uint2(pack_bf16(ln_mod(xn[0], bf_lo(ca.x), bf_lo(sa.x)), ln_mod(xn[1], bf_hi(ca.x), bf_hi(sa.x))),
                           pack_bf16(ln_mod(xn[2], bf_lo(ca.z), bf_lo(sa.z)), ln_mod(xn[3], bf_hi(ca.z), bf_hi(sa.z))));
            __syncwarp();
            uint32_t hb[8];
#pragma unroll
            for (int i = 0; i < 8; i++) hb[i] = hs[bb * 32 + 8 * (i >> 1) + 4 * (i & 1) + t];
            if (warp == 0) TSTAMP(2);
            float cq[2][4] = {};
            const int ts = warp >> 2;
            mbar_wait(bar_full + 8 * ts, 0);
            const uint32_t tb = sbase + SM_RING + ts * TILE;
#pragma unroll
            for (int s = 0; s < 4; s++) {
                const int row = 64 * (warp & 3) + 16 * s + (lane & 7) + (lane >> 4) * 8;
#pragma unroll
                for (int mt = 0; mt < 2; mt++) {
                    const int ch = 2 * mt + ((lane >> 3) & 1);
                    uint32_t a[4];
                    ldsm4t(tb + row * 64 + ((ch ^ ((row >> 1) & 3)) << 4), a);
                    mma16816(cq[mt], a, hb[2 * s], hb[2 * s + 1]);
                }
            }
            if (t < 2) {
                const float v0 = t == 0 ? cq[0][0] : cq[1][0], v1 = t == 0 ? cq[0][1] : cq[1][1];
                const float v2 = t == 0 ? cq[0][2] : cq[1][2], v3 = t == 0 ? cq[0][3] : cq[1][3];
                *(float2*)&red2[warp * 64 + (16 * t + g) * 2] = make_float2(v0, v1);
                *(float2*)&red2[warp * 64 + (16 * t + g + 8) * 2] = make_float2(v2, v3);
            }
            cons_sync();
            if (warp < 4 && lane == 0) { mbar_arrive(bar_empty + 0); mbar_arrive(bar_empty + 8); }
            if (warp == 0) {
                const int b = lane >> 4, cp = lane & 15;
                float q0 = 0.f, q1 = 0.f;
#pragma unroll
                for (int w = 0; w < 8; w++) {
                    const float4 v = *(const float4*)&red2[w * 64 + cp * 4];
                    q0 += b ? v.y : v.x; q1 += b ? v.w : v.z;
                }
                st_ll2(&sc->q[b][cta * 16 + cp], pack_bf16(q0, q1), tag);
                TSTAMP(3);
            }
        }
        const int pair = cta >> 3;
        uint32_t qf[16];
        {
            uint2* qs = (uint2*)(sgen + SM_QS);
            if (tid < 128) {
                const uint4* src = (const uint4*)&sc->q[pair >> 3][(pair & 7) * 256] + tid;
                uint4 v;
                for (int it = 0;; it++) {
                    v = ld_ll4(src);
                    if ((v.y == tag && v.w == tag) || it > SPIN_LIMIT) break;
                }
                qs[tid] = make_uint2(v.x, v.z);
            }
            cons_sync();
            const uint32_t* q32 = (const uint32_t*)(sgen + SM_QS);
#pragma unroll
            for (int s = 0; s < 8; s++) {
                qf[2 * s] = q32[(g & 3) * 64 + 8 * s + t];
                qf[2 * s + 1] = q32[(g & 3) * 64 + 8 * s + 4 + t];
            }
        }
        if (warp == 0) TSTAMP(4);

        float o[8][4];
#pragma unroll
        for (int i = 0; i < 8; i++) { o[i][0] = o[i][1] = o[i][2] = o[i][3] = 0.f; }
        uint32_t mrun = 0xff80ff80u;
        float ls[4] = {0.f, 0.f, 0.f, 0.f};
        uint4 m_sb, m_cb; uint2 m_ga0, m_ga1, m_gb0, m_gb1;
        {
            const int grp = warp >> 2, wi = warp & 3;
            const int krow = 16 * wi + (lane & 7) + ((lane >> 3) & 1) * 8;
            const uint32_t koff = krow * 128 + ((((lane >> 4) & 1) ^ (lane & 7)) << 4);
            const int vrow = 16 * wi + (lane & 7) + (lane >> 4) * 8;
            const uint32_t voff = vrow * 128 + ((((lane >> 3) & 1) ^ (lane & 7)) << 4);
            const uint32_t ones[4] = {0x3f803f80u, 0x3f803f80u, 0x3f803f80u, 0x3f803f80u};
            for (int i = grp; i < KV_TILES; i += 2) {
                if (i == MOD_AT + grp) {
                    float cm[4] = {};
                    const uint32_t* sc32 = (const uint32_t*)(sgen + SM_SC) + bb * 256 + 32 * warp + t;
                    mbar_wait(bar_full + 8 * (IDX_MOD % NST), (IDX_MOD / NST) & 1);
                    const uint32_t tb = sbase + SM_RING + (IDX_MOD % NST) * TILE;
#pragma unroll
                    for (int s = 0; s < 4; s++) {
                        const int row = 64 * warp + 16 * s + (lane & 7) + (lane >> 4) * 8;
                        const int ch = (lane >> 3) & 1;
                        uint32_t a[4];
                        ldsm4t(tb + row * 32 + ((ch ^ ((row >> 2) & 1)) << 4), a);
                        mma16816(cm, a, sc32[8 * s], sc32[8 * s + 4]);
                    }
                    if (t == 0) {
                        *(float2*)&red[warp * 64 + g * 2] = make_float2(cm[0], cm[1]);
                        *(float2*)&red[warp * 64 + (g + 8) * 2] = make_float2(cm[2], cm[3]);
                    }
                    cons_sync();
                    if (warp < 4 && lane == 0) mbar_arrive(bar_empty + 8 * (IDX_MOD % NST));
                    if (warp == 1 && lane < 16) {
                        const int b = lane >> 3, cp = lane & 7;
                        float q0 = 0.f, q1 = 0.f;
#pragma unroll
                        for (int w = 0; w < 8; w++) {
                            const float4 v = *(const float4*)&red[w * 64 + cp * 4];
                            q0 += b ? v.y : v.x; q1 += b ? v.w : v.z;
                        }
                        st_ll2(&sc->mod[b][512 + cta * 8 + cp], pack_bf16(q0, q1), tag);
                    }
                }
                if (i == 56 + grp) {
                    m_sb = ld_ll4((const uint4*)&sc->mod[eb][768 + (ec >> 1)]);
                    m_cb = ld_ll4((const uint4*)&sc->mod[eb][1024 + (ec >> 1)]);
                    m_ga0 = ld_ll2(&sc->mod[0][512 + (ocol >> 1)]); m_ga1 = ld_ll2(&sc->mod[1][512 + (ocol >> 1)]);
                    m_gb0 = ld_ll2(&sc->mod[0][1280 + (ocol >> 1)]); m_gb1 = ld_ll2(&sc->mod[1][1280 + (ocol >> 1)]);
                }
                if (i == 60 + grp) {
                    for (int it = 0;; it++) {
                        const bool ok = m_sb.y == tag && m_sb.w == tag && m_cb.y == tag && m_cb.w == tag &&
                                        m_ga0.y == tag && m_ga1.y == tag && m_gb0.y == tag && m_gb1.y == tag;
                        if (__all_sync(0xffffffffu, ok) || it > SPIN_LIMIT) break;
                        m_sb = ld_ll4((const uint4*)&sc->mod[eb][768 + (ec >> 1)]);
                        m_cb = ld_ll4((const uint4*)&sc->mod[eb][1024 + (ec >> 1)]);
                        m_ga0 = ld_ll2(&sc->mod[0][512 + (ocol >> 1)]); m_ga1 = ld_ll2(&sc->mod[1][512 + (ocol >> 1)]);
                        m_gb0 = ld_ll2(&sc->mod[0][1280 + (ocol >> 1)]); m_gb1 = ld_ll2(&sc->mod[1][1280 + (ocol >> 1)]);
                    }
                    mbar_wait(bar_clear, 0);
                }
                const int ki = kv_idx(i), ks = ki % NST, vs = (ki + 1) % NST;
                const uint32_t kph = (ki / NST) & 1, vph = ((ki + 1) / NST) & 1;
                mbar_wait(bar_full + 8 * ks, kph);
                const uint32_t kb = sbase + SM_RING + ks * TILE + koff;
                float sa[4] = {0.f, 0.f, 0.f, 0.f}, sb[4] = {0.f, 0.f, 0.f, 0.f};
#pragma unroll
                for (int s = 0; s < 8; s += 2) {
                    uint32_t a0[4], a1[4];
                    ldsm4((kb ^ ((s & 3) << 5)) + (s >> 2) * 8192, a0);
                    ldsm4((kb ^ (((s + 1) & 3) << 5)) + (s >> 2) * 8192, a1);
                    mma16816(sa, a0, qf[2 * s], qf[2 * s + 1]);
                    mma16816(sb, a1, qf[2 * s + 2], qf[2 * s + 3]);
                }
                __syncwarp();
                if (lane == 0) mbar_arrive(bar_empty + 8 * ks);
                uint32_t r01 = pack_bf16(sa[0] + sb[0], sa[1] + sb[1]);
                uint32_t r23 = pack_bf16(sa[2] + sb[2], sa[3] + sb[3]);
                r01 = pack_bf16(bf_lo(r01) * QK_SCALE, bf_hi(r01) * QK_SCALE);
                r23 = pack_bf16(bf_lo(r23) * QK_SCALE, bf_hi(r23) * QK_SCALE);
                uint32_t mx = max_bf16x2(r01, r23);
                mx = max_bf16x2(mx, __shfl_xor_sync(0xffffffffu, mx, 4));
                mx = max_bf16x2(mx, __shfl_xor_sync(0xffffffffu, mx, 8));
                mx = max_bf16x2(mx, __shfl_xor_sync(0xffffffffu, mx, 16));
                const uint32_t mnew = max_bf16x2(mrun, mx);
                const float m0 = bf_lo(mnew), m1 = bf_hi(mnew);
                if (__any_sync(0xffffffffu, mnew != mrun)) {
                    const float al0 = ex2((bf_lo(mrun) - m0) * LOG2E), al1 = ex2((bf_hi(mrun) - m1) * LOG2E);
                    ls[0] *= al0; ls[1] *= al1;
#pragma unroll
                    for (int d = 0; d < 8; d++) { o[d][0] *= al0; o[d][1] *= al1; o[d][2] *= al0; o[d][3] *= al1; }
                    mrun = mnew;
                }
                const float p0 = ex2((bf_lo(r01) - m0) * LOG2E), p1 = ex2((bf_hi(r01) - m1) * LOG2E);
                const float p2 = ex2((bf_lo(r23) - m0) * LOG2E), p3 = ex2((bf_hi(r23) - m1) * LOG2E);
                const uint32_t pb0 = movmatrix_t(pack_bf16(p0, p1)), pb1 = movmatrix_t(pack_bf16(p2, p3));
                mma16816(ls, ones, pb0, pb1);
                mbar_wait(bar_full + 8 * vs, vph);
                const uint32_t vb = sbase + SM_RING + vs * TILE + voff;
#pragma unroll
                for (int d = 0; d < 8; d++) {
                    uint32_t a[4];
                    ldsm4t((vb ^ ((d & 3) << 5)) + (d >> 2) * 8192, a);
                    mma16816(o[d], a, pb0, pb1);
                }
                __syncwarp();
                if (lane == 0) mbar_arrive(bar_empty + 8 * vs);
            }
        }
        if (warp == 7) TSTAMP(5);
        if (WO_TRIG == 1 && warp == 7 && lane == 0) mbar_arrive(bar_go_wo);
        if (FF_TRIG == 1 && warp == 7 && lane == 0) mbar_arrive(bar_go_ff);
        {
            float* mrg = (float*)(sgen + SM_MRG);
            float2* ml = (float2*)(sgen + SM_ML);
            {
                const int hp = (t & 1) * 2, up = t >> 1;
                if (g == 0 && up == 0) { ml[warp * 4 + hp] = make_float2(bf_lo(mrun), ls[0]); ml[warp * 4 + hp + 1] = make_float2(bf_hi(mrun), ls[1]); }
                float* m0p = mrg + (warp * 4 + hp) * 136 + up * 72 + g;
#pragma unroll
                for (int d = 0; d < 4; d++) {
                    m0p[16 * d] = up ? o[d + 4][0] : o[d][0]; m0p[136 + 16 * d] = up ? o[d + 4][1] : o[d][1];
                    m0p[16 * d + 8] = up ? o[d + 4][2] : o[d][2]; m0p[136 + 16 * d + 8] = up ? o[d + 4][3] : o[d][3];
                }
            }
            cons_sync();
            const int hh = tid >> 6, dp = tid & 63;
            float2 mw[8];
            float M = -INFINITY;
#pragma unroll
            for (int w = 0; w < 8; w++) { mw[w] = ml[w * 4 + hh]; M = fmaxf(M, mw[w].x); }
            float L = 0.f, o0 = 0.f, o1 = 0.f;
#pragma unroll
            for (int w = 0; w < 8; w++) {
                const float wt = ex2((mw[w].x - M) * LOG2E);
                const float2 v = *(const float2*)&mrg[(w * 4 + hh) * 136 + 2 * dp + (dp >= 32 ? 8 : 0)];
                L += wt * mw[w].y; o0 += wt * v.x; o1 += wt * v.y;
            }
            st_ll2(&sc->part_o[cta][hh][dp], tagf(o0, F_PART), tagf(o1, F_PART));
            if (dp == 0) st_ll2(&sc->part_ml[cta][hh], tagf(M, F_PART), tagf(L, F_PART));
        }
        if (WO_TRIG == 2 && tid == 0) mbar_arrive(bar_go_wo);
        if (warp == 0) TSTAMP(6);
        const uint32_t aoff = warp * 2048 + ((lane & 7) + (lane >> 4) * 8) * 128 + ((((lane >> 3) & 1) ^ (lane & 7)) << 4);
        uint32_t wf[8][4];
        if (WO_AT < KV_TILES) {
#pragma unroll
            for (int s = 0; s < 2; s++) {
                constexpr int i0 = IDX_WO;
                const int idx = i0 + s;
                mbar_wait(bar_full + 8 * (idx % NST), (idx / NST) & 1);
                const uint32_t tb = sbase + SM_RING + (idx % NST) * TILE + aoff;
#pragma unroll
                for (int mt = 0; mt < 4; mt++) ldsm4t(tb ^ (mt << 5), wf[s * 4 + mt]);
            }
        }
        {
            const int hq = cta >> 2, kvh = hq >> 2, hh = hq & 3, ds = cta & 3;
            const int b = tid >> 7, dpl = (tid >> 3) & 15, j = tid & 7;
            const int pc = (b * 8 + kvh) * 8 + j;
            const uint2* po = &sc->part_o[pc][hh][ds * 16 + dpl];
            const uint2* pm = &sc->part_ml[pc - j][hh];
            uint2 vo, vm[8];
            for (int it = 0;; it++) {
                vo = ld_ll2(po);
#pragma unroll
                for (int jj = 0; jj < 8; jj++) vm[jj] = ld_ll2(pm + jj * 4);
                uint32_t all = vo.x & vo.y;
#pragma unroll
                for (int jj = 0; jj < 8; jj++) all &= vm[jj].x & vm[jj].y;
                if (__all_sync(0xffffffffu, (all & 3u) == F_PART) || it > SPIN_LIMIT) break;
            }
            float M = untag(vm[0].x);
#pragma unroll
            for (int jj = 1; jj < 8; jj++) M = fmaxf(M, untag(vm[jj].x));
            float wt = 0.f, L = 0.f;
#pragma unroll
            for (int jj = 0; jj < 8; jj++) {
                const float w_ = ex2((untag(vm[jj].x) - M) * LOG2E);
                L += w_ * untag(vm[jj].y);
                wt = jj == j ? w_ : wt;
            }
            float o0 = wt * untag(vo.x), o1 = wt * untag(vo.y);
#pragma unroll
            for (int o_ = 1; o_ < 8; o_ <<= 1) {
                o0 += __shfl_xor_sync(0xffffffffu, o0, o_);
                o1 += __shfl_xor_sync(0xffffffffu, o1, o_);
            }
            uint32_t* os = (uint32_t*)(sgen + SM_OS);
            const float rl = rcp_approx(L);
            if (j == 0) os[b * 16 + dpl] = pack_bf16(o0 * rl, o1 * rl);
            if (WO_AT == KV_TILES) {
#pragma unroll
            for (int s = 0; s < 2; s++) {
                constexpr int i0 = IDX_WO;
                const int idx = i0 + s;
                mbar_wait(bar_full + 8 * (idx % NST), (idx / NST) & 1);
                const uint32_t tb = sbase + SM_RING + (idx % NST) * TILE + aoff;
#pragma unroll
                for (int mt = 0; mt < 4; mt++) ldsm4t(tb ^ (mt << 5), wf[s * 4 + mt]);
            }
            }
            cons_sync();
            if (FF_TRIG == 2 && tid == 0) mbar_arrive(bar_go_ff);
            if (warp == 0) TSTAMP(7);
            float y[4][4] = {};
#pragma unroll
            for (int s = 0; s < 2; s++) {
                const uint32_t b0 = os[bb * 16 + 8 * s + t], b1 = os[bb * 16 + 8 * s + 4 + t];
#pragma unroll
                for (int mt = 0; mt < 4; mt++) mma16816(y[mt], wf[s * 4 + mt], b0, b1);
            }
            float v[4];
#pragma unroll
            for (int i = 0; i < 4; i++) v[i] = t == 0 ? y[0][i] : t == 1 ? y[1][i] : t == 2 ? y[2][i] : y[3][i];
            {
                const bool odd = g & 1;
                const float sx = odd ? v[0] : v[2], sy = odd ? v[1] : v[3];
                const float rx = __shfl_xor_sync(0xffffffffu, sx, 4), ry = __shfl_xor_sync(0xffffffffu, sy, 4);
                const int c0 = 64 * warp + 16 * t + (odd ? g + 7 : g);
                const float e0 = odd ? rx : v[0], e1 = odd ? ry : v[1], e2 = odd ? v[2] : rx, e3 = odd ? v[3] : ry;
                st_v4(&sc->inbox[c0 >> 2][cta][(c0 >> 1) & 1], tagf(e0, F_WO), tagf(e1, F_WO), tagf(e2, F_WO), tagf(e3, F_WO));
            }
        }
        if (FF_TRIG == 3 && tid == 0) mbar_arrive(bar_go_ff);
        if (warp == 0) TSTAMP(8);
        float xm0 = 0.f, xm1 = 0.f;
        {
            float r0;
            {
                const uint4* pin = &sc->inbox[cta][0][0] + tid;
                uint4 v = make_uint4(F_WO, F_WO, F_WO, F_WO);
                spin_cycles(DELAY_B1);
                for (int it = 0;; it++) {
                    if (tid < NCTA * 2) v = ld_ll4(pin);
                    if (__all_sync(0xffffffffu, ((v.x & v.y & v.z & v.w & 3u) == F_WO) && (((v.x | v.y | v.z | v.w) & 3u) == F_WO)) || it > SPIN_LIMIT) break;
                }
                const bool u1 = lane & 2, u2 = lane & 4;
                const float a0 = untag(v.x), a1 = untag(v.y), a2 = untag(v.z), a3 = untag(v.w);
                const float k0 = (u1 ? a1 : a0) + __shfl_xor_sync(0xffffffffu, u1 ? a0 : a1, 2);
                const float k1 = (u1 ? a3 : a2) + __shfl_xor_sync(0xffffffffu, u1 ? a2 : a3, 2);
                r0 = (u2 ? k1 : k0) + __shfl_xor_sync(0xffffffffu, u2 ? k0 : k1, 4);
                r0 += __shfl_xor_sync(0xffffffffu, r0, 8);
                r0 += __shfl_xor_sync(0xffffffffu, r0, 16);
                if (lane < 8) red2[warp * 8 + (2 * (lane & 1) + ((lane >> 2) & 1)) * 2 + ((lane >> 1) & 1)] = r0;
            }
            cons_sync();
            if (warp == 0) {
                float a0 = 0.f, a1 = 0.f;
#pragma unroll
                for (int w = 0; w < 8; w++) { const float2 v = *(const float2*)&red2[w * 8 + (lane & 3) * 2]; a0 += v.x; a1 += v.y; }
                const bool hi = ocol & 1;
                const float ga0 = hi ? bf_hi(m_ga0.x) : bf_lo(m_ga0.x), ga1 = hi ? bf_hi(m_ga1.x) : bf_lo(m_ga1.x);
                xm0 = bf16r(xo0 + bf16r(ga0 * bf16r(a0)));
                xm1 = bf16r(xo1 + bf16r(ga1 * bf16r(a1)));
                if (lane < 4) st_ll2(&sc->x1[cta][lane], pack_bf16(xm0, xm1), F_X1);
                TSTAMP(10);
            }
        }
        if (cta < NFFN) {
            uint32_t gf[4][4], uf[4][4];
            mbar_wait(bar_full + 8 * (IDX_WG % NST), (IDX_WG / NST) & 1);
            mbar_wait(bar_full + 8 * (IDX_WU % NST), (IDX_WU / NST) & 1);
            {
                const uint32_t tg = sbase + SM_RING + (IDX_WG % NST) * TILE, tu = sbase + SM_RING + (IDX_WU % NST) * TILE;
#pragma unroll
                for (int s = 0; s < 4; s++) {
                    const int row = 64 * warp + 16 * s + (lane & 7) + (lane >> 4) * 8;
                    const uint32_t off = row * 32 + ((((lane >> 3) & 1) ^ ((row >> 2) & 1)) << 4);
                    ldsm4t(tg + off, gf[s]);
                    ldsm4t(tu + off, uf[s]);
                }
            }
            if (warp == 0) TSTAMP(11);
            uint32_t hb[8];
            {
                const uint4* px = (const uint4*)&sc->x1[ec >> 2][0];
                const uint2* pp = &sc->x1[0][0];
                uint4 va, vb; uint2 vp;
                spin_cycles(DELAY_B2);
                for (int it = 0;; it++) {
                    va = ld_ll4(px); vb = ld_ll4(px + 1); vp = ld_ll2(pp);
                    const bool ok = va.y == F_X1 && va.w == F_X1 && vb.y == F_X1 && vb.w == F_X1 && vp.y == F_X1;
                    if (__all_sync(0xffffffffu, ok) || it > SPIN_LIMIT) break;
                }
                const float xv[4] = {eb ? bf_hi(va.x) : bf_lo(va.x), eb ? bf_hi(va.z) : bf_lo(va.z),
                                     eb ? bf_hi(vb.x) : bf_lo(vb.x), eb ? bf_hi(vb.z) : bf_lo(vb.z)};
                const float pivot = eb ? bf_hi(vp.x) : bf_lo(vp.x);
                if (warp == 0) TSTAMP(9);
                const float2 ps = half_warp_sums(xv, pivot);
                if ((lane & 15) == 0) stat[warp * 2 + eb] = ps;
                cons_sync();
                float mean_bf, rstd;
                ln_stats(stat, eb, pivot, mean_bf, rstd);
                *(uint2*)&hs[eb * 32 + 2 * (lane & 15)] = make_uint2(
                    pack_bf16(ln_mod(ln_norm(xv[0], mean_bf, rstd), bf_lo(m_cb.x), bf_lo(m_sb.x)),
                              ln_mod(ln_norm(xv[1], mean_bf, rstd), bf_hi(m_cb.x), bf_hi(m_sb.x))),
                    pack_bf16(ln_mod(ln_norm(xv[2], mean_bf, rstd), bf_lo(m_cb.z), bf_lo(m_sb.z)),
                              ln_mod(ln_norm(xv[3], mean_bf, rstd), bf_hi(m_cb.z), bf_hi(m_sb.z))));
                __syncwarp();
#pragma unroll
                for (int i = 0; i < 8; i++) hb[i] = hs[bb * 32 + 8 * (i >> 1) + 4 * (i & 1) + t];
            }
            {
                float cg[2][4] = {}, cu[2][4] = {};
#pragma unroll
                for (int s = 0; s < 4; s++) {
                    mma16816(cg[s & 1], gf[s], hb[2 * s], hb[2 * s + 1]);
                    mma16816(cu[s & 1], uf[s], hb[2 * s], hb[2 * s + 1]);
                }
                if (t < 2) {
                    float v[4];
#pragma unroll
                    for (int i = 0; i < 4; i++) v[i] = t ? cu[0][i] + cu[1][i] : cg[0][i] + cg[1][i];
                    *(float2*)&red[warp * 64 + t * 32 + g * 2] = make_float2(v[0], v[1]);
                    *(float2*)&red[warp * 64 + t * 32 + (g + 8) * 2] = make_float2(v[2], v[3]);
                }
            }
            uint32_t df[4][4];
            mbar_wait(bar_full + 8 * (IDX_WD % NST), (IDX_WD / NST) & 1);
#pragma unroll
            for (int mt = 0; mt < 4; mt++) ldsm4t((sbase + SM_RING + (IDX_WD % NST) * TILE + aoff) ^ (mt << 5), df[mt]);
            cons_sync();
            {
                float gs = 0.f, us = 0.f;
#pragma unroll
                for (int w = 0; w < 8; w++) { gs += red[w * 64 + lane]; us += red[w * 64 + 32 + lane]; }
                gs = bf16r(gs);
                const float u2 = gs * (1.0f + 0.044715f * gs * gs) * (2.0f * 0.7978845608028654f * LOG2E);
                const float ge = bf16r(__fdividef(gs, 1.0f + ex2(-u2)));
                const float act = bf16r(ge * bf16r(us));
                const float a0 = __shfl_sync(0xffffffffu, act, 4 * t + bb), a1 = __shfl_sync(0xffffffffu, act, 4 * t + 2 + bb);
                const float a2 = __shfl_sync(0xffffffffu, act, 4 * t + 16 + bb), a3 = __shfl_sync(0xffffffffu, act, 4 * t + 18 + bb);
                const uint32_t b0 = pack_bf16(a0, a1), b1 = pack_bf16(a2, a3);
                float y[4][4] = {};
#pragma unroll
                for (int mt = 0; mt < 4; mt++) mma16816(y[mt], df[mt], b0, b1);
                float v[4];
#pragma unroll
                for (int i = 0; i < 4; i++) v[i] = t == 0 ? y[0][i] : t == 1 ? y[1][i] : t == 2 ? y[2][i] : y[3][i];
            {
                const bool odd = g & 1;
                const float sx = odd ? v[0] : v[2], sy = odd ? v[1] : v[3];
                const float rx = __shfl_xor_sync(0xffffffffu, sx, 4), ry = __shfl_xor_sync(0xffffffffu, sy, 4);
                const int c0 = 64 * warp + 16 * t + (odd ? g + 7 : g);
                const float e0 = odd ? rx : v[0], e1 = odd ? ry : v[1], e2 = odd ? v[2] : rx, e3 = odd ? v[3] : ry;
                st_v4(&sc->inbox[c0 >> 2][cta][(c0 >> 1) & 1], tagf(e0, F_DOWN), tagf(e1, F_DOWN), tagf(e2, F_DOWN), tagf(e3, F_DOWN));
            }
            }
            if (warp == 0) TSTAMP(12);
        }
        {
            float r0;
            {
                const uint4* pin = &sc->inbox[cta][0][0] + tid;
                uint4 v = make_uint4(F_DOWN, F_DOWN, F_DOWN, F_DOWN);
                spin_cycles(DELAY_C);
                for (int it = 0;; it++) {
                    if (tid < NFFN * 2) v = ld_ll4(pin);
                    if (__all_sync(0xffffffffu, ((v.x & v.y & v.z & v.w & 3u) == F_DOWN) && (((v.x | v.y | v.z | v.w) & 3u) == F_DOWN)) || it > SPIN_LIMIT) break;
                }
                const bool u1 = lane & 2, u2 = lane & 4;
                const float a0 = untag(v.x), a1 = untag(v.y), a2 = untag(v.z), a3 = untag(v.w);
                const float k0 = (u1 ? a1 : a0) + __shfl_xor_sync(0xffffffffu, u1 ? a0 : a1, 2);
                const float k1 = (u1 ? a3 : a2) + __shfl_xor_sync(0xffffffffu, u1 ? a2 : a3, 2);
                r0 = (u2 ? k1 : k0) + __shfl_xor_sync(0xffffffffu, u2 ? k0 : k1, 4);
                r0 += __shfl_xor_sync(0xffffffffu, r0, 8);
                r0 += __shfl_xor_sync(0xffffffffu, r0, 16);
                if (lane < 8) red2[64 + warp * 8 + (2 * (lane & 1) + ((lane >> 2) & 1)) * 2 + ((lane >> 1) & 1)] = r0;
            }
            cons_sync();
            if (warp == 0) {
                float a0 = 0.f, a1 = 0.f;
#pragma unroll
                for (int w = 0; w < 8; w++) { const float2 v = *(const float2*)&red2[64 + w * 8 + (lane & 3) * 2]; a0 += v.x; a1 += v.y; }
                const bool hi = ocol & 1;
                const float gb0 = hi ? bf_hi(m_gb0.x) : bf_lo(m_gb0.x), gb1 = hi ? bf_hi(m_gb1.x) : bf_lo(m_gb1.x);
                if (lane < 4) {
                    p.out[ocol] = __float2bfloat16_rn(xm0 + bf16r(gb0 * bf16r(a0)));
                    p.out[D_MODEL + ocol] = __float2bfloat16_rn(xm1 + bf16r(gb1 * bf16r(a1)));
                }
                if (cta == 0 && lane == 0) *(volatile unsigned*)&sc->epoch = tag;
                TSTAMP(13);
            }
        }
    }
}

typedef CUresult (*EncodeFn)(CUtensorMap*, CUtensorMapDataType, cuuint32_t, void*, const cuuint64_t*, const cuuint64_t*,
                             const cuuint32_t*, const cuuint32_t*, CUtensorMapInterleave, CUtensorMapSwizzle,
                             CUtensorMapL2promotion, CUtensorMapFloatOOBfill);

struct Maps { CUtensorMap k, v, wq, wmod, wo, wg, wu, wd; };

void encode(EncodeFn fn, CUtensorMap* m, const void* ptr, int rank, const cuuint64_t* dims, const cuuint64_t* strides,
            const cuuint32_t* box, CUtensorMapSwizzle sw) {
    const cuuint32_t es[3] = {1, 1, 1};
    fn(m, CU_TENSOR_MAP_DATA_TYPE_BFLOAT16, rank, const_cast<void*>(ptr), dims, strides, box, es,
       CU_TENSOR_MAP_INTERLEAVE_NONE, sw, CU_TENSOR_MAP_L2_PROMOTION_L2_256B, CU_TENSOR_MAP_FLOAT_OOB_FILL_NONE);
}

}

extern "C" void kernel_launch(void* const* d_in, const int* in_sizes, int n_in, void* d_out, int out_size) {
    (void)in_sizes; (void)n_in; (void)out_size;
    static EncodeFn enc = nullptr;
    static Scratch* scratch = nullptr;
    if (!enc) {
        cudaGetSymbolAddress((void**)&scratch, g_scratch);
        void* fn = nullptr;
        cudaDriverEntryPointQueryResult qr;
        cudaGetDriverEntryPoint("cuTensorMapEncodeTiled", &fn, cudaEnableDefault, &qr);
        enc = (EncodeFn)fn;
        cudaFuncSetAttribute(fused_block_kernel, cudaFuncAttributeMaxDynamicSharedMemorySize, SMEM_BYTES);
    }
    Maps m;
    {
        const cuuint64_t dims[3] = {64, (cuuint64_t)16 * SK, 2}, str[2] = {256, 128};
        const cuuint32_t box[3] = {64, 64, 2};
        encode(enc, &m.k, d_in[1], 3, dims, str, box, CU_TENSOR_MAP_SWIZZLE_128B);
        encode(enc, &m.v, d_in[2], 3, dims, str, box, CU_TENSOR_MAP_SWIZZLE_128B);
    }
    {
        const cuuint64_t dims[2] = {4096, 512}, str[1] = {8192};
        const cuuint32_t box[2] = {32, 256};
        encode(enc, &m.wq, d_in[3], 2, dims, str, box, CU_TENSOR_MAP_SWIZZLE_64B);
    }
    {
        const cuuint64_t dims[2] = {N_MOD, 512}, str[1] = {N_MOD * 2};
        const cuuint32_t box[2] = {16, 256};
        encode(enc, &m.wmod, d_in[10], 2, dims, str, box, CU_TENSOR_MAP_SWIZZLE_32B);
    }
    {
        const cuuint64_t dims_o[3] = {64, 4096, 8}, dims_d[3] = {64, D_FF, 8}, str[2] = {1024, 128};
        const cuuint32_t box[3] = {64, 16, 8};
        encode(enc, &m.wo, d_in[4], 3, dims_o, str, box, CU_TENSOR_MAP_SWIZZLE_128B);
        encode(enc, &m.wd, d_in[8], 3, dims_d, str, box, CU_TENSOR_MAP_SWIZZLE_128B);
    }
    {
        const cuuint64_t dims[2] = {D_FF, 512}, str[1] = {D_FF * 2};
        const cuuint32_t box[2] = {16, 256};
        encode(enc, &m.wg, d_in[6], 2, dims, str, box, CU_TENSOR_MAP_SWIZZLE_32B);
        encode(enc, &m.wu, d_in[7], 2, dims, str, box, CU_TENSOR_MAP_SWIZZLE_32B);
    }
    Params p;
    p.x = (const __nv_bfloat16*)d_in[0];
    p.c = (const __nv_bfloat16*)d_in[9];
    p.w_mod = (const __nv_bfloat16*)d_in[10];
    p.out = (__nv_bfloat16*)d_out;
    p.sc = scratch;
    fused_block_kernel<<<NCTA, NTHREADS, SMEM_BYTES, cudaStreamPerThread>>>(p, m.k, m.v, m.wq, m.wmod, m.wo, m.wg, m.wu, m.wd);
}
```

```cpp
#include <cuda_runtime.h>
#include <cuda.h>
#include <cuda_bf16.h>
#include <stdint.h>

namespace {

constexpr int D_MODEL = 512;
constexpr int N_HEADS = 32;
constexpr int SK = 32768;
constexpr int DH = 128;
constexpr int D_FF = 1792;
constexpr int N_MOD = 6 * D_MODEL;

constexpr int NCTA = 128;
constexpr int NFFN = D_FF / 16;
constexpr int NTHREADS = 320;
constexpr int NST = 12;
constexpr int TILE = 16384;
#define INFL_PRO 2
#define INFL_MAIN 3
#define INFL_TAIL 2
#define PACE_HI 96
#define PACE_LO 96
#define PACE_HI2 100000
#define PACE_END 16
#define GRID_SLACK 0
#define PACE_SLEEP 200
#define TR_PF_WO -1
#define TR_PF_FF -1
#define TR_LD_WO 0
#define TR_LD_GU 0
#define GU_PIECES 1
#define GU_WIN 4
#define TR_LD_WD 0
#define PRO_TILES 8
constexpr int KV_TILES = 64;
#define MOD_AT 8
#define WO_AT 64
#define GU_AT 64
#define WD_AT 64
static_assert(MOD_AT % 2 == 0 && MOD_AT < WO_AT && MOD_AT < GU_AT && MOD_AT < WD_AT, "schedule");
static_assert(WO_AT <= KV_TILES && GU_AT <= KV_TILES && WD_AT <= KV_TILES, "schedule");
__host__ __device__ constexpr int kv_idx(int i) {
    return 2 + 2 * i + (i >= MOD_AT ? 1 : 0) + (i >= WO_AT ? 2 : 0) + (i >= GU_AT ? 2 : 0) + (i >= WD_AT ? 1 : 0);
}
constexpr int IDX_MOD = 2 + 2 * MOD_AT;
constexpr int IDX_WO = 3 + 2 * WO_AT + (GU_AT < WO_AT ? 2 : 0) + (WD_AT < WO_AT ? 1 : 0);
constexpr int IDX_WG = 3 + 2 * GU_AT + (WO_AT <= GU_AT ? 2 : 0) + (WD_AT < GU_AT ? 1 : 0);
constexpr int IDX_WU = IDX_WG + 1;
constexpr int IDX_WD = 3 + 2 * WD_AT + (WO_AT <= WD_AT ? 2 : 0) + (GU_AT <= WD_AT ? 2 : 0);
constexpr int N_TILES = 2 + 2 * KV_TILES + 1 + 2 + 3;
static_assert(N_TILES - 1 - IDX_WO < NST && N_TILES - 1 - IDX_WG < NST && N_TILES - 1 - IDX_WD < NST, "weights must stay resident until the end");
constexpr int SPIN_LIMIT = 1 << 20;

constexpr float LOG2E = 1.4426950408889634f;
constexpr float QK_SCALE = 0.08838834764831845f;

constexpr int SM_RING = 0;
constexpr int SM_MRG = SM_RING + NST * TILE;
constexpr int SM_ML = SM_MRG + 8 * 4 * 136 * 4;
constexpr int SM_RED = SM_ML + 8 * 4 * 8;
constexpr int SM_RED2 = SM_RED + 8 * 64 * 4;
constexpr int SM_QS = SM_RED2 + 8 * 64 * 4;
constexpr int SM_OS = SM_QS + 512 * 2;
constexpr int SM_SC = SM_OS + 2 * 16 * 4;
constexpr int SM_HS = SM_SC + 2 * 512 * 2;
constexpr int SM_STAT = SM_HS + 8 * 2 * 32 * 4;
constexpr int SM_PACE = SM_STAT + 8 * 2 * 8;
constexpr int SM_BAR = SM_PACE + 8;
constexpr int SM_END = SM_BAR + (2 * NST + 7 + 8) * 8;
constexpr int SMEM_BYTES = SM_END + 1024;

struct Scratch {
    uint4 inbox[NCTA][NCTA][2];
    uint2 x1[NCTA][16];
    uint2 part_o[NCTA][4][64];
    uint2 part_ml[NCTA][4][4];
    uint2 mod[2][N_MOD / 2];
    uint2 q[2][N_HEADS * DH / 2];
    unsigned epoch;
    unsigned pad_[31];
    unsigned cleared;
    unsigned pad2_[31];
    unsigned progress;
};
__device__ Scratch g_scratch;
constexpr uint32_t F_PART = 1, F_WO = 1, F_DOWN = 2, F_X1 = 1;
__device__ __forceinline__ uint32_t tagf(float v, uint32_t f) { return (__float_as_uint(v) & ~3u) | f; }
__device__ __forceinline__ float untag(uint32_t v) { return __uint_as_float(v & ~3u); }

struct Params {
    const __nv_bfloat16* x;
    const __nv_bfloat16* c;
    const __nv_bfloat16* w_mod;
    __nv_bfloat16* out;
    Scratch* sc;
    const __nv_bfloat16 *wo, *wg, *wu, *wd;
};

#define TSTAMP(i) do { } while (0)

__device__ __forceinline__ uint32_t smem_u32(const void* p) { return (uint32_t)__cvta_generic_to_shared(p); }

__device__ __forceinline__ void mbar_init(uint32_t bar, uint32_t cnt) {
    asm volatile("mbarrier.init.shared::cta.b64 [%0], %1;" ::"r"(bar), "r"(cnt) : "memory");
}
__device__ __forceinline__ void mbar_expect_tx(uint32_t bar, uint32_t bytes) {
    asm volatile("mbarrier.arrive.expect_tx.shared::cta.b64 _, [%0], %1;" ::"r"(bar), "r"(bytes) : "memory");
}
__device__ __forceinline__ void mbar_arrive(uint32_t bar) {
    asm volatile("mbarrier.arrive.shared::cta.b64 _, [%0];" ::"r"(bar) : "memory");
}
__device__ __forceinline__ bool mbar_try(uint32_t bar, uint32_t parity) {
    uint32_t ok;
    asm volatile(
        "{\n\t.reg .pred p;\n\t"
        "mbarrier.try_wait.parity.shared::cta.b64 p, [%1], %2;\n\t"
        "selp.u32 %0, 1, 0, p;\n\t}"
        : "=r"(ok) : "r"(bar), "r"(parity) : "memory");
    return ok != 0;
}
__device__ __forceinline__ void mbar_wait(uint32_t bar, uint32_t parity) {
    if (mbar_try(bar, parity)) return;
    for (int i = 0; i < SPIN_LIMIT; i++)
        if (mbar_try(bar, parity)) return;
}
__device__ __forceinline__ void cons_sync() { asm volatile("bar.sync 1, 256;" ::: "memory"); }

__device__ __forceinline__ void tma_2d(uint32_t dst, const CUtensorMap* m, int c0, int c1, uint32_t bar) {
    asm volatile("cp.async.bulk.tensor.2d.shared::cluster.global.mbarrier::complete_tx::bytes [%0], [%1, {%3, %4}], [%2];"
                 ::"r"(dst), "l"(m), "r"(bar), "r"(c0), "r"(c1) : "memory");
}
__device__ __forceinline__ void tma_3d(uint32_t dst, const CUtensorMap* m, int c0, int c1, int c2, uint32_t bar) {
    asm volatile("cp.async.bulk.tensor.3d.shared::cluster.global.mbarrier::complete_tx::bytes [%0], [%1, {%3, %4, %5}], [%2];"
                 ::"r"(dst), "l"(m), "r"(bar), "r"(c0), "r"(c1), "r"(c2) : "memory");
}
__device__ __forceinline__ void tma_3d_hint(uint32_t dst, const CUtensorMap* m, int c0, int c1, int c2, uint32_t bar, uint64_t pol) {
    asm volatile("cp.async.bulk.tensor.3d.shared::cluster.global.mbarrier::complete_tx::bytes.L2::cache_hint [%0], [%1, {%3, %4, %5}], [%2], %6;"
                 ::"r"(dst), "l"(m), "r"(bar), "r"(c0), "r"(c1), "r"(c2), "l"(pol) : "memory");
}
__device__ __forceinline__ void l2pf_2d(const CUtensorMap* m, int c0, int c1) {
    asm volatile("cp.async.bulk.prefetch.tensor.2d.L2.global.tile [%0, {%1, %2}];" ::"l"(m), "r"(c0), "r"(c1) : "memory");
}
__device__ __forceinline__ void l2pf_3d(const CUtensorMap* m, int c0, int c1, int c2) {
    asm volatile("cp.async.bulk.prefetch.tensor.3d.L2.global.tile [%0, {%1, %2, %3}];" ::"l"(m), "r"(c0), "r"(c1), "r"(c2) : "memory");
}
__device__ __forceinline__ void l2pf_1d(const void* ptr, uint32_t bytes) {
    asm volatile("cp.async.bulk.prefetch.L2.global [%0], %1;" ::"l"(ptr), "r"(bytes) : "memory");
}
__device__ __forceinline__ void prefetch_tmap(const CUtensorMap* m) {
    asm volatile("prefetch.tensormap [%0];" ::"l"(m) : "memory");
}

__device__ __forceinline__ void ldsm4(uint32_t addr, uint32_t (&r)[4]) {
    asm volatile("ldmatrix.sync.aligned.m8n8.x4.shared.b16 {%0,%1,%2,%3}, [%4];"
                 : "=r"(r[0]), "=r"(r[1]), "=r"(r[2]), "=r"(r[3]) : "r"(addr) : "memory");
}
__device__ __forceinline__ void ldsm4t(uint32_t addr, uint32_t (&r)[4]) {
    asm volatile("ldmatrix.sync.aligned.m8n8.x4.trans.shared.b16 {%0,%1,%2,%3}, [%4];"
                 : "=r"(r[0]), "=r"(r[1]), "=r"(r[2]), "=r"(r[3]) : "r"(addr) : "memory");
}
__device__ __forceinline__ void mma16816(float (&c)[4], const uint32_t (&a)[4], uint32_t b0, uint32_t b1) {
    asm volatile("mma.sync.aligned.m16n8k16.row.col.f32.bf16.bf16.f32 {%0,%1,%2,%3}, {%4,%5,%6,%7}, {%8,%9}, {%0,%1,%2,%3};"
                 : "+f"(c[0]), "+f"(c[1]), "+f"(c[2]), "+f"(c[3])
                 : "r"(a[0]), "r"(a[1]), "r"(a[2]), "r"(a[3]), "r"(b0), "r"(b1));
}
__device__ __forceinline__ uint32_t movmatrix_t(uint32_t a) {
    uint32_t d;
    asm volatile("movmatrix.sync.aligned.m8n8.trans.b16 %0, %1;" : "=r"(d) : "r"(a));
    return d;
}
__device__ __forceinline__ uint32_t pack_bf16(float a, float b) {
    uint32_t r;
    asm("cvt.rn.bf16x2.f32 %0, %1, %2;" : "=r"(r) : "f"(b), "f"(a));
    return r;
}
__device__ __forceinline__ float bf_lo(uint32_t v) { return __uint_as_float(v << 16); }
__device__ __forceinline__ float bf_hi(uint32_t v) { return __uint_as_float(v & 0xffff0000u); }
__device__ __forceinline__ float bf16r(float a) { return bf_lo(pack_bf16(a, 0.f)); }
__device__ __forceinline__ uint32_t max_bf16x2(uint32_t a, uint32_t b) {
    uint32_t r;
    asm("max.bf16x2 %0, %1, %2;" : "=r"(r) : "r"(a), "r"(b));
    return r;
}
__device__ __forceinline__ float ex2(float x) {
    float r;
    asm("ex2.approx.ftz.f32 %0, %1;" : "=f"(r) : "f"(x));
    return r;
}

__device__ __forceinline__ void st_ll2(uint2* p, uint32_t v, uint32_t tag) {
    asm volatile("st.relaxed.gpu.global.v2.u32 [%0], {%1, %2};" ::"l"(p), "r"(v), "r"(tag) : "memory");
}
__device__ __forceinline__ void st_ll4(uint4* p, uint32_t v0, uint32_t v1, uint32_t tag) {
    asm volatile("st.relaxed.gpu.global.v4.u32 [%0], {%1, %2, %3, %2};" ::"l"(p), "r"(v0), "r"(tag), "r"(v1) : "memory");
}
__device__ __forceinline__ void st_v4(uint4* p, uint32_t a, uint32_t b, uint32_t c, uint32_t d) {
    asm volatile("st.relaxed.gpu.global.v4.u32 [%0], {%1, %2, %3, %4};" ::"l"(p), "r"(a), "r"(b), "r"(c), "r"(d) : "memory");
}
__device__ __forceinline__ uint2 ld_ll2(const uint2* p) {
    uint2 v;
    asm volatile("ld.relaxed.gpu.global.v2.u32 {%0, %1}, [%2];" : "=r"(v.x), "=r"(v.y) : "l"(p) : "memory");
    return v;
}
__device__ __forceinline__ uint4 ld_ll4(const uint4* p) {
    uint4 v;
    asm volatile("ld.relaxed.gpu.global.v4.u32 {%0, %1, %2, %3}, [%4];"
                 : "=r"(v.x), "=r"(v.y), "=r"(v.z), "=r"(v.w) : "l"(p) : "memory");
    return v;
}

#define DELAY_B1 450
#define DELAY_B2 0
#define DELAY_C 450
__device__ __forceinline__ uint32_t clock32() {
    uint32_t c;
    asm volatile("mov.u32 %0, %clock;" : "=r"(c));
    return c;
}
__device__ __forceinline__ void spin_cycles(uint32_t n) {
    if (n > 0) { const uint32_t c0 = clock32(); while (clock32() - c0 < n) {} }
}
__device__ __forceinline__ float rcp_approx(float x) {
    float r;
    asm("rcp.approx.ftz.f32 %0, %1;" : "=f"(r) : "f"(x));
    return r;
}
__device__ __forceinline__ float sqrt_approx(float x) {
    float r;
    asm("sqrt.approx.f32 %0, %1;" : "=f"(r) : "f"(x));
    return r;
}

__device__ __forceinline__ float silu_bf(float v) { return bf16r(v / (1.0f + expf(-v))); }

__device__ __forceinline__ float2 half_warp_sums(const float (&v)[4], float pivot) {
    float s1 = 0.f, s2 = 0.f;
#pragma unroll
    for (int i = 0; i < 4; i++) { const float d = v[i] - pivot; s1 += d; s2 += d * d; }
#pragma unroll
    for (int o = 1; o < 16; o <<= 1) { s1 += __shfl_xor_sync(0xffffffffu, s1, o); s2 += __shfl_xor_sync(0xffffffffu, s2, o); }
    return make_float2(s1, s2);
}
__device__ __forceinline__ void ln_stats(const float2* stat, int b, float pivot, float& mean_bf, float& rstd) {
    float s1 = 0.f, s2 = 0.f;
#pragma unroll
    for (int w = 0; w < 8; w++) { const float2 v = stat[w * 2 + b]; s1 += v.x; s2 += v.y; }
    const float dm = s1 * (1.0f / D_MODEL);
    const float var = fmaxf(s2 * (1.0f / D_MODEL) - dm * dm, 0.f);
    mean_bf = bf16r(pivot + dm);
    rstd = rcp_approx(bf16r(sqrt_approx(bf16r(bf16r(var) + 1e-5f))));
}
__device__ __forceinline__ float ln_norm(float xv, float mean_bf, float rstd) { return bf16r(bf16r(xv - mean_bf) * rstd); }
__device__ __forceinline__ float ln_mod(float n, float cmul, float sadd) { return bf16r(n * bf16r(1.0f + cmul)) + sadd; }

__global__ void __launch_bounds__(NTHREADS, 1)
fused_block_kernel(const Params p, const __grid_constant__ CUtensorMap tm_k, const __grid_constant__ CUtensorMap tm_v,
                   const __grid_constant__ CUtensorMap tm_wq, const __grid_constant__ CUtensorMap tm_wmod,
                   const __grid_constant__ CUtensorMap tm_wo, const __grid_constant__ CUtensorMap tm_wg,
                   const __grid_constant__ CUtensorMap tm_wu, const __grid_constant__ CUtensorMap tm_wd) {
    extern __shared__ unsigned char smem_raw[];
    const uint32_t sbase = (smem_u32(smem_raw) + 1023u) & ~1023u;
    unsigned char* sgen = smem_raw + (sbase - smem_u32(smem_raw));
    const int tid = threadIdx.x, warp = tid >> 5, lane = tid & 31;
    const int cta = blockIdx.x;
    const uint32_t bar_full = sbase + SM_BAR, bar_empty = bar_full + NST * 8;
    const uint32_t bar_clear = bar_empty + NST * 8;
    const uint32_t bar_gu = bar_clear + 7 * 8;
    const uint32_t bar_trig = bar_clear;

    if (warp == 8) {
        if (lane == 0) {
            prefetch_tmap(&tm_wq);
            for (int i = 0; i < NST; i++) { mbar_init(bar_full + 8 * i, 1); mbar_init(bar_empty + 8 * i, 4); }
            mbar_init(bar_clear, 1);
            for (int k = 1; k <= 6; k++) mbar_init(bar_trig + 8 * k, 1);
            for (int k = 0; k < 8; k++) mbar_init(bar_gu + 8 * k, 1);
            ((volatile uint32_t*)(sgen + SM_PACE))[0] = 0;
            ((volatile uint32_t*)(sgen + SM_PACE))[1] = INFL_MAIN;
            asm volatile("fence.mbarrier_init.release.cluster;" ::: "memory");
        }
        __syncwarp();
        asm volatile("bar.arrive 2, 320;" ::: "memory");
        asm volatile("bar.arrive 3, 64;" ::: "memory");
        if (lane == 0) {
            const int pair = cta >> 3, j = cta & 7;
            const int key0 = pair * SK + j * 64;
            uint64_t pol;
            asm volatile("createpolicy.fractional.L2::evict_first.b64 %0, 1.0;" : "=l"(pol));
            int slot = 0; uint32_t ph = 1;
            int landed = 0, wslot = 0; uint32_t wph = 0;
            int kv = 0;
            constexpr int N_STREAM = kv_idx(KV_TILES - 1) + 2;
            auto issue = [&](int idx) {
                const uint32_t fb = bar_full + 8 * (idx % NST), dst = sbase + SM_RING + (idx % NST) * TILE;
                if ((idx == IDX_WG || idx == IDX_WU || idx == IDX_WD) && cta >= NFFN) {
                    mbar_arrive(fb);
                    return;
                }
                mbar_expect_tx(fb, TILE);
                if (idx < 2) {
                    tma_2d(dst, &tm_wq, cta * 32, idx * 256, fb);
                } else if (idx == IDX_MOD) {
                    tma_2d(dst, &tm_wmod, 1024 + cta * 16, 0, fb);
                    tma_2d(dst + 8192, &tm_wmod, 1024 + cta * 16, 256, fb);
                } else if (idx == IDX_WO || idx == IDX_WO + 1) {
                    tma_3d(dst, &tm_wo, 0, cta * 32 + (idx - IDX_WO) * 16, 0, fb);
                } else if (idx == IDX_WG || idx == IDX_WU) {
                    const CUtensorMap* m = idx == IDX_WG ? &tm_wg : &tm_wu;
#pragma unroll
                    for (int q = 0; q < 4; q++) tma_2d(dst + q * 4096, m, cta * 16, q * 128, fb);
                } else if (idx == IDX_WD) {
                    tma_3d(dst, &tm_wd, 0, cta * 16, 0, fb);
                } else {
                    tma_3d_hint(dst, (kv & 1) ? &tm_v : &tm_k, 0, key0 + (kv >> 1) * 512, 0, fb, pol);
                    kv++;
                }
            };
            auto wait_window = [&](int idx, int window) {
                while (landed + window <= idx) {
                    mbar_wait(bar_full + 8 * wslot, wph);
                    if (++wslot == NST) { wslot = 0; wph ^= 1; }
                    landed++;
                }
            };
            for (int idx = 0; idx < N_STREAM; idx++) {
                if (idx >= NST) mbar_wait(bar_empty + 8 * slot, ph);
                wait_window(idx, idx < PRO_TILES ? INFL_PRO : (int)((volatile uint32_t*)(sgen + SM_PACE))[1]);
                if (idx == 0) { prefetch_tmap(&tm_k); prefetch_tmap(&tm_v); prefetch_tmap(&tm_wmod); }
                if (idx == 12) { prefetch_tmap(&tm_wo); prefetch_tmap(&tm_wg); prefetch_tmap(&tm_wu); prefetch_tmap(&tm_wd); }
                issue(idx);
                ((volatile uint32_t*)(sgen + SM_PACE))[0] = idx + 1;
                if (++slot == NST) { slot = 0; ph ^= 1; }
            }
            auto deferred = [&](int idx, bool windowed) {
                if (idx < N_STREAM) return;
                mbar_wait(bar_empty + 8 * (idx % NST), ((idx / NST) & 1) ^ 1);
                if (windowed) wait_window(idx, INFL_TAIL);
                issue(idx);
            };
#pragma unroll
            for (int kk = 0; kk <= 6; kk++) {
                const int k = kk == 0 ? 0 : kk == 1 ? 6 : kk - 1;
                if (TR_PF_WO != k && TR_PF_FF != k && TR_LD_WO != k && TR_LD_GU != k && TR_LD_WD != k) continue;
                if (k > 0) mbar_wait(bar_trig + 8 * k, 0);
                if (TR_PF_WO == k) l2pf_1d((const char*)p.wo + (size_t)cta * 32768, 32768);
                if (TR_PF_FF == k && cta < NFFN) {
                    l2pf_1d((const char*)p.wg + (size_t)cta * 16384, 16384);
                    l2pf_1d((const char*)p.wu + (size_t)cta * 16384, 16384);
                    l2pf_1d((const char*)p.wd + (size_t)cta * 16384, 16384);
                }
                if (TR_LD_WO == k) { deferred(IDX_WO, k == 0 || k == 6); deferred(IDX_WO + 1, k == 0 || k == 6); }
                if (TR_LD_GU == k) {
                    if (!GU_PIECES) { deferred(IDX_WG, k == 0 || k == 6); deferred(IDX_WU, k == 0 || k == 6); }
                    else if (cta < NFFN) {
                        mbar_wait(bar_empty + 8 * (IDX_WG % NST), ((IDX_WG / NST) & 1) ^ 1);
                        mbar_wait(bar_empty + 8 * (IDX_WU % NST), ((IDX_WU / NST) & 1) ^ 1);
                        if (IDX_WO >= N_STREAM && TR_LD_WO <= k) {
                            mbar_wait(bar_full + 8 * (IDX_WO % NST), (IDX_WO / NST) & 1);
                            mbar_wait(bar_full + 8 * ((IDX_WO + 1) % NST), ((IDX_WO + 1) / NST) & 1);
                        }
#pragma unroll
                        for (int st = 0; st < 8; st++) {
                            if (st >= GU_WIN) mbar_wait(bar_gu + 8 * (st - GU_WIN), 0);
                            const uint32_t dst = sbase + SM_RING + (((st & 1) ? IDX_WU : IDX_WG) % NST) * TILE + (st >> 1) * 4096;
                            mbar_expect_tx(bar_gu + 8 * st, 4096);
                            tma_2d(dst, (st & 1) ? &tm_wu : &tm_wg, cta * 16, (st >> 1) * 128, bar_gu + 8 * st);
                        }
                        mbar_wait(bar_gu + 8 * 7, 0);
                    }
                }
                if (TR_LD_WD == k) deferred(IDX_WD, !GU_PIECES && (k == 0 || k == 6));
            }
        }
    } else if (warp == 9) {
        Scratch* const sc = p.sc;
        const uint32_t tag = *(volatile unsigned*)&sc->epoch + 1;
        if (lane < 2) {
            st_ll4((uint4*)&sc->mod[lane][cta * 4], 0u, 0u, 0u);
            st_ll4((uint4*)&sc->mod[lane][cta * 4] + 1, 0u, 0u, 0u);
        }
        if (lane < 8) st_ll4((uint4*)&sc->mod[lane >> 2][512 + cta * 8] + (lane & 3), 0u, 0u, 0u);
        if (lane < 16) st_ll4((uint4*)&sc->q[lane >> 3][cta * 16] + (lane & 7), 0u, 0u, 0u);
        __syncwarp();
        asm volatile("bar.arrive 2, 320;" ::: "memory");
        asm volatile("bar.sync 3, 64;" ::: "memory");
#pragma unroll 4
        for (int i = 0; i < 8; i++) st_v4(&sc->inbox[cta][0][0] + i * 32 + lane, 0u, 0u, 0u, 0u);
#pragma unroll 4
        for (int i = 0; i < 4; i++) st_v4((uint4*)&sc->part_o[cta][0][0] + i * 32 + lane, 0u, 0u, 0u, 0u);
        if (lane < 8) st_v4((uint4*)&sc->part_ml[cta][0][0] + lane, 0u, 0u, 0u, 0u);
        if (lane < 2) st_v4((uint4*)&sc->x1[cta][0] + lane, 0u, 0u, 0u, 0u);
        if (cta == 0 && lane == 0) asm volatile("st.relaxed.gpu.global.u32 [%0], %1;" ::"l"(&sc->progress), "r"(0u) : "memory");
        asm volatile("fence.acq_rel.gpu;" ::: "memory");
        __syncwarp();
        if (lane == 0) {
            asm volatile("fence.acq_rel.gpu;" ::: "memory");
            asm volatile("red.relaxed.gpu.global.add.u32 [%0], %1;" ::"l"(&sc->cleared), "r"(1u) : "memory");
            const uint32_t target = tag * NCTA;
            for (int it = 0; it < SPIN_LIMIT; it++) {
                uint32_t v;
                asm volatile("ld.relaxed.gpu.global.u32 %0, [%1];" : "=r"(v) : "l"(&sc->cleared) : "memory");
                if ((int32_t)(v - target) >= 0) break;
                __nanosleep(500);
            }
            asm volatile("fence.acq_rel.gpu;" ::: "memory");
            mbar_arrive(bar_clear);
            volatile uint32_t* pace = (volatile uint32_t*)(sgen + SM_PACE);
            constexpr uint32_t N_STREAM = kv_idx(KV_TILES - 1) + 2;
            uint32_t posted = 0;
            for (int it = 0; it < SPIN_LIMIT; it++) {
                const uint32_t own = pace[0];
                if (own > posted) {
                    asm volatile("red.relaxed.gpu.global.add.u32 [%0], %1;" ::"l"(&sc->progress), "r"(own - posted) : "memory");
                    posted = own;
                }
                uint32_t v;
                asm volatile("ld.relaxed.gpu.global.u32 %0, [%1];" : "=r"(v) : "l"(&sc->progress) : "memory");
                if (own >= N_STREAM) {
                    if (v + GRID_SLACK >= NCTA * N_STREAM) break;
                } else {
                    const int diff = (int)v - (int)own * NCTA;
                    pace[1] = diff > PACE_HI2 && own + PACE_END >= N_STREAM ? INFL_MAIN + 2
                            : diff > PACE_HI ? INFL_MAIN + 1 : diff < -PACE_LO ? INFL_MAIN - 1 : INFL_MAIN;
                }
                __nanosleep(own + 4 >= N_STREAM ? 50 : PACE_SLEEP);
            }
            mbar_arrive(bar_trig + 8 * 6);
        }
    } else {
        const int g = lane >> 2, t = lane & 3;
        const int bb = g & 1;
        const int eb = lane >> 4;
        const int ec = 64 * warp + 4 * (lane & 15);
        if (warp == 0) TSTAMP(0);
        Scratch* const sc = p.sc;
        const uint4 w0 = __ldg((const uint4*)(p.w_mod + (size_t)tid * N_MOD + cta * 8));
        const uint4 w1 = __ldg((const uint4*)(p.w_mod + (size_t)(tid + 256) * N_MOD + cta * 8));
        const float c00 = __bfloat162float(p.c[tid]), c01 = __bfloat162float(p.c[tid + 256]);
        const float c10 = __bfloat162float(p.c[D_MODEL + tid]), c11 = __bfloat162float(p.c[D_MODEL + tid + 256]);
        const uint2 xe = __ldg((const uint2*)(p.x + eb * D_MODEL + ec));
        const float xpivot = __bfloat162float(p.x[eb * D_MODEL]);
        const uint32_t tag = *(volatile unsigned*)&sc->epoch + 1;
        const int ocol = cta * 4 + (lane & 3);
        const float xo0 = __bfloat162float(p.x[ocol]), xo1 = __bfloat162float(p.x[D_MODEL + ocol]);

        float* red = (float*)(sgen + SM_RED);
        float* red2 = (float*)(sgen + SM_RED2);
        float2* stat = (float2*)(sgen + SM_STAT);
        uint32_t* hs = (uint32_t*)(sgen + SM_HS) + warp * 64;
        float xn[4];
        {
            float xv[4] = {bf_lo(xe.x), bf_hi(xe.x), bf_lo(xe.y), bf_hi(xe.y)};
            const float2 ps = half_warp_sums(xv, xpivot);
            if ((lane & 15) == 0) stat[warp * 2 + eb] = ps;
            const float s00 = silu_bf(c00), s01 = silu_bf(c01), s10 = silu_bf(c10), s11 = silu_bf(c11);
            __nv_bfloat16* scs = (__nv_bfloat16*)(sgen + SM_SC);
            scs[tid] = __float2bfloat16_rn(s00); scs[tid + 256] = __float2bfloat16_rn(s01);
            scs[512 + tid] = __float2bfloat16_rn(s10); scs[512 + tid + 256] = __float2bfloat16_rn(s11);
            const uint32_t a[4] = {w0.x, w0.y, w0.z, w0.w}, b[4] = {w1.x, w1.y, w1.z, w1.w};
            float v[16];
#pragma unroll
            for (int i = 0; i < 4; i++) {
                v[2 * i] = s00 * bf_lo(a[i]) + s01 * bf_lo(b[i]);
                v[2 * i + 1] = s00 * bf_hi(a[i]) + s01 * bf_hi(b[i]);
                v[8 + 2 * i] = s10 * bf_lo(a[i]) + s11 * bf_lo(b[i]);
                v[8 + 2 * i + 1] = s10 * bf_hi(a[i]) + s11 * bf_hi(b[i]);
            }
#define XRED(N, O)                                                                       \
            {                                                                            \
                const bool up = lane & (O);                                              \
                _Pragma("unroll") for (int i = 0; i < (N); i++) {                        \
                    const float send = up ? v[i] : v[i + (N)], keep = up ? v[i + (N)] : v[i]; \
                    v[i] = keep + __shfl_xor_sync(0xffffffffu, send, (O));               \
                }                                                                        \
            }
            XRED(8, 16) XRED(4, 8) XRED(2, 4) XRED(1, 2)
#undef XRED
            v[0] += __shfl_xor_sync(0xffffffffu, v[0], 1);
            if (!(lane & 1)) red[warp * 16 + (lane >> 1)] = v[0];
            if (warp == 0) TSTAMP(14);
            asm volatile("bar.sync 2, 320;" ::: "memory");
            if (warp == 0) TSTAMP(23);
            if (warp == 0) {
                float s = 0.f;
#pragma unroll
                for (int w = 0; w < 8; w++) s += red[w * 16 + (lane & 15)];
                const float nx = __shfl_down_sync(0xffffffffu, s, 1);
                if (lane < 16 && !(lane & 1))
                    st_ll2(&sc->mod[lane >> 3][cta * 4 + ((lane & 7) >> 1)], pack_bf16(s, nx), tag);
                TSTAMP(1);
            }
            float mean_bf, rstd;
            ln_stats(stat, eb, xpivot, mean_bf, rstd);
#pragma unroll
            for (int i = 0; i < 4; i++) xn[i] = ln_norm(xv[i], mean_bf, rstd);
        }
        {
            uint4 sa, ca;
            for (int it = 0;; it++) {
                sa = ld_ll4((const uint4*)&sc->mod[eb][ec >> 1]);
                ca = ld_ll4((const uint4*)&sc->mod[eb][256 + (ec >> 1)]);
                const bool ok = sa.y == tag && sa.w == tag && ca.y == tag && ca.w == tag;
                if (__all_sync(0xffffffffu, ok) || it > SPIN_LIMIT) break;
            }
            *(uint2*)&hs[eb * 32 + 2 * (lane & 15)] =
                make_uint2(pack_bf16(ln_mod(xn[0], bf_lo(ca.x), bf_lo(sa.x)), ln_mod(xn[1], bf_hi(ca.x), bf_hi(sa.x))),
                           pack_bf16(ln_mod(xn[2], bf_lo(ca.z), bf_lo(sa.z)), ln_mod(xn[3], bf_hi(ca.z), bf_hi(sa.z))));
            __syncwarp();
            uint32_t hb[8];
#pragma unroll
            for (int i = 0; i < 8; i++) hb[i] = hs[bb * 32 + 8 * (i >> 1) + 4 * (i & 1) + t];
            if (warp == 0) TSTAMP(2);
            float cq[2][4] = {};
            const int ts = warp >> 2;
            mbar_wait(bar_full + 8 * ts, 0);
            const uint32_t tb = sbase + SM_RING + ts * TILE;
#pragma unroll
            for (int s = 0; s < 4; s++) {
                const int row = 64 * (warp & 3) + 16 * s + (lane & 7) + (lane >> 4) * 8;
#pragma unroll
                for (int mt = 0; mt < 2; mt++) {
                    const int ch = 2 * mt + ((lane >> 3) & 1);
                    uint32_t a[4];
                    ldsm4t(tb + row * 64 + ((ch ^ ((row >> 1) & 3)) << 4), a);
                    mma16816(cq[mt], a, hb[2 * s], hb[2 * s + 1]);
                }
            }
            if (t < 2) {
                const float v0 = t == 0 ? cq[0][0] : cq[1][0], v1 = t == 0 ? cq[0][1] : cq[1][1];
                const float v2 = t == 0 ? cq[0][2] : cq[1][2], v3 = t == 0 ? cq[0][3] : cq[1][3];
                *(float2*)&red2[warp * 64 + (16 * t + g) * 2] = make_float2(v0, v1);
                *(float2*)&red2[warp * 64 + (16 * t + g + 8) * 2] = make_float2(v2, v3);
            }
            cons_sync();
            if (warp < 4 && lane == 0) { mbar_arrive(bar_empty + 0); mbar_arrive(bar_empty + 8); }
            if (warp == 0) {
                const int b = lane >> 4, cp = lane & 15;
                float q0 = 0.f, q1 = 0.f;
#pragma unroll
                for (int w = 0; w < 8; w++) {
                    const float4 v = *(const float4*)&red2[w * 64 + cp * 4];
                    q0 += b ? v.y : v.x; q1 += b ? v.w : v.z;
                }
                st_ll2(&sc->q[b][cta * 16 + cp], pack_bf16(q0, q1), tag);
                TSTAMP(3);
            }
        }
        const int pair = cta >> 3;
        uint32_t qf[16];
        {
            uint2* qs = (uint2*)(sgen + SM_QS);
            if (tid < 128) {
                const uint4* src = (const uint4*)&sc->q[pair >> 3][(pair & 7) * 256] + tid;
                uint4 v;
                for (int it = 0;; it++) {
                    v = ld_ll4(src);
                    if ((v.y == tag && v.w == tag) || it > SPIN_LIMIT) break;
                }
                qs[tid] = make_uint2(v.x, v.z);
            }
            cons_sync();
            const uint32_t* q32 = (const uint32_t*)(sgen + SM_QS);
#pragma unroll
            for (int s = 0; s < 8; s++) {
                qf[2 * s] = q32[(g & 3) * 64 + 8 * s + t];
                qf[2 * s + 1] = q32[(g & 3) * 64 + 8 * s + 4 + t];
            }
        }
        if (warp == 0) TSTAMP(4);

        float o[8][4];
#pragma unroll
        for (int i = 0; i < 8; i++) { o[i][0] = o[i][1] = o[i][2] = o[i][3] = 0.f; }
        uint32_t mrun = 0xff80ff80u;
        float ls[4] = {0.f, 0.f, 0.f, 0.f};
        uint4 m_sb, m_cb; uint2 m_ga0, m_ga1, m_gb0, m_gb1;
        {
            const int grp = warp >> 2, wi = warp & 3;
            const int krow = 16 * wi + (lane & 7) + ((lane >> 3) & 1) * 8;
            const uint32_t koff = krow * 128 + ((((lane >> 4) & 1) ^ (lane & 7)) << 4);
            const int vrow = 16 * wi + (lane & 7) + (lane >> 4) * 8;
            const uint32_t voff = vrow * 128 + ((((lane >> 3) & 1) ^ (lane & 7)) << 4);
            const uint32_t ones[4] = {0x3f803f80u, 0x3f803f80u, 0x3f803f80u, 0x3f803f80u};
            for (int i = grp; i < KV_TILES; i += 2) {
                if (i == MOD_AT + grp) {
                    float cm[4] = {};
                    const uint32_t* sc32 = (const uint32_t*)(sgen + SM_SC) + bb * 256 + 32 * warp + t;
                    mbar_wait(bar_full + 8 * (IDX_MOD % NST), (IDX_MOD / NST) & 1);
                    const uint32_t tb = sbase + SM_RING + (IDX_MOD % NST) * TILE;
#pragma unroll
                    for (int s = 0; s < 4; s++) {
                        const int row = 64 * warp + 16 * s + (lane & 7) + (lane >> 4) * 8;
                        const int ch = (lane >> 3) & 1;
                        uint32_t a[4];
                        ldsm4t(tb + row * 32 + ((ch ^ ((row >> 2) & 1)) << 4), a);
                        mma16816(cm, a, sc32[8 * s], sc32[8 * s + 4]);
                    }
                    if (t == 0) {
                        *(float2*)&red[warp * 64 + g * 2] = make_float2(cm[0], cm[1]);
                        *(float2*)&red[warp * 64 + (g + 8) * 2] = make_float2(cm[2], cm[3]);
                    }
                    cons_sync();
                    if (warp < 4 && lane == 0) mbar_arrive(bar_empty + 8 * (IDX_MOD % NST));
                    if (warp == 1 && lane < 16) {
                        const int b = lane >> 3, cp = lane & 7;
                        float q0 = 0.f, q1 = 0.f;
#pragma unroll
                        for (int w = 0; w < 8; w++) {
                            const float4 v = *(const float4*)&red[w * 64 + cp * 4];
                            q0 += b ? v.y : v.x; q1 += b ? v.w : v.z;
                        }
                        st_ll2(&sc->mod[b][512 + cta * 8 + cp], pack_bf16(q0, q1), tag);
                    }
                }
                if (i == 56 + grp) {
                    m_sb = ld_ll4((const uint4*)&sc->mod[eb][768 + (ec >> 1)]);
                    m_cb = ld_ll4((const uint4*)&sc->mod[eb][1024 + (ec >> 1)]);
                    m_ga0 = ld_ll2(&sc->mod[0][512 + (ocol >> 1)]); m_ga1 = ld_ll2(&sc->mod[1][512 + (ocol >> 1)]);
                    m_gb0 = ld_ll2(&sc->mod[0][1280 + (ocol >> 1)]); m_gb1 = ld_ll2(&sc->mod[1][1280 + (ocol >> 1)]);
                }
                if (i == 60 + grp) {
                    for (int it = 0;; it++) {
                        const bool ok = m_sb.y == tag && m_sb.w == tag && m_cb.y == tag && m_cb.w == tag &&
                                        m_ga0.y == tag && m_ga1.y == tag && m_gb0.y == tag && m_gb1.y == tag;
                        if (__all_sync(0xffffffffu, ok) || it > SPIN_LIMIT) break;
                        m_sb = ld_ll4((const uint4*)&sc->mod[eb][768 + (ec >> 1)]);
                        m_cb = ld_ll4((const uint4*)&sc->mod[eb][1024 + (ec >> 1)]);
                        m_ga0 = ld_ll2(&sc->mod[0][512 + (ocol >> 1)]); m_ga1 = ld_ll2(&sc->mod[1][512 + (ocol >> 1)]);
                        m_gb0 = ld_ll2(&sc->mod[0][1280 + (ocol >> 1)]); m_gb1 = ld_ll2(&sc->mod[1][1280 + (ocol >> 1)]);
                    }
                    mbar_wait(bar_clear, 0);
                }
                const int ki = kv_idx(i), ks = ki % NST, vs = (ki + 1) % NST;
                const uint32_t kph = (ki / NST) & 1, vph = ((ki + 1) / NST) & 1;
                mbar_wait(bar_full + 8 * ks, kph);
                const uint32_t kb = sbase + SM_RING + ks * TILE + koff;
                float sa[4] = {0.f, 0.f, 0.f, 0.f}, sb[4] = {0.f, 0.f, 0.f, 0.f};
#pragma unroll
                for (int s = 0; s < 8; s += 2) {
                    uint32_t a0[4], a1[4];
                    ldsm4((kb ^ ((s & 3) << 5)) + (s >> 2) * 8192, a0);
                    ldsm4((kb ^ (((s + 1) & 3) << 5)) + (s >> 2) * 8192, a1);
                    mma16816(sa, a0, qf[2 * s], qf[2 * s + 1]);
                    mma16816(sb, a1, qf[2 * s + 2], qf[2 * s + 3]);
                }
                __syncwarp();
                if (lane == 0) mbar_arrive(bar_empty + 8 * ks);
                uint32_t r01 = pack_bf16(sa[0] + sb[0], sa[1] + sb[1]);
                uint32_t r23 = pack_bf16(sa[2] + sb[2], sa[3] + sb[3]);
                r01 = pack_bf16(bf_lo(r01) * QK_SCALE, bf_hi(r01) * QK_SCALE);
                r23 = pack_bf16(bf_lo(r23) * QK_SCALE, bf_hi(r23) * QK_SCALE);
                uint32_t mx = max_bf16x2(r01, r23);
                mx = max_bf16x2(mx, __shfl_xor_sync(0xffffffffu, mx, 4));
                mx = max_bf16x2(mx, __shfl_xor_sync(0xffffffffu, mx, 8));
                mx = max_bf16x2(mx, __shfl_xor_sync(0xffffffffu, mx, 16));
                const uint32_t mnew = max_bf16x2(mrun, mx);
                const float m0 = bf_lo(mnew), m1 = bf_hi(mnew);
                if (__any_sync(0xffffffffu, mnew != mrun)) {
                    const float al0 = ex2((bf_lo(mrun) - m0) * LOG2E), al1 = ex2((bf_hi(mrun) - m1) * LOG2E);
                    ls[0] *= al0; ls[1] *= al1;
#pragma unroll
                    for (int d = 0; d < 8; d++) { o[d][0] *= al0; o[d][1] *= al1; o[d][2] *= al0; o[d][3] *= al1; }
                    mrun = mnew;
                }
                const float p0 = ex2((bf_lo(r01) - m0) * LOG2E), p1 = ex2((bf_hi(r01) - m1) * LOG2E);
                const float p2 = ex2((bf_lo(r23) - m0) * LOG2E), p3 = ex2((bf_hi(r23) - m1) * LOG2E);
                const uint32_t pb0 = movmatrix_t(pack_bf16(p0, p1)), pb1 = movmatrix_t(pack_bf16(p2, p3));
                mma16816(ls, ones, pb0, pb1);
                mbar_wait(bar_full + 8 * vs, vph);
                const uint32_t vb = sbase + SM_RING + vs * TILE + voff;
#pragma unroll
                for (int d = 0; d < 8; d++) {
                    uint32_t a[4];
                    ldsm4t((vb ^ ((d & 3) << 5)) + (d >> 2) * 8192, a);
                    mma16816(o[d], a, pb0, pb1);
                }
                __syncwarp();
                if (lane == 0) mbar_arrive(bar_empty + 8 * vs);
            }
        }
        if (warp == 7) TSTAMP(5);
        if (warp == 7 && lane == 0) mbar_arrive(bar_trig + 8 * 1);
        {
            float* mrg = (float*)(sgen + SM_MRG);
            float2* ml = (float2*)(sgen + SM_ML);
            {
                const int hp = (t & 1) * 2, up = t >> 1;
                if (g == 0 && up == 0) { ml[warp * 4 + hp] = make_float2(bf_lo(mrun), ls[0]); ml[warp * 4 + hp + 1] = make_float2(bf_hi(mrun), ls[1]); }
                float* m0p = mrg + (warp * 4 + hp) * 136 + up * 72 + g;
#pragma unroll
                for (int d = 0; d < 4; d++) {
                    m0p[16 * d] = up ? o[d + 4][0] : o[d][0]; m0p[136 + 16 * d] = up ? o[d + 4][1] : o[d][1];
                    m0p[16 * d + 8] = up ? o[d + 4][2] : o[d][2]; m0p[136 + 16 * d + 8] = up ? o[d + 4][3] : o[d][3];
                }
            }
            cons_sync();
            const int hh = tid >> 6, dp = tid & 63;
            float2 mw[8];
            float M = -INFINITY;
#pragma unroll
            for (int w = 0; w < 8; w++) { mw[w] = ml[w * 4 + hh]; M = fmaxf(M, mw[w].x); }
            float L = 0.f, o0 = 0.f, o1 = 0.f;
#pragma unroll
            for (int w = 0; w < 8; w++) {
                const float wt = ex2((mw[w].x - M) * LOG2E);
                const float2 v = *(const float2*)&mrg[(w * 4 + hh) * 136 + 2 * dp + (dp >= 32 ? 8 : 0)];
                L += wt * mw[w].y; o0 += wt * v.x; o1 += wt * v.y;
            }
            st_ll2(&sc->part_o[cta][hh][dp], tagf(o0, F_PART), tagf(o1, F_PART));
            if (dp < 4) st_ll2(&sc->part_ml[cta][hh][dp], tagf(M, F_PART), tagf(L, F_PART));
        }
        if (tid == 0) mbar_arrive(bar_trig + 8 * 2);
        if (warp == 0) TSTAMP(6);
        const uint32_t aoff = warp * 2048 + ((lane & 7) + (lane >> 4) * 8) * 128 + ((((lane >> 3) & 1) ^ (lane & 7)) << 4);
        uint32_t wf[8][4];
        if (WO_AT < KV_TILES) {
#pragma unroll
            for (int s = 0; s < 2; s++) {
                constexpr int i0 = IDX_WO;
                const int idx = i0 + s;
                mbar_wait(bar_full + 8 * (idx % NST), (idx / NST) & 1);
                const uint32_t tb = sbase + SM_RING + (idx % NST) * TILE + aoff;
#pragma unroll
                for (int mt = 0; mt < 4; mt++) ldsm4t(tb ^ (mt << 5), wf[s * 4 + mt]);
            }
        }
        {
            const int hq = cta >> 2, kvh = hq >> 2, hh = hq & 3, ds = cta & 3;
            const int b = tid >> 7, dpl = (tid >> 3) & 15, j = tid & 7;
            const int pc = (b * 8 + kvh) * 8 + j;
            const uint2* po = &sc->part_o[pc][hh][ds * 16 + dpl];
            const uint2* pm = &sc->part_ml[pc - j][hh][0];
            uint2 vo, vm[8];
            for (int it = 0;; it++) {
                vo = ld_ll2(po);
#pragma unroll
                for (int jj = 0; jj < 8; jj++) vm[jj] = ld_ll2(pm + jj * 16);
                uint32_t all = vo.x & vo.y;
#pragma unroll
                for (int jj = 0; jj < 8; jj++) all &= vm[jj].x & vm[jj].y;
                if (__all_sync(0xffffffffu, (all & 3u) == F_PART) || it > SPIN_LIMIT) break;
            }
            float M = untag(vm[0].x);
#pragma unroll
            for (int jj = 1; jj < 8; jj++) M = fmaxf(M, untag(vm[jj].x));
            float wt = 0.f, L = 0.f;
#pragma unroll
            for (int jj = 0; jj < 8; jj++) {
                const float w_ = ex2((untag(vm[jj].x) - M) * LOG2E);
                L += w_ * untag(vm[jj].y);
                wt = jj == j ? w_ : wt;
            }
            float o0 = wt * untag(vo.x), o1 = wt * untag(vo.y);
#pragma unroll
            for (int o_ = 1; o_ < 8; o_ <<= 1) {
                o0 += __shfl_xor_sync(0xffffffffu, o0, o_);
                o1 += __shfl_xor_sync(0xffffffffu, o1, o_);
            }
            uint32_t* os = (uint32_t*)(sgen + SM_OS);
            const float rl = rcp_approx(L);
            if (j == 0) os[b * 16 + dpl] = pack_bf16(o0 * rl, o1 * rl);
            if (warp == 0) TSTAMP(15);
            if (WO_AT == KV_TILES) {
#pragma unroll
            for (int s = 0; s < 2; s++) {
                constexpr int i0 = IDX_WO;
                const int idx = i0 + s;
                mbar_wait(bar_full + 8 * (idx % NST), (idx / NST) & 1);
                const uint32_t tb = sbase + SM_RING + (idx % NST) * TILE + aoff;
#pragma unroll
                for (int mt = 0; mt < 4; mt++) ldsm4t(tb ^ (mt << 5), wf[s * 4 + mt]);
            }
            }
            cons_sync();
            if (tid == 0) mbar_arrive(bar_trig + 8 * 3);
            if (warp == 0) TSTAMP(7);
            float y[4][4] = {};
#pragma unroll
            for (int s = 0; s < 2; s++) {
                const uint32_t b0 = os[bb * 16 + 8 * s + t], b1 = os[bb * 16 + 8 * s + 4 + t];
#pragma unroll
                for (int mt = 0; mt < 4; mt++) mma16816(y[mt], wf[s * 4 + mt], b0, b1);
            }
            float v[4];
#pragma unroll
            for (int i = 0; i < 4; i++) v[i] = t == 0 ? y[0][i] : t == 1 ? y[1][i] : t == 2 ? y[2][i] : y[3][i];
            {
                const bool odd = g & 1;
                const float sx = odd ? v[0] : v[2], sy = odd ? v[1] : v[3];
                const float rx = __shfl_xor_sync(0xffffffffu, sx, 4), ry = __shfl_xor_sync(0xffffffffu, sy, 4);
                const int c0 = 64 * warp + 16 * t + (odd ? g + 7 : g);
                const float e0 = odd ? rx : v[0], e1 = odd ? ry : v[1], e2 = odd ? v[2] : rx, e3 = odd ? v[3] : ry;
                st_v4(&sc->inbox[c0 >> 2][cta][(c0 >> 1) & 1], tagf(e0, F_WO), tagf(e1, F_WO), tagf(e2, F_WO), tagf(e3, F_WO));
            }
        }
        if (tid == 0) mbar_arrive(bar_trig + 8 * 4);
        if (warp == 0) TSTAMP(8);
        float xm0 = 0.f, xm1 = 0.f;
        {
            float r0;
            {
                const uint4* pin = &sc->inbox[cta][0][0] + tid;
                uint4 v = make_uint4(F_WO, F_WO, F_WO, F_WO);
                spin_cycles(DELAY_B1);
                for (int it = 0;; it++) {
                    if (tid < NCTA * 2) v = ld_ll4(pin);
                    if (__all_sync(0xffffffffu, ((v.x & v.y & v.z & v.w & 3u) == F_WO) && (((v.x | v.y | v.z | v.w) & 3u) == F_WO)) || it > SPIN_LIMIT) break;
                }
                const bool u1 = lane & 2, u2 = lane & 4;
                const float a0 = untag(v.x), a1 = untag(v.y), a2 = untag(v.z), a3 = untag(v.w);
                const float k0 = (u1 ? a1 : a0) + __shfl_xor_sync(0xffffffffu, u1 ? a0 : a1, 2);
                const float k1 = (u1 ? a3 : a2) + __shfl_xor_sync(0xffffffffu, u1 ? a2 : a3, 2);
                r0 = (u2 ? k1 : k0) + __shfl_xor_sync(0xffffffffu, u2 ? k0 : k1, 4);
                r0 += __shfl_xor_sync(0xffffffffu, r0, 8);
                r0 += __shfl_xor_sync(0xffffffffu, r0, 16);
                if (lane < 8) red2[warp * 8 + (2 * (lane & 1) + ((lane >> 2) & 1)) * 2 + ((lane >> 1) & 1)] = r0;
            }
            cons_sync();
            if (tid == 32) mbar_arrive(bar_trig + 8 * 5);
            if (warp == 0) {
                float a0 = 0.f, a1 = 0.f;
#pragma unroll
                for (int w = 0; w < 8; w++) { const float2 v = *(const float2*)&red2[w * 8 + (lane & 3) * 2]; a0 += v.x; a1 += v.y; }
                const bool hi = ocol & 1;
                const float ga0 = hi ? bf_hi(m_ga0.x) : bf_lo(m_ga0.x), ga1 = hi ? bf_hi(m_ga1.x) : bf_lo(m_ga1.x);
                xm0 = bf16r(xo0 + bf16r(ga0 * bf16r(a0)));
                xm1 = bf16r(xo1 + bf16r(ga1 * bf16r(a1)));
                if (lane < 4) st_ll2(&sc->x1[cta][lane], pack_bf16(xm0, xm1), F_X1);
                TSTAMP(10);
            }
        }
        if (cta < NFFN) {
            uint32_t gf[4][4], uf[4][4];
            if (GU_PIECES && IDX_WG >= kv_idx(KV_TILES - 1) + 2) {
                mbar_wait(bar_gu + 8 * (2 * (warp >> 1)), 0);
                mbar_wait(bar_gu + 8 * (2 * (warp >> 1) + 1), 0);
            } else {
                mbar_wait(bar_full + 8 * (IDX_WG % NST), (IDX_WG / NST) & 1);
                mbar_wait(bar_full + 8 * (IDX_WU % NST), (IDX_WU / NST) & 1);
            }
            {
                const uint32_t tg = sbase + SM_RING + (IDX_WG % NST) * TILE, tu = sbase + SM_RING + (IDX_WU % NST) * TILE;
#pragma unroll
                for (int s = 0; s < 4; s++) {
                    const int row = 64 * warp + 16 * s + (lane & 7) + (lane >> 4) * 8;
                    const uint32_t off = row * 32 + ((((lane >> 3) & 1) ^ ((row >> 2) & 1)) << 4);
                    ldsm4t(tg + off, gf[s]);
                    ldsm4t(tu + off, uf[s]);
                }
            }
            const float c1v[4] = {bf16r(1.0f + bf_lo(m_cb.x)), bf16r(1.0f + bf_hi(m_cb.x)), bf16r(1.0f + bf_lo(m_cb.z)), bf16r(1.0f + bf_hi(m_cb.z))};
            float bg, cgc, bu, cuc;
            {
                uint32_t* pre = (uint32_t*)(sgen + SM_MRG) + warp * 128;
                float* bc = (float*)(sgen + SM_MRG + 4096);
                *(uint2*)&pre[eb * 32 + 2 * (lane & 15)] = make_uint2(pack_bf16(c1v[0], c1v[1]), pack_bf16(c1v[2], c1v[3]));
                *(uint2*)&pre[64 + eb * 32 + 2 * (lane & 15)] = make_uint2(m_sb.x, m_sb.z);
                __syncwarp();
                float yg[4] = {}, yu[4] = {};
                const uint32_t* pb = pre + ((g >> 1) & 1) * 64 + bb * 32 + t;
#pragma unroll
                for (int s = 0; s < 4; s++) {
                    const uint32_t b0 = pb[8 * s], b1 = pb[8 * s + 4];
                    mma16816(yg, gf[s], b0, b1);
                    mma16816(yu, uf[s], b0, b1);
                }
                const float y0 = t < 2 ? yg[0] : yu[0], y1 = t < 2 ? yg[1] : yu[1], y2 = t < 2 ? yg[2] : yu[2], y3 = t < 2 ? yg[3] : yu[3];
                float* dstp = bc + warp * 128 + (t >> 1) * 64 + (t & 1) * 32;
                *(float2*)&dstp[g * 2] = make_float2(y0, y1);
                *(float2*)&dstp[(g + 8) * 2] = make_float2(y2, y3);
                cons_sync();
                bg = cgc = bu = cuc = 0.f;
#pragma unroll
                for (int w = 0; w < 8; w++) {
                    bg += bc[w * 128 + lane]; cgc += bc[w * 128 + 32 + lane];
                    bu += bc[w * 128 + 64 + lane]; cuc += bc[w * 128 + 96 + lane];
                }
            }
            if (warp == 0) TSTAMP(11);
            float pivot2;
            {
                const uint4* px = (const uint4*)&sc->x1[ec >> 2][0];
                const uint4* pp = (const uint4*)&sc->x1[0][0];
                uint4 va, vb, pa, pb;
                spin_cycles(DELAY_B2);
                for (int it = 0;; it++) {
                    va = ld_ll4(px); vb = ld_ll4(px + 1); pa = ld_ll4(pp); pb = ld_ll4(pp + 1);
                    const bool ok = va.y == F_X1 && va.w == F_X1 && vb.y == F_X1 && vb.w == F_X1 &&
                                    pa.y == F_X1 && pa.w == F_X1 && pb.y == F_X1 && pb.w == F_X1;
                    if (__all_sync(0xffffffffu, ok) || it > SPIN_LIMIT) break;
                }
                if (warp == 0) TSTAMP(9);
                const float xv[4] = {eb ? bf_hi(va.x) : bf_lo(va.x), eb ? bf_hi(va.z) : bf_lo(va.z),
                                     eb ? bf_hi(vb.x) : bf_lo(vb.x), eb ? bf_hi(vb.z) : bf_lo(vb.z)};
                const float p0 = 0.25f * ((bf_lo(pa.x) + bf_lo(pa.z)) + (bf_lo(pb.x) + bf_lo(pb.z)));
                const float p1 = 0.25f * ((bf_hi(pa.x) + bf_hi(pa.z)) + (bf_hi(pb.x) + bf_hi(pb.z)));
                const float pivot = eb ? p1 : p0;
                pivot2 = (lane & 1) ? p1 : p0;
                *(uint2*)&hs[eb * 32 + 2 * (lane & 15)] =
                    make_uint2(pack_bf16((xv[0] - pivot) * c1v[0], (xv[1] - pivot) * c1v[1]),
                               pack_bf16((xv[2] - pivot) * c1v[2], (xv[3] - pivot) * c1v[3]));
                __syncwarp();
                float cg[2][4] = {}, cu[2][4] = {};
#pragma unroll
                for (int s = 0; s < 4; s++) {
                    const uint32_t b0 = hs[bb * 32 + 8 * s + t], b1 = hs[bb * 32 + 8 * s + 4 + t];
                    mma16816(cg[s & 1], gf[s], b0, b1);
                    mma16816(cu[s & 1], uf[s], b0, b1);
                }
                const float2 ps = half_warp_sums(xv, pivot);
                if ((lane & 15) == 0) stat[warp * 2 + eb] = ps;
                if (t < 2) {
                    float v[4];
#pragma unroll
                    for (int i = 0; i < 4; i++) v[i] = t ? cu[0][i] + cu[1][i] : cg[0][i] + cg[1][i];
                    *(float2*)&red[warp * 64 + t * 32 + g * 2] = make_float2(v[0], v[1]);
                    *(float2*)&red[warp * 64 + t * 32 + (g + 8) * 2] = make_float2(v[2], v[3]);
                }
            }
            uint32_t df[4][4];
            mbar_wait(bar_full + 8 * (IDX_WD % NST), (IDX_WD / NST) & 1);
#pragma unroll
            for (int mt = 0; mt < 4; mt++) ldsm4t((sbase + SM_RING + (IDX_WD % NST) * TILE + aoff) ^ (mt << 5), df[mt]);
            cons_sync();
            {
                float gs = 0.f, us = 0.f;
#pragma unroll
                for (int w = 0; w < 8; w++) { gs += red[w * 64 + lane]; us += red[w * 64 + 32 + lane]; }
                float mean_bf, rstd;
                ln_stats(stat, lane & 1, pivot2, mean_bf, rstd);
                const float dm = mean_bf - pivot2;
                gs = bf16r(rstd * (gs - dm * bg) + cgc);
                us = rstd * (us - dm * bu) + cuc;
                const float u2 = gs * (1.0f + 0.044715f * gs * gs) * (2.0f * 0.7978845608028654f * LOG2E);
                const float ge = bf16r(__fdividef(gs, 1.0f + ex2(-u2)));
                const float act = bf16r(ge * bf16r(us));
                const float a0 = __shfl_sync(0xffffffffu, act, 4 * t + bb), a1 = __shfl_sync(0xffffffffu, act, 4 * t + 2 + bb);
                const float a2 = __shfl_sync(0xffffffffu, act, 4 * t + 16 + bb), a3 = __shfl_sync(0xffffffffu, act, 4 * t + 18 + bb);
                const uint32_t b0 = pack_bf16(a0, a1), b1 = pack_bf16(a2, a3);
                float y[4][4] = {};
#pragma unroll
                for (int mt = 0; mt < 4; mt++) mma16816(y[mt], df[mt], b0, b1);
                float v[4];
#pragma unroll
                for (int i = 0; i < 4; i++) v[i] = t == 0 ? y[0][i] : t == 1 ? y[1][i] : t == 2 ? y[2][i] : y[3][i];
            {
                const bool odd = g & 1;
                const float sx = odd ? v[0] : v[2], sy = odd ? v[1] : v[3];
                const float rx = __shfl_xor_sync(0xffffffffu, sx, 4), ry = __shfl_xor_sync(0xffffffffu, sy, 4);
                const int c0 = 64 * warp + 16 * t + (odd ? g + 7 : g);
                const float e0 = odd ? rx : v[0], e1 = odd ? ry : v[1], e2 = odd ? v[2] : rx, e3 = odd ? v[3] : ry;
                st_v4(&sc->inbox[c0 >> 2][cta][(c0 >> 1) & 1], tagf(e0, F_DOWN), tagf(e1, F_DOWN), tagf(e2, F_DOWN), tagf(e3, F_DOWN));
            }
            }
            if (warp == 0) TSTAMP(12);
        }
        {
            float r0;
            {
                const uint4* pin = &sc->inbox[cta][0][0] + tid;
                uint4 v = make_uint4(F_DOWN, F_DOWN, F_DOWN, F_DOWN);
                spin_cycles(DELAY_C);
                for (int it = 0;; it++) {
                    if (tid < NFFN * 2) v = ld_ll4(pin);
                    if (__all_sync(0xffffffffu, ((v.x & v.y & v.z & v.w & 3u) == F_DOWN) && (((v.x | v.y | v.z | v.w) & 3u) == F_DOWN)) || it > SPIN_LIMIT) break;
                }
                const bool u1 = lane & 2, u2 = lane & 4;
                const float a0 = untag(v.x), a1 = untag(v.y), a2 = untag(v.z), a3 = untag(v.w);
                const float k0 = (u1 ? a1 : a0) + __shfl_xor_sync(0xffffffffu, u1 ? a0 : a1, 2);
                const float k1 = (u1 ? a3 : a2) + __shfl_xor_sync(0xffffffffu, u1 ? a2 : a3, 2);
                r0 = (u2 ? k1 : k0) + __shfl_xor_sync(0xffffffffu, u2 ? k0 : k1, 4);
                r0 += __shfl_xor_sync(0xffffffffu, r0, 8);
                r0 += __shfl_xor_sync(0xffffffffu, r0, 16);
                if (lane < 8) red2[64 + warp * 8 + (2 * (lane & 1) + ((lane >> 2) & 1)) * 2 + ((lane >> 1) & 1)] = r0;
            }
            cons_sync();
            if (warp == 0) {
                float a0 = 0.f, a1 = 0.f;
#pragma unroll
                for (int w = 0; w < 8; w++) { const float2 v = *(const float2*)&red2[64 + w * 8 + (lane & 3) * 2]; a0 += v.x; a1 += v.y; }
                const bool hi = ocol & 1;
                const float gb0 = hi ? bf_hi(m_gb0.x) : bf_lo(m_gb0.x), gb1 = hi ? bf_hi(m_gb1.x) : bf_lo(m_gb1.x);
                if (lane < 4) {
                    p.out[ocol] = __float2bfloat16_rn(xm0 + bf16r(gb0 * bf16r(a0)));
                    p.out[D_MODEL + ocol] = __float2bfloat16_rn(xm1 + bf16r(gb1 * bf16r(a1)));
                }
                if (cta == 0 && lane == 0) *(volatile unsigned*)&sc->epoch = tag;
                TSTAMP(13);
            }
        }
    }
}

typedef CUresult (*EncodeFn)(CUtensorMap*, CUtensorMapDataType, cuuint32_t, void*, const cuuint64_t*, const cuuint64_t*,
                             const cuuint32_t*, const cuuint32_t*, CUtensorMapInterleave, CUtensorMapSwizzle,
                             CUtensorMapL2promotion, CUtensorMapFloatOOBfill);

struct Maps { CUtensorMap k, v, wq, wmod, wo, wg, wu, wd; };

void encode(EncodeFn fn, CUtensorMap* m, const void* ptr, int rank, const cuuint64_t* dims, const cuuint64_t* strides,
            const cuuint32_t* box, CUtensorMapSwizzle sw) {
    const cuuint32_t es[3] = {1, 1, 1};
    fn(m, CU_TENSOR_MAP_DATA_TYPE_BFLOAT16, rank, const_cast<void*>(ptr), dims, strides, box, es,
       CU_TENSOR_MAP_INTERLEAVE_NONE, sw, CU_TENSOR_MAP_L2_PROMOTION_L2_256B, CU_TENSOR_MAP_FLOAT_OOB_FILL_NONE);
}

}

extern "C" void kernel_launch(void* const* d_in, const int* in_sizes, int n_in, void* d_out, int out_size) {
    (void)in_sizes; (void)n_in; (void)out_size;
    static EncodeFn enc = nullptr;
    static Scratch* scratch = nullptr;
    if (!enc) {
        cudaGetSymbolAddress((void**)&scratch, g_scratch);
        void* fn = nullptr;
        cudaDriverEntryPointQueryResult qr;
        cudaGetDriverEntryPoint("cuTensorMapEncodeTiled", &fn, cudaEnableDefault, &qr);
        enc = (EncodeFn)fn;
        cudaFuncSetAttribute(fused_block_kernel, cudaFuncAttributeMaxDynamicSharedMemorySize, SMEM_BYTES);
    }
    Maps m;
    {
        const cuuint64_t dims[3] = {64, (cuuint64_t)16 * SK, 2}, str[2] = {256, 128};
        const cuuint32_t box[3] = {64, 64, 2};
        encode(enc, &m.k, d_in[1], 3, dims, str, box, CU_TENSOR_MAP_SWIZZLE_128B);
        encode(enc, &m.v, d_in[2], 3, dims, str, box, CU_TENSOR_MAP_SWIZZLE_128B);
    }
    {
        const cuuint64_t dims[2] = {4096, 512}, str[1] = {8192};
        const cuuint32_t box[2] = {32, 256};
        encode(enc, &m.wq, d_in[3], 2, dims, str, box, CU_TENSOR_MAP_SWIZZLE_64B);
    }
    {
        const cuuint64_t dims[2] = {N_MOD, 512}, str[1] = {N_MOD * 2};
        const cuuint32_t box[2] = {16, 256};
        encode(enc, &m.wmod, d_in[10], 2, dims, str, box, CU_TENSOR_MAP_SWIZZLE_32B);
    }
    {
        const cuuint64_t dims_o[3] = {64, 4096, 8}, dims_d[3] = {64, D_FF, 8}, str[2] = {1024, 128};
        const cuuint32_t box[3] = {64, 16, 8};
        encode(enc, &m.wo, d_in[4], 3, dims_o, str, box, CU_TENSOR_MAP_SWIZZLE_128B);
        encode(enc, &m.wd, d_in[8], 3, dims_d, str, box, CU_TENSOR_MAP_SWIZZLE_128B);
    }
    {
        const cuuint64_t dims[2] = {D_FF, 512}, str[1] = {D_FF * 2};
        const cuuint32_t box[2] = {16, 128};
        encode(enc, &m.wg, d_in[6], 2, dims, str, box, CU_TENSOR_MAP_SWIZZLE_32B);
        encode(enc, &m.wu, d_in[7], 2, dims, str, box, CU_TENSOR_MAP_SWIZZLE_32B);
    }
    Params p;
    p.x = (const __nv_bfloat16*)d_in[0];
    p.c = (const __nv_bfloat16*)d_in[9];
    p.w_mod = (const __nv_bfloat16*)d_in[10];
    p.out = (__nv_bfloat16*)d_out;
    p.sc = scratch;
    p.wo = (const __nv_bfloat16*)d_in[4];
    p.wg = (const __nv_bfloat16*)d_in[6];
    p.wu = (const __nv_bfloat16*)d_in[7];
    p.wd = (const __nv_bfloat16*)d_in[8];
    fused_block_kernel<<<NCTA, NTHREADS, SMEM_BYTES, cudaStreamPerThread>>>(p, m.k, m.v, m.wq, m.wmod, m.wo, m.wg, m.wu, m.wd);
}
```

```cpp
#include <cuda_runtime.h>
#include <cuda.h>
#include <cuda_bf16.h>
#include <stdint.h>

namespace {

constexpr int D_MODEL = 512;
constexpr int N_HEADS = 32;
constexpr int SK = 32768;
constexpr int DH = 128;
constexpr int D_FF = 1792;
constexpr int N_MOD = 6 * D_MODEL;

constexpr int NCTA = 128;
constexpr int NFFN = D_FF / 16;
constexpr int NTHREADS = 320;
constexpr int NST = 12;
constexpr int TILE = 16384;
#define INFL_PRO 2
#define INFL_MAIN 3
#define INFL_TAIL 2
#define PACE_HI 96
#define PACE_LO 96
#define PACE_HI2 100000
#define PACE_END 16
#define GRID_SLACK 0
#define PACE_SLEEP 200
#define TR_PF_WO -1
#define TR_PF_FF -1
#define TR_LD_WO 0
#define TR_LD_GU 0
#define GU_PIECES 1
#define GU_WIN 3
#define TR_LD_WD 0
#define PRO_TILES 8
constexpr int KV_TILES = 64;
#define MOD_AT 8
#define WO_AT 64
#define GU_AT 64
#define WD_AT 64
static_assert(MOD_AT % 2 == 0 && MOD_AT < WO_AT && MOD_AT < GU_AT && MOD_AT < WD_AT, "schedule");
static_assert(WO_AT <= KV_TILES && GU_AT <= KV_TILES && WD_AT <= KV_TILES, "schedule");
#define WQ_AT 0
constexpr int IDX_WQ = 2 * WQ_AT;
__host__ __device__ constexpr int kv_idx(int i) {
    return (i >= WQ_AT ? 2 : 0) + 2 * i + (i >= MOD_AT ? 1 : 0) + (i >= WO_AT ? 2 : 0) + (i >= GU_AT ? 2 : 0) + (i >= WD_AT ? 1 : 0);
}
constexpr int IDX_MOD = 2 + 2 * MOD_AT;
constexpr int IDX_WO = 3 + 2 * WO_AT + (GU_AT < WO_AT ? 2 : 0) + (WD_AT < WO_AT ? 1 : 0);
constexpr int IDX_WG = 3 + 2 * GU_AT + (WO_AT <= GU_AT ? 2 : 0) + (WD_AT < GU_AT ? 1 : 0);
constexpr int IDX_WU = IDX_WG + 1;
constexpr int IDX_WD = 3 + 2 * WD_AT + (WO_AT <= WD_AT ? 2 : 0) + (GU_AT <= WD_AT ? 2 : 0);
constexpr int N_TILES = 2 + 2 * KV_TILES + 1 + 2 + 3;
static_assert(N_TILES - 1 - IDX_WO < NST && N_TILES - 1 - IDX_WG < NST && N_TILES - 1 - IDX_WD < NST, "weights must stay resident until the end");
constexpr int SPIN_LIMIT = 1 << 20;

constexpr float LOG2E = 1.4426950408889634f;
constexpr float QK_SCALE = 0.08838834764831845f;

constexpr int SM_RING = 0;
constexpr int SM_MRG = SM_RING + NST * TILE;
constexpr int SM_ML = SM_MRG + 8 * 4 * 136 * 4;
constexpr int SM_RED = SM_ML + 8 * 4 * 8;
constexpr int SM_RED2 = SM_RED + 8 * 64 * 4;
constexpr int SM_QS = SM_RED2 + 8 * 64 * 4;
constexpr int SM_OS = SM_QS + 512 * 2;
constexpr int SM_SC = SM_OS + 2 * 16 * 4;
constexpr int SM_HS = SM_SC + 2 * 512 * 2;
constexpr int SM_STAT = SM_HS + 8 * 2 * 32 * 4;
constexpr int SM_PACE = SM_STAT + 8 * 2 * 8;
constexpr int SM_BAR = SM_PACE + 8;
constexpr int SM_END = SM_BAR + (2 * NST + 7 + 8 + 1) * 8;
constexpr int SMEM_BYTES = SM_END + 1024;

struct Scratch {
    uint4 inbox[NCTA][NCTA][2];
    uint2 x1[NCTA][16];
    uint2 part_o[NCTA][4][64];
    uint2 part_ml[NCTA][4][4];
    uint2 mod[2][N_MOD / 2];
    uint2 q[2][N_HEADS * DH / 2];
    unsigned epoch;
    unsigned pad_[31];
    unsigned cleared;
    unsigned pad2_[31];
    unsigned progress;
};
__device__ Scratch g_scratch;
constexpr uint32_t F_PART = 1, F_WO = 1, F_DOWN = 2, F_X1 = 1;
__device__ __forceinline__ uint32_t tagf(float v, uint32_t f) { return (__float_as_uint(v) & ~3u) | f; }
__device__ __forceinline__ float untag(uint32_t v) { return __uint_as_float(v & ~3u); }

struct Params {
    const __nv_bfloat16* x;
    const __nv_bfloat16* c;
    const __nv_bfloat16* w_mod;
    __nv_bfloat16* out;
    Scratch* sc;
    const __nv_bfloat16 *wo, *wg, *wu, *wd;
};

#define TSTAMP(i) do { } while (0)

__device__ __forceinline__ uint32_t smem_u32(const void* p) { return (uint32_t)__cvta_generic_to_shared(p); }

__device__ __forceinline__ void mbar_init(uint32_t bar, uint32_t cnt) {
    asm volatile("mbarrier.init.shared::cta.b64 [%0], %1;" ::"r"(bar), "r"(cnt) : "memory");
}
__device__ __forceinline__ void mbar_expect_tx(uint32_t bar, uint32_t bytes) {
    asm volatile("mbarrier.arrive.expect_tx.shared::cta.b64 _, [%0], %1;" ::"r"(bar), "r"(bytes) : "memory");
}
__device__ __forceinline__ void mbar_arrive(uint32_t bar) {
    asm volatile("mbarrier.arrive.shared::cta.b64 _, [%0];" ::"r"(bar) : "memory");
}
__device__ __forceinline__ bool mbar_try(uint32_t bar, uint32_t parity) {
    uint32_t ok;
    asm volatile(
        "{\n\t.reg .pred p;\n\t"
        "mbarrier.try_wait.parity.shared::cta.b64 p, [%1], %2;\n\t"
        "selp.u32 %0, 1, 0, p;\n\t}"
        : "=r"(ok) : "r"(bar), "r"(parity) : "memory");
    return ok != 0;
}
__device__ __forceinline__ void mbar_wait(uint32_t bar, uint32_t parity) {
    if (mbar_try(bar, parity)) return;
    for (int i = 0; i < SPIN_LIMIT; i++)
        if (mbar_try(bar, parity)) return;
}
__device__ __forceinline__ void cons_sync() { asm volatile("bar.sync 1, 256;" ::: "memory"); }

__device__ __forceinline__ void tma_2d(uint32_t dst, const CUtensorMap* m, int c0, int c1, uint32_t bar) {
    asm volatile("cp.async.bulk.tensor.2d.shared::cluster.global.mbarrier::complete_tx::bytes [%0], [%1, {%3, %4}], [%2];"
                 ::"r"(dst), "l"(m), "r"(bar), "r"(c0), "r"(c1) : "memory");
}
__device__ __forceinline__ void tma_3d(uint32_t dst, const CUtensorMap* m, int c0, int c1, int c2, uint32_t bar) {
    asm volatile("cp.async.bulk.tensor.3d.shared::cluster.global.mbarrier::complete_tx::bytes [%0], [%1, {%3, %4, %5}], [%2];"
                 ::"r"(dst), "l"(m), "r"(bar), "r"(c0), "r"(c1), "r"(c2) : "memory");
}
__device__ __forceinline__ void tma_3d_hint(uint32_t dst, const CUtensorMap* m, int c0, int c1, int c2, uint32_t bar, uint64_t pol) {
    asm volatile("cp.async.bulk.tensor.3d.shared::cluster.global.mbarrier::complete_tx::bytes.L2::cache_hint [%0], [%1, {%3, %4, %5}], [%2], %6;"
                 ::"r"(dst), "l"(m), "r"(bar), "r"(c0), "r"(c1), "r"(c2), "l"(pol) : "memory");
}
__device__ __forceinline__ void l2pf_2d(const CUtensorMap* m, int c0, int c1) {
    asm volatile("cp.async.bulk.prefetch.tensor.2d.L2.global.tile [%0, {%1, %2}];" ::"l"(m), "r"(c0), "r"(c1) : "memory");
}
__device__ __forceinline__ void l2pf_3d(const CUtensorMap* m, int c0, int c1, int c2) {
    asm volatile("cp.async.bulk.prefetch.tensor.3d.L2.global.tile [%0, {%1, %2, %3}];" ::"l"(m), "r"(c0), "r"(c1), "r"(c2) : "memory");
}
__device__ __forceinline__ void l2pf_1d(const void* ptr, uint32_t bytes) {
    asm volatile("cp.async.bulk.prefetch.L2.global [%0], %1;" ::"l"(ptr), "r"(bytes) : "memory");
}
__device__ __forceinline__ void prefetch_tmap(const CUtensorMap* m) {
    asm volatile("prefetch.tensormap [%0];" ::"l"(m) : "memory");
}

__device__ __forceinline__ void ldsm4(uint32_t addr, uint32_t (&r)[4]) {
    asm volatile("ldmatrix.sync.aligned.m8n8.x4.shared.b16 {%0,%1,%2,%3}, [%4];"
                 : "=r"(r[0]), "=r"(r[1]), "=r"(r[2]), "=r"(r[3]) : "r"(addr) : "memory");
}
__device__ __forceinline__ void ldsm4t(uint32_t addr, uint32_t (&r)[4]) {
    asm volatile("ldmatrix.sync.aligned.m8n8.x4.trans.shared.b16 {%0,%1,%2,%3}, [%4];"
                 : "=r"(r[0]), "=r"(r[1]), "=r"(r[2]), "=r"(r[3]) : "r"(addr) : "memory");
}
__device__ __forceinline__ void mma16816(float (&c)[4], const uint32_t (&a)[4], uint32_t b0, uint32_t b1) {
    asm volatile("mma.sync.aligned.m16n8k16.row.col.f32.bf16.bf16.f32 {%0,%1,%2,%3}, {%4,%5,%6,%7}, {%8,%9}, {%0,%1,%2,%3};"
                 : "+f"(c[0]), "+f"(c[1]), "+f"(c[2]), "+f"(c[3])
                 : "r"(a[0]), "r"(a[1]), "r"(a[2]), "r"(a[3]), "r"(b0), "r"(b1));
}
__device__ __forceinline__ uint32_t movmatrix_t(uint32_t a) {
    uint32_t d;
    asm volatile("movmatrix.sync.aligned.m8n8.trans.b16 %0, %1;" : "=r"(d) : "r"(a));
    return d;
}
__device__ __forceinline__ uint32_t pack_bf16(float a, float b) {
    uint32_t r;
    asm("cvt.rn.bf16x2.f32 %0, %1, %2;" : "=r"(r) : "f"(b), "f"(a));
    return r;
}
__device__ __forceinline__ float bf_lo(uint32_t v) { return __uint_as_float(v << 16); }
__device__ __forceinline__ float bf_hi(uint32_t v) { return __uint_as_float(v & 0xffff0000u); }
__device__ __forceinline__ float bf16r(float a) { return bf_lo(pack_bf16(a, 0.f)); }
__device__ __forceinline__ uint32_t max_bf16x2(uint32_t a, uint32_t b) {
    uint32_t r;
    asm("max.bf16x2 %0, %1, %2;" : "=r"(r) : "r"(a), "r"(b));
    return r;
}
__device__ __forceinline__ float ex2(float x) {
    float r;
    asm("ex2.approx.ftz.f32 %0, %1;" : "=f"(r) : "f"(x));
    return r;
}

__device__ __forceinline__ void st_ll2(uint2* p, uint32_t v, uint32_t tag) {
    asm volatile("st.relaxed.gpu.global.v2.u32 [%0], {%1, %2};" ::"l"(p), "r"(v), "r"(tag) : "memory");
}
__device__ __forceinline__ void st_ll4(uint4* p, uint32_t v0, uint32_t v1, uint32_t tag) {
    asm volatile("st.relaxed.gpu.global.v4.u32 [%0], {%1, %2, %3, %2};" ::"l"(p), "r"(v0), "r"(tag), "r"(v1) : "memory");
}
__device__ __forceinline__ void st_v4(uint4* p, uint32_t a, uint32_t b, uint32_t c, uint32_t d) {
    asm volatile("st.relaxed.gpu.global.v4.u32 [%0], {%1, %2, %3, %4};" ::"l"(p), "r"(a), "r"(b), "r"(c), "r"(d) : "memory");
}
__device__ __forceinline__ uint2 ld_ll2(const uint2* p) {
    uint2 v;
    asm volatile("ld.relaxed.gpu.global.v2.u32 {%0, %1}, [%2];" : "=r"(v.x), "=r"(v.y) : "l"(p) : "memory");
    return v;
}
__device__ __forceinline__ uint4 ld_ll4(const uint4* p) {
    uint4 v;
    asm volatile("ld.relaxed.gpu.global.v4.u32 {%0, %1, %2, %3}, [%4];"
                 : "=r"(v.x), "=r"(v.y), "=r"(v.z), "=r"(v.w) : "l"(p) : "memory");
    return v;
}

#define DELAY_B1 450
#define DELAY_B2 0
#define DELAY_C 450
__device__ __forceinline__ uint32_t clock32() {
    uint32_t c;
    asm volatile("mov.u32 %0, %clock;" : "=r"(c));
    return c;
}
__device__ __forceinline__ void spin_cycles(uint32_t n) {
    if (n > 0) { const uint32_t c0 = clock32(); while (clock32() - c0 < n) {} }
}
__device__ __forceinline__ float rcp_approx(float x) {
    float r;
    asm("rcp.approx.ftz.f32 %0, %1;" : "=f"(r) : "f"(x));
    return r;
}
__device__ __forceinline__ float sqrt_approx(float x) {
    float r;
    asm("sqrt.approx.f32 %0, %1;" : "=f"(r) : "f"(x));
    return r;
}

__device__ __forceinline__ float silu_bf(float v) { return bf16r(v / (1.0f + expf(-v))); }

__device__ __forceinline__ float2 half_warp_sums(const float (&v)[4], float pivot) {
    float s1 = 0.f, s2 = 0.f;
#pragma unroll
    for (int i = 0; i < 4; i++) { const float d = v[i] - pivot; s1 += d; s2 += d * d; }
#pragma unroll
    for (int o = 1; o < 16; o <<= 1) { s1 += __shfl_xor_sync(0xffffffffu, s1, o); s2 += __shfl_xor_sync(0xffffffffu, s2, o); }
    return make_float2(s1, s2);
}
__device__ __forceinline__ void ln_stats(const float2* stat, int b, float pivot, float& mean_bf, float& rstd) {
    float s1 = 0.f, s2 = 0.f;
#pragma unroll
    for (int w = 0; w < 8; w++) { const float2 v = stat[w * 2 + b]; s1 += v.x; s2 += v.y; }
    const float dm = s1 * (1.0f / D_MODEL);
    const float var = fmaxf(s2 * (1.0f / D_MODEL) - dm * dm, 0.f);
    mean_bf = bf16r(pivot + dm);
    rstd = rcp_approx(bf16r(sqrt_approx(bf16r(bf16r(var) + 1e-5f))));
}
__device__ __forceinline__ float ln_norm(float xv, float mean_bf, float rstd) { return bf16r(bf16r(xv - mean_bf) * rstd); }
__device__ __forceinline__ float ln_mod(float n, float cmul, float sadd) { return bf16r(n * bf16r(1.0f + cmul)) + sadd; }

__global__ void __launch_bounds__(NTHREADS, 1)
fused_block_kernel(const Params p, const __grid_constant__ CUtensorMap tm_k, const __grid_constant__ CUtensorMap tm_v,
                   const __grid_constant__ CUtensorMap tm_wq, const __grid_constant__ CUtensorMap tm_wmod,
                   const __grid_constant__ CUtensorMap tm_wo, const __grid_constant__ CUtensorMap tm_wg,
                   const __grid_constant__ CUtensorMap tm_wu, const __grid_constant__ CUtensorMap tm_wd) {
    extern __shared__ unsigned char smem_raw[];
    const uint32_t sbase = (smem_u32(smem_raw) + 1023u) & ~1023u;
    unsigned char* sgen = smem_raw + (sbase - smem_u32(smem_raw));
    const int tid = threadIdx.x, warp = tid >> 5, lane = tid & 31;
    const int cta = blockIdx.x;
    const uint32_t bar_full = sbase + SM_BAR, bar_empty = bar_full + NST * 8;
    const uint32_t bar_clear = bar_empty + NST * 8;
    const uint32_t bar_gu = bar_clear + 7 * 8;
    const uint32_t bar_bc = bar_gu + 8 * 8;
    const uint32_t bar_trig = bar_clear;

    const int key0 = (cta >> 3) * SK + (cta & 7) * 64;
    uint64_t pol = 0;
    if (tid == 256) {
        asm volatile("createpolicy.fractional.L2::evict_first.b64 %0, 1.0;" : "=l"(pol));
#pragma unroll
        for (int i = 0; i < 4; i++) mbar_init(bar_full + 8 * i, 1);
        asm volatile("fence.mbarrier_init.release.cluster;" ::: "memory");
#pragma unroll
        for (int i = 0; i < 4; i++) mbar_expect_tx(bar_full + 8 * i, TILE);
        tma_2d(sbase + SM_RING, &tm_wq, cta * 32, 0, bar_full);
        tma_2d(sbase + SM_RING + TILE, &tm_wq, cta * 32, 256, bar_full + 8);
        tma_3d_hint(sbase + SM_RING + 2 * TILE, &tm_k, 0, key0, 0, bar_full + 16, pol);
        tma_3d_hint(sbase + SM_RING + 3 * TILE, &tm_v, 0, key0, 0, bar_full + 24, pol);
    }
    static_assert(WQ_AT == 0 && MOD_AT >= 1, "the fast start assumes the sequence wq0 wq1 K0 V0");

    if (warp == 8) {
        if (lane == 0) {
            for (int i = 0; i < NST; i++) { if (i >= 4) mbar_init(bar_full + 8 * i, 1); mbar_init(bar_empty + 8 * i, 4); }
            mbar_init(bar_clear, 1);
            for (int k = 1; k <= 6; k++) mbar_init(bar_trig + 8 * k, 1);
            for (int k = 0; k < 8; k++) mbar_init(bar_gu + 8 * k, 1);
            mbar_init(bar_bc, 8);
            ((volatile uint32_t*)(sgen + SM_PACE))[0] = 0;
            ((volatile uint32_t*)(sgen + SM_PACE))[1] = INFL_MAIN;
            asm volatile("fence.mbarrier_init.release.cluster;" ::: "memory");
        }
        __syncwarp();
        asm volatile("bar.arrive 2, 320;" ::: "memory");
        asm volatile("bar.arrive 3, 64;" ::: "memory");
        if (lane == 0) {
            int slot = 4; uint32_t ph = 1;
            int landed = 0, wslot = 0; uint32_t wph = 0;
            int kv = 2;
            constexpr int N_STREAM = kv_idx(KV_TILES - 1) + 2;
            auto issue = [&](int idx) {
                const uint32_t fb = bar_full + 8 * (idx % NST), dst = sbase + SM_RING + (idx % NST) * TILE;
                if ((idx == IDX_WG || idx == IDX_WU || idx == IDX_WD) && cta >= NFFN) {
                    mbar_arrive(fb);
                    return;
                }
                mbar_expect_tx(fb, TILE);
                if (idx == IDX_WQ || idx == IDX_WQ + 1) {
                    tma_2d(dst, &tm_wq, cta * 32, (idx - IDX_WQ) * 256, fb);
                } else if (idx == IDX_MOD) {
                    tma_2d(dst, &tm_wmod, 1024 + cta * 16, 0, fb);
                    tma_2d(dst + 8192, &tm_wmod, 1024 + cta * 16, 256, fb);
                } else if (idx == IDX_WO || idx == IDX_WO + 1) {
                    tma_3d(dst, &tm_wo, 0, cta * 32 + (idx - IDX_WO) * 16, 0, fb);
                } else if (idx == IDX_WG || idx == IDX_WU) {
                    const CUtensorMap* m = idx == IDX_WG ? &tm_wg : &tm_wu;
#pragma unroll
                    for (int q = 0; q < 4; q++) tma_2d(dst + q * 4096, m, cta * 16, q * 128, fb);
                } else if (idx == IDX_WD) {
                    tma_3d(dst, &tm_wd, 0, cta * 16, 0, fb);
                } else {
                    tma_3d_hint(dst, (kv & 1) ? &tm_v : &tm_k, 0, key0 + (kv >> 1) * 512, 0, fb, pol);
                    kv++;
                }
            };
            auto wait_window = [&](int idx, int window) {
                while (landed + window <= idx) {
                    mbar_wait(bar_full + 8 * wslot, wph);
                    if (++wslot == NST) { wslot = 0; wph ^= 1; }
                    landed++;
                }
            };
            prefetch_tmap(&tm_wmod);
            ((volatile uint32_t*)(sgen + SM_PACE))[0] = 4;
            for (int idx = 4; idx < N_STREAM; idx++) {
                if (idx >= NST) mbar_wait(bar_empty + 8 * slot, ph);
                wait_window(idx, idx < PRO_TILES ? INFL_PRO : (int)((volatile uint32_t*)(sgen + SM_PACE))[1]);
                if (idx == 12) { prefetch_tmap(&tm_wo); prefetch_tmap(&tm_wg); prefetch_tmap(&tm_wu); prefetch_tmap(&tm_wd); }
                issue(idx);
                ((volatile uint32_t*)(sgen + SM_PACE))[0] = idx + 1;
                if (++slot == NST) { slot = 0; ph ^= 1; }
            }
            auto deferred = [&](int idx, bool windowed) {
                if (idx < N_STREAM) return;
                mbar_wait(bar_empty + 8 * (idx % NST), ((idx / NST) & 1) ^ 1);
                if (windowed) wait_window(idx, INFL_TAIL);
                issue(idx);
            };
#pragma unroll
            for (int kk = 0; kk <= 6; kk++) {
                const int k = kk == 0 ? 0 : kk == 1 ? 6 : kk - 1;
                if (TR_PF_WO != k && TR_PF_FF != k && TR_LD_WO != k && TR_LD_GU != k && TR_LD_WD != k) continue;
                if (k > 0) mbar_wait(bar_trig + 8 * k, 0);
                if (TR_PF_WO == k) l2pf_1d((const char*)p.wo + (size_t)cta * 32768, 32768);
                if (TR_PF_FF == k && cta < NFFN) {
                    l2pf_1d((const char*)p.wg + (size_t)cta * 16384, 16384);
                    l2pf_1d((const char*)p.wu + (size_t)cta * 16384, 16384);
                    l2pf_1d((const char*)p.wd + (size_t)cta * 16384, 16384);
                }
                if (TR_LD_WO == k) { deferred(IDX_WO, k == 0 || k == 6); deferred(IDX_WO + 1, k == 0 || k == 6); }
                if (TR_LD_GU == k) {
                    if (!GU_PIECES) { deferred(IDX_WG, k == 0 || k == 6); deferred(IDX_WU, k == 0 || k == 6); }
                    else if (cta < NFFN) {
                        mbar_wait(bar_empty + 8 * (IDX_WG % NST), ((IDX_WG / NST) & 1) ^ 1);
                        mbar_wait(bar_empty + 8 * (IDX_WU % NST), ((IDX_WU / NST) & 1) ^ 1);
                        if (IDX_WO >= N_STREAM && TR_LD_WO <= k) {
                            mbar_wait(bar_full + 8 * (IDX_WO % NST), (IDX_WO / NST) & 1);
                            mbar_wait(bar_full + 8 * ((IDX_WO + 1) % NST), ((IDX_WO + 1) / NST) & 1);
                        }
#pragma unroll
                        for (int st = 0; st < 8; st++) {
                            if (st >= GU_WIN) mbar_wait(bar_gu + 8 * (st - GU_WIN), 0);
                            const uint32_t dst = sbase + SM_RING + (((st & 1) ? IDX_WU : IDX_WG) % NST) * TILE + (st >> 1) * 4096;
                            mbar_expect_tx(bar_gu + 8 * st, 4096);
                            tma_2d(dst, (st & 1) ? &tm_wu : &tm_wg, cta * 16, (st >> 1) * 128, bar_gu + 8 * st);
                        }
                        mbar_wait(bar_gu + 8 * 7, 0);
                    }
                }
                if (TR_LD_WD == k) deferred(IDX_WD, !GU_PIECES && (k == 0 || k == 6));
            }
        }
    } else if (warp == 9) {
        Scratch* const sc = p.sc;
        const uint32_t tag = *(volatile unsigned*)&sc->epoch + 1;
        if (lane < 2) {
            st_ll4((uint4*)&sc->mod[lane][cta * 4], 0u, 0u, 0u);
            st_ll4((uint4*)&sc->mod[lane][cta * 4] + 1, 0u, 0u, 0u);
        }
        if (lane < 8) st_ll4((uint4*)&sc->mod[lane >> 2][512 + cta * 8] + (lane & 3), 0u, 0u, 0u);
        if (lane < 16) st_ll4((uint4*)&sc->q[lane >> 3][cta * 16] + (lane & 7), 0u, 0u, 0u);
        __syncwarp();
        asm volatile("bar.arrive 2, 320;" ::: "memory");
        asm volatile("bar.sync 3, 64;" ::: "memory");
#pragma unroll 4
        for (int i = 0; i < 8; i++) st_v4(&sc->inbox[cta][0][0] + i * 32 + lane, 0u, 0u, 0u, 0u);
#pragma unroll 4
        for (int i = 0; i < 4; i++) st_v4((uint4*)&sc->part_o[cta][0][0] + i * 32 + lane, 0u, 0u, 0u, 0u);
        if (lane < 8) st_v4((uint4*)&sc->part_ml[cta][0][0] + lane, 0u, 0u, 0u, 0u);
        if (lane < 2) st_v4((uint4*)&sc->x1[cta][0] + lane, 0u, 0u, 0u, 0u);
        if (cta == 0 && lane == 0) asm volatile("st.relaxed.gpu.global.u32 [%0], %1;" ::"l"(&sc->progress), "r"(0u) : "memory");
        asm volatile("fence.acq_rel.gpu;" ::: "memory");
        __syncwarp();
        if (lane == 0) {
            asm volatile("fence.acq_rel.gpu;" ::: "memory");
            asm volatile("red.relaxed.gpu.global.add.u32 [%0], %1;" ::"l"(&sc->cleared), "r"(1u) : "memory");
            const uint32_t target = tag * NCTA;
            for (int it = 0; it < SPIN_LIMIT; it++) {
                uint32_t v;
                asm volatile("ld.relaxed.gpu.global.u32 %0, [%1];" : "=r"(v) : "l"(&sc->cleared) : "memory");
                if ((int32_t)(v - target) >= 0) break;
                __nanosleep(500);
            }
            asm volatile("fence.acq_rel.gpu;" ::: "memory");
            mbar_arrive(bar_clear);
            volatile uint32_t* pace = (volatile uint32_t*)(sgen + SM_PACE);
            constexpr uint32_t N_STREAM = kv_idx(KV_TILES - 1) + 2;
            uint32_t posted = 0;
            for (int it = 0; it < SPIN_LIMIT; it++) {
                const uint32_t own = pace[0];
                if (own > posted) {
                    asm volatile("red.relaxed.gpu.global.add.u32 [%0], %1;" ::"l"(&sc->progress), "r"(own - posted) : "memory");
                    posted = own;
                }
                uint32_t v;
                asm volatile("ld.relaxed.gpu.global.u32 %0, [%1];" : "=r"(v) : "l"(&sc->progress) : "memory");
                if (own >= N_STREAM) {
                    if (v + GRID_SLACK >= NCTA * N_STREAM) break;
                } else {
                    const int diff = (int)v - (int)own * NCTA;
                    pace[1] = diff > PACE_HI2 && own + PACE_END >= N_STREAM ? INFL_MAIN + 2
                            : diff > PACE_HI ? INFL_MAIN + 1 : diff < -PACE_LO ? INFL_MAIN - 1 : INFL_MAIN;
                }
                __nanosleep(own + 4 >= N_STREAM ? 50 : PACE_SLEEP);
            }
            mbar_arrive(bar_trig + 8 * 6);
        }
    } else {
        const int g = lane >> 2, t = lane & 3;
        const int bb = g & 1;
        const int eb = lane >> 4;
        const int ec = 64 * warp + 4 * (lane & 15);
        if (warp == 0) TSTAMP(0);
        Scratch* const sc = p.sc;
        const uint4 w0 = __ldg((const uint4*)(p.w_mod + (size_t)tid * N_MOD + cta * 8));
        const uint4 w1 = __ldg((const uint4*)(p.w_mod + (size_t)(tid + 256) * N_MOD + cta * 8));
        const float c00 = __bfloat162float(p.c[tid]), c01 = __bfloat162float(p.c[tid + 256]);
        const float c10 = __bfloat162float(p.c[D_MODEL + tid]), c11 = __bfloat162float(p.c[D_MODEL + tid + 256]);
        const uint2 xe = __ldg((const uint2*)(p.x + eb * D_MODEL + ec));
        const float xpivot = __bfloat162float(p.x[eb * D_MODEL]);
        const uint32_t tag = *(volatile unsigned*)&sc->epoch + 1;
        const int ocol = cta * 4 + (lane & 3);
        const float xo0 = __bfloat162float(p.x[ocol]), xo1 = __bfloat162float(p.x[D_MODEL + ocol]);

        float* red = (float*)(sgen + SM_RED);
        float* red2 = (float*)(sgen + SM_RED2);
        float2* stat = (float2*)(sgen + SM_STAT);
        uint32_t* hs = (uint32_t*)(sgen + SM_HS) + warp * 64;
        float xn[4];
        {
            float xv[4] = {bf_lo(xe.x), bf_hi(xe.x), bf_lo(xe.y), bf_hi(xe.y)};
            const float2 ps = half_warp_sums(xv, xpivot);
            if ((lane & 15) == 0) stat[warp * 2 + eb] = ps;
            const float s00 = silu_bf(c00), s01 = silu_bf(c01), s10 = silu_bf(c10), s11 = silu_bf(c11);
            __nv_bfloat16* scs = (__nv_bfloat16*)(sgen + SM_SC);
            scs[tid] = __float2bfloat16_rn(s00); scs[tid + 256] = __float2bfloat16_rn(s01);
            scs[512 + tid] = __float2bfloat16_rn(s10); scs[512 + tid + 256] = __float2bfloat16_rn(s11);
            const uint32_t a[4] = {w0.x, w0.y, w0.z, w0.w}, b[4] = {w1.x, w1.y, w1.z, w1.w};
            float v[16];
#pragma unroll
            for (int i = 0; i < 4; i++) {
                v[2 * i] = s00 * bf_lo(a[i]) + s01 * bf_lo(b[i]);
                v[2 * i + 1] = s00 * bf_hi(a[i]) + s01 * bf_hi(b[i]);
                v[8 + 2 * i] = s10 * bf_lo(a[i]) + s11 * bf_lo(b[i]);
                v[8 + 2 * i + 1] = s10 * bf_hi(a[i]) + s11 * bf_hi(b[i]);
            }
#define XRED(N, O)                                                                       \
            {                                                                            \
                const bool up = lane & (O);                                              \
                _Pragma("unroll") for (int i = 0; i < (N); i++) {                        \
                    const float send = up ? v[i] : v[i + (N)], keep = up ? v[i + (N)] : v[i]; \
                    v[i] = keep + __shfl_xor_sync(0xffffffffu, send, (O));               \
                }                                                                        \
            }
            XRED(8, 16) XRED(4, 8) XRED(2, 4) XRED(1, 2)
#undef XRED
            v[0] += __shfl_xor_sync(0xffffffffu, v[0], 1);
            if (!(lane & 1)) red[warp * 16 + (lane >> 1)] = v[0];
            if (warp == 0) TSTAMP(14);
            asm volatile("bar.sync 2, 320;" ::: "memory");
            if (warp == 0) TSTAMP(23);
            if (warp == 0) {
                float s = 0.f;
#pragma unroll
                for (int w = 0; w < 8; w++) s += red[w * 16 + (lane & 15)];
                const float nx = __shfl_down_sync(0xffffffffu, s, 1);
                if (lane < 16 && !(lane & 1))
                    st_ll2(&sc->mod[lane >> 3][cta * 4 + ((lane & 7) >> 1)], pack_bf16(s, nx), tag);
                TSTAMP(1);
            }
            float mean_bf, rstd;
            ln_stats(stat, eb, xpivot, mean_bf, rstd);
#pragma unroll
            for (int i = 0; i < 4; i++) xn[i] = ln_norm(xv[i], mean_bf, rstd);
        }
        {
            uint4 sa, ca;
            for (int it = 0;; it++) {
                sa = ld_ll4((const uint4*)&sc->mod[eb][ec >> 1]);
                ca = ld_ll4((const uint4*)&sc->mod[eb][256 + (ec >> 1)]);
                const bool ok = sa.y == tag && sa.w == tag && ca.y == tag && ca.w == tag;
                if (__all_sync(0xffffffffu, ok) || it > SPIN_LIMIT) break;
            }
            *(uint2*)&hs[eb * 32 + 2 * (lane & 15)] =
                make_uint2(pack_bf16(ln_mod(xn[0], bf_lo(ca.x), bf_lo(sa.x)), ln_mod(xn[1], bf_hi(ca.x), bf_hi(sa.x))),
                           pack_bf16(ln_mod(xn[2], bf_lo(ca.z), bf_lo(sa.z)), ln_mod(xn[3], bf_hi(ca.z), bf_hi(sa.z))));
            __syncwarp();
            uint32_t hb[8];
#pragma unroll
            for (int i = 0; i < 8; i++) hb[i] = hs[bb * 32 + 8 * (i >> 1) + 4 * (i & 1) + t];
            if (warp == 0) TSTAMP(2);
            float cq[2][4] = {};
            const int ts = warp >> 2;
            mbar_wait(bar_full + 8 * (IDX_WQ + ts), 0);
            const uint32_t tb = sbase + SM_RING + (IDX_WQ + ts) * TILE;
#pragma unroll
            for (int s = 0; s < 4; s++) {
                const int row = 64 * (warp & 3) + 16 * s + (lane & 7) + (lane >> 4) * 8;
#pragma unroll
                for (int mt = 0; mt < 2; mt++) {
                    const int ch = 2 * mt + ((lane >> 3) & 1);
                    uint32_t a[4];
                    ldsm4t(tb + row * 64 + ((ch ^ ((row >> 1) & 3)) << 4), a);
                    mma16816(cq[mt], a, hb[2 * s], hb[2 * s + 1]);
                }
            }
            if (t < 2) {
                const float v0 = t == 0 ? cq[0][0] : cq[1][0], v1 = t == 0 ? cq[0][1] : cq[1][1];
                const float v2 = t == 0 ? cq[0][2] : cq[1][2], v3 = t == 0 ? cq[0][3] : cq[1][3];
                *(float2*)&red2[warp * 64 + (16 * t + g) * 2] = make_float2(v0, v1);
                *(float2*)&red2[warp * 64 + (16 * t + g + 8) * 2] = make_float2(v2, v3);
            }
            cons_sync();
            if (warp < 4 && lane == 0) { mbar_arrive(bar_empty + 8 * IDX_WQ); mbar_arrive(bar_empty + 8 * IDX_WQ + 8); }
            if (warp == 0) {
                const int b = lane >> 4, cp = lane & 15;
                float q0 = 0.f, q1 = 0.f;
#pragma unroll
                for (int w = 0; w < 8; w++) {
                    const float4 v = *(const float4*)&red2[w * 64 + cp * 4];
                    q0 += b ? v.y : v.x; q1 += b ? v.w : v.z;
                }
                st_ll2(&sc->q[b][cta * 16 + cp], pack_bf16(q0, q1), tag);
                TSTAMP(3);
            }
        }
        const int pair = cta >> 3;
        uint32_t qf[16];
        {
            uint2* qs = (uint2*)(sgen + SM_QS);
            if (tid < 128) {
                const uint4* src = (const uint4*)&sc->q[pair >> 3][(pair & 7) * 256] + tid;
                uint4 v;
                for (int it = 0;; it++) {
                    v = ld_ll4(src);
                    if ((v.y == tag && v.w == tag) || it > SPIN_LIMIT) break;
                }
                qs[tid] = make_uint2(v.x, v.z);
            }
            cons_sync();
            const uint32_t* q32 = (const uint32_t*)(sgen + SM_QS);
#pragma unroll
            for (int s = 0; s < 8; s++) {
                qf[2 * s] = q32[(g & 3) * 64 + 8 * s + t];
                qf[2 * s + 1] = q32[(g & 3) * 64 + 8 * s + 4 + t];
            }
        }
        if (warp == 0) TSTAMP(4);

        float o[8][4];
#pragma unroll
        for (int i = 0; i < 8; i++) { o[i][0] = o[i][1] = o[i][2] = o[i][3] = 0.f; }
        uint32_t mrun = 0xff80ff80u;
        float ls[4] = {0.f, 0.f, 0.f, 0.f};
        uint4 m_sb, m_cb; uint2 m_ga0, m_ga1, m_gb0, m_gb1;
        {
            const int grp = warp >> 2, wi = warp & 3;
            const int krow = 16 * wi + (lane & 7) + ((lane >> 3) & 1) * 8;
            const uint32_t koff = krow * 128 + ((((lane >> 4) & 1) ^ (lane & 7)) << 4);
            const int vrow = 16 * wi + (lane & 7) + (lane >> 4) * 8;
            const uint32_t voff = vrow * 128 + ((((lane >> 3) & 1) ^ (lane & 7)) << 4);
            const uint32_t ones[4] = {0x3f803f80u, 0x3f803f80u, 0x3f803f80u, 0x3f803f80u};
            for (int i = grp; i < KV_TILES; i += 2) {
                if (i == MOD_AT + grp) {
                    float cm[4] = {};
                    const uint32_t* sc32 = (const uint32_t*)(sgen + SM_SC) + bb * 256 + 32 * warp + t;
                    mbar_wait(bar_full + 8 * (IDX_MOD % NST), (IDX_MOD / NST) & 1);
                    const uint32_t tb = sbase + SM_RING + (IDX_MOD % NST) * TILE;
#pragma unroll
                    for (int s = 0; s < 4; s++) {
                        const int row = 64 * warp + 16 * s + (lane & 7) + (lane >> 4) * 8;
                        const int ch = (lane >> 3) & 1;
                        uint32_t a[4];
                        ldsm4t(tb + row * 32 + ((ch ^ ((row >> 2) & 1)) << 4), a);
                        mma16816(cm, a, sc32[8 * s], sc32[8 * s + 4]);
                    }
                    if (t == 0) {
                        *(float2*)&red[warp * 64 + g * 2] = make_float2(cm[0], cm[1]);
                        *(float2*)&red[warp * 64 + (g + 8) * 2] = make_float2(cm[2], cm[3]);
                    }
                    cons_sync();
                    if (warp < 4 && lane == 0) mbar_arrive(bar_empty + 8 * (IDX_MOD % NST));
                    if (warp == 1 && lane < 16) {
                        const int b = lane >> 3, cp = lane & 7;
                        float q0 = 0.f, q1 = 0.f;
#pragma unroll
                        for (int w = 0; w < 8; w++) {
                            const float4 v = *(const float4*)&red[w * 64 + cp * 4];
                            q0 += b ? v.y : v.x; q1 += b ? v.w : v.z;
                        }
                        st_ll2(&sc->mod[b][512 + cta * 8 + cp], pack_bf16(q0, q1), tag);
                    }
                }
                if (i == 56 + grp) {
                    m_sb = ld_ll4((const uint4*)&sc->mod[eb][768 + (ec >> 1)]);
                    m_cb = ld_ll4((const uint4*)&sc->mod[eb][1024 + (ec >> 1)]);
                    m_ga0 = ld_ll2(&sc->mod[0][512 + (ocol >> 1)]); m_ga1 = ld_ll2(&sc->mod[1][512 + (ocol >> 1)]);
                    m_gb0 = ld_ll2(&sc->mod[0][1280 + (ocol >> 1)]); m_gb1 = ld_ll2(&sc->mod[1][1280 + (ocol >> 1)]);
                }
                if (i == 60 + grp) {
                    for (int it = 0;; it++) {
                        const bool ok = m_sb.y == tag && m_sb.w == tag && m_cb.y == tag && m_cb.w == tag &&
                                        m_ga0.y == tag && m_ga1.y == tag && m_gb0.y == tag && m_gb1.y == tag;
                        if (__all_sync(0xffffffffu, ok) || it > SPIN_LIMIT) break;
                        m_sb = ld_ll4((const uint4*)&sc->mod[eb][768 + (ec >> 1)]);
                        m_cb = ld_ll4((const uint4*)&sc->mod[eb][1024 + (ec >> 1)]);
                        m_ga0 = ld_ll2(&sc->mod[0][512 + (ocol >> 1)]); m_ga1 = ld_ll2(&sc->mod[1][512 + (ocol >> 1)]);
                        m_gb0 = ld_ll2(&sc->mod[0][1280 + (ocol >> 1)]); m_gb1 = ld_ll2(&sc->mod[1][1280 + (ocol >> 1)]);
                    }
                    mbar_wait(bar_clear, 0);
                }
                const int ki = kv_idx(i), ks = ki % NST, vs = (ki + 1) % NST;
                const uint32_t kph = (ki / NST) & 1, vph = ((ki + 1) / NST) & 1;
                mbar_wait(bar_full + 8 * ks, kph);
                const uint32_t kb = sbase + SM_RING + ks * TILE + koff;
                float sa[4] = {0.f, 0.f, 0.f, 0.f}, sb[4] = {0.f, 0.f, 0.f, 0.f};
#pragma unroll
                for (int s = 0; s < 8; s += 2) {
                    uint32_t a0[4], a1[4];
                    ldsm4((kb ^ ((s & 3) << 5)) + (s >> 2) * 8192, a0);
                    ldsm4((kb ^ (((s + 1) & 3) << 5)) + (s >> 2) * 8192, a1);
                    mma16816(sa, a0, qf[2 * s], qf[2 * s + 1]);
                    mma16816(sb, a1, qf[2 * s + 2], qf[2 * s + 3]);
                }
                __syncwarp();
                if (lane == 0) mbar_arrive(bar_empty + 8 * ks);
                uint32_t r01 = pack_bf16(sa[0] + sb[0], sa[1] + sb[1]);
                uint32_t r23 = pack_bf16(sa[2] + sb[2], sa[3] + sb[3]);
                r01 = pack_bf16(bf_lo(r01) * QK_SCALE, bf_hi(r01) * QK_SCALE);
                r23 = pack_bf16(bf_lo(r23) * QK_SCALE, bf_hi(r23) * QK_SCALE);
                uint32_t mx = max_bf16x2(r01, r23);
                mx = max_bf16x2(mx, __shfl_xor_sync(0xffffffffu, mx, 4));
                mx = max_bf16x2(mx, __shfl_xor_sync(0xffffffffu, mx, 8));
                mx = max_bf16x2(mx, __shfl_xor_sync(0xffffffffu, mx, 16));
                const uint32_t mnew = max_bf16x2(mrun, mx);
                const float m0 = bf_lo(mnew), m1 = bf_hi(mnew);
                if (__any_sync(0xffffffffu, mnew != mrun)) {
                    const float al0 = ex2((bf_lo(mrun) - m0) * LOG2E), al1 = ex2((bf_hi(mrun) - m1) * LOG2E);
                    ls[0] *= al0; ls[1] *= al1;
#pragma unroll
                    for (int d = 0; d < 8; d++) { o[d][0] *= al0; o[d][1] *= al1; o[d][2] *= al0; o[d][3] *= al1; }
                    mrun = mnew;
                }
                const float p0 = ex2((bf_lo(r01) - m0) * LOG2E), p1 = ex2((bf_hi(r01) - m1) * LOG2E);
                const float p2 = ex2((bf_lo(r23) - m0) * LOG2E), p3 = ex2((bf_hi(r23) - m1) * LOG2E);
                const uint32_t pb0 = movmatrix_t(pack_bf16(p0, p1)), pb1 = movmatrix_t(pack_bf16(p2, p3));
                mma16816(ls, ones, pb0, pb1);
                mbar_wait(bar_full + 8 * vs, vph);
                const uint32_t vb = sbase + SM_RING + vs * TILE + voff;
#pragma unroll
                for (int d = 0; d < 8; d++) {
                    uint32_t a[4];
                    ldsm4t((vb ^ ((d & 3) << 5)) + (d >> 2) * 8192, a);
                    mma16816(o[d], a, pb0, pb1);
                }
                __syncwarp();
                if (lane == 0) mbar_arrive(bar_empty + 8 * vs);
            }
        }
        if (warp == 7) TSTAMP(5);
        if (warp == 7 && lane == 0) mbar_arrive(bar_trig + 8 * 1);
        {
            float* mrg = (float*)(sgen + SM_MRG);
            float2* ml = (float2*)(sgen + SM_ML);
            {
                const int hp = (t & 1) * 2, up = t >> 1;
                if (g == 0 && up == 0) { ml[warp * 4 + hp] = make_float2(bf_lo(mrun), ls[0]); ml[warp * 4 + hp + 1] = make_float2(bf_hi(mrun), ls[1]); }
                float* m0p = mrg + (warp * 4 + hp) * 136 + up * 72 + g;
#pragma unroll
                for (int d = 0; d < 4; d++) {
                    m0p[16 * d] = up ? o[d + 4][0] : o[d][0]; m0p[136 + 16 * d] = up ? o[d + 4][1] : o[d][1];
                    m0p[16 * d + 8] = up ? o[d + 4][2] : o[d][2]; m0p[136 + 16 * d + 8] = up ? o[d + 4][3] : o[d][3];
                }
            }
            cons_sync();
            const int hh = tid >> 6, dp = tid & 63;
            float2 mw[8];
            float M = -INFINITY;
#pragma unroll
            for (int w = 0; w < 8; w++) { mw[w] = ml[w * 4 + hh]; M = fmaxf(M, mw[w].x); }
            float L = 0.f, o0 = 0.f, o1 = 0.f;
#pragma unroll
            for (int w = 0; w < 8; w++) {
                const float wt = ex2((mw[w].x - M) * LOG2E);
                const float2 v = *(const float2*)&mrg[(w * 4 + hh) * 136 + 2 * dp + (dp >= 32 ? 8 : 0)];
                L += wt * mw[w].y; o0 += wt * v.x; o1 += wt * v.y;
            }
            st_ll2(&sc->part_o[cta][hh][dp], tagf(o0, F_PART), tagf(o1, F_PART));
            if (dp < 4) st_ll2(&sc->part_ml[cta][hh][dp], tagf(M, F_PART), tagf(L, F_PART));
        }
        if (tid == 0) mbar_arrive(bar_trig + 8 * 2);
        if (warp == 0) TSTAMP(6);
        const uint32_t aoff = warp * 2048 + ((lane & 7) + (lane >> 4) * 8) * 128 + ((((lane >> 3) & 1) ^ (lane & 7)) << 4);
        uint32_t wf[8][4];
        if (WO_AT < KV_TILES) {
#pragma unroll
            for (int s = 0; s < 2; s++) {
                constexpr int i0 = IDX_WO;
                const int idx = i0 + s;
                mbar_wait(bar_full + 8 * (idx % NST), (idx / NST) & 1);
                const uint32_t tb = sbase + SM_RING + (idx % NST) * TILE + aoff;
#pragma unroll
                for (int mt = 0; mt < 4; mt++) ldsm4t(tb ^ (mt << 5), wf[s * 4 + mt]);
            }
        }
        {
            const int hq = cta >> 2, kvh = hq >> 2, hh = hq & 3, ds = cta & 3;
            const int b = tid >> 7, dpl = (tid >> 3) & 15, j = tid & 7;
            const int pc = (b * 8 + kvh) * 8 + j;
            const uint2* po = &sc->part_o[pc][hh][ds * 16 + dpl];
            const uint2* pm = &sc->part_ml[pc - j][hh][0];
            uint2 vo, vm[8];
            for (int it = 0;; it++) {
                vo = ld_ll2(po);
#pragma unroll
                for (int jj = 0; jj < 8; jj++) vm[jj] = ld_ll2(pm + jj * 16);
                uint32_t all = vo.x & vo.y;
#pragma unroll
                for (int jj = 0; jj < 8; jj++) all &= vm[jj].x & vm[jj].y;
                if (__all_sync(0xffffffffu, (all & 3u) == F_PART) || it > SPIN_LIMIT) break;
            }
            float M = untag(vm[0].x);
#pragma unroll
            for (int jj = 1; jj < 8; jj++) M = fmaxf(M, untag(vm[jj].x));
            float wt = 0.f, L = 0.f;
#pragma unroll
            for (int jj = 0; jj < 8; jj++) {
                const float w_ = ex2((untag(vm[jj].x) - M) * LOG2E);
                L += w_ * untag(vm[jj].y);
                wt = jj == j ? w_ : wt;
            }
            float o0 = wt * untag(vo.x), o1 = wt * untag(vo.y);
#pragma unroll
            for (int o_ = 1; o_ < 8; o_ <<= 1) {
                o0 += __shfl_xor_sync(0xffffffffu, o0, o_);
                o1 += __shfl_xor_sync(0xffffffffu, o1, o_);
            }
            uint32_t* os = (uint32_t*)(sgen + SM_OS);
            const float rl = rcp_approx(L);
            if (j == 0) os[b * 16 + dpl] = pack_bf16(o0 * rl, o1 * rl);
            if (warp == 0) TSTAMP(15);
            if (WO_AT == KV_TILES) {
#pragma unroll
            for (int s = 0; s < 2; s++) {
                constexpr int i0 = IDX_WO;
                const int idx = i0 + s;
                mbar_wait(bar_full + 8 * (idx % NST), (idx / NST) & 1);
                const uint32_t tb = sbase + SM_RING + (idx % NST) * TILE + aoff;
#pragma unroll
                for (int mt = 0; mt < 4; mt++) ldsm4t(tb ^ (mt << 5), wf[s * 4 + mt]);
            }
            }
            cons_sync();
            if (tid == 0) mbar_arrive(bar_trig + 8 * 3);
            if (warp == 0) TSTAMP(7);
            float y[4][4] = {};
#pragma unroll
            for (int s = 0; s < 2; s++) {
                const uint32_t b0 = os[bb * 16 + 8 * s + t], b1 = os[bb * 16 + 8 * s + 4 + t];
#pragma unroll
                for (int mt = 0; mt < 4; mt++) mma16816(y[mt], wf[s * 4 + mt], b0, b1);
            }
            float v[4];
#pragma unroll
            for (int i = 0; i < 4; i++) v[i] = t == 0 ? y[0][i] : t == 1 ? y[1][i] : t == 2 ? y[2][i] : y[3][i];
            {
                const bool odd = g & 1;
                const float sx = odd ? v[0] : v[2], sy = odd ? v[1] : v[3];
                const float rx = __shfl_xor_sync(0xffffffffu, sx, 4), ry = __shfl_xor_sync(0xffffffffu, sy, 4);
                const int c0 = 64 * warp + 16 * t + (odd ? g + 7 : g);
                const float e0 = odd ? rx : v[0], e1 = odd ? ry : v[1], e2 = odd ? v[2] : rx, e3 = odd ? v[3] : ry;
                st_v4(&sc->inbox[c0 >> 2][cta][(c0 >> 1) & 1], tagf(e0, F_WO), tagf(e1, F_WO), tagf(e2, F_WO), tagf(e3, F_WO));
            }
        }
        if (tid == 0) mbar_arrive(bar_trig + 8 * 4);
        if (warp == 0) TSTAMP(8);
        float xm0 = 0.f, xm1 = 0.f;
        {
            float r0;
            {
                const uint4* pin = &sc->inbox[cta][0][0] + tid;
                uint4 v = make_uint4(F_WO, F_WO, F_WO, F_WO);
                spin_cycles(DELAY_B1);
                for (int it = 0;; it++) {
                    if (tid < NCTA * 2) v = ld_ll4(pin);
                    if (__all_sync(0xffffffffu, ((v.x & v.y & v.z & v.w & 3u) == F_WO) && (((v.x | v.y | v.z | v.w) & 3u) == F_WO)) || it > SPIN_LIMIT) break;
                }
                const bool u1 = lane & 2, u2 = lane & 4;
                const float a0 = untag(v.x), a1 = untag(v.y), a2 = untag(v.z), a3 = untag(v.w);
                const float k0 = (u1 ? a1 : a0) + __shfl_xor_sync(0xffffffffu, u1 ? a0 : a1, 2);
                const float k1 = (u1 ? a3 : a2) + __shfl_xor_sync(0xffffffffu, u1 ? a2 : a3, 2);
                r0 = (u2 ? k1 : k0) + __shfl_xor_sync(0xffffffffu, u2 ? k0 : k1, 4);
                r0 += __shfl_xor_sync(0xffffffffu, r0, 8);
                r0 += __shfl_xor_sync(0xffffffffu, r0, 16);
                if (lane < 8) red2[warp * 8 + (2 * (lane & 1) + ((lane >> 2) & 1)) * 2 + ((lane >> 1) & 1)] = r0;
            }
            cons_sync();
            if (tid == 32) mbar_arrive(bar_trig + 8 * 5);
            if (warp == 0) {
                float a0 = 0.f, a1 = 0.f;
#pragma unroll
                for (int w = 0; w < 8; w++) { const float2 v = *(const float2*)&red2[w * 8 + (lane & 3) * 2]; a0 += v.x; a1 += v.y; }
                const bool hi = ocol & 1;
                const float ga0 = hi ? bf_hi(m_ga0.x) : bf_lo(m_ga0.x), ga1 = hi ? bf_hi(m_ga1.x) : bf_lo(m_ga1.x);
                xm0 = bf16r(xo0 + bf16r(ga0 * bf16r(a0)));
                xm1 = bf16r(xo1 + bf16r(ga1 * bf16r(a1)));
                if (lane < 4) st_ll2(&sc->x1[cta][lane], pack_bf16(xm0, xm1), F_X1);
                TSTAMP(10);
            }
        }
        if (cta < NFFN) {
            const uint4* px = (const uint4*)&sc->x1[ec >> 2][0];
            const uint4* pp = (const uint4*)&sc->x1[0][0];
            uint4 va, vb, pa, pb;
            uint32_t gf[4][4], uf[4][4];
            if (GU_PIECES && IDX_WG >= kv_idx(KV_TILES - 1) + 2) {
                mbar_wait(bar_gu + 8 * (2 * (warp >> 1)), 0);
                mbar_wait(bar_gu + 8 * (2 * (warp >> 1) + 1), 0);
            } else {
                mbar_wait(bar_full + 8 * (IDX_WG % NST), (IDX_WG / NST) & 1);
                mbar_wait(bar_full + 8 * (IDX_WU % NST), (IDX_WU / NST) & 1);
            }
            {
                const uint32_t tg = sbase + SM_RING + (IDX_WG % NST) * TILE, tu = sbase + SM_RING + (IDX_WU % NST) * TILE;
#pragma unroll
                for (int s = 0; s < 4; s++) {
                    const int row = 64 * warp + 16 * s + (lane & 7) + (lane >> 4) * 8;
                    const uint32_t off = row * 32 + ((((lane >> 3) & 1) ^ ((row >> 2) & 1)) << 4);
                    ldsm4t(tg + off, gf[s]);
                    ldsm4t(tu + off, uf[s]);
                }
            }
            va = ld_ll4(px); vb = ld_ll4(px + 1); pa = ld_ll4(pp); pb = ld_ll4(pp + 1);
            const float c1v[4] = {bf16r(1.0f + bf_lo(m_cb.x)), bf16r(1.0f + bf_hi(m_cb.x)), bf16r(1.0f + bf_lo(m_cb.z)), bf16r(1.0f + bf_hi(m_cb.z))};
            float bg = 0.f, cgc = 0.f, bu = 0.f, cuc = 0.f;
            {
                uint32_t* pre = (uint32_t*)(sgen + SM_MRG) + warp * 128;
                float* bc = (float*)(sgen + SM_MRG + 4096);
                *(uint2*)&pre[eb * 32 + 2 * (lane & 15)] = make_uint2(pack_bf16(c1v[0], c1v[1]), pack_bf16(c1v[2], c1v[3]));
                *(uint2*)&pre[64 + eb * 32 + 2 * (lane & 15)] = make_uint2(m_sb.x, m_sb.z);
                __syncwarp();
                float yg[4] = {}, yu[4] = {};
                const uint32_t* pb = pre + ((g >> 1) & 1) * 64 + bb * 32 + t;
#pragma unroll
                for (int s = 0; s < 4; s++) {
                    const uint32_t b0 = pb[8 * s], b1 = pb[8 * s + 4];
                    mma16816(yg, gf[s], b0, b1);
                    mma16816(yu, uf[s], b0, b1);
                }
                const float y0 = t < 2 ? yg[0] : yu[0], y1 = t < 2 ? yg[1] : yu[1], y2 = t < 2 ? yg[2] : yu[2], y3 = t < 2 ? yg[3] : yu[3];
                float* dstp = bc + warp * 128 + (t >> 1) * 64 + (t & 1) * 32;
                *(float2*)&dstp[g * 2] = make_float2(y0, y1);
                *(float2*)&dstp[(g + 8) * 2] = make_float2(y2, y3);
                __syncwarp();
                if (lane == 0) mbar_arrive(bar_bc);
            }
            if (warp == 0) TSTAMP(11);
            float pivot2;
            {
                for (int it = 0;; it++) {
                    const bool ok = va.y == F_X1 && va.w == F_X1 && vb.y == F_X1 && vb.w == F_X1 &&
                                    pa.y == F_X1 && pa.w == F_X1 && pb.y == F_X1 && pb.w == F_X1;
                    if (__all_sync(0xffffffffu, ok) || it > SPIN_LIMIT) break;
                    va = ld_ll4(px); vb = ld_ll4(px + 1); pa = ld_ll4(pp); pb = ld_ll4(pp + 1);
                }
                if (warp == 0) TSTAMP(9);
                const float xv[4] = {eb ? bf_hi(va.x) : bf_lo(va.x), eb ? bf_hi(va.z) : bf_lo(va.z),
                                     eb ? bf_hi(vb.x) : bf_lo(vb.x), eb ? bf_hi(vb.z) : bf_lo(vb.z)};
                const float p0 = 0.25f * ((bf_lo(pa.x) + bf_lo(pa.z)) + (bf_lo(pb.x) + bf_lo(pb.z)));
                const float p1 = 0.25f * ((bf_hi(pa.x) + bf_hi(pa.z)) + (bf_hi(pb.x) + bf_hi(pb.z)));
                const float pivot = eb ? p1 : p0;
                pivot2 = (lane & 1) ? p1 : p0;
                *(uint2*)&hs[eb * 32 + 2 * (lane & 15)] =
                    make_uint2(pack_bf16((xv[0] - pivot) * c1v[0], (xv[1] - pivot) * c1v[1]),
                               pack_bf16((xv[2] - pivot) * c1v[2], (xv[3] - pivot) * c1v[3]));
                __syncwarp();
                float cg[2][4] = {}, cu[2][4] = {};
#pragma unroll
                for (int s = 0; s < 4; s++) {
                    const uint32_t b0 = hs[bb * 32 + 8 * s + t], b1 = hs[bb * 32 + 8 * s + 4 + t];
                    mma16816(cg[s & 1], gf[s], b0, b1);
                    mma16816(cu[s & 1], uf[s], b0, b1);
                }
                const float2 ps = half_warp_sums(xv, pivot);
                if ((lane & 15) == 0) stat[warp * 2 + eb] = ps;
                {
                    const float* bc = (const float*)(sgen + SM_MRG + 4096);
                    mbar_wait(bar_bc, 0);
#pragma unroll
                    for (int w = 0; w < 8; w++) {
                        bg += bc[w * 128 + lane]; cgc += bc[w * 128 + 32 + lane];
                        bu += bc[w * 128 + 64 + lane]; cuc += bc[w * 128 + 96 + lane];
                    }
                }
                if (t < 2) {
                    float v[4];
#pragma unroll
                    for (int i = 0; i < 4; i++) v[i] = t ? cu[0][i] + cu[1][i] : cg[0][i] + cg[1][i];
                    *(float2*)&red[warp * 64 + t * 32 + g * 2] = make_float2(v[0], v[1]);
                    *(float2*)&red[warp * 64 + t * 32 + (g + 8) * 2] = make_float2(v[2], v[3]);
                }
            }
            uint32_t df[4][4];
            mbar_wait(bar_full + 8 * (IDX_WD % NST), (IDX_WD / NST) & 1);
#pragma unroll
            for (int mt = 0; mt < 4; mt++) ldsm4t((sbase + SM_RING + (IDX_WD % NST) * TILE + aoff) ^ (mt << 5), df[mt]);
            cons_sync();
            {
                float gs = 0.f, us = 0.f;
#pragma unroll
                for (int w = 0; w < 8; w++) { gs += red[w * 64 + lane]; us += red[w * 64 + 32 + lane]; }
                float mean_bf, rstd;
                ln_stats(stat, lane & 1, pivot2, mean_bf, rstd);
                const float dm = mean_bf - pivot2;
                gs = bf16r(rstd * (gs - dm * bg) + cgc);
                us = rstd * (us - dm * bu) + cuc;
                const float u2 = gs * (1.0f + 0.044715f * gs * gs) * (2.0f * 0.7978845608028654f * LOG2E);
                const float ge = bf16r(__fdividef(gs, 1.0f + ex2(-u2)));
                const float act = bf16r(ge * bf16r(us));
                const float a0 = __shfl_sync(0xffffffffu, act, 4 * t + bb), a1 = __shfl_sync(0xffffffffu, act, 4 * t + 2 + bb);
                const float a2 = __shfl_sync(0xffffffffu, act, 4 * t + 16 + bb), a3 = __shfl_sync(0xffffffffu, act, 4 * t + 18 + bb);
                const uint32_t b0 = pack_bf16(a0, a1), b1 = pack_bf16(a2, a3);
                float y[4][4] = {};
#pragma unroll
                for (int mt = 0; mt < 4; mt++) mma16816(y[mt], df[mt], b0, b1);
                float v[4];
#pragma unroll
                for (int i = 0; i < 4; i++) v[i] = t == 0 ? y[0][i] : t == 1 ? y[1][i] : t == 2 ? y[2][i] : y[3][i];
            {
                const bool odd = g & 1;
                const float sx = odd ? v[0] : v[2], sy = odd ? v[1] : v[3];
                const float rx = __shfl_xor_sync(0xffffffffu, sx, 4), ry = __shfl_xor_sync(0xffffffffu, sy, 4);
                const int c0 = 64 * warp + 16 * t + (odd ? g + 7 : g);
                const float e0 = odd ? rx : v[0], e1 = odd ? ry : v[1], e2 = odd ? v[2] : rx, e3 = odd ? v[3] : ry;
                st_v4(&sc->inbox[c0 >> 2][cta][(c0 >> 1) & 1], tagf(e0, F_DOWN), tagf(e1, F_DOWN), tagf(e2, F_DOWN), tagf(e3, F_DOWN));
            }
            }
            if (warp == 0) TSTAMP(12);
        }
        {
            float r0;
            {
                const uint4* pin = &sc->inbox[cta][0][0] + tid;
                uint4 v = make_uint4(F_DOWN, F_DOWN, F_DOWN, F_DOWN);
                spin_cycles(DELAY_C);
                for (int it = 0;; it++) {
                    if (tid < NFFN * 2) v = ld_ll4(pin);
                    if (__all_sync(0xffffffffu, ((v.x & v.y & v.z & v.w & 3u) == F_DOWN) && (((v.x | v.y | v.z | v.w) & 3u) == F_DOWN)) || it > SPIN_LIMIT) break;
                }
                const bool u1 = lane & 2, u2 = lane & 4;
                const float a0 = untag(v.x), a1 = untag(v.y), a2 = untag(v.z), a3 = untag(v.w);
                const float k0 = (u1 ? a1 : a0) + __shfl_xor_sync(0xffffffffu, u1 ? a0 : a1, 2);
                const float k1 = (u1 ? a3 : a2) + __shfl_xor_sync(0xffffffffu, u1 ? a2 : a3, 2);
                r0 = (u2 ? k1 : k0) + __shfl_xor_sync(0xffffffffu, u2 ? k0 : k1, 4);
                r0 += __shfl_xor_sync(0xffffffffu, r0, 8);
                r0 += __shfl_xor_sync(0xffffffffu, r0, 16);
                if (lane < 8) red2[64 + warp * 8 + (2 * (lane & 1) + ((lane >> 2) & 1)) * 2 + ((lane >> 1) & 1)] = r0;
            }
            cons_sync();
            if (warp == 0) {
                float a0 = 0.f, a1 = 0.f;
#pragma unroll
                for (int w = 0; w < 8; w++) { const float2 v = *(const float2*)&red2[64 + w * 8 + (lane & 3) * 2]; a0 += v.x; a1 += v.y; }
                const bool hi = ocol & 1;
                const float gb0 = hi ? bf_hi(m_gb0.x) : bf_lo(m_gb0.x), gb1 = hi ? bf_hi(m_gb1.x) : bf_lo(m_gb1.x);
                if (lane < 4) {
                    p.out[ocol] = __float2bfloat16_rn(xm0 + bf16r(gb0 * bf16r(a0)));
                    p.out[D_MODEL + ocol] = __float2bfloat16_rn(xm1 + bf16r(gb1 * bf16r(a1)));
                }
                if (cta == 0 && lane == 0) *(volatile unsigned*)&sc->epoch = tag;
                TSTAMP(13);
            }
        }
    }
}

typedef CUresult (*EncodeFn)(CUtensorMap*, CUtensorMapDataType, cuuint32_t, void*, const cuuint64_t*, const cuuint64_t*,
                             const cuuint32_t*, const cuuint32_t*, CUtensorMapInterleave, CUtensorMapSwizzle,
                             CUtensorMapL2promotion, CUtensorMapFloatOOBfill);

struct Maps { CUtensorMap k, v, wq, wmod, wo, wg, wu, wd; };

void encode(EncodeFn fn, CUtensorMap* m, const void* ptr, int rank, const cuuint64_t* dims, const cuuint64_t* strides,
            const cuuint32_t* box, CUtensorMapSwizzle sw) {
    const cuuint32_t es[3] = {1, 1, 1};
    fn(m, CU_TENSOR_MAP_DATA_TYPE_BFLOAT16, rank, const_cast<void*>(ptr), dims, strides, box, es,
       CU_TENSOR_MAP_INTERLEAVE_NONE, sw, CU_TENSOR_MAP_L2_PROMOTION_L2_256B, CU_TENSOR_MAP_FLOAT_OOB_FILL_NONE);
}

}

extern "C" void kernel_launch(void* const* d_in, const int* in_sizes, int n_in, void* d_out, int out_size) {
    (void)in_sizes; (void)n_in; (void)out_size;
    static EncodeFn enc = nullptr;
    static Scratch* scratch = nullptr;
    if (!enc) {
        cudaGetSymbolAddress((void**)&scratch, g_scratch);
        void* fn = nullptr;
        cudaDriverEntryPointQueryResult qr;
        cudaGetDriverEntryPoint("cuTensorMapEncodeTiled", &fn, cudaEnableDefault, &qr);
        enc = (EncodeFn)fn;
        cudaFuncSetAttribute(fused_block_kernel, cudaFuncAttributeMaxDynamicSharedMemorySize, SMEM_BYTES);
    }
    Maps m;
    {
        const cuuint64_t dims[3] = {64, (cuuint64_t)16 * SK, 2}, str[2] = {256, 128};
        const cuuint32_t box[3] = {64, 64, 2};
        encode(enc, &m.k, d_in[1], 3, dims, str, box, CU_TENSOR_MAP_SWIZZLE_128B);
        encode(enc, &m.v, d_in[2], 3, dims, str, box, CU_TENSOR_MAP_SWIZZLE_128B);
    }
    {
        const cuuint64_t dims[2] = {4096, 512}, str[1] = {8192};
        const cuuint32_t box[2] = {32, 256};
        encode(enc, &m.wq, d_in[3], 2, dims, str, box, CU_TENSOR_MAP_SWIZZLE_64B);
    }
    {
        const cuuint64_t dims[2] = {N_MOD, 512}, str[1] = {N_MOD * 2};
        const cuuint32_t box[2] = {16, 256};
        encode(enc, &m.wmod, d_in[10], 2, dims, str, box, CU_TENSOR_MAP_SWIZZLE_32B);
    }
    {
        const cuuint64_t dims_o[3] = {64, 4096, 8}, dims_d[3] = {64, D_FF, 8}, str[2] = {1024, 128};
        const cuuint32_t box[3] = {64, 16, 8};
        encode(enc, &m.wo, d_in[4], 3, dims_o, str, box, CU_TENSOR_MAP_SWIZZLE_128B);
        encode(enc, &m.wd, d_in[8], 3, dims_d, str, box, CU_TENSOR_MAP_SWIZZLE_128B);
    }
    {
        const cuuint64_t dims[2] = {D_FF, 512}, str[1] = {D_FF * 2};
        const cuuint32_t box[2] = {16, 128};
        encode(enc, &m.wg, d_in[6], 2, dims, str, box, CU_TENSOR_MAP_SWIZZLE_32B);
        encode(enc, &m.wu, d_in[7], 2, dims, str, box, CU_TENSOR_MAP_SWIZZLE_32B);
    }
    Params p;
    p.x = (const __nv_bfloat16*)d_in[0];
    p.c = (const __nv_bfloat16*)d_in[9];
    p.w_mod = (const __nv_bfloat16*)d_in[10];
    p.out = (__nv_bfloat16*)d_out;
    p.sc = scratch;
    p.wo = (const __nv_bfloat16*)d_in[4];
    p.wg = (const __nv_bfloat16*)d_in[6];
    p.wu = (const __nv_bfloat16*)d_in[7];
    p.wd = (const __nv_bfloat16*)d_in[8];
    fused_block_kernel<<<NCTA, NTHREADS, SMEM_BYTES, cudaStreamPerThread>>>(p, m.k, m.v, m.wq, m.wmod, m.wo, m.wg, m.wu, m.wd);
}
```

```cpp
#include <cuda_runtime.h>
#include <cuda.h>
#include <cuda_bf16.h>
#include <stdint.h>

namespace {

constexpr int D_MODEL = 512;
constexpr int N_HEADS = 32;
constexpr int SK = 32768;
constexpr int DH = 128;
constexpr int D_FF = 1792;
constexpr int N_MOD = 6 * D_MODEL;

constexpr int NCTA = 128;
constexpr int NFFN = D_FF / 16;
constexpr int NTHREADS = 320;
constexpr int NST = 12;
constexpr int TILE = 16384;
#define INFL_PRO 3
#define INFL_MAIN 3
#define INFL_TAIL 2
#define PACE_HI 96
#define PACE_LO 96
#define PACE_HI2 100000
#define PACE_END 16
#define GRID_SLACK 0
#define PACE_SLEEP 200
#define TR_PF_WO -1
#define TR_PF_FF -1
#define TR_LD_WO 0
#define TR_LD_GU 0
#define GU_PIECES 1
#define GU_WIN 3
#define TR_LD_WD 0
#define PRO_TILES 8
constexpr int KV_TILES = 64;
#define MOD_AT 8
#define WO_AT 64
#define GU_AT 64
#define WD_AT 64
static_assert(MOD_AT % 2 == 0 && MOD_AT < WO_AT && MOD_AT < GU_AT && MOD_AT < WD_AT, "schedule");
static_assert(WO_AT <= KV_TILES && GU_AT <= KV_TILES && WD_AT <= KV_TILES, "schedule");
#define WQ_AT 0
constexpr int IDX_WQ = 2 * WQ_AT;
__host__ __device__ constexpr int kv_idx(int i) {
    return (i >= WQ_AT ? 2 : 0) + 2 * i + (i >= MOD_AT ? 1 : 0) + (i >= WO_AT ? 2 : 0) + (i >= GU_AT ? 2 : 0) + (i >= WD_AT ? 1 : 0);
}
constexpr int IDX_MOD = 2 + 2 * MOD_AT;
constexpr int IDX_WO = 3 + 2 * WO_AT + (GU_AT < WO_AT ? 2 : 0) + (WD_AT < WO_AT ? 1 : 0);
constexpr int IDX_WG = 3 + 2 * GU_AT + (WO_AT <= GU_AT ? 2 : 0) + (WD_AT < GU_AT ? 1 : 0);
constexpr int IDX_WU = IDX_WG + 1;
constexpr int IDX_WD = 3 + 2 * WD_AT + (WO_AT <= WD_AT ? 2 : 0) + (GU_AT <= WD_AT ? 2 : 0);
constexpr int N_TILES = 2 + 2 * KV_TILES + 1 + 2 + 3;
static_assert(N_TILES - 1 - IDX_WO < NST && N_TILES - 1 - IDX_WG < NST && N_TILES - 1 - IDX_WD < NST, "weights must stay resident until the end");
constexpr int SPIN_LIMIT = 1 << 20;

constexpr float LOG2E = 1.4426950408889634f;
constexpr float QK_SCALE = 0.08838834764831845f;

constexpr int SM_RING = 0;
constexpr int SM_MRG = SM_RING + NST * TILE;
constexpr int SM_ML = SM_MRG + 8 * 4 * 136 * 4;
constexpr int SM_RED = SM_ML + 8 * 4 * 8;
constexpr int SM_RED2 = SM_RED + 8 * 64 * 4;
constexpr int SM_QS = SM_RED2 + 8 * 64 * 4;
constexpr int SM_OS = SM_QS + 512 * 2;
constexpr int SM_SC = SM_OS + 2 * 16 * 4;
constexpr int SM_HS = SM_SC + 2 * 512 * 2;
constexpr int SM_STAT = SM_HS + 8 * 2 * 32 * 4;
constexpr int SM_PACE = SM_STAT + 8 * 2 * 8;
constexpr int SM_BAR = SM_PACE + 8;
constexpr int SM_END = SM_BAR + (2 * NST + 7 + 8 + 2) * 8;
constexpr int SMEM_BYTES = SM_END + 1024;

struct Scratch {
    uint4 inbox[NCTA][NCTA][2];
    uint2 x1[NCTA][16];
    uint2 part_o[NCTA][4][64];
    uint2 part_ml[NCTA][4][4];
    uint2 mod[2][N_MOD / 2];
    uint2 q[2][N_HEADS * DH / 2];
    unsigned epoch;
    unsigned pad_[31];
    unsigned cleared;
    unsigned pad2_[31];
    unsigned progress;
};
__device__ Scratch g_scratch;
constexpr uint32_t F_PART = 1, F_WO = 1, F_DOWN = 2, F_X1 = 1;
__device__ __forceinline__ uint32_t tagf(float v, uint32_t f) { return (__float_as_uint(v) & ~3u) | f; }
__device__ __forceinline__ float untag(uint32_t v) { return __uint_as_float(v & ~3u); }

struct Params {
    const __nv_bfloat16* x;
    const __nv_bfloat16* c;
    const __nv_bfloat16* w_mod;
    __nv_bfloat16* out;
    Scratch* sc;
    const __nv_bfloat16 *wo, *wg, *wu, *wd;
};

#define TSTAMP(i) do { } while (0)

__device__ __forceinline__ uint32_t smem_u32(const void* p) { return (uint32_t)__cvta_generic_to_shared(p); }

__device__ __forceinline__ void mbar_init(uint32_t bar, uint32_t cnt) {
    asm volatile("mbarrier.init.shared::cta.b64 [%0], %1;" ::"r"(bar), "r"(cnt) : "memory");
}
__device__ __forceinline__ void mbar_expect_tx(uint32_t bar, uint32_t bytes) {
    asm volatile("mbarrier.arrive.expect_tx.shared::cta.b64 _, [%0], %1;" ::"r"(bar), "r"(bytes) : "memory");
}
__device__ __forceinline__ void mbar_arrive(uint32_t bar) {
    asm volatile("mbarrier.arrive.shared::cta.b64 _, [%0];" ::"r"(bar) : "memory");
}
__device__ __forceinline__ bool mbar_try(uint32_t bar, uint32_t parity) {
    uint32_t ok;
    asm volatile(
        "{\n\t.reg .pred p;\n\t"
        "mbarrier.try_wait.parity.shared::cta.b64 p, [%1], %2;\n\t"
        "selp.u32 %0, 1, 0, p;\n\t}"
        : "=r"(ok) : "r"(bar), "r"(parity) : "memory");
    return ok != 0;
}
__device__ __forceinline__ void mbar_wait(uint32_t bar, uint32_t parity) {
    if (mbar_try(bar, parity)) return;
    for (int i = 0; i < SPIN_LIMIT; i++)
        if (mbar_try(bar, parity)) return;
}
__device__ __forceinline__ void cons_sync() { asm volatile("bar.sync 1, 256;" ::: "memory"); }

__device__ __forceinline__ void tma_2d(uint32_t dst, const CUtensorMap* m, int c0, int c1, uint32_t bar) {
    asm volatile("cp.async.bulk.tensor.2d.shared::cluster.global.mbarrier::complete_tx::bytes [%0], [%1, {%3, %4}], [%2];"
                 ::"r"(dst), "l"(m), "r"(bar), "r"(c0), "r"(c1) : "memory");
}
__device__ __forceinline__ void tma_3d(uint32_t dst, const CUtensorMap* m, int c0, int c1, int c2, uint32_t bar) {
    asm volatile("cp.async.bulk.tensor.3d.shared::cluster.global.mbarrier::complete_tx::bytes [%0], [%1, {%3, %4, %5}], [%2];"
                 ::"r"(dst), "l"(m), "r"(bar), "r"(c0), "r"(c1), "r"(c2) : "memory");
}
__device__ __forceinline__ void tma_3d_hint(uint32_t dst, const CUtensorMap* m, int c0, int c1, int c2, uint32_t bar, uint64_t pol) {
    asm volatile("cp.async.bulk.tensor.3d.shared::cluster.global.mbarrier::complete_tx::bytes.L2::cache_hint [%0], [%1, {%3, %4, %5}], [%2], %6;"
                 ::"r"(dst), "l"(m), "r"(bar), "r"(c0), "r"(c1), "r"(c2), "l"(pol) : "memory");
}
__device__ __forceinline__ void l2pf_2d(const CUtensorMap* m, int c0, int c1) {
    asm volatile("cp.async.bulk.prefetch.tensor.2d.L2.global.tile [%0, {%1, %2}];" ::"l"(m), "r"(c0), "r"(c1) : "memory");
}
__device__ __forceinline__ void l2pf_3d(const CUtensorMap* m, int c0, int c1, int c2) {
    asm volatile("cp.async.bulk.prefetch.tensor.3d.L2.global.tile [%0, {%1, %2, %3}];" ::"l"(m), "r"(c0), "r"(c1), "r"(c2) : "memory");
}
__device__ __forceinline__ void l2pf_1d(const void* ptr, uint32_t bytes) {
    asm volatile("cp.async.bulk.prefetch.L2.global [%0], %1;" ::"l"(ptr), "r"(bytes) : "memory");
}
__device__ __forceinline__ void prefetch_tmap(const CUtensorMap* m) {
    asm volatile("prefetch.tensormap [%0];" ::"l"(m) : "memory");
}

__device__ __forceinline__ void ldsm4(uint32_t addr, uint32_t (&r)[4]) {
    asm volatile("ldmatrix.sync.aligned.m8n8.x4.shared.b16 {%0,%1,%2,%3}, [%4];"
                 : "=r"(r[0]), "=r"(r[1]), "=r"(r[2]), "=r"(r[3]) : "r"(addr) : "memory");
}
__device__ __forceinline__ void ldsm4t(uint32_t addr, uint32_t (&r)[4]) {
    asm volatile("ldmatrix.sync.aligned.m8n8.x4.trans.shared.b16 {%0,%1,%2,%3}, [%4];"
                 : "=r"(r[0]), "=r"(r[1]), "=r"(r[2]), "=r"(r[3]) : "r"(addr) : "memory");
}
__device__ __forceinline__ void mma16816(float (&c)[4], const uint32_t (&a)[4], uint32_t b0, uint32_t b1) {
    asm volatile("mma.sync.aligned.m16n8k16.row.col.f32.bf16.bf16.f32 {%0,%1,%2,%3}, {%4,%5,%6,%7}, {%8,%9}, {%0,%1,%2,%3};"
                 : "+f"(c[0]), "+f"(c[1]), "+f"(c[2]), "+f"(c[3])
                 : "r"(a[0]), "r"(a[1]), "r"(a[2]), "r"(a[3]), "r"(b0), "r"(b1));
}
__device__ __forceinline__ uint32_t movmatrix_t(uint32_t a) {
    uint32_t d;
    asm volatile("movmatrix.sync.aligned.m8n8.trans.b16 %0, %1;" : "=r"(d) : "r"(a));
    return d;
}
__device__ __forceinline__ uint32_t pack_bf16(float a, float b) {
    uint32_t r;
    asm("cvt.rn.bf16x2.f32 %0, %1, %2;" : "=r"(r) : "f"(b), "f"(a));
    return r;
}
__device__ __forceinline__ float bf_lo(uint32_t v) { return __uint_as_float(v << 16); }
__device__ __forceinline__ float bf_hi(uint32_t v) { return __uint_as_float(v & 0xffff0000u); }
__device__ __forceinline__ float bf16r(float a) { return bf_lo(pack_bf16(a, 0.f)); }
__device__ __forceinline__ uint32_t max_bf16x2(uint32_t a, uint32_t b) {
    uint32_t r;
    asm("max.bf16x2 %0, %1, %2;" : "=r"(r) : "r"(a), "r"(b));
    return r;
}
__device__ __forceinline__ float ex2(float x) {
    float r;
    asm("ex2.approx.ftz.f32 %0, %1;" : "=f"(r) : "f"(x));
    return r;
}

__device__ __forceinline__ void st_ll2(uint2* p, uint32_t v, uint32_t tag) {
    asm volatile("st.relaxed.gpu.global.v2.u32 [%0], {%1, %2};" ::"l"(p), "r"(v), "r"(tag) : "memory");
}
__device__ __forceinline__ void st_ll4(uint4* p, uint32_t v0, uint32_t v1, uint32_t tag) {
    asm volatile("st.relaxed.gpu.global.v4.u32 [%0], {%1, %2, %3, %2};" ::"l"(p), "r"(v0), "r"(tag), "r"(v1) : "memory");
}
__device__ __forceinline__ void st_v4(uint4* p, uint32_t a, uint32_t b, uint32_t c, uint32_t d) {
    asm volatile("st.relaxed.gpu.global.v4.u32 [%0], {%1, %2, %3, %4};" ::"l"(p), "r"(a), "r"(b), "r"(c), "r"(d) : "memory");
}
__device__ __forceinline__ uint2 ld_ll2(const uint2* p) {
    uint2 v;
    asm volatile("ld.relaxed.gpu.global.v2.u32 {%0, %1}, [%2];" : "=r"(v.x), "=r"(v.y) : "l"(p) : "memory");
    return v;
}
__device__ __forceinline__ uint4 ld_ll4(const uint4* p) {
    uint4 v;
    asm volatile("ld.relaxed.gpu.global.v4.u32 {%0, %1, %2, %3}, [%4];"
                 : "=r"(v.x), "=r"(v.y), "=r"(v.z), "=r"(v.w) : "l"(p) : "memory");
    return v;
}

#define DELAY_B1 450
#define DELAY_B2 0
#define DELAY_C 450
__device__ __forceinline__ uint32_t clock32() {
    uint32_t c;
    asm volatile("mov.u32 %0, %clock;" : "=r"(c));
    return c;
}
__device__ __forceinline__ void spin_cycles(uint32_t n) {
    if (n > 0) { const uint32_t c0 = clock32(); while (clock32() - c0 < n) {} }
}
__device__ __forceinline__ float rcp_approx(float x) {
    float r;
    asm("rcp.approx.ftz.f32 %0, %1;" : "=f"(r) : "f"(x));
    return r;
}
__device__ __forceinline__ float sqrt_approx(float x) {
    float r;
    asm("sqrt.approx.f32 %0, %1;" : "=f"(r) : "f"(x));
    return r;
}

__device__ __forceinline__ float silu_bf(float v) { return bf16r(v / (1.0f + expf(-v))); }

__device__ __forceinline__ float2 half_warp_sums(const float (&v)[4], float pivot) {
    float s1 = 0.f, s2 = 0.f;
#pragma unroll
    for (int i = 0; i < 4; i++) { const float d = v[i] - pivot; s1 += d; s2 += d * d; }
#pragma unroll
    for (int o = 1; o < 16; o <<= 1) { s1 += __shfl_xor_sync(0xffffffffu, s1, o); s2 += __shfl_xor_sync(0xffffffffu, s2, o); }
    return make_float2(s1, s2);
}
__device__ __forceinline__ void ln_stats(const float2* stat, int b, float pivot, float& mean_bf, float& rstd) {
    float s1 = 0.f, s2 = 0.f;
#pragma unroll
    for (int w = 0; w < 8; w++) { const float2 v = stat[w * 2 + b]; s1 += v.x; s2 += v.y; }
    const float dm = s1 * (1.0f / D_MODEL);
    const float var = fmaxf(s2 * (1.0f / D_MODEL) - dm * dm, 0.f);
    mean_bf = bf16r(pivot + dm);
    rstd = rcp_approx(bf16r(sqrt_approx(bf16r(bf16r(var) + 1e-5f))));
}
__device__ __forceinline__ float ln_norm(float xv, float mean_bf, float rstd) { return bf16r(bf16r(xv - mean_bf) * rstd); }
__device__ __forceinline__ float ln_mod(float n, float cmul, float sadd) { return bf16r(n * bf16r(1.0f + cmul)) + sadd; }

__global__ void __launch_bounds__(NTHREADS, 1)
fused_block_kernel(const Params p, const __grid_constant__ CUtensorMap tm_k, const __grid_constant__ CUtensorMap tm_v,
                   const __grid_constant__ CUtensorMap tm_wq, const __grid_constant__ CUtensorMap tm_wmod,
                   const __grid_constant__ CUtensorMap tm_wmod8,
                   const __grid_constant__ CUtensorMap tm_wo, const __grid_constant__ CUtensorMap tm_wg,
                   const __grid_constant__ CUtensorMap tm_wu, const __grid_constant__ CUtensorMap tm_wd) {
    extern __shared__ unsigned char smem_raw[];
    const uint32_t sbase = (smem_u32(smem_raw) + 1023u) & ~1023u;
    unsigned char* sgen = smem_raw + (sbase - smem_u32(smem_raw));
    const int tid = threadIdx.x, warp = tid >> 5, lane = tid & 31;
    const int cta = blockIdx.x;
    const uint32_t bar_full = sbase + SM_BAR, bar_empty = bar_full + NST * 8;
    const uint32_t bar_clear = bar_empty + NST * 8;
    const uint32_t bar_gu = bar_clear + 7 * 8;
    const uint32_t bar_bc = bar_gu + 8 * 8;
    const uint32_t bar_p0w = bar_bc + 8;
    const uint32_t bar_trig = bar_clear;

    const int key0 = (cta >> 3) * SK + (cta & 7) * 64;
    uint64_t pol = 0;
    if (tid == 256) {
        asm volatile("createpolicy.fractional.L2::evict_first.b64 %0, 1.0;" : "=l"(pol));
        mbar_init(bar_p0w, 1);
#pragma unroll
        for (int i = 0; i < 4; i++) mbar_init(bar_full + 8 * i, 1);
        asm volatile("fence.mbarrier_init.release.cluster;" ::: "memory");
        mbar_expect_tx(bar_p0w, 8192);
        tma_2d(sbase + SM_MRG, &tm_wmod8, cta * 8, 0, bar_p0w);
        tma_2d(sbase + SM_MRG + 4096, &tm_wmod8, cta * 8, 256, bar_p0w);
#pragma unroll
        for (int i = 0; i < 4; i++) mbar_expect_tx(bar_full + 8 * i, TILE);
        tma_2d(sbase + SM_RING, &tm_wq, cta * 32, 0, bar_full);
        tma_2d(sbase + SM_RING + TILE, &tm_wq, cta * 32, 256, bar_full + 8);
        tma_3d_hint(sbase + SM_RING + 2 * TILE, &tm_k, 0, key0, 0, bar_full + 16, pol);
        tma_3d_hint(sbase + SM_RING + 3 * TILE, &tm_v, 0, key0, 0, bar_full + 24, pol);
    }
    static_assert(WQ_AT == 0 && MOD_AT >= 1, "the fast start assumes the sequence wq0 wq1 K0 V0");

    if (warp == 8) {
        if (lane == 0) {
            for (int i = 0; i < NST; i++) { if (i >= 4) mbar_init(bar_full + 8 * i, 1); mbar_init(bar_empty + 8 * i, 4); }
            mbar_init(bar_clear, 1);
            for (int k = 1; k <= 6; k++) mbar_init(bar_trig + 8 * k, 1);
            for (int k = 0; k < 8; k++) mbar_init(bar_gu + 8 * k, 1);
            mbar_init(bar_bc, 8);
            ((volatile uint32_t*)(sgen + SM_PACE))[0] = 0;
            ((volatile uint32_t*)(sgen + SM_PACE))[1] = INFL_MAIN;
            asm volatile("fence.mbarrier_init.release.cluster;" ::: "memory");
        }
        __syncwarp();
        asm volatile("bar.arrive 2, 320;" ::: "memory");
        asm volatile("bar.arrive 3, 64;" ::: "memory");
        if (lane == 0) {
            int slot = 4; uint32_t ph = 1;
            int landed = 0, wslot = 0; uint32_t wph = 0;
            int kv = 2;
            constexpr int N_STREAM = kv_idx(KV_TILES - 1) + 2;
            auto issue = [&](int idx) {
                const uint32_t fb = bar_full + 8 * (idx % NST), dst = sbase + SM_RING + (idx % NST) * TILE;
                if ((idx == IDX_WG || idx == IDX_WU || idx == IDX_WD) && cta >= NFFN) {
                    mbar_arrive(fb);
                    return;
                }
                mbar_expect_tx(fb, TILE);
                if (idx == IDX_WQ || idx == IDX_WQ + 1) {
                    tma_2d(dst, &tm_wq, cta * 32, (idx - IDX_WQ) * 256, fb);
                } else if (idx == IDX_MOD) {
                    tma_2d(dst, &tm_wmod, 1024 + cta * 16, 0, fb);
                    tma_2d(dst + 8192, &tm_wmod, 1024 + cta * 16, 256, fb);
                } else if (idx == IDX_WO || idx == IDX_WO + 1) {
                    tma_3d(dst, &tm_wo, 0, cta * 32 + (idx - IDX_WO) * 16, 0, fb);
                } else if (idx == IDX_WG || idx == IDX_WU) {
                    const CUtensorMap* m = idx == IDX_WG ? &tm_wg : &tm_wu;
#pragma unroll
                    for (int q = 0; q < 4; q++) tma_2d(dst + q * 4096, m, cta * 16, q * 128, fb);
                } else if (idx == IDX_WD) {
                    tma_3d(dst, &tm_wd, 0, cta * 16, 0, fb);
                } else {
                    tma_3d_hint(dst, (kv & 1) ? &tm_v : &tm_k, 0, key0 + (kv >> 1) * 512, 0, fb, pol);
                    kv++;
                }
            };
            auto wait_window = [&](int idx, int window) {
                while (landed + window <= idx) {
                    mbar_wait(bar_full + 8 * wslot, wph);
                    if (++wslot == NST) { wslot = 0; wph ^= 1; }
                    landed++;
                }
            };
            prefetch_tmap(&tm_wmod);
            ((volatile uint32_t*)(sgen + SM_PACE))[0] = 4;
            for (int idx = 4; idx < N_STREAM; idx++) {
                if (idx >= NST) mbar_wait(bar_empty + 8 * slot, ph);
                wait_window(idx, idx < PRO_TILES ? INFL_PRO : (int)((volatile uint32_t*)(sgen + SM_PACE))[1]);
                if (idx == 12) { prefetch_tmap(&tm_wo); prefetch_tmap(&tm_wg); prefetch_tmap(&tm_wu); prefetch_tmap(&tm_wd); }
                issue(idx);
                ((volatile uint32_t*)(sgen + SM_PACE))[0] = idx + 1;
                if (++slot == NST) { slot = 0; ph ^= 1; }
            }
            auto deferred = [&](int idx, bool windowed) {
                if (idx < N_STREAM) return;
                mbar_wait(bar_empty + 8 * (idx % NST), ((idx / NST) & 1) ^ 1);
                if (windowed) wait_window(idx, INFL_TAIL);
                issue(idx);
            };
#pragma unroll
            for (int kk = 0; kk <= 6; kk++) {
                const int k = kk == 0 ? 0 : kk == 1 ? 6 : kk - 1;
                if (TR_PF_WO != k && TR_PF_FF != k && TR_LD_WO != k && TR_LD_GU != k && TR_LD_WD != k) continue;
                if (k > 0) mbar_wait(bar_trig + 8 * k, 0);
                if (TR_PF_WO == k) l2pf_1d((const char*)p.wo + (size_t)cta * 32768, 32768);
                if (TR_PF_FF == k && cta < NFFN) {
                    l2pf_1d((const char*)p.wg + (size_t)cta * 16384, 16384);
                    l2pf_1d((const char*)p.wu + (size_t)cta * 16384, 16384);
                    l2pf_1d((const char*)p.wd + (size_t)cta * 16384, 16384);
                }
                if (TR_LD_WO == k) { deferred(IDX_WO, k == 0 || k == 6); deferred(IDX_WO + 1, k == 0 || k == 6); }
                if (TR_LD_GU == k) {
                    if (!GU_PIECES) { deferred(IDX_WG, k == 0 || k == 6); deferred(IDX_WU, k == 0 || k == 6); }
                    else if (cta < NFFN) {
                        mbar_wait(bar_empty + 8 * (IDX_WG % NST), ((IDX_WG / NST) & 1) ^ 1);
                        mbar_wait(bar_empty + 8 * (IDX_WU % NST), ((IDX_WU / NST) & 1) ^ 1);
                        if (IDX_WO >= N_STREAM && TR_LD_WO <= k) {
                            mbar_wait(bar_full + 8 * (IDX_WO % NST), (IDX_WO / NST) & 1);
                            mbar_wait(bar_full + 8 * ((IDX_WO + 1) % NST), ((IDX_WO + 1) / NST) & 1);
                        }
#pragma unroll
                        for (int st = 0; st < 8; st++) {
                            if (st >= GU_WIN) mbar_wait(bar_gu + 8 * (st - GU_WIN), 0);
                            const uint32_t dst = sbase + SM_RING + (((st & 1) ? IDX_WU : IDX_WG) % NST) * TILE + (st >> 1) * 4096;
                            mbar_expect_tx(bar_gu + 8 * st, 4096);
                            tma_2d(dst, (st & 1) ? &tm_wu : &tm_wg, cta * 16, (st >> 1) * 128, bar_gu + 8 * st);
                        }
                        mbar_wait(bar_gu + 8 * 7, 0);
                    }
                }
                if (TR_LD_WD == k) deferred(IDX_WD, !GU_PIECES && (k == 0 || k == 6));
            }
        }
    } else if (warp == 9) {
        Scratch* const sc = p.sc;
        const uint32_t tag = *(volatile unsigned*)&sc->epoch + 1;
        if (lane < 2) {
            st_ll4((uint4*)&sc->mod[lane][cta * 4], 0u, 0u, 0u);
            st_ll4((uint4*)&sc->mod[lane][cta * 4] + 1, 0u, 0u, 0u);
        }
        if (lane < 8) st_ll4((uint4*)&sc->mod[lane >> 2][512 + cta * 8] + (lane & 3), 0u, 0u, 0u);
        if (lane < 16) st_ll4((uint4*)&sc->q[lane >> 3][cta * 16] + (lane & 7), 0u, 0u, 0u);
        __syncwarp();
        asm volatile("bar.arrive 2, 320;" ::: "memory");
        asm volatile("bar.sync 3, 64;" ::: "memory");
#pragma unroll 4
        for (int i = 0; i < 8; i++) st_v4(&sc->inbox[cta][0][0] + i * 32 + lane, 0u, 0u, 0u, 0u);
#pragma unroll 4
        for (int i = 0; i < 4; i++) st_v4((uint4*)&sc->part_o[cta][0][0] + i * 32 + lane, 0u, 0u, 0u, 0u);
        if (lane < 8) st_v4((uint4*)&sc->part_ml[cta][0][0] + lane, 0u, 0u, 0u, 0u);
        if (lane < 2) st_v4((uint4*)&sc->x1[cta][0] + lane, 0u, 0u, 0u, 0u);
        if (cta == 0 && lane == 0) asm volatile("st.relaxed.gpu.global.u32 [%0], %1;" ::"l"(&sc->progress), "r"(0u) : "memory");
        asm volatile("fence.acq_rel.gpu;" ::: "memory");
        __syncwarp();
        if (lane == 0) {
            asm volatile("fence.acq_rel.gpu;" ::: "memory");
            asm volatile("red.relaxed.gpu.global.add.u32 [%0], %1;" ::"l"(&sc->cleared), "r"(1u) : "memory");
            const uint32_t target = tag * NCTA;
            for (int it = 0; it < SPIN_LIMIT; it++) {
                uint32_t v;
                asm volatile("ld.relaxed.gpu.global.u32 %0, [%1];" : "=r"(v) : "l"(&sc->cleared) : "memory");
                if ((int32_t)(v - target) >= 0) break;
                __nanosleep(500);
            }
            asm volatile("fence.acq_rel.gpu;" ::: "memory");
            mbar_arrive(bar_clear);
            volatile uint32_t* pace = (volatile uint32_t*)(sgen + SM_PACE);
            constexpr uint32_t N_STREAM = kv_idx(KV_TILES - 1) + 2;
            uint32_t posted = 0;
            for (int it = 0; it < SPIN_LIMIT; it++) {
                const uint32_t own = pace[0];
                if (own > posted) {
                    asm volatile("red.relaxed.gpu.global.add.u32 [%0], %1;" ::"l"(&sc->progress), "r"(own - posted) : "memory");
                    posted = own;
                }
                uint32_t v;
                asm volatile("ld.relaxed.gpu.global.u32 %0, [%1];" : "=r"(v) : "l"(&sc->progress) : "memory");
                if (own >= N_STREAM) {
                    if (v + GRID_SLACK >= NCTA * N_STREAM) break;
                } else {
                    const int diff = (int)v - (int)own * NCTA;
                    pace[1] = diff > PACE_HI2 && own + PACE_END >= N_STREAM ? INFL_MAIN + 2
                            : diff > PACE_HI ? INFL_MAIN + 1 : diff < -PACE_LO ? INFL_MAIN - 1 : INFL_MAIN;
                }
                __nanosleep(own + 4 >= N_STREAM ? 50 : PACE_SLEEP);
            }
            mbar_arrive(bar_trig + 8 * 6);
        }
    } else {
        const int g = lane >> 2, t = lane & 3;
        const int bb = g & 1;
        const int eb = lane >> 4;
        const int ec = 64 * warp + 4 * (lane & 15);
        if (warp == 0) TSTAMP(0);
        Scratch* const sc = p.sc;
        const float c00 = __bfloat162float(p.c[tid]), c01 = __bfloat162float(p.c[tid + 256]);
        const float c10 = __bfloat162float(p.c[D_MODEL + tid]), c11 = __bfloat162float(p.c[D_MODEL + tid + 256]);
        const uint2 xe = __ldg((const uint2*)(p.x + eb * D_MODEL + ec));
        const float xpivot = __bfloat162float(p.x[eb * D_MODEL]);
        const uint32_t tag = *(volatile unsigned*)&sc->epoch + 1;
        const int ocol = cta * 4 + (lane & 3);
        const float xo0 = __bfloat162float(p.x[ocol]), xo1 = __bfloat162float(p.x[D_MODEL + ocol]);

        float* red = (float*)(sgen + SM_RED);
        float* red2 = (float*)(sgen + SM_RED2);
        float2* stat = (float2*)(sgen + SM_STAT);
        uint32_t* hs = (uint32_t*)(sgen + SM_HS) + warp * 64;
        float xn[4];
        {
            float xv[4] = {bf_lo(xe.x), bf_hi(xe.x), bf_lo(xe.y), bf_hi(xe.y)};
            const float2 ps = half_warp_sums(xv, xpivot);
            if ((lane & 15) == 0) stat[warp * 2 + eb] = ps;
            const float s00 = silu_bf(c00), s01 = silu_bf(c01), s10 = silu_bf(c10), s11 = silu_bf(c11);
            __nv_bfloat16* scs = (__nv_bfloat16*)(sgen + SM_SC);
            scs[tid] = __float2bfloat16_rn(s00); scs[tid + 256] = __float2bfloat16_rn(s01);
            scs[512 + tid] = __float2bfloat16_rn(s10); scs[512 + tid + 256] = __float2bfloat16_rn(s11);
            asm volatile("bar.sync 2, 320;" ::: "memory");
            if (warp == 0) TSTAMP(23);
            float cp[4] = {0.f, 0.f, 0.f, 0.f};
            const uint32_t* sc32 = (const uint32_t*)(sgen + SM_SC) + bb * 256 + 32 * warp + t;
            mbar_wait(bar_p0w, 0);
#pragma unroll
            for (int s = 0; s < 4; s++) {
                uint32_t r0, r1;
                asm volatile("ldmatrix.sync.aligned.m8n8.x2.trans.shared.b16 {%0,%1}, [%2];"
                             : "=r"(r0), "=r"(r1) : "r"(sbase + SM_MRG + (64 * warp + 16 * s + (lane & 15)) * 16) : "memory");
                const uint32_t a[4] = {r0, r0, r1, r1};
                mma16816(cp, a, sc32[8 * s], sc32[8 * s + 4]);
            }
            if (t == 0) { red[warp * 16 + g] = cp[0]; red[warp * 16 + 8 + g] = cp[1]; }
            if (warp == 0) TSTAMP(14);
            cons_sync();
            if (warp == 0) {
                float s = 0.f;
#pragma unroll
                for (int w = 0; w < 8; w++) s += red[w * 16 + (lane & 15)];
                const float nx = __shfl_down_sync(0xffffffffu, s, 1);
                if (lane < 16 && !(lane & 1))
                    st_ll2(&sc->mod[lane >> 3][cta * 4 + ((lane & 7) >> 1)], pack_bf16(s, nx), tag);
                TSTAMP(1);
            }
            float mean_bf, rstd;
            ln_stats(stat, eb, xpivot, mean_bf, rstd);
#pragma unroll
            for (int i = 0; i < 4; i++) xn[i] = ln_norm(xv[i], mean_bf, rstd);
        }
        {
            uint4 sa, ca;
            for (int it = 0;; it++) {
                sa = ld_ll4((const uint4*)&sc->mod[eb][ec >> 1]);
                ca = ld_ll4((const uint4*)&sc->mod[eb][256 + (ec >> 1)]);
                const bool ok = sa.y == tag && sa.w == tag && ca.y == tag && ca.w == tag;
                if (__all_sync(0xffffffffu, ok) || it > SPIN_LIMIT) break;
            }
            *(uint2*)&hs[eb * 32 + 2 * (lane & 15)] =
                make_uint2(pack_bf16(ln_mod(xn[0], bf_lo(ca.x), bf_lo(sa.x)), ln_mod(xn[1], bf_hi(ca.x), bf_hi(sa.x))),
                           pack_bf16(ln_mod(xn[2], bf_lo(ca.z), bf_lo(sa.z)), ln_mod(xn[3], bf_hi(ca.z), bf_hi(sa.z))));
            __syncwarp();
            uint32_t hb[8];
#pragma unroll
            for (int i = 0; i < 8; i++) hb[i] = hs[bb * 32 + 8 * (i >> 1) + 4 * (i & 1) + t];
            if (warp == 0) TSTAMP(2);
            float cq[2][4] = {};
            const int ts = warp >> 2;
            mbar_wait(bar_full + 8 * (IDX_WQ + ts), 0);
            const uint32_t tb = sbase + SM_RING + (IDX_WQ + ts) * TILE;
#pragma unroll
            for (int s = 0; s < 4; s++) {
                const int row = 64 * (warp & 3) + 16 * s + (lane & 7) + (lane >> 4) * 8;
#pragma unroll
                for (int mt = 0; mt < 2; mt++) {
                    const int ch = 2 * mt + ((lane >> 3) & 1);
                    uint32_t a[4];
                    ldsm4t(tb + row * 64 + ((ch ^ ((row >> 1) & 3)) << 4), a);
                    mma16816(cq[mt], a, hb[2 * s], hb[2 * s + 1]);
                }
            }
            if (t < 2) {
                const float v0 = t == 0 ? cq[0][0] : cq[1][0], v1 = t == 0 ? cq[0][1] : cq[1][1];
                const float v2 = t == 0 ? cq[0][2] : cq[1][2], v3 = t == 0 ? cq[0][3] : cq[1][3];
                *(float2*)&red2[warp * 64 + (16 * t + g) * 2] = make_float2(v0, v1);
                *(float2*)&red2[warp * 64 + (16 * t + g + 8) * 2] = make_float2(v2, v3);
            }
            cons_sync();
            if (warp < 4 && lane == 0) { mbar_arrive(bar_empty + 8 * IDX_WQ); mbar_arrive(bar_empty + 8 * IDX_WQ + 8); }
            if (warp == 0) {
                const int b = lane >> 4, cp = lane & 15;
                float q0 = 0.f, q1 = 0.f;
#pragma unroll
                for (int w = 0; w < 8; w++) {
                    const float4 v = *(const float4*)&red2[w * 64 + cp * 4];
                    q0 += b ? v.y : v.x; q1 += b ? v.w : v.z;
                }
                st_ll2(&sc->q[b][cta * 16 + cp], pack_bf16(q0, q1), tag);
                TSTAMP(3);
            }
        }
        const int pair = cta >> 3;
        uint32_t qf[16];
        {
            uint2* qs = (uint2*)(sgen + SM_QS);
            if (tid < 128) {
                const uint4* src = (const uint4*)&sc->q[pair >> 3][(pair & 7) * 256] + tid;
                uint4 v;
                for (int it = 0;; it++) {
                    v = ld_ll4(src);
                    if ((v.y == tag && v.w == tag) || it > SPIN_LIMIT) break;
                }
                qs[tid] = make_uint2(v.x, v.z);
            }
            cons_sync();
            const uint32_t* q32 = (const uint32_t*)(sgen + SM_QS);
#pragma unroll
            for (int s = 0; s < 8; s++) {
                qf[2 * s] = q32[(g & 3) * 64 + 8 * s + t];
                qf[2 * s + 1] = q32[(g & 3) * 64 + 8 * s + 4 + t];
            }
        }
        if (warp == 0) TSTAMP(4);

        float o[8][4];
#pragma unroll
        for (int i = 0; i < 8; i++) { o[i][0] = o[i][1] = o[i][2] = o[i][3] = 0.f; }
        uint32_t mrun = 0xff80ff80u;
        float ls[4] = {0.f, 0.f, 0.f, 0.f};
        uint4 m_sb, m_cb; uint2 m_ga0, m_ga1, m_gb0, m_gb1;
        {
            const int grp = warp >> 2, wi = warp & 3;
            const int krow = 16 * wi + (lane & 7) + ((lane >> 3) & 1) * 8;
            const uint32_t koff = krow * 128 + ((((lane >> 4) & 1) ^ (lane & 7)) << 4);
            const int vrow = 16 * wi + (lane & 7) + (lane >> 4) * 8;
            const uint32_t voff = vrow * 128 + ((((lane >> 3) & 1) ^ (lane & 7)) << 4);
            const uint32_t ones[4] = {0x3f803f80u, 0x3f803f80u, 0x3f803f80u, 0x3f803f80u};
            for (int i = grp; i < KV_TILES; i += 2) {
                if (i == MOD_AT + grp) {
                    float cm[4] = {};
                    const uint32_t* sc32 = (const uint32_t*)(sgen + SM_SC) + bb * 256 + 32 * warp + t;
                    mbar_wait(bar_full + 8 * (IDX_MOD % NST), (IDX_MOD / NST) & 1);
                    const uint32_t tb = sbase + SM_RING + (IDX_MOD % NST) * TILE;
#pragma unroll
                    for (int s = 0; s < 4; s++) {
                        const int row = 64 * warp + 16 * s + (lane & 7) + (lane >> 4) * 8;
                        const int ch = (lane >> 3) & 1;
                        uint32_t a[4];
                        ldsm4t(tb + row * 32 + ((ch ^ ((row >> 2) & 1)) << 4), a);
                        mma16816(cm, a, sc32[8 * s], sc32[8 * s + 4]);
                    }
                    if (t == 0) {
                        *(float2*)&red[warp * 64 + g * 2] = make_float2(cm[0], cm[1]);
                        *(float2*)&red[warp * 64 + (g + 8) * 2] = make_float2(cm[2], cm[3]);
                    }
                    cons_sync();
                    if (warp < 4 && lane == 0) mbar_arrive(bar_empty + 8 * (IDX_MOD % NST));
                    if (warp == 1 && lane < 16) {
                        const int b = lane >> 3, cp = lane & 7;
                        float q0 = 0.f, q1 = 0.f;
#pragma unroll
                        for (int w = 0; w < 8; w++) {
                            const float4 v = *(const float4*)&red[w * 64 + cp * 4];
                            q0 += b ? v.y : v.x; q1 += b ? v.w : v.z;
                        }
                        st_ll2(&sc->mod[b][512 + cta * 8 + cp], pack_bf16(q0, q1), tag);
                    }
                }
                if (i == 56 + grp) {
                    m_sb = ld_ll4((const uint4*)&sc->mod[eb][768 + (ec >> 1)]);
                    m_cb = ld_ll4((const uint4*)&sc->mod[eb][1024 + (ec >> 1)]);
                    m_ga0 = ld_ll2(&sc->mod[0][512 + (ocol >> 1)]); m_ga1 = ld_ll2(&sc->mod[1][512 + (ocol >> 1)]);
                    m_gb0 = ld_ll2(&sc->mod[0][1280 + (ocol >> 1)]); m_gb1 = ld_ll2(&sc->mod[1][1280 + (ocol >> 1)]);
                }
                if (i == 60 + grp) {
                    for (int it = 0;; it++) {
                        const bool ok = m_sb.y == tag && m_sb.w == tag && m_cb.y == tag && m_cb.w == tag &&
                                        m_ga0.y == tag && m_ga1.y == tag && m_gb0.y == tag && m_gb1.y == tag;
                        if (__all_sync(0xffffffffu, ok) || it > SPIN_LIMIT) break;
                        m_sb = ld_ll4((const uint4*)&sc->mod[eb][768 + (ec >> 1)]);
                        m_cb = ld_ll4((const uint4*)&sc->mod[eb][1024 + (ec >> 1)]);
                        m_ga0 = ld_ll2(&sc->mod[0][512 + (ocol >> 1)]); m_ga1 = ld_ll2(&sc->mod[1][512 + (ocol >> 1)]);
                        m_gb0 = ld_ll2(&sc->mod[0][1280 + (ocol >> 1)]); m_gb1 = ld_ll2(&sc->mod[1][1280 + (ocol >> 1)]);
                    }
                    mbar_wait(bar_clear, 0);
                }
                const int ki = kv_idx(i), ks = ki % NST, vs = (ki + 1) % NST;
                const uint32_t kph = (ki / NST) & 1, vph = ((ki + 1) / NST) & 1;
                mbar_wait(bar_full + 8 * ks, kph);
                const uint32_t kb = sbase + SM_RING + ks * TILE + koff;
                float sa[4] = {0.f, 0.f, 0.f, 0.f}, sb[4] = {0.f, 0.f, 0.f, 0.f};
#pragma unroll
                for (int s = 0; s < 8; s += 2) {
                    uint32_t a0[4], a1[4];
                    ldsm4((kb ^ ((s & 3) << 5)) + (s >> 2) * 8192, a0);
                    ldsm4((kb ^ (((s + 1) & 3) << 5)) + (s >> 2) * 8192, a1);
                    mma16816(sa, a0, qf[2 * s], qf[2 * s + 1]);
                    mma16816(sb, a1, qf[2 * s + 2], qf[2 * s + 3]);
                }
                __syncwarp();
                if (lane == 0) mbar_arrive(bar_empty + 8 * ks);
                uint32_t r01 = pack_bf16(sa[0] + sb[0], sa[1] + sb[1]);
                uint32_t r23 = pack_bf16(sa[2] + sb[2], sa[3] + sb[3]);
                r01 = pack_bf16(bf_lo(r01) * QK_SCALE, bf_hi(r01) * QK_SCALE);
                r23 = pack_bf16(bf_lo(r23) * QK_SCALE, bf_hi(r23) * QK_SCALE);
                uint32_t mx = max_bf16x2(r01, r23);
                mx = max_bf16x2(mx, __shfl_xor_sync(0xffffffffu, mx, 4));
                mx = max_bf16x2(mx, __shfl_xor_sync(0xffffffffu, mx, 8));
                mx = max_bf16x2(mx, __shfl_xor_sync(0xffffffffu, mx, 16));
                const uint32_t mnew = max_bf16x2(mrun, mx);
                const float m0 = bf_lo(mnew), m1 = bf_hi(mnew);
                if (__any_sync(0xffffffffu, mnew != mrun)) {
                    const float al0 = ex2((bf_lo(mrun) - m0) * LOG2E), al1 = ex2((bf_hi(mrun) - m1) * LOG2E);
                    ls[0] *= al0; ls[1] *= al1;
#pragma unroll
                    for (int d = 0; d < 8; d++) { o[d][0] *= al0; o[d][1] *= al1; o[d][2] *= al0; o[d][3] *= al1; }
                    mrun = mnew;
                }
                const float p0 = ex2((bf_lo(r01) - m0) * LOG2E), p1 = ex2((bf_hi(r01) - m1) * LOG2E);
                const float p2 = ex2((bf_lo(r23) - m0) * LOG2E), p3 = ex2((bf_hi(r23) - m1) * LOG2E);
                const uint32_t pb0 = movmatrix_t(pack_bf16(p0, p1)), pb1 = movmatrix_t(pack_bf16(p2, p3));
                mma16816(ls, ones, pb0, pb1);
                mbar_wait(bar_full + 8 * vs, vph);
                const uint32_t vb = sbase + SM_RING + vs * TILE + voff;
#pragma unroll
                for (int d = 0; d < 8; d++) {
                    uint32_t a[4];
                    ldsm4t((vb ^ ((d & 3) << 5)) + (d >> 2) * 8192, a);
                    mma16816(o[d], a, pb0, pb1);
                }
                __syncwarp();
                if (lane == 0) mbar_arrive(bar_empty + 8 * vs);
            }
        }
        if (warp == 7) TSTAMP(5);
        if (warp == 7 && lane == 0) mbar_arrive(bar_trig + 8 * 1);
        {
            float* mrg = (float*)(sgen + SM_MRG);
            float2* ml = (float2*)(sgen + SM_ML);
            {
                const int hp = (t & 1) * 2, up = t >> 1;
                if (g == 0 && up == 0) { ml[warp * 4 + hp] = make_float2(bf_lo(mrun), ls[0]); ml[warp * 4 + hp + 1] = make_float2(bf_hi(mrun), ls[1]); }
                float* m0p = mrg + (warp * 4 + hp) * 136 + up * 72 + g;
#pragma unroll
                for (int d = 0; d < 4; d++) {
                    m0p[16 * d] = up ? o[d + 4][0] : o[d][0]; m0p[136 + 16 * d] = up ? o[d + 4][1] : o[d][1];
                    m0p[16 * d + 8] = up ? o[d + 4][2] : o[d][2]; m0p[136 + 16 * d + 8] = up ? o[d + 4][3] : o[d][3];
                }
            }
            cons_sync();
            const int hh = tid >> 6, dp = tid & 63;
            float2 mw[8];
            float M = -INFINITY;
#pragma unroll
            for (int w = 0; w < 8; w++) { mw[w] = ml[w * 4 + hh]; M = fmaxf(M, mw[w].x); }
            float L = 0.f, o0 = 0.f, o1 = 0.f;
#pragma unroll
            for (int w = 0; w < 8; w++) {
                const float wt = ex2((mw[w].x - M) * LOG2E);
                const float2 v = *(const float2*)&mrg[(w * 4 + hh) * 136 + 2 * dp + (dp >= 32 ? 8 : 0)];
                L += wt * mw[w].y; o0 += wt * v.x; o1 += wt * v.y;
            }
            st_ll2(&sc->part_o[cta][hh][dp], tagf(o0, F_PART), tagf(o1, F_PART));
            if (dp < 4) st_ll2(&sc->part_ml[cta][hh][dp], tagf(M, F_PART), tagf(L, F_PART));
        }
        if (tid == 0) mbar_arrive(bar_trig + 8 * 2);
        if (warp == 0) TSTAMP(6);
        const uint32_t aoff = warp * 2048 + ((lane & 7) + (lane >> 4) * 8) * 128 + ((((lane >> 3) & 1) ^ (lane & 7)) << 4);
        uint32_t wf[8][4];
        if (WO_AT < KV_TILES) {
#pragma unroll
            for (int s = 0; s < 2; s++) {
                constexpr int i0 = IDX_WO;
                const int idx = i0 + s;
                mbar_wait(bar_full + 8 * (idx % NST), (idx / NST) & 1);
                const uint32_t tb = sbase + SM_RING + (idx % NST) * TILE + aoff;
#pragma unroll
                for (int mt = 0; mt < 4; mt++) ldsm4t(tb ^ (mt << 5), wf[s * 4 + mt]);
            }
        }
        {
            const int hq = cta >> 2, kvh = hq >> 2, hh = hq & 3, ds = cta & 3;
            const int b = tid >> 7, dpl = (tid >> 3) & 15, j = tid & 7;
            const int pc = (b * 8 + kvh) * 8 + j;
            const uint2* po = &sc->part_o[pc][hh][ds * 16 + dpl];
            const uint2* pm = &sc->part_ml[pc - j][hh][0];
            uint2 vo, vm[8];
            for (int it = 0;; it++) {
                vo = ld_ll2(po);
#pragma unroll
                for (int jj = 0; jj < 8; jj++) vm[jj] = ld_ll2(pm + jj * 16);
                uint32_t all = vo.x & vo.y;
#pragma unroll
                for (int jj = 0; jj < 8; jj++) all &= vm[jj].x & vm[jj].y;
                if (__all_sync(0xffffffffu, (all & 3u) == F_PART) || it > SPIN_LIMIT) break;
            }
            float M = untag(vm[0].x);
#pragma unroll
            for (int jj = 1; jj < 8; jj++) M = fmaxf(M, untag(vm[jj].x));
            float wt = 0.f, L = 0.f;
#pragma unroll
            for (int jj = 0; jj < 8; jj++) {
                const float w_ = ex2((untag(vm[jj].x) - M) * LOG2E);
                L += w_ * untag(vm[jj].y);
                wt = jj == j ? w_ : wt;
            }
            float o0 = wt * untag(vo.x), o1 = wt * untag(vo.y);
#pragma unroll
            for (int o_ = 1; o_ < 8; o_ <<= 1) {
                o0 += __shfl_xor_sync(0xffffffffu, o0, o_);
                o1 += __shfl_xor_sync(0xffffffffu, o1, o_);
            }
            uint32_t* os = (uint32_t*)(sgen + SM_OS);
            const float rl = rcp_approx(L);
            if (j == 0) os[b * 16 + dpl] = pack_bf16(o0 * rl, o1 * rl);
            if (warp == 0) TSTAMP(15);
            if (WO_AT == KV_TILES) {
#pragma unroll
            for (int s = 0; s < 2; s++) {
                constexpr int i0 = IDX_WO;
                const int idx = i0 + s;
                mbar_wait(bar_full + 8 * (idx % NST), (idx / NST) & 1);
                const uint32_t tb = sbase + SM_RING + (idx % NST) * TILE + aoff;
#pragma unroll
                for (int mt = 0; mt < 4; mt++) ldsm4t(tb ^ (mt << 5), wf[s * 4 + mt]);
            }
            }
            cons_sync();
            if (tid == 0) mbar_arrive(bar_trig + 8 * 3);
            if (warp == 0) TSTAMP(7);
            float y[4][4] = {};
#pragma unroll
            for (int s = 0; s < 2; s++) {
                const uint32_t b0 = os[bb * 16 + 8 * s + t], b1 = os[bb * 16 + 8 * s + 4 + t];
#pragma unroll
                for (int mt = 0; mt < 4; mt++) mma16816(y[mt], wf[s * 4 + mt], b0, b1);
            }
            float v[4];
#pragma unroll
            for (int i = 0; i < 4; i++) v[i] = t == 0 ? y[0][i] : t == 1 ? y[1][i] : t == 2 ? y[2][i] : y[3][i];
            {
                const bool odd = g & 1;
                const float sx = odd ? v[0] : v[2], sy = odd ? v[1] : v[3];
                const float rx = __shfl_xor_sync(0xffffffffu, sx, 4), ry = __shfl_xor_sync(0xffffffffu, sy, 4);
                const int c0 = 64 * warp + 16 * t + (odd ? g + 7 : g);
                const float e0 = odd ? rx : v[0], e1 = odd ? ry : v[1], e2 = odd ? v[2] : rx, e3 = odd ? v[3] : ry;
                st_v4(&sc->inbox[c0 >> 2][cta][(c0 >> 1) & 1], tagf(e0, F_WO), tagf(e1, F_WO), tagf(e2, F_WO), tagf(e3, F_WO));
            }
        }
        if (tid == 0) mbar_arrive(bar_trig + 8 * 4);
        if (warp == 0) TSTAMP(8);
        float xm0 = 0.f, xm1 = 0.f;
        {
            float r0;
            {
                const uint4* pin = &sc->inbox[cta][0][0] + tid;
                uint4 v = make_uint4(F_WO, F_WO, F_WO, F_WO);
                spin_cycles(DELAY_B1);
                for (int it = 0;; it++) {
                    if (tid < NCTA * 2) v = ld_ll4(pin);
                    if (__all_sync(0xffffffffu, ((v.x & v.y & v.z & v.w & 3u) == F_WO) && (((v.x | v.y | v.z | v.w) & 3u) == F_WO)) || it > SPIN_LIMIT) break;
                }
                const bool u1 = lane & 2, u2 = lane & 4;
                const float a0 = untag(v.x), a1 = untag(v.y), a2 = untag(v.z), a3 = untag(v.w);
                const float k0 = (u1 ? a1 : a0) + __shfl_xor_sync(0xffffffffu, u1 ? a0 : a1, 2);
                const float k1 = (u1 ? a3 : a2) + __shfl_xor_sync(0xffffffffu, u1 ? a2 : a3, 2);
                r0 = (u2 ? k1 : k0) + __shfl_xor_sync(0xffffffffu, u2 ? k0 : k1, 4);
                r0 += __shfl_xor_sync(0xffffffffu, r0, 8);
                r0 += __shfl_xor_sync(0xffffffffu, r0, 16);
                if (lane < 8) red2[warp * 8 + (2 * (lane & 1) + ((lane >> 2) & 1)) * 2 + ((lane >> 1) & 1)] = r0;
            }
            cons_sync();
            if (tid == 32) mbar_arrive(bar_trig + 8 * 5);
            if (warp == 0) {
                float a0 = 0.f, a1 = 0.f;
#pragma unroll
                for (int w = 0; w < 8; w++) { const float2 v = *(const float2*)&red2[w * 8 + (lane & 3) * 2]; a0 += v.x; a1 += v.y; }
                const bool hi = ocol & 1;
                const float ga0 = hi ? bf_hi(m_ga0.x) : bf_lo(m_ga0.x), ga1 = hi ? bf_hi(m_ga1.x) : bf_lo(m_ga1.x);
                xm0 = bf16r(xo0 + bf16r(ga0 * bf16r(a0)));
                xm1 = bf16r(xo1 + bf16r(ga1 * bf16r(a1)));
                if (lane < 4) st_ll2(&sc->x1[cta][lane], pack_bf16(xm0, xm1), F_X1);
                TSTAMP(10);
            }
        }
        if (cta < NFFN) {
            const uint4* px = (const uint4*)&sc->x1[ec >> 2][0];
            const uint4* pp = (const uint4*)&sc->x1[0][0];
            uint4 va, vb, pa, pb;
            uint32_t gf[4][4], uf[4][4];
            if (GU_PIECES && IDX_WG >= kv_idx(KV_TILES - 1) + 2) {
                mbar_wait(bar_gu + 8 * (2 * (warp >> 1)), 0);
                mbar_wait(bar_gu + 8 * (2 * (warp >> 1) + 1), 0);
            } else {
                mbar_wait(bar_full + 8 * (IDX_WG % NST), (IDX_WG / NST) & 1);
                mbar_wait(bar_full + 8 * (IDX_WU % NST), (IDX_WU / NST) & 1);
            }
            {
                const uint32_t tg = sbase + SM_RING + (IDX_WG % NST) * TILE, tu = sbase + SM_RING + (IDX_WU % NST) * TILE;
#pragma unroll
                for (int s = 0; s < 4; s++) {
                    const int row = 64 * warp + 16 * s + (lane & 7) + (lane >> 4) * 8;
                    const uint32_t off = row * 32 + ((((lane >> 3) & 1) ^ ((row >> 2) & 1)) << 4);
                    ldsm4t(tg + off, gf[s]);
                    ldsm4t(tu + off, uf[s]);
                }
            }
            va = ld_ll4(px); vb = ld_ll4(px + 1); pa = ld_ll4(pp); pb = ld_ll4(pp + 1);
            const float c1v[4] = {bf16r(1.0f + bf_lo(m_cb.x)), bf16r(1.0f + bf_hi(m_cb.x)), bf16r(1.0f + bf_lo(m_cb.z)), bf16r(1.0f + bf_hi(m_cb.z))};
            float bg = 0.f, cgc = 0.f, bu = 0.f, cuc = 0.f;
            {
                uint32_t* pre = (uint32_t*)(sgen + SM_MRG) + warp * 128;
                float* bc = (float*)(sgen + SM_MRG + 4096);
                *(uint2*)&pre[eb * 32 + 2 * (lane & 15)] = make_uint2(pack_bf16(c1v[0], c1v[1]), pack_bf16(c1v[2], c1v[3]));
                *(uint2*)&pre[64 + eb * 32 + 2 * (lane & 15)] = make_uint2(m_sb.x, m_sb.z);
                __syncwarp();
                float yg[4] = {}, yu[4] = {};
                const uint32_t* pb = pre + ((g >> 1) & 1) * 64 + bb * 32 + t;
#pragma unroll
                for (int s = 0; s < 4; s++) {
                    const uint32_t b0 = pb[8 * s], b1 = pb[8 * s + 4];
                    mma16816(yg, gf[s], b0, b1);
                    mma16816(yu, uf[s], b0, b1);
                }
                const float y0 = t < 2 ? yg[0] : yu[0], y1 = t < 2 ? yg[1] : yu[1], y2 = t < 2 ? yg[2] : yu[2], y3 = t < 2 ? yg[3] : yu[3];
                float* dstp = bc + warp * 128 + (t >> 1) * 64 + (t & 1) * 32;
                *(float2*)&dstp[g * 2] = make_float2(y0, y1);
                *(float2*)&dstp[(g + 8) * 2] = make_float2(y2, y3);
                __syncwarp();
                if (lane == 0) mbar_arrive(bar_bc);
            }
            if (warp == 0) TSTAMP(11);
            float pivot2;
            {
                for (int it = 0;; it++) {
                    const bool ok = va.y == F_X1 && va.w == F_X1 && vb.y == F_X1 && vb.w == F_X1 &&
                                    pa.y == F_X1 && pa.w == F_X1 && pb.y == F_X1 && pb.w == F_X1;
                    if (__all_sync(0xffffffffu, ok) || it > SPIN_LIMIT) break;
                    va = ld_ll4(px); vb = ld_ll4(px + 1); pa = ld_ll4(pp); pb = ld_ll4(pp + 1);
                }
                if (warp == 0) TSTAMP(9);
                const float xv[4] = {eb ? bf_hi(va.x) : bf_lo(va.x), eb ? bf_hi(va.z) : bf_lo(va.z),
                                     eb ? bf_hi(vb.x) : bf_lo(vb.x), eb ? bf_hi(vb.z) : bf_lo(vb.z)};
                const float p0 = 0.25f * ((bf_lo(pa.x) + bf_lo(pa.z)) + (bf_lo(pb.x) + bf_lo(pb.z)));
                const float p1 = 0.25f * ((bf_hi(pa.x) + bf_hi(pa.z)) + (bf_hi(pb.x) + bf_hi(pb.z)));
                const float pivot = eb ? p1 : p0;
                pivot2 = (lane & 1) ? p1 : p0;
                *(uint2*)&hs[eb * 32 + 2 * (lane & 15)] =
                    make_uint2(pack_bf16((xv[0] - pivot) * c1v[0], (xv[1] - pivot) * c1v[1]),
                               pack_bf16((xv[2] - pivot) * c1v[2], (xv[3] - pivot) * c1v[3]));
                __syncwarp();
                float cg[2][4] = {}, cu[2][4] = {};
#pragma unroll
                for (int s = 0; s < 4; s++) {
                    const uint32_t b0 = hs[bb * 32 + 8 * s + t], b1 = hs[bb * 32 + 8 * s + 4 + t];
                    mma16816(cg[s & 1], gf[s], b0, b1);
                    mma16816(cu[s & 1], uf[s], b0, b1);
                }
                const float2 ps = half_warp_sums(xv, pivot);
                if ((lane & 15) == 0) stat[warp * 2 + eb] = ps;
                {
                    const float* bc = (const float*)(sgen + SM_MRG + 4096);
                    mbar_wait(bar_bc, 0);
#pragma unroll
                    for (int w = 0; w < 8; w++) {
                        bg += bc[w * 128 + lane]; cgc += bc[w * 128 + 32 + lane];
                        bu += bc[w * 128 + 64 + lane]; cuc += bc[w * 128 + 96 + lane];
                    }
                }
                if (t < 2) {
                    float v[4];
#pragma unroll
                    for (int i = 0; i < 4; i++) v[i] = t ? cu[0][i] + cu[1][i] : cg[0][i] + cg[1][i];
                    *(float2*)&red[warp * 64 + t * 32 + g * 2] = make_float2(v[0], v[1]);
                    *(float2*)&red[warp * 64 + t * 32 + (g + 8) * 2] = make_float2(v[2], v[3]);
                }
            }
            uint32_t df[4][4];
            mbar_wait(bar_full + 8 * (IDX_WD % NST), (IDX_WD / NST) & 1);
#pragma unroll
            for (int mt = 0; mt < 4; mt++) ldsm4t((sbase + SM_RING + (IDX_WD % NST) * TILE + aoff) ^ (mt << 5), df[mt]);
            cons_sync();
            {
                float gs = 0.f, us = 0.f;
#pragma unroll
                for (int w = 0; w < 8; w++) { gs += red[w * 64 + lane]; us += red[w * 64 + 32 + lane]; }
                float mean_bf, rstd;
                ln_stats(stat, lane & 1, pivot2, mean_bf, rstd);
                const float dm = mean_bf - pivot2;
                gs = bf16r(rstd * (gs - dm * bg) + cgc);
                us = rstd * (us - dm * bu) + cuc;
                const float u2 = gs * (1.0f + 0.044715f * gs * gs) * (2.0f * 0.7978845608028654f * LOG2E);
                const float ge = bf16r(__fdividef(gs, 1.0f + ex2(-u2)));
                const float act = bf16r(ge * bf16r(us));
                const float a0 = __shfl_sync(0xffffffffu, act, 4 * t + bb), a1 = __shfl_sync(0xffffffffu, act, 4 * t + 2 + bb);
                const float a2 = __shfl_sync(0xffffffffu, act, 4 * t + 16 + bb), a3 = __shfl_sync(0xffffffffu, act, 4 * t + 18 + bb);
                const uint32_t b0 = pack_bf16(a0, a1), b1 = pack_bf16(a2, a3);
                float y[4][4] = {};
#pragma unroll
                for (int mt = 0; mt < 4; mt++) mma16816(y[mt], df[mt], b0, b1);
                float v[4];
#pragma unroll
                for (int i = 0; i < 4; i++) v[i] = t == 0 ? y[0][i] : t == 1 ? y[1][i] : t == 2 ? y[2][i] : y[3][i];
            {
                const bool odd = g & 1;
                const float sx = odd ? v[0] : v[2], sy = odd ? v[1] : v[3];
                const float rx = __shfl_xor_sync(0xffffffffu, sx, 4), ry = __shfl_xor_sync(0xffffffffu, sy, 4);
                const int c0 = 64 * warp + 16 * t + (odd ? g + 7 : g);
                const float e0 = odd ? rx : v[0], e1 = odd ? ry : v[1], e2 = odd ? v[2] : rx, e3 = odd ? v[3] : ry;
                st_v4(&sc->inbox[c0 >> 2][cta][(c0 >> 1) & 1], tagf(e0, F_DOWN), tagf(e1, F_DOWN), tagf(e2, F_DOWN), tagf(e3, F_DOWN));
            }
            }
            if (warp == 0) TSTAMP(12);
        }
        {
            float r0;
            {
                const uint4* pin = &sc->inbox[cta][0][0] + tid;
                uint4 v = make_uint4(F_DOWN, F_DOWN, F_DOWN, F_DOWN);
                spin_cycles(DELAY_C);
                for (int it = 0;; it++) {
                    if (tid < NFFN * 2) v = ld_ll4(pin);
                    if (__all_sync(0xffffffffu, ((v.x & v.y & v.z & v.w & 3u) == F_DOWN) && (((v.x | v.y | v.z | v.w) & 3u) == F_DOWN)) || it > SPIN_LIMIT) break;
                }
                const bool u1 = lane & 2, u2 = lane & 4;
                const float a0 = untag(v.x), a1 = untag(v.y), a2 = untag(v.z), a3 = untag(v.w);
                const float k0 = (u1 ? a1 : a0) + __shfl_xor_sync(0xffffffffu, u1 ? a0 : a1, 2);
                const float k1 = (u1 ? a3 : a2) + __shfl_xor_sync(0xffffffffu, u1 ? a2 : a3, 2);
                r0 = (u2 ? k1 : k0) + __shfl_xor_sync(0xffffffffu, u2 ? k0 : k1, 4);
                r0 += __shfl_xor_sync(0xffffffffu, r0, 8);
                r0 += __shfl_xor_sync(0xffffffffu, r0, 16);
                if (lane < 8) red2[64 + warp * 8 + (2 * (lane & 1) + ((lane >> 2) & 1)) * 2 + ((lane >> 1) & 1)] = r0;
            }
            cons_sync();
            if (warp == 0) {
                float a0 = 0.f, a1 = 0.f;
#pragma unroll
                for (int w = 0; w < 8; w++) { const float2 v = *(const float2*)&red2[64 + w * 8 + (lane & 3) * 2]; a0 += v.x; a1 += v.y; }
                const bool hi = ocol & 1;
                const float gb0 = hi ? bf_hi(m_gb0.x) : bf_lo(m_gb0.x), gb1 = hi ? bf_hi(m_gb1.x) : bf_lo(m_gb1.x);
                if (lane < 4) {
                    p.out[ocol] = __float2bfloat16_rn(xm0 + bf16r(gb0 * bf16r(a0)));
                    p.out[D_MODEL + ocol] = __float2bfloat16_rn(xm1 + bf16r(gb1 * bf16r(a1)));
                }
                if (cta == 0 && lane == 0) *(volatile unsigned*)&sc->epoch = tag;
                TSTAMP(13);
            }
        }
    }
}

typedef CUresult (*EncodeFn)(CUtensorMap*, CUtensorMapDataType, cuuint32_t, void*, const cuuint64_t*, const cuuint64_t*,
                             const cuuint32_t*, const cuuint32_t*, CUtensorMapInterleave, CUtensorMapSwizzle,
                             CUtensorMapL2promotion, CUtensorMapFloatOOBfill);

struct Maps { CUtensorMap k, v, wq, wmod, wmod8, wo, wg, wu, wd; };

void encode(EncodeFn fn, CUtensorMap* m, const void* ptr, int rank, const cuuint64_t* dims, const cuuint64_t* strides,
            const cuuint32_t* box, CUtensorMapSwizzle sw) {
    const cuuint32_t es[3] = {1, 1, 1};
    fn(m, CU_TENSOR_MAP_DATA_TYPE_BFLOAT16, rank, const_cast<void*>(ptr), dims, strides, box, es,
       CU_TENSOR_MAP_INTERLEAVE_NONE, sw, CU_TENSOR_MAP_L2_PROMOTION_L2_256B, CU_TENSOR_MAP_FLOAT_OOB_FILL_NONE);
}

}

extern "C" void kernel_launch(void* const* d_in, const int* in_sizes, int n_in, void* d_out, int out_size) {
    (void)in_sizes; (void)n_in; (void)out_size;
    static EncodeFn enc = nullptr;
    static Scratch* scratch = nullptr;
    if (!enc) {
        cudaGetSymbolAddress((void**)&scratch, g_scratch);
        void* fn = nullptr;
        cudaDriverEntryPointQueryResult qr;
        cudaGetDriverEntryPoint("cuTensorMapEncodeTiled", &fn, cudaEnableDefault, &qr);
        enc = (EncodeFn)fn;
        cudaFuncSetAttribute(fused_block_kernel, cudaFuncAttributeMaxDynamicSharedMemorySize, SMEM_BYTES);
    }
    Maps m;
    {
        const cuuint64_t dims[3] = {64, (cuuint64_t)16 * SK, 2}, str[2] = {256, 128};
        const cuuint32_t box[3] = {64, 64, 2};
        encode(enc, &m.k, d_in[1], 3, dims, str, box, CU_TENSOR_MAP_SWIZZLE_128B);
        encode(enc, &m.v, d_in[2], 3, dims, str, box, CU_TENSOR_MAP_SWIZZLE_128B);
    }
    {
        const cuuint64_t dims[2] = {4096, 512}, str[1] = {8192};
        const cuuint32_t box[2] = {32, 256};
        encode(enc, &m.wq, d_in[3], 2, dims, str, box, CU_TENSOR_MAP_SWIZZLE_64B);
    }
    {
        const cuuint64_t dims[2] = {N_MOD, 512}, str[1] = {N_MOD * 2};
        const cuuint32_t box[2] = {16, 256};
        encode(enc, &m.wmod, d_in[10], 2, dims, str, box, CU_TENSOR_MAP_SWIZZLE_32B);
        const cuuint32_t box8[2] = {8, 256};
        encode(enc, &m.wmod8, d_in[10], 2, dims, str, box8, CU_TENSOR_MAP_SWIZZLE_NONE);
    }
    {
        const cuuint64_t dims_o[3] = {64, 4096, 8}, dims_d[3] = {64, D_FF, 8}, str[2] = {1024, 128};
        const cuuint32_t box[3] = {64, 16, 8};
        encode(enc, &m.wo, d_in[4], 3, dims_o, str, box, CU_TENSOR_MAP_SWIZZLE_128B);
        encode(enc, &m.wd, d_in[8], 3, dims_d, str, box, CU_TENSOR_MAP_SWIZZLE_128B);
    }
    {
        const cuuint64_t dims[2] = {D_FF, 512}, str[1] = {D_FF * 2};
        const cuuint32_t box[2] = {16, 128};
        encode(enc, &m.wg, d_in[6], 2, dims, str, box, CU_TENSOR_MAP_SWIZZLE_32B);
        encode(enc, &m.wu, d_in[7], 2, dims, str, box, CU_TENSOR_MAP_SWIZZLE_32B);
    }
    Params p;
    p.x = (const __nv_bfloat16*)d_in[0];
    p.c = (const __nv_bfloat16*)d_in[9];
    p.w_mod = (const __nv_bfloat16*)d_in[10];
    p.out = (__nv_bfloat16*)d_out;
    p.sc = scratch;
    p.wo = (const __nv_bfloat16*)d_in[4];
    p.wg = (const __nv_bfloat16*)d_in[6];
    p.wu = (const __nv_bfloat16*)d_in[7];
    p.wd = (const __nv_bfloat16*)d_in[8];
    fused_block_kernel<<<NCTA, NTHREADS, SMEM_BYTES, cudaStreamPerThread>>>(p, m.k, m.v, m.wq, m.wmod, m.wmod8, m.wo, m.wg, m.wu, m.wd);
}
```

```cpp
#include <cuda_runtime.h>
#include <cuda.h>
#include <cuda_bf16.h>
#include <stdint.h>

namespace {

constexpr int D_MODEL = 512;
constexpr int N_HEADS = 32;
constexpr int SK = 32768;
constexpr int DH = 128;
constexpr int D_FF = 1792;
constexpr int N_MOD = 6 * D_MODEL;

constexpr int NCTA = 128;
constexpr int NFFN = D_FF / 16;
constexpr int NTHREADS = 320;
constexpr int NST = 12;
constexpr int TILE = 16384;
#define INFL_PRO 3
#define INFL_MAIN 3
#define INFL_TAIL 2
#define PACE_HI 96
#define PACE_LO 96
#define END_TILES 0
#define END_WIN 5
#define PACE_HI2 100000
#define PACE_END 16
#define GRID_SLACK 0
#define PACE_SLEEP 200
#define TR_PF_WO -1
#define TR_PF_FF -1
#define TR_LD_WO 0
#define TR_LD_GU 0
#define GU_PIECES 1
#define GU_WIN 3
#define TR_LD_WD 0
#define PRO_TILES 8
constexpr int KV_TILES = 64;
#define MOD_AT 8
#define WO_AT 64
#define GU_AT 64
#define WD_AT 64
static_assert(MOD_AT % 2 == 0 && MOD_AT < WO_AT && MOD_AT < GU_AT && MOD_AT < WD_AT, "schedule");
static_assert(WO_AT <= KV_TILES && GU_AT <= KV_TILES && WD_AT <= KV_TILES, "schedule");
#define WQ_AT 0
constexpr int IDX_WQ = 2 * WQ_AT;
__host__ __device__ constexpr int kv_idx(int i) {
    return (i >= WQ_AT ? 2 : 0) + 2 * i + (i >= MOD_AT ? 1 : 0) + (i >= WO_AT ? 2 : 0) + (i >= GU_AT ? 2 : 0) + (i >= WD_AT ? 1 : 0);
}
constexpr int IDX_MOD = 2 + 2 * MOD_AT;
constexpr int IDX_WO = 3 + 2 * WO_AT + (GU_AT < WO_AT ? 2 : 0) + (WD_AT < WO_AT ? 1 : 0);
constexpr int IDX_WG = 3 + 2 * GU_AT + (WO_AT <= GU_AT ? 2 : 0) + (WD_AT < GU_AT ? 1 : 0);
constexpr int IDX_WU = IDX_WG + 1;
constexpr int IDX_WD = 3 + 2 * WD_AT + (WO_AT <= WD_AT ? 2 : 0) + (GU_AT <= WD_AT ? 2 : 0);
constexpr int N_TILES = 2 + 2 * KV_TILES + 1 + 2 + 3;
static_assert(N_TILES - 1 - IDX_WO < NST && N_TILES - 1 - IDX_WG < NST && N_TILES - 1 - IDX_WD < NST, "weights must stay resident until the end");
constexpr int SPIN_LIMIT = 1 << 20;

constexpr float LOG2E = 1.4426950408889634f;
constexpr float QK_SCALE = 0.08838834764831845f;

constexpr int SM_RING = 0;
constexpr int SM_MRG = SM_RING + NST * TILE;
constexpr int SM_ML = SM_MRG + 8 * 4 * 136 * 4;
constexpr int SM_RED = SM_ML + 8 * 4 * 8;
constexpr int SM_RED2 = SM_RED + 8 * 64 * 4;
constexpr int SM_QS = SM_RED2 + 8 * 64 * 4;
constexpr int SM_OS = SM_QS + 512 * 2;
constexpr int SM_SC = SM_OS + 2 * 16 * 4;
constexpr int SM_HS = SM_SC + 2 * 512 * 2;
constexpr int SM_STAT = SM_HS + 8 * 2 * 32 * 4;
constexpr int SM_PACE = SM_STAT + 8 * 2 * 8;
constexpr int SM_BAR = SM_PACE + 8;
constexpr int SM_END = SM_BAR + (2 * NST + 7 + 8 + 2) * 8;
constexpr int SMEM_BYTES = SM_END + 1024;

struct Scratch {
    uint4 inbox[NCTA][NCTA][2];
    uint2 x1[NCTA][16];
    uint2 part_o[NCTA][4][64];
    uint2 part_ml[NCTA][4][4];
    uint2 mod[2][N_MOD / 2];
    uint2 q[2][N_HEADS * DH / 2];
    unsigned epoch;
    unsigned pad_[31];
    unsigned cleared;
    unsigned pad2_[31];
    unsigned progress;
};
__device__ Scratch g_scratch;
constexpr uint32_t F_PART = 1, F_WO = 1, F_DOWN = 2, F_X1 = 1;
__device__ __forceinline__ uint32_t tagf(float v, uint32_t f) { return (__float_as_uint(v) & ~3u) | f; }
__device__ __forceinline__ float untag(uint32_t v) { return __uint_as_float(v & ~3u); }

struct Params {
    const __nv_bfloat16* x;
    const __nv_bfloat16* c;
    const __nv_bfloat16* w_mod;
    __nv_bfloat16* out;
    Scratch* sc;
    const __nv_bfloat16 *wo, *wg, *wu, *wd;
};

#define TSTAMP(i) do { } while (0)

__device__ __forceinline__ uint32_t smem_u32(const void* p) { return (uint32_t)__cvta_generic_to_shared(p); }

__device__ __forceinline__ void mbar_init(uint32_t bar, uint32_t cnt) {
    asm volatile("mbarrier.init.shared::cta.b64 [%0], %1;" ::"r"(bar), "r"(cnt) : "memory");
}
__device__ __forceinline__ void mbar_expect_tx(uint32_t bar, uint32_t bytes) {
    asm volatile("mbarrier.arrive.expect_tx.shared::cta.b64 _, [%0], %1;" ::"r"(bar), "r"(bytes) : "memory");
}
__device__ __forceinline__ void mbar_arrive(uint32_t bar) {
    asm volatile("mbarrier.arrive.shared::cta.b64 _, [%0];" ::"r"(bar) : "memory");
}
__device__ __forceinline__ bool mbar_try(uint32_t bar, uint32_t parity) {
    uint32_t ok;
    asm volatile(
        "{\n\t.reg .pred p;\n\t"
        "mbarrier.try_wait.parity.shared::cta.b64 p, [%1], %2;\n\t"
        "selp.u32 %0, 1, 0, p;\n\t}"
        : "=r"(ok) : "r"(bar), "r"(parity) : "memory");
    return ok != 0;
}
__device__ __forceinline__ void mbar_wait(uint32_t bar, uint32_t parity) {
    if (mbar_try(bar, parity)) return;
    for (int i = 0; i < SPIN_LIMIT; i++)
        if (mbar_try(bar, parity)) return;
}
__device__ __forceinline__ void cons_sync() { asm volatile("bar.sync 1, 256;" ::: "memory"); }

__device__ __forceinline__ void tma_2d(uint32_t dst, const CUtensorMap* m, int c0, int c1, uint32_t bar) {
    asm volatile("cp.async.bulk.tensor.2d.shared::cluster.global.mbarrier::complete_tx::bytes [%0], [%1, {%3, %4}], [%2];"
                 ::"r"(dst), "l"(m), "r"(bar), "r"(c0), "r"(c1) : "memory");
}
__device__ __forceinline__ void tma_3d(uint32_t dst, const CUtensorMap* m, int c0, int c1, int c2, uint32_t bar) {
    asm volatile("cp.async.bulk.tensor.3d.shared::cluster.global.mbarrier::complete_tx::bytes [%0], [%1, {%3, %4, %5}], [%2];"
                 ::"r"(dst), "l"(m), "r"(bar), "r"(c0), "r"(c1), "r"(c2) : "memory");
}
__device__ __forceinline__ void tma_3d_hint(uint32_t dst, const CUtensorMap* m, int c0, int c1, int c2, uint32_t bar, uint64_t pol) {
    asm volatile("cp.async.bulk.tensor.3d.shared::cluster.global.mbarrier::complete_tx::bytes.L2::cache_hint [%0], [%1, {%3, %4, %5}], [%2], %6;"
                 ::"r"(dst), "l"(m), "r"(bar), "r"(c0), "r"(c1), "r"(c2), "l"(pol) : "memory");
}
__device__ __forceinline__ void l2pf_2d(const CUtensorMap* m, int c0, int c1) {
    asm volatile("cp.async.bulk.prefetch.tensor.2d.L2.global.tile [%0, {%1, %2}];" ::"l"(m), "r"(c0), "r"(c1) : "memory");
}
__device__ __forceinline__ void l2pf_3d(const CUtensorMap* m, int c0, int c1, int c2) {
    asm volatile("cp.async.bulk.prefetch.tensor.3d.L2.global.tile [%0, {%1, %2, %3}];" ::"l"(m), "r"(c0), "r"(c1), "r"(c2) : "memory");
}
__device__ __forceinline__ void l2pf_1d(const void* ptr, uint32_t bytes) {
    asm volatile("cp.async.bulk.prefetch.L2.global [%0], %1;" ::"l"(ptr), "r"(bytes) : "memory");
}
__device__ __forceinline__ void prefetch_tmap(const CUtensorMap* m) {
    asm volatile("prefetch.tensormap [%0];" ::"l"(m) : "memory");
}

__device__ __forceinline__ void ldsm4(uint32_t addr, uint32_t (&r)[4]) {
    asm volatile("ldmatrix.sync.aligned.m8n8.x4.shared.b16 {%0,%1,%2,%3}, [%4];"
                 : "=r"(r[0]), "=r"(r[1]), "=r"(r[2]), "=r"(r[3]) : "r"(addr) : "memory");
}
__device__ __forceinline__ void ldsm4t(uint32_t addr, uint32_t (&r)[4]) {
    asm volatile("ldmatrix.sync.aligned.m8n8.x4.trans.shared.b16 {%0,%1,%2,%3}, [%4];"
                 : "=r"(r[0]), "=r"(r[1]), "=r"(r[2]), "=r"(r[3]) : "r"(addr) : "memory");
}
__device__ __forceinline__ void mma16816(float (&c)[4], const uint32_t (&a)[4], uint32_t b0, uint32_t b1) {
    asm volatile("mma.sync.aligned.m16n8k16.row.col.f32.bf16.bf16.f32 {%0,%1,%2,%3}, {%4,%5,%6,%7}, {%8,%9}, {%0,%1,%2,%3};"
                 : "+f"(c[0]), "+f"(c[1]), "+f"(c[2]), "+f"(c[3])
                 : "r"(a[0]), "r"(a[1]), "r"(a[2]), "r"(a[3]), "r"(b0), "r"(b1));
}
__device__ __forceinline__ uint32_t movmatrix_t(uint32_t a) {
    uint32_t d;
    asm volatile("movmatrix.sync.aligned.m8n8.trans.b16 %0, %1;" : "=r"(d) : "r"(a));
    return d;
}
__device__ __forceinline__ uint32_t pack_bf16(float a, float b) {
    uint32_t r;
    asm("cvt.rn.bf16x2.f32 %0, %1, %2;" : "=r"(r) : "f"(b), "f"(a));
    return r;
}
__device__ __forceinline__ float bf_lo(uint32_t v) { return __uint_as_float(v << 16); }
__device__ __forceinline__ float bf_hi(uint32_t v) { return __uint_as_float(v & 0xffff0000u); }
__device__ __forceinline__ float bf16r(float a) { return bf_lo(pack_bf16(a, 0.f)); }
__device__ __forceinline__ uint32_t max_bf16x2(uint32_t a, uint32_t b) {
    uint32_t r;
    asm("max.bf16x2 %0, %1, %2;" : "=r"(r) : "r"(a), "r"(b));
    return r;
}
__device__ __forceinline__ float ex2(float x) {
    float r;
    asm("ex2.approx.ftz.f32 %0, %1;" : "=f"(r) : "f"(x));
    return r;
}

__device__ __forceinline__ void st_ll2(uint2* p, uint32_t v, uint32_t tag) {
    asm volatile("st.relaxed.gpu.global.v2.u32 [%0], {%1, %2};" ::"l"(p), "r"(v), "r"(tag) : "memory");
}
__device__ __forceinline__ void st_ll4(uint4* p, uint32_t v0, uint32_t v1, uint32_t tag) {
    asm volatile("st.relaxed.gpu.global.v4.u32 [%0], {%1, %2, %3, %2};" ::"l"(p), "r"(v0), "r"(tag), "r"(v1) : "memory");
}
__device__ __forceinline__ void st_v4(uint4* p, uint32_t a, uint32_t b, uint32_t c, uint32_t d) {
    asm volatile("st.relaxed.gpu.global.v4.u32 [%0], {%1, %2, %3, %4};" ::"l"(p), "r"(a), "r"(b), "r"(c), "r"(d) : "memory");
}
__device__ __forceinline__ uint2 ld_ll2(const uint2* p) {
    uint2 v;
    asm volatile("ld.relaxed.gpu.global.v2.u32 {%0, %1}, [%2];" : "=r"(v.x), "=r"(v.y) : "l"(p) : "memory");
    return v;
}
__device__ __forceinline__ uint4 ld_ll4(const uint4* p) {
    uint4 v;
    asm volatile("ld.relaxed.gpu.global.v4.u32 {%0, %1, %2, %3}, [%4];"
                 : "=r"(v.x), "=r"(v.y), "=r"(v.z), "=r"(v.w) : "l"(p) : "memory");
    return v;
}

#define DELAY_B1 450
#define DELAY_B2 0
#define DELAY_C 450
__device__ __forceinline__ uint32_t clock32() {
    uint32_t c;
    asm volatile("mov.u32 %0, %clock;" : "=r"(c));
    return c;
}
__device__ __forceinline__ void spin_cycles(uint32_t n) {
    if (n > 0) { const uint32_t c0 = clock32(); while (clock32() - c0 < n) {} }
}
__device__ __forceinline__ float rcp_approx(float x) {
    float r;
    asm("rcp.approx.ftz.f32 %0, %1;" : "=f"(r) : "f"(x));
    return r;
}
__device__ __forceinline__ float sqrt_approx(float x) {
    float r;
    asm("sqrt.approx.f32 %0, %1;" : "=f"(r) : "f"(x));
    return r;
}

__device__ __forceinline__ float silu_bf(float v) { return bf16r(v / (1.0f + expf(-v))); }

__device__ __forceinline__ float2 half_warp_sums(const float (&v)[4], float pivot) {
    float s1 = 0.f, s2 = 0.f;
#pragma unroll
    for (int i = 0; i < 4; i++) { const float d = v[i] - pivot; s1 += d; s2 += d * d; }
#pragma unroll
    for (int o = 1; o < 16; o <<= 1) { s1 += __shfl_xor_sync(0xffffffffu, s1, o); s2 += __shfl_xor_sync(0xffffffffu, s2, o); }
    return make_float2(s1, s2);
}
__device__ __forceinline__ void ln_stats(const float2* stat, int b, float pivot, float& mean_bf, float& rstd) {
    float s1 = 0.f, s2 = 0.f;
#pragma unroll
    for (int w = 0; w < 8; w++) { const float2 v = stat[w * 2 + b]; s1 += v.x; s2 += v.y; }
    const float dm = s1 * (1.0f / D_MODEL);
    const float var = fmaxf(s2 * (1.0f / D_MODEL) - dm * dm, 0.f);
    mean_bf = bf16r(pivot + dm);
    rstd = rcp_approx(bf16r(sqrt_approx(bf16r(bf16r(var) + 1e-5f))));
}
__device__ __forceinline__ float ln_norm(float xv, float mean_bf, float rstd) { return bf16r(bf16r(xv - mean_bf) * rstd); }
__device__ __forceinline__ float ln_mod(float n, float cmul, float sadd) { return bf16r(n * bf16r(1.0f + cmul)) + sadd; }

__global__ void __launch_bounds__(NTHREADS, 1)
fused_block_kernel(const Params p, const __grid_constant__ CUtensorMap tm_k, const __grid_constant__ CUtensorMap tm_v,
                   const __grid_constant__ CUtensorMap tm_wq, const __grid_constant__ CUtensorMap tm_wmod,
                   const __grid_constant__ CUtensorMap tm_wmod8,
                   const __grid_constant__ CUtensorMap tm_wo, const __grid_constant__ CUtensorMap tm_wg,
                   const __grid_constant__ CUtensorMap tm_wu, const __grid_constant__ CUtensorMap tm_wd) {
    extern __shared__ unsigned char smem_raw[];
    const uint32_t sbase = (smem_u32(smem_raw) + 1023u) & ~1023u;
    unsigned char* sgen = smem_raw + (sbase - smem_u32(smem_raw));
    const int tid = threadIdx.x, warp = tid >> 5, lane = tid & 31;
    const int cta = blockIdx.x;
    const uint32_t bar_full = sbase + SM_BAR, bar_empty = bar_full + NST * 8;
    const uint32_t bar_clear = bar_empty + NST * 8;
    const uint32_t bar_gu = bar_clear + 7 * 8;
    const uint32_t bar_bc = bar_gu + 8 * 8;
    const uint32_t bar_p0w = bar_bc + 8;
    const uint32_t bar_trig = bar_clear;

    const int key0 = (cta >> 3) * SK + (cta & 7) * 64;
    uint64_t pol = 0;
    if (tid == 256) {
        asm volatile("createpolicy.fractional.L2::evict_first.b64 %0, 1.0;" : "=l"(pol));
        mbar_init(bar_p0w, 1);
#pragma unroll
        for (int i = 0; i < 4; i++) mbar_init(bar_full + 8 * i, 1);
        asm volatile("fence.mbarrier_init.release.cluster;" ::: "memory");
        mbar_expect_tx(bar_p0w, 8192);
        tma_2d(sbase + SM_MRG, &tm_wmod8, cta * 8, 0, bar_p0w);
        tma_2d(sbase + SM_MRG + 4096, &tm_wmod8, cta * 8, 256, bar_p0w);
#pragma unroll
        for (int i = 0; i < 4; i++) mbar_expect_tx(bar_full + 8 * i, TILE);
        tma_2d(sbase + SM_RING, &tm_wq, cta * 32, 0, bar_full);
        tma_2d(sbase + SM_RING + TILE, &tm_wq, cta * 32, 256, bar_full + 8);
        tma_3d_hint(sbase + SM_RING + 2 * TILE, &tm_k, 0, key0, 0, bar_full + 16, pol);
        tma_3d_hint(sbase + SM_RING + 3 * TILE, &tm_v, 0, key0, 0, bar_full + 24, pol);
    }
    static_assert(WQ_AT == 0 && MOD_AT >= 1, "the fast start assumes the sequence wq0 wq1 K0 V0");

    if (warp == 8) {
        if (lane == 0) {
            for (int i = 0; i < NST; i++) { if (i >= 4) mbar_init(bar_full + 8 * i, 1); mbar_init(bar_empty + 8 * i, 4); }
            mbar_init(bar_clear, 1);
            for (int k = 1; k <= 6; k++) mbar_init(bar_trig + 8 * k, 1);
            for (int k = 0; k < 8; k++) mbar_init(bar_gu + 8 * k, 1);
            mbar_init(bar_bc, 8);
            ((volatile uint32_t*)(sgen + SM_PACE))[0] = 0;
            ((volatile uint32_t*)(sgen + SM_PACE))[1] = INFL_MAIN;
            asm volatile("fence.mbarrier_init.release.cluster;" ::: "memory");
        }
        __syncwarp();
        asm volatile("bar.arrive 2, 320;" ::: "memory");
        asm volatile("bar.arrive 3, 64;" ::: "memory");
        if (lane == 0) {
            int slot = 4; uint32_t ph = 1;
            int landed = 0, wslot = 0; uint32_t wph = 0;
            int kv = 2;
            constexpr int N_STREAM = kv_idx(KV_TILES - 1) + 2;
            auto issue = [&](int idx) {
                const uint32_t fb = bar_full + 8 * (idx % NST), dst = sbase + SM_RING + (idx % NST) * TILE;
                if ((idx == IDX_WG || idx == IDX_WU || idx == IDX_WD) && cta >= NFFN) {
                    mbar_arrive(fb);
                    return;
                }
                mbar_expect_tx(fb, TILE);
                if (idx == IDX_WQ || idx == IDX_WQ + 1) {
                    tma_2d(dst, &tm_wq, cta * 32, (idx - IDX_WQ) * 256, fb);
                } else if (idx == IDX_MOD) {
                    tma_2d(dst, &tm_wmod, 1024 + cta * 16, 0, fb);
                    tma_2d(dst + 8192, &tm_wmod, 1024 + cta * 16, 256, fb);
                } else if (idx == IDX_WO || idx == IDX_WO + 1) {
                    tma_3d(dst, &tm_wo, 0, cta * 32 + (idx - IDX_WO) * 16, 0, fb);
                } else if (idx == IDX_WG || idx == IDX_WU) {
                    const CUtensorMap* m = idx == IDX_WG ? &tm_wg : &tm_wu;
#pragma unroll
                    for (int q = 0; q < 4; q++) tma_2d(dst + q * 4096, m, cta * 16, q * 128, fb);
                } else if (idx == IDX_WD) {
                    tma_3d(dst, &tm_wd, 0, cta * 16, 0, fb);
                } else {
                    tma_3d_hint(dst, (kv & 1) ? &tm_v : &tm_k, 0, key0 + (kv >> 1) * 512, 0, fb, pol);
                    kv++;
                }
            };
            auto wait_window = [&](int idx, int window) {
                while (landed + window <= idx) {
                    mbar_wait(bar_full + 8 * wslot, wph);
                    if (++wslot == NST) { wslot = 0; wph ^= 1; }
                    landed++;
                }
            };
            prefetch_tmap(&tm_wmod);
            ((volatile uint32_t*)(sgen + SM_PACE))[0] = 4;
            for (int idx = 4; idx < N_STREAM; idx++) {
                if (idx >= NST) mbar_wait(bar_empty + 8 * slot, ph);
                wait_window(idx, idx < PRO_TILES ? INFL_PRO : idx >= N_STREAM - END_TILES ? END_WIN
                                                            : (int)((volatile uint32_t*)(sgen + SM_PACE))[1]);
                if (idx == 12) { prefetch_tmap(&tm_wo); prefetch_tmap(&tm_wg); prefetch_tmap(&tm_wu); prefetch_tmap(&tm_wd); }
                issue(idx);
                ((volatile uint32_t*)(sgen + SM_PACE))[0] = idx + 1;
                if (++slot == NST) { slot = 0; ph ^= 1; }
            }
            auto deferred = [&](int idx, bool windowed) {
                if (idx < N_STREAM) return;
                mbar_wait(bar_empty + 8 * (idx % NST), ((idx / NST) & 1) ^ 1);
                if (windowed) wait_window(idx, INFL_TAIL);
                issue(idx);
            };
#pragma unroll
            for (int kk = 0; kk <= 6; kk++) {
                const int k = kk == 0 ? 0 : kk == 1 ? 6 : kk - 1;
                if (TR_PF_WO != k && TR_PF_FF != k && TR_LD_WO != k && TR_LD_GU != k && TR_LD_WD != k) continue;
                if (k > 0) mbar_wait(bar_trig + 8 * k, 0);
                if (TR_PF_WO == k) l2pf_1d((const char*)p.wo + (size_t)cta * 32768, 32768);
                if (TR_PF_FF == k && cta < NFFN) {
                    l2pf_1d((const char*)p.wg + (size_t)cta * 16384, 16384);
                    l2pf_1d((const char*)p.wu + (size_t)cta * 16384, 16384);
                    l2pf_1d((const char*)p.wd + (size_t)cta * 16384, 16384);
                }
                if (TR_LD_WO == k) { deferred(IDX_WO, k == 0 || k == 6); deferred(IDX_WO + 1, k == 0 || k == 6); }
                if (TR_LD_GU == k) {
                    if (!GU_PIECES) { deferred(IDX_WG, k == 0 || k == 6); deferred(IDX_WU, k == 0 || k == 6); }
                    else if (cta < NFFN) {
                        mbar_wait(bar_empty + 8 * (IDX_WG % NST), ((IDX_WG / NST) & 1) ^ 1);
                        mbar_wait(bar_empty + 8 * (IDX_WU % NST), ((IDX_WU / NST) & 1) ^ 1);
                        if (IDX_WO >= N_STREAM && TR_LD_WO <= k) {
                            mbar_wait(bar_full + 8 * (IDX_WO % NST), (IDX_WO / NST) & 1);
                            mbar_wait(bar_full + 8 * ((IDX_WO + 1) % NST), ((IDX_WO + 1) / NST) & 1);
                        }
#pragma unroll
                        for (int st = 0; st < 8; st++) {
                            if (st >= GU_WIN) mbar_wait(bar_gu + 8 * (st - GU_WIN), 0);
                            const uint32_t dst = sbase + SM_RING + (((st & 1) ? IDX_WU : IDX_WG) % NST) * TILE + (st >> 1) * 4096;
                            mbar_expect_tx(bar_gu + 8 * st, 4096);
                            tma_2d(dst, (st & 1) ? &tm_wu : &tm_wg, cta * 16, (st >> 1) * 128, bar_gu + 8 * st);
                        }
                        mbar_wait(bar_gu + 8 * 7, 0);
                    }
                }
                if (TR_LD_WD == k) deferred(IDX_WD, !GU_PIECES && (k == 0 || k == 6));
            }
        }
    } else if (warp == 9) {
        Scratch* const sc = p.sc;
        const uint32_t tag = *(volatile unsigned*)&sc->epoch + 1;
        if (lane < 2) {
            st_ll4((uint4*)&sc->mod[lane][cta * 4], 0u, 0u, 0u);
            st_ll4((uint4*)&sc->mod[lane][cta * 4] + 1, 0u, 0u, 0u);
        }
        if (lane < 8) st_ll4((uint4*)&sc->mod[lane >> 2][512 + cta * 8] + (lane & 3), 0u, 0u, 0u);
        if (lane < 16) st_ll4((uint4*)&sc->q[lane >> 3][cta * 16] + (lane & 7), 0u, 0u, 0u);
        __syncwarp();
        asm volatile("bar.arrive 2, 320;" ::: "memory");
        asm volatile("bar.sync 3, 64;" ::: "memory");
#pragma unroll 4
        for (int i = 0; i < 8; i++) st_v4(&sc->inbox[cta][0][0] + i * 32 + lane, 0u, 0u, 0u, 0u);
#pragma unroll 4
        for (int i = 0; i < 4; i++) st_v4((uint4*)&sc->part_o[cta][0][0] + i * 32 + lane, 0u, 0u, 0u, 0u);
        if (lane < 8) st_v4((uint4*)&sc->part_ml[cta][0][0] + lane, 0u, 0u, 0u, 0u);
        if (lane < 2) st_v4((uint4*)&sc->x1[cta][0] + lane, 0u, 0u, 0u, 0u);
        if (cta == 0 && lane == 0) asm volatile("st.relaxed.gpu.global.u32 [%0], %1;" ::"l"(&sc->progress), "r"(0u) : "memory");
        asm volatile("fence.acq_rel.gpu;" ::: "memory");
        __syncwarp();
        if (lane == 0) {
            asm volatile("fence.acq_rel.gpu;" ::: "memory");
            asm volatile("red.relaxed.gpu.global.add.u32 [%0], %1;" ::"l"(&sc->cleared), "r"(1u) : "memory");
            const uint32_t target = tag * NCTA;
            for (int it = 0; it < SPIN_LIMIT; it++) {
                uint32_t v;
                asm volatile("ld.relaxed.gpu.global.u32 %0, [%1];" : "=r"(v) : "l"(&sc->cleared) : "memory");
                if ((int32_t)(v - target) >= 0) break;
                __nanosleep(500);
            }
            asm volatile("fence.acq_rel.gpu;" ::: "memory");
            mbar_arrive(bar_clear);
            volatile uint32_t* pace = (volatile uint32_t*)(sgen + SM_PACE);
            constexpr uint32_t N_STREAM = kv_idx(KV_TILES - 1) + 2;
            uint32_t posted = 0;
            for (int it = 0; it < SPIN_LIMIT; it++) {
                const uint32_t own = pace[0];
                if (own > posted) {
                    asm volatile("red.relaxed.gpu.global.add.u32 [%0], %1;" ::"l"(&sc->progress), "r"(own - posted) : "memory");
                    posted = own;
                }
                uint32_t v;
                asm volatile("ld.relaxed.gpu.global.u32 %0, [%1];" : "=r"(v) : "l"(&sc->progress) : "memory");
                if (own >= N_STREAM) {
                    if (v + GRID_SLACK >= NCTA * N_STREAM) break;
                } else {
                    const int diff = (int)v - (int)own * NCTA;
                    pace[1] = diff > PACE_HI2 && own + PACE_END >= N_STREAM ? INFL_MAIN + 2
                            : diff > PACE_HI ? INFL_MAIN + 1 : diff < -PACE_LO ? INFL_MAIN - 1 : INFL_MAIN;
                }
                __nanosleep(own + 4 >= N_STREAM ? 50 : PACE_SLEEP);
            }
            mbar_arrive(bar_trig + 8 * 6);
        }
    } else {
        const int g = lane >> 2, t = lane & 3;
        const int bb = g & 1;
        const int eb = lane >> 4;
        const int ec = 64 * warp + 4 * (lane & 15);
        if (warp == 0) TSTAMP(0);
        Scratch* const sc = p.sc;
        const float c00 = __bfloat162float(p.c[tid]), c01 = __bfloat162float(p.c[tid + 256]);
        const float c10 = __bfloat162float(p.c[D_MODEL + tid]), c11 = __bfloat162float(p.c[D_MODEL + tid + 256]);
        const uint2 xe = __ldg((const uint2*)(p.x + eb * D_MODEL + ec));
        const float xpivot = __bfloat162float(p.x[eb * D_MODEL]);
        const uint32_t tag = *(volatile unsigned*)&sc->epoch + 1;
        const int ocol = cta * 4 + (lane & 3);
        const float xo0 = __bfloat162float(p.x[ocol]), xo1 = __bfloat162float(p.x[D_MODEL + ocol]);

        float* red = (float*)(sgen + SM_RED);
        float* red2 = (float*)(sgen + SM_RED2);
        float2* stat = (float2*)(sgen + SM_STAT);
        uint32_t* hs = (uint32_t*)(sgen + SM_HS) + warp * 64;
        float xn[4];
        {
            float xv[4] = {bf_lo(xe.x), bf_hi(xe.x), bf_lo(xe.y), bf_hi(xe.y)};
            const float2 ps = half_warp_sums(xv, xpivot);
            if ((lane & 15) == 0) stat[warp * 2 + eb] = ps;
            const float s00 = silu_bf(c00), s01 = silu_bf(c01), s10 = silu_bf(c10), s11 = silu_bf(c11);
            __nv_bfloat16* scs = (__nv_bfloat16*)(sgen + SM_SC);
            scs[tid] = __float2bfloat16_rn(s00); scs[tid + 256] = __float2bfloat16_rn(s01);
            scs[512 + tid] = __float2bfloat16_rn(s10); scs[512 + tid + 256] = __float2bfloat16_rn(s11);
            asm volatile("bar.sync 2, 320;" ::: "memory");
            if (warp == 0) TSTAMP(23);
            float cp[4] = {0.f, 0.f, 0.f, 0.f};
            const uint32_t* sc32 = (const uint32_t*)(sgen + SM_SC) + bb * 256 + 32 * warp + t;
            mbar_wait(bar_p0w, 0);
#pragma unroll
            for (int s = 0; s < 4; s++) {
                uint32_t r0, r1;
                asm volatile("ldmatrix.sync.aligned.m8n8.x2.trans.shared.b16 {%0,%1}, [%2];"
                             : "=r"(r0), "=r"(r1) : "r"(sbase + SM_MRG + (64 * warp + 16 * s + (lane & 15)) * 16) : "memory");
                const uint32_t a[4] = {r0, r0, r1, r1};
                mma16816(cp, a, sc32[8 * s], sc32[8 * s + 4]);
            }
            if (t == 0) { red[warp * 16 + g] = cp[0]; red[warp * 16 + 8 + g] = cp[1]; }
            if (warp == 0) TSTAMP(14);
            cons_sync();
            if (warp == 0) {
                float s = 0.f;
#pragma unroll
                for (int w = 0; w < 8; w++) s += red[w * 16 + (lane & 15)];
                const float nx = __shfl_down_sync(0xffffffffu, s, 1);
                if (lane < 16 && !(lane & 1))
                    st_ll2(&sc->mod[lane >> 3][cta * 4 + ((lane & 7) >> 1)], pack_bf16(s, nx), tag);
                TSTAMP(1);
            }
            float mean_bf, rstd;
            ln_stats(stat, eb, xpivot, mean_bf, rstd);
#pragma unroll
            for (int i = 0; i < 4; i++) xn[i] = ln_norm(xv[i], mean_bf, rstd);
        }
        {
            uint4 sa, ca;
            for (int it = 0;; it++) {
                sa = ld_ll4((const uint4*)&sc->mod[eb][ec >> 1]);
                ca = ld_ll4((const uint4*)&sc->mod[eb][256 + (ec >> 1)]);
                const bool ok = sa.y == tag && sa.w == tag && ca.y == tag && ca.w == tag;
                if (__all_sync(0xffffffffu, ok) || it > SPIN_LIMIT) break;
            }
            *(uint2*)&hs[eb * 32 + 2 * (lane & 15)] =
                make_uint2(pack_bf16(ln_mod(xn[0], bf_lo(ca.x), bf_lo(sa.x)), ln_mod(xn[1], bf_hi(ca.x), bf_hi(sa.x))),
                           pack_bf16(ln_mod(xn[2], bf_lo(ca.z), bf_lo(sa.z)), ln_mod(xn[3], bf_hi(ca.z), bf_hi(sa.z))));
            __syncwarp();
            uint32_t hb[8];
#pragma unroll
            for (int i = 0; i < 8; i++) hb[i] = hs[bb * 32 + 8 * (i >> 1) + 4 * (i & 1) + t];
            if (warp == 0) TSTAMP(2);
            float cq[2][4] = {};
            const int ts = warp >> 2;
            mbar_wait(bar_full + 8 * (IDX_WQ + ts), 0);
            const uint32_t tb = sbase + SM_RING + (IDX_WQ + ts) * TILE;
#pragma unroll
            for (int s = 0; s < 4; s++) {
                const int row = 64 * (warp & 3) + 16 * s + (lane & 7) + (lane >> 4) * 8;
#pragma unroll
                for (int mt = 0; mt < 2; mt++) {
                    const int ch = 2 * mt + ((lane >> 3) & 1);
                    uint32_t a[4];
                    ldsm4t(tb + row * 64 + ((ch ^ ((row >> 1) & 3)) << 4), a);
                    mma16816(cq[mt], a, hb[2 * s], hb[2 * s + 1]);
                }
            }
            if (t < 2) {
                const float v0 = t == 0 ? cq[0][0] : cq[1][0], v1 = t == 0 ? cq[0][1] : cq[1][1];
                const float v2 = t == 0 ? cq[0][2] : cq[1][2], v3 = t == 0 ? cq[0][3] : cq[1][3];
                *(float2*)&red2[warp * 64 + (16 * t + g) * 2] = make_float2(v0, v1);
                *(float2*)&red2[warp * 64 + (16 * t + g + 8) * 2] = make_float2(v2, v3);
            }
            cons_sync();
            if (warp < 4 && lane == 0) { mbar_arrive(bar_empty + 8 * IDX_WQ); mbar_arrive(bar_empty + 8 * IDX_WQ + 8); }
            if (warp == 0) {
                const int b = lane >> 4, cp = lane & 15;
                float q0 = 0.f, q1 = 0.f;
#pragma unroll
                for (int w = 0; w < 8; w++) {
                    const float4 v = *(const float4*)&red2[w * 64 + cp * 4];
                    q0 += b ? v.y : v.x; q1 += b ? v.w : v.z;
                }
                st_ll2(&sc->q[b][cta * 16 + cp], pack_bf16(q0, q1), tag);
                TSTAMP(3);
            }
        }
        const int pair = cta >> 3;
        uint32_t qf[16];
        {
            uint2* qs = (uint2*)(sgen + SM_QS);
            if (tid < 128) {
                const uint4* src = (const uint4*)&sc->q[pair >> 3][(pair & 7) * 256] + tid;
                uint4 v;
                for (int it = 0;; it++) {
                    v = ld_ll4(src);
                    if ((v.y == tag && v.w == tag) || it > SPIN_LIMIT) break;
                }
                qs[tid] = make_uint2(v.x, v.z);
            }
            cons_sync();
            const uint32_t* q32 = (const uint32_t*)(sgen + SM_QS);
#pragma unroll
            for (int s = 0; s < 8; s++) {
                qf[2 * s] = q32[(g & 3) * 64 + 8 * s + t];
                qf[2 * s + 1] = q32[(g & 3) * 64 + 8 * s + 4 + t];
            }
        }
        if (warp == 0) TSTAMP(4);

        float o[8][4];
#pragma unroll
        for (int i = 0; i < 8; i++) { o[i][0] = o[i][1] = o[i][2] = o[i][3] = 0.f; }
        uint32_t mrun = 0xff80ff80u;
        float ls[4] = {0.f, 0.f, 0.f, 0.f};
        uint4 m_sb, m_cb; uint2 m_ga0, m_ga1, m_gb0, m_gb1;
        {
            const int grp = warp >> 2, wi = warp & 3;
            const int krow = 16 * wi + (lane & 7) + ((lane >> 3) & 1) * 8;
            const uint32_t koff = krow * 128 + ((((lane >> 4) & 1) ^ (lane & 7)) << 4);
            const int vrow = 16 * wi + (lane & 7) + (lane >> 4) * 8;
            const uint32_t voff = vrow * 128 + ((((lane >> 3) & 1) ^ (lane & 7)) << 4);
            const uint32_t ones[4] = {0x3f803f80u, 0x3f803f80u, 0x3f803f80u, 0x3f803f80u};
            for (int i = grp; i < KV_TILES; i += 2) {
                if (i == MOD_AT + grp) {
                    float cm[4] = {};
                    const uint32_t* sc32 = (const uint32_t*)(sgen + SM_SC) + bb * 256 + 32 * warp + t;
                    mbar_wait(bar_full + 8 * (IDX_MOD % NST), (IDX_MOD / NST) & 1);
                    const uint32_t tb = sbase + SM_RING + (IDX_MOD % NST) * TILE;
#pragma unroll
                    for (int s = 0; s < 4; s++) {
                        const int row = 64 * warp + 16 * s + (lane & 7) + (lane >> 4) * 8;
                        const int ch = (lane >> 3) & 1;
                        uint32_t a[4];
                        ldsm4t(tb + row * 32 + ((ch ^ ((row >> 2) & 1)) << 4), a);
                        mma16816(cm, a, sc32[8 * s], sc32[8 * s + 4]);
                    }
                    if (t == 0) {
                        *(float2*)&red[warp * 64 + g * 2] = make_float2(cm[0], cm[1]);
                        *(float2*)&red[warp * 64 + (g + 8) * 2] = make_float2(cm[2], cm[3]);
                    }
                    cons_sync();
                    if (warp < 4 && lane == 0) mbar_arrive(bar_empty + 8 * (IDX_MOD % NST));
                    if (warp == 1 && lane < 16) {
                        const int b = lane >> 3, cp = lane & 7;
                        float q0 = 0.f, q1 = 0.f;
#pragma unroll
                        for (int w = 0; w < 8; w++) {
                            const float4 v = *(const float4*)&red[w * 64 + cp * 4];
                            q0 += b ? v.y : v.x; q1 += b ? v.w : v.z;
                        }
                        st_ll2(&sc->mod[b][512 + cta * 8 + cp], pack_bf16(q0, q1), tag);
                    }
                }
                if (i == 56 + grp) {
                    m_sb = ld_ll4((const uint4*)&sc->mod[eb][768 + (ec >> 1)]);
                    m_cb = ld_ll4((const uint4*)&sc->mod[eb][1024 + (ec >> 1)]);
                    m_ga0 = ld_ll2(&sc->mod[0][512 + (ocol >> 1)]); m_ga1 = ld_ll2(&sc->mod[1][512 + (ocol >> 1)]);
                    m_gb0 = ld_ll2(&sc->mod[0][1280 + (ocol >> 1)]); m_gb1 = ld_ll2(&sc->mod[1][1280 + (ocol >> 1)]);
                }
                if (i == 60 + grp) {
                    for (int it = 0;; it++) {
                        const bool ok = m_sb.y == tag && m_sb.w == tag && m_cb.y == tag && m_cb.w == tag &&
                                        m_ga0.y == tag && m_ga1.y == tag && m_gb0.y == tag && m_gb1.y == tag;
                        if (__all_sync(0xffffffffu, ok) || it > SPIN_LIMIT) break;
                        m_sb = ld_ll4((const uint4*)&sc->mod[eb][768 + (ec >> 1)]);
                        m_cb = ld_ll4((const uint4*)&sc->mod[eb][1024 + (ec >> 1)]);
                        m_ga0 = ld_ll2(&sc->mod[0][512 + (ocol >> 1)]); m_ga1 = ld_ll2(&sc->mod[1][512 + (ocol >> 1)]);
                        m_gb0 = ld_ll2(&sc->mod[0][1280 + (ocol >> 1)]); m_gb1 = ld_ll2(&sc->mod[1][1280 + (ocol >> 1)]);
                    }
                    mbar_wait(bar_clear, 0);
                }
                const int ki = kv_idx(i), ks = ki % NST, vs = (ki + 1) % NST;
                const uint32_t kph = (ki / NST) & 1, vph = ((ki + 1) / NST) & 1;
                mbar_wait(bar_full + 8 * ks, kph);
                const uint32_t kb = sbase + SM_RING + ks * TILE + koff;
                float sa[4] = {0.f, 0.f, 0.f, 0.f}, sb[4] = {0.f, 0.f, 0.f, 0.f};
#pragma unroll
                for (int s = 0; s < 8; s += 2) {
                    uint32_t a0[4], a1[4];
                    ldsm4((kb ^ ((s & 3) << 5)) + (s >> 2) * 8192, a0);
                    ldsm4((kb ^ (((s + 1) & 3) << 5)) + (s >> 2) * 8192, a1);
                    mma16816(sa, a0, qf[2 * s], qf[2 * s + 1]);
                    mma16816(sb, a1, qf[2 * s + 2], qf[2 * s + 3]);
                }
                __syncwarp();
                if (lane == 0) mbar_arrive(bar_empty + 8 * ks);
                uint32_t r01 = pack_bf16(sa[0] + sb[0], sa[1] + sb[1]);
                uint32_t r23 = pack_bf16(sa[2] + sb[2], sa[3] + sb[3]);
                r01 = pack_bf16(bf_lo(r01) * QK_SCALE, bf_hi(r01) * QK_SCALE);
                r23 = pack_bf16(bf_lo(r23) * QK_SCALE, bf_hi(r23) * QK_SCALE);
                uint32_t mx = max_bf16x2(r01, r23);
                mx = max_bf16x2(mx, __shfl_xor_sync(0xffffffffu, mx, 4));
                mx = max_bf16x2(mx, __shfl_xor_sync(0xffffffffu, mx, 8));
                mx = max_bf16x2(mx, __shfl_xor_sync(0xffffffffu, mx, 16));
                const uint32_t mnew = max_bf16x2(mrun, mx);
                const float m0 = bf_lo(mnew), m1 = bf_hi(mnew);
                if (__any_sync(0xffffffffu, mnew != mrun)) {
                    const float al0 = ex2((bf_lo(mrun) - m0) * LOG2E), al1 = ex2((bf_hi(mrun) - m1) * LOG2E);
                    ls[0] *= al0; ls[1] *= al1;
#pragma unroll
                    for (int d = 0; d < 8; d++) { o[d][0] *= al0; o[d][1] *= al1; o[d][2] *= al0; o[d][3] *= al1; }
                    mrun = mnew;
                }
                const float p0 = ex2((bf_lo(r01) - m0) * LOG2E), p1 = ex2((bf_hi(r01) - m1) * LOG2E);
                const float p2 = ex2((bf_lo(r23) - m0) * LOG2E), p3 = ex2((bf_hi(r23) - m1) * LOG2E);
                const uint32_t pb0 = movmatrix_t(pack_bf16(p0, p1)), pb1 = movmatrix_t(pack_bf16(p2, p3));
                mma16816(ls, ones, pb0, pb1);
                mbar_wait(bar_full + 8 * vs, vph);
                const uint32_t vb = sbase + SM_RING + vs * TILE + voff;
#pragma unroll
                for (int d = 0; d < 8; d++) {
                    uint32_t a[4];
                    ldsm4t((vb ^ ((d & 3) << 5)) + (d >> 2) * 8192, a);
                    mma16816(o[d], a, pb0, pb1);
                }
                __syncwarp();
                if (lane == 0) mbar_arrive(bar_empty + 8 * vs);
            }
        }
        if (warp == 7) TSTAMP(5);
        if (warp == 7 && lane == 0) mbar_arrive(bar_trig + 8 * 1);
        {
            float* mrg = (float*)(sgen + SM_MRG);
            float2* ml = (float2*)(sgen + SM_ML);
            {
                const int hp = (t & 1) * 2, up = t >> 1;
                if (g == 0 && up == 0) { ml[warp * 4 + hp] = make_float2(bf_lo(mrun), ls[0]); ml[warp * 4 + hp + 1] = make_float2(bf_hi(mrun), ls[1]); }
                float* m0p = mrg + (warp * 4 + hp) * 136 + up * 72 + g;
#pragma unroll
                for (int d = 0; d < 4; d++) {
                    m0p[16 * d] = up ? o[d + 4][0] : o[d][0]; m0p[136 + 16 * d] = up ? o[d + 4][1] : o[d][1];
                    m0p[16 * d + 8] = up ? o[d + 4][2] : o[d][2]; m0p[136 + 16 * d + 8] = up ? o[d + 4][3] : o[d][3];
                }
            }
            cons_sync();
            const int hh = tid >> 6, dp = tid & 63;
            float2 mw[8];
            float M = -INFINITY;
#pragma unroll
            for (int w = 0; w < 8; w++) { mw[w] = ml[w * 4 + hh]; M = fmaxf(M, mw[w].x); }
            float L = 0.f, o0 = 0.f, o1 = 0.f;
#pragma unroll
            for (int w = 0; w < 8; w++) {
                const float wt = ex2((mw[w].x - M) * LOG2E);
                const float2 v = *(const float2*)&mrg[(w * 4 + hh) * 136 + 2 * dp + (dp >= 32 ? 8 : 0)];
                L += wt * mw[w].y; o0 += wt * v.x; o1 += wt * v.y;
            }
            st_ll2(&sc->part_o[cta][hh][dp], tagf(o0, F_PART), tagf(o1, F_PART));
            if (dp < 4) st_ll2(&sc->part_ml[cta][hh][dp], tagf(M, F_PART), tagf(L, F_PART));
        }
        if (tid == 0) mbar_arrive(bar_trig + 8 * 2);
        if (warp == 0) TSTAMP(6);
        const uint32_t aoff = warp * 2048 + ((lane & 7) + (lane >> 4) * 8) * 128 + ((((lane >> 3) & 1) ^ (lane & 7)) << 4);
        uint32_t wf[8][4];
        if (WO_AT < KV_TILES) {
#pragma unroll
            for (int s = 0; s < 2; s++) {
                constexpr int i0 = IDX_WO;
                const int idx = i0 + s;
                mbar_wait(bar_full + 8 * (idx % NST), (idx / NST) & 1);
                const uint32_t tb = sbase + SM_RING + (idx % NST) * TILE + aoff;
#pragma unroll
                for (int mt = 0; mt < 4; mt++) ldsm4t(tb ^ (mt << 5), wf[s * 4 + mt]);
            }
        }
        {
            const int hq = cta >> 2, kvh = hq >> 2, hh = hq & 3, ds = cta & 3;
            const int b = tid >> 7, dpl = (tid >> 3) & 15, j = tid & 7;
            const int pc = (b * 8 + kvh) * 8 + j;
            const uint2* po = &sc->part_o[pc][hh][ds * 16 + dpl];
            const uint2* pm = &sc->part_ml[pc - j][hh][0];
            uint2 vo, vm[8];
            for (int it = 0;; it++) {
                vo = ld_ll2(po);
#pragma unroll
                for (int jj = 0; jj < 8; jj++) vm[jj] = ld_ll2(pm + jj * 16);
                uint32_t all = vo.x & vo.y;
#pragma unroll
                for (int jj = 0; jj < 8; jj++) all &= vm[jj].x & vm[jj].y;
                if (__all_sync(0xffffffffu, (all & 3u) == F_PART) || it > SPIN_LIMIT) break;
            }
            float M = untag(vm[0].x);
#pragma unroll
            for (int jj = 1; jj < 8; jj++) M = fmaxf(M, untag(vm[jj].x));
            float wt = 0.f, L = 0.f;
#pragma unroll
            for (int jj = 0; jj < 8; jj++) {
                const float w_ = ex2((untag(vm[jj].x) - M) * LOG2E);
                L += w_ * untag(vm[jj].y);
                wt = jj == j ? w_ : wt;
            }
            float o0 = wt * untag(vo.x), o1 = wt * untag(vo.y);
#pragma unroll
            for (int o_ = 1; o_ < 8; o_ <<= 1) {
                o0 += __shfl_xor_sync(0xffffffffu, o0, o_);
                o1 += __shfl_xor_sync(0xffffffffu, o1, o_);
            }
            uint32_t* os = (uint32_t*)(sgen + SM_OS);
            const float rl = rcp_approx(L);
            if (j == 0) os[b * 16 + dpl] = pack_bf16(o0 * rl, o1 * rl);
            if (warp == 0) TSTAMP(15);
            if (WO_AT == KV_TILES) {
#pragma unroll
            for (int s = 0; s < 2; s++) {
                constexpr int i0 = IDX_WO;
                const int idx = i0 + s;
                mbar_wait(bar_full + 8 * (idx % NST), (idx / NST) & 1);
                const uint32_t tb = sbase + SM_RING + (idx % NST) * TILE + aoff;
#pragma unroll
                for (int mt = 0; mt < 4; mt++) ldsm4t(tb ^ (mt << 5), wf[s * 4 + mt]);
            }
            }
            cons_sync();
            if (tid == 0) mbar_arrive(bar_trig + 8 * 3);
            if (warp == 0) TSTAMP(7);
            float y[4][4] = {};
#pragma unroll
            for (int s = 0; s < 2; s++) {
                const uint32_t b0 = os[bb * 16 + 8 * s + t], b1 = os[bb * 16 + 8 * s + 4 + t];
#pragma unroll
                for (int mt = 0; mt < 4; mt++) mma16816(y[mt], wf[s * 4 + mt], b0, b1);
            }
            float v[4];
#pragma unroll
            for (int i = 0; i < 4; i++) v[i] = t == 0 ? y[0][i] : t == 1 ? y[1][i] : t == 2 ? y[2][i] : y[3][i];
            {
                const bool odd = g & 1;
                const float sx = odd ? v[0] : v[2], sy = odd ? v[1] : v[3];
                const float rx = __shfl_xor_sync(0xffffffffu, sx, 4), ry = __shfl_xor_sync(0xffffffffu, sy, 4);
                const int c0 = 64 * warp + 16 * t + (odd ? g + 7 : g);
                const float e0 = odd ? rx : v[0], e1 = odd ? ry : v[1], e2 = odd ? v[2] : rx, e3 = odd ? v[3] : ry;
                st_v4(&sc->inbox[c0 >> 2][cta][(c0 >> 1) & 1], tagf(e0, F_WO), tagf(e1, F_WO), tagf(e2, F_WO), tagf(e3, F_WO));
            }
        }
        if (tid == 0) mbar_arrive(bar_trig + 8 * 4);
        if (warp == 0) TSTAMP(8);
        float xm0 = 0.f, xm1 = 0.f;
        {
            float r0;
            {
                const uint4* pin = &sc->inbox[cta][0][0] + tid;
                uint4 v = make_uint4(F_WO, F_WO, F_WO, F_WO);
                spin_cycles(DELAY_B1);
                for (int it = 0;; it++) {
                    if (tid < NCTA * 2) v = ld_ll4(pin);
                    if (__all_sync(0xffffffffu, ((v.x & v.y & v.z & v.w & 3u) == F_WO) && (((v.x | v.y | v.z | v.w) & 3u) == F_WO)) || it > SPIN_LIMIT) break;
                }
                const bool u1 = lane & 2, u2 = lane & 4;
                const float a0 = untag(v.x), a1 = untag(v.y), a2 = untag(v.z), a3 = untag(v.w);
                const float k0 = (u1 ? a1 : a0) + __shfl_xor_sync(0xffffffffu, u1 ? a0 : a1, 2);
                const float k1 = (u1 ? a3 : a2) + __shfl_xor_sync(0xffffffffu, u1 ? a2 : a3, 2);
                r0 = (u2 ? k1 : k0) + __shfl_xor_sync(0xffffffffu, u2 ? k0 : k1, 4);
                r0 += __shfl_xor_sync(0xffffffffu, r0, 8);
                r0 += __shfl_xor_sync(0xffffffffu, r0, 16);
                if (lane < 8) red2[warp * 8 + (2 * (lane & 1) + ((lane >> 2) & 1)) * 2 + ((lane >> 1) & 1)] = r0;
            }
            cons_sync();
            if (tid == 32) mbar_arrive(bar_trig + 8 * 5);
            if (warp == 0) {
                float a0 = 0.f, a1 = 0.f;
#pragma unroll
                for (int w = 0; w < 8; w++) { const float2 v = *(const float2*)&red2[w * 8 + (lane & 3) * 2]; a0 += v.x; a1 += v.y; }
                const bool hi = ocol & 1;
                const float ga0 = hi ? bf_hi(m_ga0.x) : bf_lo(m_ga0.x), ga1 = hi ? bf_hi(m_ga1.x) : bf_lo(m_ga1.x);
                xm0 = bf16r(xo0 + bf16r(ga0 * bf16r(a0)));
                xm1 = bf16r(xo1 + bf16r(ga1 * bf16r(a1)));
                if (lane < 4) st_ll2(&sc->x1[cta][lane], pack_bf16(xm0, xm1), F_X1);
                TSTAMP(10);
            }
        }
        if (cta < NFFN) {
            const uint4* px = (const uint4*)&sc->x1[ec >> 2][0];
            const uint4* pp = (const uint4*)&sc->x1[0][0];
            uint4 va, vb, pa, pb;
            uint32_t gf[4][4], uf[4][4];
            if (GU_PIECES && IDX_WG >= kv_idx(KV_TILES - 1) + 2) {
                mbar_wait(bar_gu + 8 * (2 * (warp >> 1)), 0);
                mbar_wait(bar_gu + 8 * (2 * (warp >> 1) + 1), 0);
            } else {
                mbar_wait(bar_full + 8 * (IDX_WG % NST), (IDX_WG / NST) & 1);
                mbar_wait(bar_full + 8 * (IDX_WU % NST), (IDX_WU / NST) & 1);
            }
            {
                const uint32_t tg = sbase + SM_RING + (IDX_WG % NST) * TILE, tu = sbase + SM_RING + (IDX_WU % NST) * TILE;
#pragma unroll
                for (int s = 0; s < 4; s++) {
                    const int row = 64 * warp + 16 * s + (lane & 7) + (lane >> 4) * 8;
                    const uint32_t off = row * 32 + ((((lane >> 3) & 1) ^ ((row >> 2) & 1)) << 4);
                    ldsm4t(tg + off, gf[s]);
                    ldsm4t(tu + off, uf[s]);
                }
            }
            const float c1v[4] = {bf16r(1.0f + bf_lo(m_cb.x)), bf16r(1.0f + bf_hi(m_cb.x)), bf16r(1.0f + bf_lo(m_cb.z)), bf16r(1.0f + bf_hi(m_cb.z))};
            float bg = 0.f, cgc = 0.f, bu = 0.f, cuc = 0.f;
            {
                uint32_t* pre = (uint32_t*)(sgen + SM_MRG) + warp * 128;
                float* bc = (float*)(sgen + SM_MRG + 4096);
                *(uint2*)&pre[eb * 32 + 2 * (lane & 15)] = make_uint2(pack_bf16(c1v[0], c1v[1]), pack_bf16(c1v[2], c1v[3]));
                *(uint2*)&pre[64 + eb * 32 + 2 * (lane & 15)] = make_uint2(m_sb.x, m_sb.z);
                __syncwarp();
                float yg[4] = {}, yu[4] = {};
                const uint32_t* pb = pre + ((g >> 1) & 1) * 64 + bb * 32 + t;
#pragma unroll
                for (int s = 0; s < 4; s++) {
                    const uint32_t b0 = pb[8 * s], b1 = pb[8 * s + 4];
                    mma16816(yg, gf[s], b0, b1);
                    mma16816(yu, uf[s], b0, b1);
                }
                const float y0 = t < 2 ? yg[0] : yu[0], y1 = t < 2 ? yg[1] : yu[1], y2 = t < 2 ? yg[2] : yu[2], y3 = t < 2 ? yg[3] : yu[3];
                float* dstp = bc + warp * 128 + (t >> 1) * 64 + (t & 1) * 32;
                *(float2*)&dstp[g * 2] = make_float2(y0, y1);
                *(float2*)&dstp[(g + 8) * 2] = make_float2(y2, y3);
                __syncwarp();
                if (lane == 0) mbar_arrive(bar_bc);
            }
            if (warp == 0) TSTAMP(11);
            float pivot2;
            {
                spin_cycles(DELAY_B2);
                for (int it = 0;; it++) {
                    va = ld_ll4(px); vb = ld_ll4(px + 1); pa = ld_ll4(pp); pb = ld_ll4(pp + 1);
                    const bool ok = va.y == F_X1 && va.w == F_X1 && vb.y == F_X1 && vb.w == F_X1 &&
                                    pa.y == F_X1 && pa.w == F_X1 && pb.y == F_X1 && pb.w == F_X1;
                    if (__all_sync(0xffffffffu, ok) || it > SPIN_LIMIT) break;
                }
                if (warp == 0) TSTAMP(9);
                const float xv[4] = {eb ? bf_hi(va.x) : bf_lo(va.x), eb ? bf_hi(va.z) : bf_lo(va.z),
                                     eb ? bf_hi(vb.x) : bf_lo(vb.x), eb ? bf_hi(vb.z) : bf_lo(vb.z)};
                const float p0 = 0.25f * ((bf_lo(pa.x) + bf_lo(pa.z)) + (bf_lo(pb.x) + bf_lo(pb.z)));
                const float p1 = 0.25f * ((bf_hi(pa.x) + bf_hi(pa.z)) + (bf_hi(pb.x) + bf_hi(pb.z)));
                const float pivot = eb ? p1 : p0;
                pivot2 = (lane & 1) ? p1 : p0;
                *(uint2*)&hs[eb * 32 + 2 * (lane & 15)] =
                    make_uint2(pack_bf16((xv[0] - pivot) * c1v[0], (xv[1] - pivot) * c1v[1]),
                               pack_bf16((xv[2] - pivot) * c1v[2], (xv[3] - pivot) * c1v[3]));
                __syncwarp();
                float cg[2][4] = {}, cu[2][4] = {};
#pragma unroll
                for (int s = 0; s < 4; s++) {
                    const uint32_t b0 = hs[bb * 32 + 8 * s + t], b1 = hs[bb * 32 + 8 * s + 4 + t];
                    mma16816(cg[s & 1], gf[s], b0, b1);
                    mma16816(cu[s & 1], uf[s], b0, b1);
                }
                const float2 ps = half_warp_sums(xv, pivot);
                if ((lane & 15) == 0) stat[warp * 2 + eb] = ps;
                {
                    const float* bc = (const float*)(sgen + SM_MRG + 4096);
                    mbar_wait(bar_bc, 0);
#pragma unroll
                    for (int w = 0; w < 8; w++) {
                        bg += bc[w * 128 + lane]; cgc += bc[w * 128 + 32 + lane];
                        bu += bc[w * 128 + 64 + lane]; cuc += bc[w * 128 + 96 + lane];
                    }
                }
                if (t < 2) {
                    float v[4];
#pragma unroll
                    for (int i = 0; i < 4; i++) v[i] = t ? cu[0][i] + cu[1][i] : cg[0][i] + cg[1][i];
                    *(float2*)&red[warp * 64 + t * 32 + g * 2] = make_float2(v[0], v[1]);
                    *(float2*)&red[warp * 64 + t * 32 + (g + 8) * 2] = make_float2(v[2], v[3]);
                }
            }
            uint32_t df[4][4];
            mbar_wait(bar_full + 8 * (IDX_WD % NST), (IDX_WD / NST) & 1);
#pragma unroll
            for (int mt = 0; mt < 4; mt++) ldsm4t((sbase + SM_RING + (IDX_WD % NST) * TILE + aoff) ^ (mt << 5), df[mt]);
            cons_sync();
            {
                float gs = 0.f, us = 0.f;
#pragma unroll
                for (int w = 0; w < 8; w++) { gs += red[w * 64 + lane]; us += red[w * 64 + 32 + lane]; }
                float mean_bf, rstd;
                ln_stats(stat, lane & 1, pivot2, mean_bf, rstd);
                const float dm = mean_bf - pivot2;
                gs = bf16r(rstd * (gs - dm * bg) + cgc);
                us = rstd * (us - dm * bu) + cuc;
                const float u2 = gs * (1.0f + 0.044715f * gs * gs) * (2.0f * 0.7978845608028654f * LOG2E);
                const float ge = bf16r(__fdividef(gs, 1.0f + ex2(-u2)));
                const float act = bf16r(ge * bf16r(us));
                const float a0 = __shfl_sync(0xffffffffu, act, 4 * t + bb), a1 = __shfl_sync(0xffffffffu, act, 4 * t + 2 + bb);
                const float a2 = __shfl_sync(0xffffffffu, act, 4 * t + 16 + bb), a3 = __shfl_sync(0xffffffffu, act, 4 * t + 18 + bb);
                const uint32_t b0 = pack_bf16(a0, a1), b1 = pack_bf16(a2, a3);
                float y[4][4] = {};
#pragma unroll
                for (int mt = 0; mt < 4; mt++) mma16816(y[mt], df[mt], b0, b1);
                float v[4];
#pragma unroll
                for (int i = 0; i < 4; i++) v[i] = t == 0 ? y[0][i] : t == 1 ? y[1][i] : t == 2 ? y[2][i] : y[3][i];
            {
                const bool odd = g & 1;
                const float sx = odd ? v[0] : v[2], sy = odd ? v[1] : v[3];
                const float rx = __shfl_xor_sync(0xffffffffu, sx, 4), ry = __shfl_xor_sync(0xffffffffu, sy, 4);
                const int c0 = 64 * warp + 16 * t + (odd ? g + 7 : g);
                const float e0 = odd ? rx : v[0], e1 = odd ? ry : v[1], e2 = odd ? v[2] : rx, e3 = odd ? v[3] : ry;
                st_v4(&sc->inbox[c0 >> 2][cta][(c0 >> 1) & 1], tagf(e0, F_DOWN), tagf(e1, F_DOWN), tagf(e2, F_DOWN), tagf(e3, F_DOWN));
            }
            }
            if (warp == 0) TSTAMP(12);
        }
        {
            float r0;
            {
                const uint4* pin = &sc->inbox[cta][0][0] + tid;
                uint4 v = make_uint4(F_DOWN, F_DOWN, F_DOWN, F_DOWN);
                spin_cycles(DELAY_C);
                for (int it = 0;; it++) {
                    if (tid < NFFN * 2) v = ld_ll4(pin);
                    if (__all_sync(0xffffffffu, ((v.x & v.y & v.z & v.w & 3u) == F_DOWN) && (((v.x | v.y | v.z | v.w) & 3u) == F_DOWN)) || it > SPIN_LIMIT) break;
                }
                const bool u1 = lane & 2, u2 = lane & 4;
                const float a0 = untag(v.x), a1 = untag(v.y), a2 = untag(v.z), a3 = untag(v.w);
                const float k0 = (u1 ? a1 : a0) + __shfl_xor_sync(0xffffffffu, u1 ? a0 : a1, 2);
                const float k1 = (u1 ? a3 : a2) + __shfl_xor_sync(0xffffffffu, u1 ? a2 : a3, 2);
                r0 = (u2 ? k1 : k0) + __shfl_xor_sync(0xffffffffu, u2 ? k0 : k1, 4);
                r0 += __shfl_xor_sync(0xffffffffu, r0, 8);
                r0 += __shfl_xor_sync(0xffffffffu, r0, 16);
                if (lane < 8) red2[64 + warp * 8 + (2 * (lane & 1) + ((lane >> 2) & 1)) * 2 + ((lane >> 1) & 1)] = r0;
            }
            cons_sync();
            if (warp == 0) {
                float a0 = 0.f, a1 = 0.f;
#pragma unroll
                for (int w = 0; w < 8; w++) { const float2 v = *(const float2*)&red2[64 + w * 8 + (lane & 3) * 2]; a0 += v.x; a1 += v.y; }
                const bool hi = ocol & 1;
                const float gb0 = hi ? bf_hi(m_gb0.x) : bf_lo(m_gb0.x), gb1 = hi ? bf_hi(m_gb1.x) : bf_lo(m_gb1.x);
                if (lane < 4) {
                    p.out[ocol] = __float2bfloat16_rn(xm0 + bf16r(gb0 * bf16r(a0)));
                    p.out[D_MODEL + ocol] = __float2bfloat16_rn(xm1 + bf16r(gb1 * bf16r(a1)));
                }
                if (cta == 0 && lane == 0) *(volatile unsigned*)&sc->epoch = tag;
                TSTAMP(13);
            }
        }
    }
}

typedef CUresult (*EncodeFn)(CUtensorMap*, CUtensorMapDataType, cuuint32_t, void*, const cuuint64_t*, const cuuint64_t*,
                             const cuuint32_t*, const cuuint32_t*, CUtensorMapInterleave, CUtensorMapSwizzle,
                             CUtensorMapL2promotion, CUtensorMapFloatOOBfill);

struct Maps { CUtensorMap k, v, wq, wmod, wmod8, wo, wg, wu, wd; };

void encode(EncodeFn fn, CUtensorMap* m, const void* ptr, int rank, const cuuint64_t* dims, const cuuint64_t* strides,
            const cuuint32_t* box, CUtensorMapSwizzle sw) {
    const cuuint32_t es[3] = {1, 1, 1};
    fn(m, CU_TENSOR_MAP_DATA_TYPE_BFLOAT16, rank, const_cast<void*>(ptr), dims, strides, box, es,
       CU_TENSOR_MAP_INTERLEAVE_NONE, sw, CU_TENSOR_MAP_L2_PROMOTION_L2_256B, CU_TENSOR_MAP_FLOAT_OOB_FILL_NONE);
}

}

extern "C" void kernel_launch(void* const* d_in, const int* in_sizes, int n_in, void* d_out, int out_size) {
    (void)in_sizes; (void)n_in; (void)out_size;
    static EncodeFn enc = nullptr;
    static Scratch* scratch = nullptr;
    if (!enc) {
        cudaGetSymbolAddress((void**)&scratch, g_scratch);
        void* fn = nullptr;
        cudaDriverEntryPointQueryResult qr;
        cudaGetDriverEntryPoint("cuTensorMapEncodeTiled", &fn, cudaEnableDefault, &qr);
        enc = (EncodeFn)fn;
        cudaFuncSetAttribute(fused_block_kernel, cudaFuncAttributeMaxDynamicSharedMemorySize, SMEM_BYTES);
    }
    Maps m;
    {
        const cuuint64_t dims[3] = {64, (cuuint64_t)16 * SK, 2}, str[2] = {256, 128};
        const cuuint32_t box[3] = {64, 64, 2};
        encode(enc, &m.k, d_in[1], 3, dims, str, box, CU_TENSOR_MAP_SWIZZLE_128B);
        encode(enc, &m.v, d_in[2], 3, dims, str, box, CU_TENSOR_MAP_SWIZZLE_128B);
    }
    {
        const cuuint64_t dims[2] = {4096, 512}, str[1] = {8192};
        const cuuint32_t box[2] = {32, 256};
        encode(enc, &m.wq, d_in[3], 2, dims, str, box, CU_TENSOR_MAP_SWIZZLE_64B);
    }
    {
        const cuuint64_t dims[2] = {N_MOD, 512}, str[1] = {N_MOD * 2};
        const cuuint32_t box[2] = {16, 256};
        encode(enc, &m.wmod, d_in[10], 2, dims, str, box, CU_TENSOR_MAP_SWIZZLE_32B);
        const cuuint32_t box8[2] = {8, 256};
        encode(enc, &m.wmod8, d_in[10], 2, dims, str, box8, CU_TENSOR_MAP_SWIZZLE_NONE);
    }
    {
        const cuuint64_t dims_o[3] = {64, 4096, 8}, dims_d[3] = {64, D_FF, 8}, str[2] = {1024, 128};
        const cuuint32_t box[3] = {64, 16, 8};
        encode(enc, &m.wo, d_in[4], 3, dims_o, str, box, CU_TENSOR_MAP_SWIZZLE_128B);
        encode(enc, &m.wd, d_in[8], 3, dims_d, str, box, CU_TENSOR_MAP_SWIZZLE_128B);
    }
    {
        const cuuint64_t dims[2] = {D_FF, 512}, str[1] = {D_FF * 2};
        const cuuint32_t box[2] = {16, 128};
        encode(enc, &m.wg, d_in[6], 2, dims, str, box, CU_TENSOR_MAP_SWIZZLE_32B);
        encode(enc, &m.wu, d_in[7], 2, dims, str, box, CU_TENSOR_MAP_SWIZZLE_32B);
    }
    Params p;
    p.x = (const __nv_bfloat16*)d_in[0];
    p.c = (const __nv_bfloat16*)d_in[9];
    p.w_mod = (const __nv_bfloat16*)d_in[10];
    p.out = (__nv_bfloat16*)d_out;
    p.sc = scratch;
    p.wo = (const __nv_bfloat16*)d_in[4];
    p.wg = (const __nv_bfloat16*)d_in[6];
    p.wu = (const __nv_bfloat16*)d_in[7];
    p.wd = (const __nv_bfloat16*)d_in[8];
    fused_block_kernel<<<NCTA, NTHREADS, SMEM_BYTES, cudaStreamPerThread>>>(p, m.k, m.v, m.wq, m.wmod, m.wmod8, m.wo, m.wg, m.wu, m.wd);
}
```

```cpp
#include <cuda_runtime.h>
#include <cuda.h>
#include <cuda_bf16.h>
#include <stdint.h>

namespace {

constexpr int D_MODEL = 512;
constexpr int N_HEADS = 32;
constexpr int SK = 32768;
constexpr int DH = 128;
constexpr int D_FF = 1792;
constexpr int N_MOD = 6 * D_MODEL;

constexpr int NCTA = 128;
constexpr int NFFN = D_FF / 16;
constexpr int NTHREADS = 320;
constexpr int NST = 12;
constexpr int TILE = 16384;
#define INFL_PRO 3
#define INFL_MAIN 3
#define INFL_TAIL 2
#define PACE_HI 96
#define PACE_LO 96
#define END_TILES 0
#define END_WIN 5
#define PACE_HI2 100000
#define PACE_END 16
#define GRID_SLACK 0
#define PACE_SLEEP 200
#define TR_PF_WO -1
#define TR_PF_FF -1
#define TR_LD_WO 0
#define TR_LD_GU 0
#define GU_PIECES 1
#define GU_WIN 3
#define TR_LD_WD 0
#define PRO_TILES 8
constexpr int KV_TILES = 64;
#define MOD_AT 8
#define WO_AT 64
#define GU_AT 64
#define WD_AT 64
static_assert(MOD_AT % 2 == 0 && MOD_AT < WO_AT && MOD_AT < GU_AT && MOD_AT < WD_AT, "schedule");
static_assert(WO_AT <= KV_TILES && GU_AT <= KV_TILES && WD_AT <= KV_TILES, "schedule");
#define WQ_AT 0
constexpr int IDX_WQ = 2 * WQ_AT;
__host__ __device__ constexpr int kv_idx(int i) {
    return (i >= WQ_AT ? 2 : 0) + 2 * i + (i >= MOD_AT ? 1 : 0) + (i >= WO_AT ? 2 : 0) + (i >= GU_AT ? 2 : 0) + (i >= WD_AT ? 1 : 0);
}
constexpr int IDX_MOD = 2 + 2 * MOD_AT;
constexpr int IDX_WO = 3 + 2 * WO_AT + (GU_AT < WO_AT ? 2 : 0) + (WD_AT < WO_AT ? 1 : 0);
constexpr int IDX_WG = 3 + 2 * GU_AT + (WO_AT <= GU_AT ? 2 : 0) + (WD_AT < GU_AT ? 1 : 0);
constexpr int IDX_WU = IDX_WG + 1;
constexpr int IDX_WD = 3 + 2 * WD_AT + (WO_AT <= WD_AT ? 2 : 0) + (GU_AT <= WD_AT ? 2 : 0);
constexpr int N_TILES = 2 + 2 * KV_TILES + 1 + 2 + 3;
static_assert(N_TILES - 1 - IDX_WO < NST && N_TILES - 1 - IDX_WG < NST && N_TILES - 1 - IDX_WD < NST, "weights must stay resident until the end");
constexpr int SPIN_LIMIT = 1 << 20;

constexpr float LOG2E = 1.4426950408889634f;
constexpr float QK_SCALE = 0.08838834764831845f;

constexpr int SM_RING = 0;
constexpr int SM_MRG = SM_RING + NST * TILE;
constexpr int SM_ML = SM_MRG + 8 * 4 * 136 * 4;
constexpr int SM_RED = SM_ML + 8 * 4 * 8;
constexpr int SM_RED2 = SM_RED + 8 * 64 * 4;
constexpr int SM_QS = SM_RED2 + 8 * 64 * 4;
constexpr int SM_OS = SM_QS + 512 * 2;
constexpr int SM_SC = SM_OS + 2 * 16 * 4;
constexpr int SM_HS = SM_SC + 2 * 512 * 2;
constexpr int SM_STAT = SM_HS + 8 * 2 * 32 * 4;
constexpr int SM_PACE = SM_STAT + 8 * 2 * 8;
constexpr int SM_BAR = SM_PACE + 8;
constexpr int SM_END = SM_BAR + (2 * NST + 7 + 8 + 2) * 8;
constexpr int SMEM_BYTES = SM_END + 1024;

struct Scratch {
    uint4 inbox[NCTA][NCTA][2];
    uint2 x1[NCTA][16];
    uint2 part_o[NCTA][4][64];
    uint2 part_ml[NCTA][4][4];
    uint2 mod[2][N_MOD / 2];
    uint2 q[2][N_HEADS * DH / 2];
    unsigned epoch;
    unsigned pad_[31];
    unsigned cleared;
    unsigned pad2_[31];
    unsigned progress;
};
__device__ Scratch g_scratch;
constexpr uint32_t F_PART = 1, F_WO = 1, F_DOWN = 2, F_X1 = 1;
__device__ __forceinline__ uint32_t tagf(float v, uint32_t f) { return (__float_as_uint(v) & ~3u) | f; }
__device__ __forceinline__ float untag(uint32_t v) { return __uint_as_float(v & ~3u); }

struct Params {
    const __nv_bfloat16* x;
    const __nv_bfloat16* c;
    const __nv_bfloat16* w_mod;
    __nv_bfloat16* out;
    Scratch* sc;
    const __nv_bfloat16 *wo, *wg, *wu, *wd;
};

#define TSTAMP(i) do { } while (0)

__device__ __forceinline__ uint32_t smem_u32(const void* p) { return (uint32_t)__cvta_generic_to_shared(p); }

__device__ __forceinline__ void mbar_init(uint32_t bar, uint32_t cnt) {
    asm volatile("mbarrier.init.shared::cta.b64 [%0], %1;" ::"r"(bar), "r"(cnt) : "memory");
}
__device__ __forceinline__ void mbar_expect_tx(uint32_t bar, uint32_t bytes) {
    asm volatile("mbarrier.arrive.expect_tx.shared::cta.b64 _, [%0], %1;" ::"r"(bar), "r"(bytes) : "memory");
}
__device__ __forceinline__ void mbar_arrive(uint32_t bar) {
    asm volatile("mbarrier.arrive.shared::cta.b64 _, [%0];" ::"r"(bar) : "memory");
}
__device__ __forceinline__ bool mbar_try(uint32_t bar, uint32_t parity) {
    uint32_t ok;
    asm volatile(
        "{\n\t.reg .pred p;\n\t"
        "mbarrier.try_wait.parity.shared::cta.b64 p, [%1], %2;\n\t"
        "selp.u32 %0, 1, 0, p;\n\t}"
        : "=r"(ok) : "r"(bar), "r"(parity) : "memory");
    return ok != 0;
}
__device__ __forceinline__ void mbar_wait(uint32_t bar, uint32_t parity) {
    if (mbar_try(bar, parity)) return;
    for (int i = 0; i < SPIN_LIMIT; i++)
        if (mbar_try(bar, parity)) return;
}
__device__ __forceinline__ void cons_sync() { asm volatile("bar.sync 1, 256;" ::: "memory"); }

__device__ __forceinline__ void tma_2d(uint32_t dst, const CUtensorMap* m, int c0, int c1, uint32_t bar) {
    asm volatile("cp.async.bulk.tensor.2d.shared::cluster.global.mbarrier::complete_tx::bytes [%0], [%1, {%3, %4}], [%2];"
                 ::"r"(dst), "l"(m), "r"(bar), "r"(c0), "r"(c1) : "memory");
}
__device__ __forceinline__ void tma_3d(uint32_t dst, const CUtensorMap* m, int c0, int c1, int c2, uint32_t bar) {
    asm volatile("cp.async.bulk.tensor.3d.shared::cluster.global.mbarrier::complete_tx::bytes [%0], [%1, {%3, %4, %5}], [%2];"
                 ::"r"(dst), "l"(m), "r"(bar), "r"(c0), "r"(c1), "r"(c2) : "memory");
}
__device__ __forceinline__ void tma_3d_hint(uint32_t dst, const CUtensorMap* m, int c0, int c1, int c2, uint32_t bar, uint64_t pol) {
    asm volatile("cp.async.bulk.tensor.3d.shared::cluster.global.mbarrier::complete_tx::bytes.L2::cache_hint [%0], [%1, {%3, %4, %5}], [%2], %6;"
                 ::"r"(dst), "l"(m), "r"(bar), "r"(c0), "r"(c1), "r"(c2), "l"(pol) : "memory");
}
__device__ __forceinline__ void l2pf_2d(const CUtensorMap* m, int c0, int c1) {
    asm volatile("cp.async.bulk.prefetch.tensor.2d.L2.global.tile [%0, {%1, %2}];" ::"l"(m), "r"(c0), "r"(c1) : "memory");
}
__device__ __forceinline__ void l2pf_3d(const CUtensorMap* m, int c0, int c1, int c2) {
    asm volatile("cp.async.bulk.prefetch.tensor.3d.L2.global.tile [%0, {%1, %2, %3}];" ::"l"(m), "r"(c0), "r"(c1), "r"(c2) : "memory");
}
__device__ __forceinline__ void l2pf_1d(const void* ptr, uint32_t bytes) {
    asm volatile("cp.async.bulk.prefetch.L2.global [%0], %1;" ::"l"(ptr), "r"(bytes) : "memory");
}
__device__ __forceinline__ void prefetch_tmap(const CUtensorMap* m) {
    asm volatile("prefetch.tensormap [%0];" ::"l"(m) : "memory");
}

__device__ __forceinline__ void ldsm4(uint32_t addr, uint32_t (&r)[4]) {
    asm volatile("ldmatrix.sync.aligned.m8n8.x4.shared.b16 {%0,%1,%2,%3}, [%4];"
                 : "=r"(r[0]), "=r"(r[1]), "=r"(r[2]), "=r"(r[3]) : "r"(addr) : "memory");
}
__device__ __forceinline__ void ldsm4t(uint32_t addr, uint32_t (&r)[4]) {
    asm volatile("ldmatrix.sync.aligned.m8n8.x4.trans.shared.b16 {%0,%1,%2,%3}, [%4];"
                 : "=r"(r[0]), "=r"(r[1]), "=r"(r[2]), "=r"(r[3]) : "r"(addr) : "memory");
}
__device__ __forceinline__ void mma16816(float (&c)[4], const uint32_t (&a)[4], uint32_t b0, uint32_t b1) {
    asm volatile("mma.sync.aligned.m16n8k16.row.col.f32.bf16.bf16.f32 {%0,%1,%2,%3}, {%4,%5,%6,%7}, {%8,%9}, {%0,%1,%2,%3};"
                 : "+f"(c[0]), "+f"(c[1]), "+f"(c[2]), "+f"(c[3])
                 : "r"(a[0]), "r"(a[1]), "r"(a[2]), "r"(a[3]), "r"(b0), "r"(b1));
}
__device__ __forceinline__ uint32_t movmatrix_t(uint32_t a) {
    uint32_t d;
    asm volatile("movmatrix.sync.aligned.m8n8.trans.b16 %0, %1;" : "=r"(d) : "r"(a));
    return d;
}
__device__ __forceinline__ uint32_t pack_bf16(float a, float b) {
    uint32_t r;
    asm("cvt.rn.bf16x2.f32 %0, %1, %2;" : "=r"(r) : "f"(b), "f"(a));
    return r;
}
__device__ __forceinline__ float bf_lo(uint32_t v) { return __uint_as_float(v << 16); }
__device__ __forceinline__ float bf_hi(uint32_t v) { return __uint_as_float(v & 0xffff0000u); }
__device__ __forceinline__ float bf16r(float a) { return bf_lo(pack_bf16(a, 0.f)); }
__device__ __forceinline__ uint32_t max_bf16x2(uint32_t a, uint32_t b) {
    uint32_t r;
    asm("max.bf16x2 %0, %1, %2;" : "=r"(r) : "r"(a), "r"(b));
    return r;
}
__device__ __forceinline__ float ex2(float x) {
    float r;
    asm("ex2.approx.ftz.f32 %0, %1;" : "=f"(r) : "f"(x));
    return r;
}

__device__ __forceinline__ void st_ll2(uint2* p, uint32_t v, uint32_t tag) {
    asm volatile("st.relaxed.gpu.global.v2.u32 [%0], {%1, %2};" ::"l"(p), "r"(v), "r"(tag) : "memory");
}
__device__ __forceinline__ void st_ll4(uint4* p, uint32_t v0, uint32_t v1, uint32_t tag) {
    asm volatile("st.relaxed.gpu.global.v4.u32 [%0], {%1, %2, %3, %2};" ::"l"(p), "r"(v0), "r"(tag), "r"(v1) : "memory");
}
__device__ __forceinline__ void st_v4(uint4* p, uint32_t a, uint32_t b, uint32_t c, uint32_t d) {
    asm volatile("st.relaxed.gpu.global.v4.u32 [%0], {%1, %2, %3, %4};" ::"l"(p), "r"(a), "r"(b), "r"(c), "r"(d) : "memory");
}
__device__ __forceinline__ uint2 ld_ll2(const uint2* p) {
    uint2 v;
    asm volatile("ld.relaxed.gpu.global.v2.u32 {%0, %1}, [%2];" : "=r"(v.x), "=r"(v.y) : "l"(p) : "memory");
    return v;
}
__device__ __forceinline__ uint4 ld_ll4(const uint4* p) {
    uint4 v;
    asm volatile("ld.relaxed.gpu.global.v4.u32 {%0, %1, %2, %3}, [%4];"
                 : "=r"(v.x), "=r"(v.y), "=r"(v.z), "=r"(v.w) : "l"(p) : "memory");
    return v;
}

#define DELAY_B1 450
#define DELAY_B2 0
#define DELAY_C 450
__device__ __forceinline__ uint32_t clock32() {
    uint32_t c;
    asm volatile("mov.u32 %0, %clock;" : "=r"(c));
    return c;
}
__device__ __forceinline__ void spin_cycles(uint32_t n) {
    if (n > 0) { const uint32_t c0 = clock32(); while (clock32() - c0 < n) {} }
}
__device__ __forceinline__ float rcp_approx(float x) {
    float r;
    asm("rcp.approx.ftz.f32 %0, %1;" : "=f"(r) : "f"(x));
    return r;
}
__device__ __forceinline__ float sqrt_approx(float x) {
    float r;
    asm("sqrt.approx.f32 %0, %1;" : "=f"(r) : "f"(x));
    return r;
}

__device__ __forceinline__ float silu_bf(float v) { return bf16r(v / (1.0f + expf(-v))); }

__device__ __forceinline__ float2 half_warp_sums(const float (&v)[4], float pivot) {
    float s1 = 0.f, s2 = 0.f;
#pragma unroll
    for (int i = 0; i < 4; i++) { const float d = v[i] - pivot; s1 += d; s2 += d * d; }
#pragma unroll
    for (int o = 1; o < 16; o <<= 1) { s1 += __shfl_xor_sync(0xffffffffu, s1, o); s2 += __shfl_xor_sync(0xffffffffu, s2, o); }
    return make_float2(s1, s2);
}
__device__ __forceinline__ void ln_stats(const float2* stat, int b, float pivot, float& mean_bf, float& rstd) {
    float s1 = 0.f, s2 = 0.f;
#pragma unroll
    for (int w = 0; w < 8; w++) { const float2 v = stat[w * 2 + b]; s1 += v.x; s2 += v.y; }
    const float dm = s1 * (1.0f / D_MODEL);
    const float var = fmaxf(s2 * (1.0f / D_MODEL) - dm * dm, 0.f);
    mean_bf = bf16r(pivot + dm);
    rstd = rcp_approx(bf16r(sqrt_approx(bf16r(bf16r(var) + 1e-5f))));
}
__device__ __forceinline__ float ln_norm(float xv, float mean_bf, float rstd) { return bf16r(bf16r(xv - mean_bf) * rstd); }
__device__ __forceinline__ float ln_mod(float n, float cmul, float sadd) { return bf16r(n * bf16r(1.0f + cmul)) + sadd; }

__global__ void __launch_bounds__(NTHREADS, 1)
fused_block_kernel(const Params p, const __grid_constant__ CUtensorMap tm_k, const __grid_constant__ CUtensorMap tm_v,
                   const __grid_constant__ CUtensorMap tm_wq, const __grid_constant__ CUtensorMap tm_wmod,
                   const __grid_constant__ CUtensorMap tm_wmod8,
                   const __grid_constant__ CUtensorMap tm_wo, const __grid_constant__ CUtensorMap tm_wg,
                   const __grid_constant__ CUtensorMap tm_wu, const __grid_constant__ CUtensorMap tm_wd) {
    extern __shared__ unsigned char smem_raw[];
    const uint32_t sbase = (smem_u32(smem_raw) + 1023u) & ~1023u;
    unsigned char* sgen = smem_raw + (sbase - smem_u32(smem_raw));
    const int tid = threadIdx.x, warp = tid >> 5, lane = tid & 31;
    const int cta = blockIdx.x;
    const uint32_t bar_full = sbase + SM_BAR, bar_empty = bar_full + NST * 8;
    const uint32_t bar_clear = bar_empty + NST * 8;
    const uint32_t bar_gu = bar_clear + 7 * 8;
    const uint32_t bar_bc = bar_gu + 8 * 8;
    const uint32_t bar_p0w = bar_bc + 8;
    const uint32_t bar_trig = bar_clear;

    const int key0 = (cta >> 3) * SK + (cta & 7) * 64;
    uint64_t pol = 0;
    if (tid == 256) {
        asm volatile("createpolicy.fractional.L2::evict_first.b64 %0, 1.0;" : "=l"(pol));
        mbar_init(bar_p0w, 1);
#pragma unroll
        for (int i = 0; i < 4; i++) mbar_init(bar_full + 8 * i, 1);
        asm volatile("fence.mbarrier_init.release.cluster;" ::: "memory");
        mbar_expect_tx(bar_p0w, 8192);
        tma_2d(sbase + SM_MRG, &tm_wmod8, cta * 8, 0, bar_p0w);
        tma_2d(sbase + SM_MRG + 4096, &tm_wmod8, cta * 8, 256, bar_p0w);
#pragma unroll
        for (int i = 0; i < 4; i++) mbar_expect_tx(bar_full + 8 * i, TILE);
        tma_2d(sbase + SM_RING, &tm_wq, cta * 32, 0, bar_full);
        tma_2d(sbase + SM_RING + TILE, &tm_wq, cta * 32, 256, bar_full + 8);
        tma_3d_hint(sbase + SM_RING + 2 * TILE, &tm_k, 0, key0, 0, bar_full + 16, pol);
        tma_3d_hint(sbase + SM_RING + 3 * TILE, &tm_v, 0, key0, 0, bar_full + 24, pol);
    }
    static_assert(WQ_AT == 0 && MOD_AT >= 1, "the fast start assumes the sequence wq0 wq1 K0 V0");

    if (warp == 8) {
        if (lane == 0) {
            for (int i = 0; i < NST; i++) { if (i >= 4) mbar_init(bar_full + 8 * i, 1); mbar_init(bar_empty + 8 * i, 4); }
            mbar_init(bar_clear, 1);
            for (int k = 1; k <= 6; k++) mbar_init(bar_trig + 8 * k, 1);
            for (int k = 0; k < 8; k++) mbar_init(bar_gu + 8 * k, 1);
            mbar_init(bar_bc, 8);
            ((volatile uint32_t*)(sgen + SM_PACE))[0] = 0;
            ((volatile uint32_t*)(sgen + SM_PACE))[1] = INFL_MAIN;
            asm volatile("fence.mbarrier_init.release.cluster;" ::: "memory");
        }
        __syncwarp();
        asm volatile("bar.arrive 2, 320;" ::: "memory");
        asm volatile("bar.arrive 3, 64;" ::: "memory");
        if (lane == 0) {
            int slot = 4; uint32_t ph = 1;
            int landed = 0, wslot = 0; uint32_t wph = 0;
            int kv = 2;
            constexpr int N_STREAM = kv_idx(KV_TILES - 1) + 2;
            auto issue = [&](int idx) {
                const uint32_t fb = bar_full + 8 * (idx % NST), dst = sbase + SM_RING + (idx % NST) * TILE;
                if ((idx == IDX_WG || idx == IDX_WU || idx == IDX_WD) && cta >= NFFN) {
                    mbar_arrive(fb);
                    return;
                }
                mbar_expect_tx(fb, TILE);
                if (idx == IDX_WQ || idx == IDX_WQ + 1) {
                    tma_2d(dst, &tm_wq, cta * 32, (idx - IDX_WQ) * 256, fb);
                } else if (idx == IDX_MOD) {
                    tma_2d(dst, &tm_wmod, 1024 + cta * 16, 0, fb);
                    tma_2d(dst + 8192, &tm_wmod, 1024 + cta * 16, 256, fb);
                } else if (idx == IDX_WO || idx == IDX_WO + 1) {
                    tma_3d(dst, &tm_wo, 0, cta * 32 + (idx - IDX_WO) * 16, 0, fb);
                } else if (idx == IDX_WG || idx == IDX_WU) {
                    const CUtensorMap* m = idx == IDX_WG ? &tm_wg : &tm_wu;
#pragma unroll
                    for (int q = 0; q < 4; q++) tma_2d(dst + q * 4096, m, cta * 16, q * 128, fb);
                } else if (idx == IDX_WD) {
                    tma_3d(dst, &tm_wd, 0, cta * 16, 0, fb);
                } else {
                    tma_3d_hint(dst, (kv & 1) ? &tm_v : &tm_k, 0, key0 + (kv >> 1) * 512, 0, fb, pol);
                    kv++;
                }
            };
            auto wait_window = [&](int idx, int window) {
                while (landed + window <= idx) {
                    mbar_wait(bar_full + 8 * wslot, wph);
                    if (++wslot == NST) { wslot = 0; wph ^= 1; }
                    landed++;
                }
            };
            prefetch_tmap(&tm_wmod);
            ((volatile uint32_t*)(sgen + SM_PACE))[0] = 4;
            for (int idx = 4; idx < N_STREAM; idx++) {
                if (idx >= NST) mbar_wait(bar_empty + 8 * slot, ph);
                wait_window(idx, idx < PRO_TILES ? INFL_PRO : idx >= N_STREAM - END_TILES ? END_WIN
                                                            : (int)((volatile uint32_t*)(sgen + SM_PACE))[1]);
                if (idx == 12) { prefetch_tmap(&tm_wo); prefetch_tmap(&tm_wg); prefetch_tmap(&tm_wu); prefetch_tmap(&tm_wd); }
                issue(idx);
                ((volatile uint32_t*)(sgen + SM_PACE))[0] = idx + 1;
                if (++slot == NST) { slot = 0; ph ^= 1; }
            }
            auto deferred = [&](int idx, bool windowed) {
                if (idx < N_STREAM) return;
                mbar_wait(bar_empty + 8 * (idx % NST), ((idx / NST) & 1) ^ 1);
                if (windowed) wait_window(idx, INFL_TAIL);
                issue(idx);
            };
#pragma unroll
            for (int kk = 0; kk <= 6; kk++) {
                const int k = kk == 0 ? 0 : kk == 1 ? 6 : kk - 1;
                if (TR_PF_WO != k && TR_PF_FF != k && TR_LD_WO != k && TR_LD_GU != k && TR_LD_WD != k) continue;
                if (k > 0) mbar_wait(bar_trig + 8 * k, 0);
                if (TR_PF_WO == k) l2pf_1d((const char*)p.wo + (size_t)cta * 32768, 32768);
                if (TR_PF_FF == k && cta < NFFN) {
                    l2pf_1d((const char*)p.wg + (size_t)cta * 16384, 16384);
                    l2pf_1d((const char*)p.wu + (size_t)cta * 16384, 16384);
                    l2pf_1d((const char*)p.wd + (size_t)cta * 16384, 16384);
                }
                if (TR_LD_WO == k) { deferred(IDX_WO, k == 0 || k == 6); deferred(IDX_WO + 1, k == 0 || k == 6); }
                if (TR_LD_GU == k) {
                    if (!GU_PIECES) { deferred(IDX_WG, k == 0 || k == 6); deferred(IDX_WU, k == 0 || k == 6); }
                    else if (cta < NFFN) {
                        mbar_wait(bar_empty + 8 * (IDX_WG % NST), ((IDX_WG / NST) & 1) ^ 1);
                        mbar_wait(bar_empty + 8 * (IDX_WU % NST), ((IDX_WU / NST) & 1) ^ 1);
                        if (IDX_WO >= N_STREAM && TR_LD_WO <= k) {
                            mbar_wait(bar_full + 8 * (IDX_WO % NST), (IDX_WO / NST) & 1);
                            mbar_wait(bar_full + 8 * ((IDX_WO + 1) % NST), ((IDX_WO + 1) / NST) & 1);
                        }
#pragma unroll
                        for (int st = 0; st < 8; st++) {
                            if (st >= GU_WIN) mbar_wait(bar_gu + 8 * (st - GU_WIN), 0);
                            const uint32_t dst = sbase + SM_RING + (((st & 1) ? IDX_WU : IDX_WG) % NST) * TILE + (st >> 1) * 4096;
                            mbar_expect_tx(bar_gu + 8 * st, 4096);
                            tma_2d(dst, (st & 1) ? &tm_wu : &tm_wg, cta * 16, (st >> 1) * 128, bar_gu + 8 * st);
                        }
                        mbar_wait(bar_gu + 8 * 7, 0);
                    }
                }
                if (TR_LD_WD == k) deferred(IDX_WD, !GU_PIECES && (k == 0 || k == 6));
            }
        }
    } else if (warp == 9) {
        Scratch* const sc = p.sc;
        const uint32_t tag = *(volatile unsigned*)&sc->epoch + 1;
        if (lane < 2) {
            st_ll4((uint4*)&sc->mod[lane][cta * 4], 0u, 0u, 0u);
            st_ll4((uint4*)&sc->mod[lane][cta * 4] + 1, 0u, 0u, 0u);
        }
        if (lane < 8) st_ll4((uint4*)&sc->mod[lane >> 2][512 + cta * 8] + (lane & 3), 0u, 0u, 0u);
        if (lane < 16) st_ll4((uint4*)&sc->q[lane >> 3][cta * 16] + (lane & 7), 0u, 0u, 0u);
        __syncwarp();
        asm volatile("bar.arrive 2, 320;" ::: "memory");
        asm volatile("bar.sync 3, 64;" ::: "memory");
#pragma unroll 4
        for (int i = 0; i < 8; i++) st_v4(&sc->inbox[cta][0][0] + i * 32 + lane, 0u, 0u, 0u, 0u);
#pragma unroll 4
        for (int i = 0; i < 4; i++) st_v4((uint4*)&sc->part_o[cta][0][0] + i * 32 + lane, 0u, 0u, 0u, 0u);
        if (lane < 8) st_v4((uint4*)&sc->part_ml[cta][0][0] + lane, 0u, 0u, 0u, 0u);
        if (lane < 2) st_v4((uint4*)&sc->x1[cta][0] + lane, 0u, 0u, 0u, 0u);
        if (cta == 0 && lane == 0) asm volatile("st.relaxed.gpu.global.u32 [%0], %1;" ::"l"(&sc->progress), "r"(0u) : "memory");
        asm volatile("fence.acq_rel.gpu;" ::: "memory");
        __syncwarp();
        if (lane == 0) {
            asm volatile("fence.acq_rel.gpu;" ::: "memory");
            asm volatile("red.relaxed.gpu.global.add.u32 [%0], %1;" ::"l"(&sc->cleared), "r"(1u) : "memory");
            const uint32_t target = tag * NCTA;
            for (int it = 0; it < SPIN_LIMIT; it++) {
                uint32_t v;
                asm volatile("ld.relaxed.gpu.global.u32 %0, [%1];" : "=r"(v) : "l"(&sc->cleared) : "memory");
                if ((int32_t)(v - target) >= 0) break;
                __nanosleep(500);
            }
            asm volatile("fence.acq_rel.gpu;" ::: "memory");
            mbar_arrive(bar_clear);
            volatile uint32_t* pace = (volatile uint32_t*)(sgen + SM_PACE);
            constexpr uint32_t N_STREAM = kv_idx(KV_TILES - 1) + 2;
            uint32_t posted = 0;
            for (int it = 0; it < SPIN_LIMIT; it++) {
                const uint32_t own = pace[0];
                if (own > posted) {
                    asm volatile("red.relaxed.gpu.global.add.u32 [%0], %1;" ::"l"(&sc->progress), "r"(own - posted) : "memory");
                    posted = own;
                }
                uint32_t v;
                asm volatile("ld.relaxed.gpu.global.u32 %0, [%1];" : "=r"(v) : "l"(&sc->progress) : "memory");
                if (own >= N_STREAM) {
                    if (v + GRID_SLACK >= NCTA * N_STREAM) break;
                } else {
                    const int diff = (int)v - (int)own * NCTA;
                    pace[1] = diff > PACE_HI2 && own + PACE_END >= N_STREAM ? INFL_MAIN + 2
                            : diff > PACE_HI ? INFL_MAIN + 1 : diff < -PACE_LO ? INFL_MAIN - 1 : INFL_MAIN;
                }
                __nanosleep(own + 4 >= N_STREAM ? 50 : PACE_SLEEP);
            }
            mbar_arrive(bar_trig + 8 * 6);
        }
    } else {
        const int g = lane >> 2, t = lane & 3;
        const int bb = g & 1;
        const int eb = lane >> 4;
        const int ec = 64 * warp + 4 * (lane & 15);
        if (warp == 0) TSTAMP(0);
        Scratch* const sc = p.sc;
        const float c00 = __bfloat162float(p.c[tid]), c01 = __bfloat162float(p.c[tid + 256]);
        const float c10 = __bfloat162float(p.c[D_MODEL + tid]), c11 = __bfloat162float(p.c[D_MODEL + tid + 256]);
        const uint2 xe = __ldg((const uint2*)(p.x + eb * D_MODEL + ec));
        const float xpivot = __bfloat162float(p.x[eb * D_MODEL]);
        const uint32_t tag = *(volatile unsigned*)&sc->epoch + 1;
        const int ocol = cta * 4 + (lane & 3);
        const float xo0 = __bfloat162float(p.x[ocol]), xo1 = __bfloat162float(p.x[D_MODEL + ocol]);

        float* red = (float*)(sgen + SM_RED);
        float* red2 = (float*)(sgen + SM_RED2);
        float2* stat = (float2*)(sgen + SM_STAT);
        uint32_t* hs = (uint32_t*)(sgen + SM_HS) + warp * 64;
        float xn[4];
        {
            float xv[4] = {bf_lo(xe.x), bf_hi(xe.x), bf_lo(xe.y), bf_hi(xe.y)};
            const float2 ps = half_warp_sums(xv, xpivot);
            if ((lane & 15) == 0) stat[warp * 2 + eb] = ps;
            const float s00 = silu_bf(c00), s01 = silu_bf(c01), s10 = silu_bf(c10), s11 = silu_bf(c11);
            __nv_bfloat16* scs = (__nv_bfloat16*)(sgen + SM_SC);
            scs[tid] = __float2bfloat16_rn(s00); scs[tid + 256] = __float2bfloat16_rn(s01);
            scs[512 + tid] = __float2bfloat16_rn(s10); scs[512 + tid + 256] = __float2bfloat16_rn(s11);
            asm volatile("bar.sync 2, 320;" ::: "memory");
            if (warp == 0) TSTAMP(23);
            float cp[4] = {0.f, 0.f, 0.f, 0.f};
            const uint32_t* sc32 = (const uint32_t*)(sgen + SM_SC) + bb * 256 + 32 * warp + t;
            mbar_wait(bar_p0w, 0);
#pragma unroll
            for (int s = 0; s < 4; s++) {
                uint32_t r0, r1;
                asm volatile("ldmatrix.sync.aligned.m8n8.x2.trans.shared.b16 {%0,%1}, [%2];"
                             : "=r"(r0), "=r"(r1) : "r"(sbase + SM_MRG + (64 * warp + 16 * s + (lane & 15)) * 16) : "memory");
                const uint32_t a[4] = {r0, r0, r1, r1};
                mma16816(cp, a, sc32[8 * s], sc32[8 * s + 4]);
            }
            if (t == 0) { red[warp * 16 + g] = cp[0]; red[warp * 16 + 8 + g] = cp[1]; }
            if (warp == 0) TSTAMP(14);
            cons_sync();
            if (warp == 0) {
                float s = 0.f;
#pragma unroll
                for (int w = 0; w < 8; w++) s += red[w * 16 + (lane & 15)];
                const float nx = __shfl_down_sync(0xffffffffu, s, 1);
                if (lane < 16 && !(lane & 1))
                    st_ll2(&sc->mod[lane >> 3][cta * 4 + ((lane & 7) >> 1)], pack_bf16(s, nx), tag);
                TSTAMP(1);
            }
            float mean_bf, rstd;
            ln_stats(stat, eb, xpivot, mean_bf, rstd);
#pragma unroll
            for (int i = 0; i < 4; i++) xn[i] = ln_norm(xv[i], mean_bf, rstd);
        }
        {
            uint4 sa, ca;
            for (int it = 0;; it++) {
                sa = ld_ll4((const uint4*)&sc->mod[eb][ec >> 1]);
                ca = ld_ll4((const uint4*)&sc->mod[eb][256 + (ec >> 1)]);
                const bool ok = sa.y == tag && sa.w == tag && ca.y == tag && ca.w == tag;
                if (__all_sync(0xffffffffu, ok) || it > SPIN_LIMIT) break;
            }
            *(uint2*)&hs[eb * 32 + 2 * (lane & 15)] =
                make_uint2(pack_bf16(ln_mod(xn[0], bf_lo(ca.x), bf_lo(sa.x)), ln_mod(xn[1], bf_hi(ca.x), bf_hi(sa.x))),
                           pack_bf16(ln_mod(xn[2], bf_lo(ca.z), bf_lo(sa.z)), ln_mod(xn[3], bf_hi(ca.z), bf_hi(sa.z))));
            __syncwarp();
            uint32_t hb[8];
#pragma unroll
            for (int i = 0; i < 8; i++) hb[i] = hs[bb * 32 + 8 * (i >> 1) + 4 * (i & 1) + t];
            if (warp == 0) TSTAMP(2);
            float cq[2][4] = {};
            const int ts = warp >> 2;
            mbar_wait(bar_full + 8 * (IDX_WQ + ts), 0);
            const uint32_t tb = sbase + SM_RING + (IDX_WQ + ts) * TILE;
#pragma unroll
            for (int s = 0; s < 4; s++) {
                const int row = 64 * (warp & 3) + 16 * s + (lane & 7) + (lane >> 4) * 8;
#pragma unroll
                for (int mt = 0; mt < 2; mt++) {
                    const int ch = 2 * mt + ((lane >> 3) & 1);
                    uint32_t a[4];
                    ldsm4t(tb + row * 64 + ((ch ^ ((row >> 1) & 3)) << 4), a);
                    mma16816(cq[mt], a, hb[2 * s], hb[2 * s + 1]);
                }
            }
            if (t < 2) {
                const float v0 = t == 0 ? cq[0][0] : cq[1][0], v1 = t == 0 ? cq[0][1] : cq[1][1];
                const float v2 = t == 0 ? cq[0][2] : cq[1][2], v3 = t == 0 ? cq[0][3] : cq[1][3];
                *(float2*)&red2[warp * 64 + (16 * t + g) * 2] = make_float2(v0, v1);
                *(float2*)&red2[warp * 64 + (16 * t + g + 8) * 2] = make_float2(v2, v3);
            }
            cons_sync();
            if (warp < 4 && lane == 0) { mbar_arrive(bar_empty + 8 * IDX_WQ); mbar_arrive(bar_empty + 8 * IDX_WQ + 8); }
            if (warp == 0) {
                const int b = lane >> 4, cp = lane & 15;
                float q0 = 0.f, q1 = 0.f;
#pragma unroll
                for (int w = 0; w < 8; w++) {
                    const float4 v = *(const float4*)&red2[w * 64 + cp * 4];
                    q0 += b ? v.y : v.x; q1 += b ? v.w : v.z;
                }
                st_ll2(&sc->q[b][cta * 16 + cp], pack_bf16(q0, q1), tag);
                TSTAMP(3);
            }
        }
        const int pair = cta >> 3;
        uint32_t qf[16];
        {
            uint2* qs = (uint2*)(sgen + SM_QS);
            if (tid < 128) {
                const uint4* src = (const uint4*)&sc->q[pair >> 3][(pair & 7) * 256] + tid;
                uint4 v;
                for (int it = 0;; it++) {
                    v = ld_ll4(src);
                    if ((v.y == tag && v.w == tag) || it > SPIN_LIMIT) break;
                }
                qs[tid] = make_uint2(v.x, v.z);
            }
            cons_sync();
            const uint32_t* q32 = (const uint32_t*)(sgen + SM_QS);
#pragma unroll
            for (int s = 0; s < 8; s++) {
                qf[2 * s] = q32[(g & 3) * 64 + 8 * s + t];
                qf[2 * s + 1] = q32[(g & 3) * 64 + 8 * s + 4 + t];
            }
        }
        if (warp == 0) TSTAMP(4);

        float o[8][4];
#pragma unroll
        for (int i = 0; i < 8; i++) { o[i][0] = o[i][1] = o[i][2] = o[i][3] = 0.f; }
        uint32_t mrun = 0xff80ff80u;
        float ls[4] = {0.f, 0.f, 0.f, 0.f};
        uint4 m_sb, m_cb; uint2 m_ga0, m_ga1, m_gb0, m_gb1;
        {
            const int grp = warp >> 2, wi = warp & 3;
            const int krow = 16 * wi + (lane & 7) + ((lane >> 3) & 1) * 8;
            const uint32_t koff = krow * 128 + ((((lane >> 4) & 1) ^ (lane & 7)) << 4);
            const int vrow = 16 * wi + (lane & 7) + (lane >> 4) * 8;
            const uint32_t voff = vrow * 128 + ((((lane >> 3) & 1) ^ (lane & 7)) << 4);
            const uint32_t ones[4] = {0x3f803f80u, 0x3f803f80u, 0x3f803f80u, 0x3f803f80u};
            for (int i = grp; i < KV_TILES; i += 2) {
                if (i == MOD_AT + grp) {
                    float cm[4] = {};
                    const uint32_t* sc32 = (const uint32_t*)(sgen + SM_SC) + bb * 256 + 32 * warp + t;
                    mbar_wait(bar_full + 8 * (IDX_MOD % NST), (IDX_MOD / NST) & 1);
                    const uint32_t tb = sbase + SM_RING + (IDX_MOD % NST) * TILE;
#pragma unroll
                    for (int s = 0; s < 4; s++) {
                        const int row = 64 * warp + 16 * s + (lane & 7) + (lane >> 4) * 8;
                        const int ch = (lane >> 3) & 1;
                        uint32_t a[4];
                        ldsm4t(tb + row * 32 + ((ch ^ ((row >> 2) & 1)) << 4), a);
                        mma16816(cm, a, sc32[8 * s], sc32[8 * s + 4]);
                    }
                    if (t == 0) {
                        *(float2*)&red[warp * 64 + g * 2] = make_float2(cm[0], cm[1]);
                        *(float2*)&red[warp * 64 + (g + 8) * 2] = make_float2(cm[2], cm[3]);
                    }
                    cons_sync();
                    if (warp < 4 && lane == 0) mbar_arrive(bar_empty + 8 * (IDX_MOD % NST));
                    if (warp == 1 && lane < 16) {
                        const int b = lane >> 3, cp = lane & 7;
                        float q0 = 0.f, q1 = 0.f;
#pragma unroll
                        for (int w = 0; w < 8; w++) {
                            const float4 v = *(const float4*)&red[w * 64 + cp * 4];
                            q0 += b ? v.y : v.x; q1 += b ? v.w : v.z;
                        }
                        st_ll2(&sc->mod[b][512 + cta * 8 + cp], pack_bf16(q0, q1), tag);
                    }
                }
                if (i == 56 + grp) {
                    m_sb = ld_ll4((const uint4*)&sc->mod[eb][768 + (ec >> 1)]);
                    m_cb = ld_ll4((const uint4*)&sc->mod[eb][1024 + (ec >> 1)]);
                    m_ga0 = ld_ll2(&sc->mod[0][512 + (ocol >> 1)]); m_ga1 = ld_ll2(&sc->mod[1][512 + (ocol >> 1)]);
                    m_gb0 = ld_ll2(&sc->mod[0][1280 + (ocol >> 1)]); m_gb1 = ld_ll2(&sc->mod[1][1280 + (ocol >> 1)]);
                }
                if (i == 60 + grp) {
                    for (int it = 0;; it++) {
                        const bool ok = m_sb.y == tag && m_sb.w == tag && m_cb.y == tag && m_cb.w == tag &&
                                        m_ga0.y == tag && m_ga1.y == tag && m_gb0.y == tag && m_gb1.y == tag;
                        if (__all_sync(0xffffffffu, ok) || it > SPIN_LIMIT) break;
                        m_sb = ld_ll4((const uint4*)&sc->mod[eb][768 + (ec >> 1)]);
                        m_cb = ld_ll4((const uint4*)&sc->mod[eb][1024 + (ec >> 1)]);
                        m_ga0 = ld_ll2(&sc->mod[0][512 + (ocol >> 1)]); m_ga1 = ld_ll2(&sc->mod[1][512 + (ocol >> 1)]);
                        m_gb0 = ld_ll2(&sc->mod[0][1280 + (ocol >> 1)]); m_gb1 = ld_ll2(&sc->mod[1][1280 + (ocol >> 1)]);
                    }
                    mbar_wait(bar_clear, 0);
                }
                const int ki = kv_idx(i), ks = ki % NST, vs = (ki + 1) % NST;
                const uint32_t kph = (ki / NST) & 1, vph = ((ki + 1) / NST) & 1;
                mbar_wait(bar_full + 8 * ks, kph);
                const uint32_t kb = sbase + SM_RING + ks * TILE + koff;
                float sa[4] = {0.f, 0.f, 0.f, 0.f}, sb[4] = {0.f, 0.f, 0.f, 0.f};
#pragma unroll
                for (int s = 0; s < 8; s += 2) {
                    uint32_t a0[4], a1[4];
                    ldsm4((kb ^ ((s & 3) << 5)) + (s >> 2) * 8192, a0);
                    ldsm4((kb ^ (((s + 1) & 3) << 5)) + (s >> 2) * 8192, a1);
                    mma16816(sa, a0, qf[2 * s], qf[2 * s + 1]);
                    mma16816(sb, a1, qf[2 * s + 2], qf[2 * s + 3]);
                }
                __syncwarp();
                if (lane == 0) mbar_arrive(bar_empty + 8 * ks);
                uint32_t r01 = pack_bf16(sa[0] + sb[0], sa[1] + sb[1]);
                uint32_t r23 = pack_bf16(sa[2] + sb[2], sa[3] + sb[3]);
                r01 = pack_bf16(bf_lo(r01) * QK_SCALE, bf_hi(r01) * QK_SCALE);
                r23 = pack_bf16(bf_lo(r23) * QK_SCALE, bf_hi(r23) * QK_SCALE);
                uint32_t mx = max_bf16x2(r01, r23);
                mx = max_bf16x2(mx, __shfl_xor_sync(0xffffffffu, mx, 4));
                mx = max_bf16x2(mx, __shfl_xor_sync(0xffffffffu, mx, 8));
                mx = max_bf16x2(mx, __shfl_xor_sync(0xffffffffu, mx, 16));
                const uint32_t mnew = max_bf16x2(mrun, mx);
                const float m0 = bf_lo(mnew), m1 = bf_hi(mnew);
                if (__any_sync(0xffffffffu, mnew != mrun)) {
                    const float al0 = ex2((bf_lo(mrun) - m0) * LOG2E), al1 = ex2((bf_hi(mrun) - m1) * LOG2E);
                    ls[0] *= al0; ls[1] *= al1;
#pragma unroll
                    for (int d = 0; d < 8; d++) { o[d][0] *= al0; o[d][1] *= al1; o[d][2] *= al0; o[d][3] *= al1; }
                    mrun = mnew;
                }
                const float p0 = ex2((bf_lo(r01) - m0) * LOG2E), p1 = ex2((bf_hi(r01) - m1) * LOG2E);
                const float p2 = ex2((bf_lo(r23) - m0) * LOG2E), p3 = ex2((bf_hi(r23) - m1) * LOG2E);
                const uint32_t pb0 = movmatrix_t(pack_bf16(p0, p1)), pb1 = movmatrix_t(pack_bf16(p2, p3));
                mma16816(ls, ones, pb0, pb1);
                mbar_wait(bar_full + 8 * vs, vph);
                const uint32_t vb = sbase + SM_RING + vs * TILE + voff;
#pragma unroll
                for (int d = 0; d < 8; d++) {
                    uint32_t a[4];
                    ldsm4t((vb ^ ((d & 3) << 5)) + (d >> 2) * 8192, a);
                    mma16816(o[d], a, pb0, pb1);
                }
                __syncwarp();
                if (lane == 0) mbar_arrive(bar_empty + 8 * vs);
            }
        }
        if (warp == 7) TSTAMP(5);
        if (warp == 7 && lane == 0) mbar_arrive(bar_trig + 8 * 1);
        {
            float* mrg = (float*)(sgen + SM_MRG);
            float2* ml = (float2*)(sgen + SM_ML);
            {
                const int hp = (t & 1) * 2, up = t >> 1;
                if (g == 0 && up == 0) { ml[warp * 4 + hp] = make_float2(bf_lo(mrun), ls[0]); ml[warp * 4 + hp + 1] = make_float2(bf_hi(mrun), ls[1]); }
                float* m0p = mrg + (warp * 4 + hp) * 136 + up * 72 + g;
#pragma unroll
                for (int d = 0; d < 4; d++) {
                    m0p[16 * d] = up ? o[d + 4][0] : o[d][0]; m0p[136 + 16 * d] = up ? o[d + 4][1] : o[d][1];
                    m0p[16 * d + 8] = up ? o[d + 4][2] : o[d][2]; m0p[136 + 16 * d + 8] = up ? o[d + 4][3] : o[d][3];
                }
            }
            cons_sync();
            const int hh = tid >> 6, dp = tid & 63;
            float2 mw[8];
            float M = -INFINITY;
#pragma unroll
            for (int w = 0; w < 8; w++) { mw[w] = ml[w * 4 + hh]; M = fmaxf(M, mw[w].x); }
            float L = 0.f, o0 = 0.f, o1 = 0.f;
#pragma unroll
            for (int w = 0; w < 8; w++) {
                const float wt = ex2((mw[w].x - M) * LOG2E);
                const float2 v = *(const float2*)&mrg[(w * 4 + hh) * 136 + 2 * dp + (dp >= 32 ? 8 : 0)];
                L += wt * mw[w].y; o0 += wt * v.x; o1 += wt * v.y;
            }
            st_ll2(&sc->part_o[cta][hh][dp], tagf(o0, F_PART), tagf(o1, F_PART));
            if (dp < 4) st_ll2(&sc->part_ml[cta][hh][dp], tagf(M, F_PART), tagf(L, F_PART));
        }
        if (tid == 0) mbar_arrive(bar_trig + 8 * 2);
        if (warp == 0) TSTAMP(6);
        const uint32_t aoff = warp * 2048 + ((lane & 7) + (lane >> 4) * 8) * 128 + ((((lane >> 3) & 1) ^ (lane & 7)) << 4);
        uint32_t wf[8][4];
        if (WO_AT < KV_TILES) {
#pragma unroll
            for (int s = 0; s < 2; s++) {
                constexpr int i0 = IDX_WO;
                const int idx = i0 + s;
                mbar_wait(bar_full + 8 * (idx % NST), (idx / NST) & 1);
                const uint32_t tb = sbase + SM_RING + (idx % NST) * TILE + aoff;
#pragma unroll
                for (int mt = 0; mt < 4; mt++) ldsm4t(tb ^ (mt << 5), wf[s * 4 + mt]);
            }
        }
        {
            const int hq = cta >> 2, kvh = hq >> 2, hh = hq & 3, ds = cta & 3;
            const int b = tid >> 7, dpl = (tid >> 3) & 15, j = tid & 7;
            const int pc = (b * 8 + kvh) * 8 + j;
            const uint2* po = &sc->part_o[pc][hh][ds * 16 + dpl];
            const uint2* pm = &sc->part_ml[pc - j][hh][0];
            uint2 vo, vm[8];
            bool oko = false, okm = false;
            for (int it = 0;; it++) {
                if (!oko) vo = ld_ll2(po);
                if (!okm) {
#pragma unroll
                    for (int jj = 0; jj < 8; jj++) vm[jj] = ld_ll2(pm + jj * 16);
                }
                oko = (vo.x & vo.y & 3u) == F_PART;
                uint32_t all = vm[0].x & vm[0].y;
#pragma unroll
                for (int jj = 1; jj < 8; jj++) all &= vm[jj].x & vm[jj].y;
                okm = (all & 3u) == F_PART;
                if (__all_sync(0xffffffffu, oko && okm) || it > SPIN_LIMIT) break;
            }
            float M = untag(vm[0].x);
#pragma unroll
            for (int jj = 1; jj < 8; jj++) M = fmaxf(M, untag(vm[jj].x));
            float wt = 0.f, L = 0.f;
#pragma unroll
            for (int jj = 0; jj < 8; jj++) {
                const float w_ = ex2((untag(vm[jj].x) - M) * LOG2E);
                L += w_ * untag(vm[jj].y);
                wt = jj == j ? w_ : wt;
            }
            float o0 = wt * untag(vo.x), o1 = wt * untag(vo.y);
#pragma unroll
            for (int o_ = 1; o_ < 8; o_ <<= 1) {
                o0 += __shfl_xor_sync(0xffffffffu, o0, o_);
                o1 += __shfl_xor_sync(0xffffffffu, o1, o_);
            }
            uint32_t* os = (uint32_t*)(sgen + SM_OS);
            const float rl = rcp_approx(L);
            if (j == 0) os[b * 16 + dpl] = pack_bf16(o0 * rl, o1 * rl);
            if (warp == 0) TSTAMP(15);
            if (WO_AT == KV_TILES) {
#pragma unroll
            for (int s = 0; s < 2; s++) {
                constexpr int i0 = IDX_WO;
                const int idx = i0 + s;
                mbar_wait(bar_full + 8 * (idx % NST), (idx / NST) & 1);
                const uint32_t tb = sbase + SM_RING + (idx % NST) * TILE + aoff;
#pragma unroll
                for (int mt = 0; mt < 4; mt++) ldsm4t(tb ^ (mt << 5), wf[s * 4 + mt]);
            }
            }
            cons_sync();
            if (tid == 0) mbar_arrive(bar_trig + 8 * 3);
            if (warp == 0) TSTAMP(7);
            float y[4][4] = {};
#pragma unroll
            for (int s = 0; s < 2; s++) {
                const uint32_t b0 = os[bb * 16 + 8 * s + t], b1 = os[bb * 16 + 8 * s + 4 + t];
#pragma unroll
                for (int mt = 0; mt < 4; mt++) mma16816(y[mt], wf[s * 4 + mt], b0, b1);
            }
            float v[4];
#pragma unroll
            for (int i = 0; i < 4; i++) v[i] = t == 0 ? y[0][i] : t == 1 ? y[1][i] : t == 2 ? y[2][i] : y[3][i];
            {
                const bool odd = g & 1;
                const float sx = odd ? v[0] : v[2], sy = odd ? v[1] : v[3];
                const float rx = __shfl_xor_sync(0xffffffffu, sx, 4), ry = __shfl_xor_sync(0xffffffffu, sy, 4);
                const int c0 = 64 * warp + 16 * t + (odd ? g + 7 : g);
                const float e0 = odd ? rx : v[0], e1 = odd ? ry : v[1], e2 = odd ? v[2] : rx, e3 = odd ? v[3] : ry;
                st_v4(&sc->inbox[c0 >> 2][cta][(c0 >> 1) & 1], tagf(e0, F_WO), tagf(e1, F_WO), tagf(e2, F_WO), tagf(e3, F_WO));
            }
        }
        if (tid == 0) mbar_arrive(bar_trig + 8 * 4);
        if (warp == 0) TSTAMP(8);
        float xm0 = 0.f, xm1 = 0.f;
#define DRAIN_POLLS() { }
        {
            float r0;
            {
                const uint4* pin = &sc->inbox[cta][0][0] + tid;
                uint4 v = make_uint4(F_WO, F_WO, F_WO, F_WO);
                spin_cycles(DELAY_B1);
                bool ok = tid >= NCTA * 2;
                for (int it = 0;; it++) {
                    if (!ok) {
                        v = ld_ll4(pin);
                        ok = ((v.x & v.y & v.z & v.w & 3u) == F_WO) && (((v.x | v.y | v.z | v.w) & 3u) == F_WO);
                    }
                    if (__all_sync(0xffffffffu, ok) || it > SPIN_LIMIT) break;
                }
                const bool u1 = lane & 2, u2 = lane & 4;
                const float a0 = untag(v.x), a1 = untag(v.y), a2 = untag(v.z), a3 = untag(v.w);
                const float k0 = (u1 ? a1 : a0) + __shfl_xor_sync(0xffffffffu, u1 ? a0 : a1, 2);
                const float k1 = (u1 ? a3 : a2) + __shfl_xor_sync(0xffffffffu, u1 ? a2 : a3, 2);
                r0 = (u2 ? k1 : k0) + __shfl_xor_sync(0xffffffffu, u2 ? k0 : k1, 4);
                r0 += __shfl_xor_sync(0xffffffffu, r0, 8);
                r0 += __shfl_xor_sync(0xffffffffu, r0, 16);
                if (lane < 8) red2[warp * 8 + (2 * (lane & 1) + ((lane >> 2) & 1)) * 2 + ((lane >> 1) & 1)] = r0;
            }
            cons_sync();
            if (tid == 32) mbar_arrive(bar_trig + 8 * 5);
            if (warp == 0) {
                float a0 = 0.f, a1 = 0.f;
#pragma unroll
                for (int w = 0; w < 8; w++) { const float2 v = *(const float2*)&red2[w * 8 + (lane & 3) * 2]; a0 += v.x; a1 += v.y; }
                const bool hi = ocol & 1;
                const float ga0 = hi ? bf_hi(m_ga0.x) : bf_lo(m_ga0.x), ga1 = hi ? bf_hi(m_ga1.x) : bf_lo(m_ga1.x);
                xm0 = bf16r(xo0 + bf16r(ga0 * bf16r(a0)));
                xm1 = bf16r(xo1 + bf16r(ga1 * bf16r(a1)));
                if (lane < 4) st_ll2(&sc->x1[cta][lane], pack_bf16(xm0, xm1), F_X1);
                TSTAMP(10);
            }
            DRAIN_POLLS()
        }
        if (cta < NFFN) {
            const uint4* px = (const uint4*)&sc->x1[ec >> 2][0];
            const uint4* pp = (const uint4*)&sc->x1[0][0];
            uint4 va, vb, pa, pb;
            uint32_t gf[4][4], uf[4][4];
            if (GU_PIECES && IDX_WG >= kv_idx(KV_TILES - 1) + 2) {
                mbar_wait(bar_gu + 8 * (2 * (warp >> 1)), 0);
                mbar_wait(bar_gu + 8 * (2 * (warp >> 1) + 1), 0);
            } else {
                mbar_wait(bar_full + 8 * (IDX_WG % NST), (IDX_WG / NST) & 1);
                mbar_wait(bar_full + 8 * (IDX_WU % NST), (IDX_WU / NST) & 1);
            }
            {
                const uint32_t tg = sbase + SM_RING + (IDX_WG % NST) * TILE, tu = sbase + SM_RING + (IDX_WU % NST) * TILE;
#pragma unroll
                for (int s = 0; s < 4; s++) {
                    const int row = 64 * warp + 16 * s + (lane & 7) + (lane >> 4) * 8;
                    const uint32_t off = row * 32 + ((((lane >> 3) & 1) ^ ((row >> 2) & 1)) << 4);
                    ldsm4t(tg + off, gf[s]);
                    ldsm4t(tu + off, uf[s]);
                }
            }
            const float c1v[4] = {bf16r(1.0f + bf_lo(m_cb.x)), bf16r(1.0f + bf_hi(m_cb.x)), bf16r(1.0f + bf_lo(m_cb.z)), bf16r(1.0f + bf_hi(m_cb.z))};
            float bg = 0.f, cgc = 0.f, bu = 0.f, cuc = 0.f;
            {
                uint32_t* pre = (uint32_t*)(sgen + SM_MRG) + warp * 128;
                float* bc = (float*)(sgen + SM_MRG + 4096);
                *(uint2*)&pre[eb * 32 + 2 * (lane & 15)] = make_uint2(pack_bf16(c1v[0], c1v[1]), pack_bf16(c1v[2], c1v[3]));
                *(uint2*)&pre[64 + eb * 32 + 2 * (lane & 15)] = make_uint2(m_sb.x, m_sb.z);
                __syncwarp();
                float yg[4] = {}, yu[4] = {};
                const uint32_t* pb = pre + ((g >> 1) & 1) * 64 + bb * 32 + t;
#pragma unroll
                for (int s = 0; s < 4; s++) {
                    const uint32_t b0 = pb[8 * s], b1 = pb[8 * s + 4];
                    mma16816(yg, gf[s], b0, b1);
                    mma16816(yu, uf[s], b0, b1);
                }
                const float y0 = t < 2 ? yg[0] : yu[0], y1 = t < 2 ? yg[1] : yu[1], y2 = t < 2 ? yg[2] : yu[2], y3 = t < 2 ? yg[3] : yu[3];
                float* dstp = bc + warp * 128 + (t >> 1) * 64 + (t & 1) * 32;
                *(float2*)&dstp[g * 2] = make_float2(y0, y1);
                *(float2*)&dstp[(g + 8) * 2] = make_float2(y2, y3);
                __syncwarp();
                if (lane == 0) mbar_arrive(bar_bc);
            }
            if (warp == 0) TSTAMP(11);
            float pivot2;
            {
                spin_cycles(DELAY_B2);
                bool okx = false, okp = false;
                for (int it = 0;; it++) {
                    if (!okx) { va = ld_ll4(px); vb = ld_ll4(px + 1); }
                    if (!okp) { pa = ld_ll4(pp); pb = ld_ll4(pp + 1); }
                    okx = va.y == F_X1 && va.w == F_X1 && vb.y == F_X1 && vb.w == F_X1;
                    okp = pa.y == F_X1 && pa.w == F_X1 && pb.y == F_X1 && pb.w == F_X1;
                    if (__all_sync(0xffffffffu, okx && okp) || it > SPIN_LIMIT) break;
                }
                if (warp == 0) TSTAMP(9);
                const float xv[4] = {eb ? bf_hi(va.x) : bf_lo(va.x), eb ? bf_hi(va.z) : bf_lo(va.z),
                                     eb ? bf_hi(vb.x) : bf_lo(vb.x), eb ? bf_hi(vb.z) : bf_lo(vb.z)};
                const float p0 = 0.25f * ((bf_lo(pa.x) + bf_lo(pa.z)) + (bf_lo(pb.x) + bf_lo(pb.z)));
                const float p1 = 0.25f * ((bf_hi(pa.x) + bf_hi(pa.z)) + (bf_hi(pb.x) + bf_hi(pb.z)));
                const float pivot = eb ? p1 : p0;
                pivot2 = (lane & 1) ? p1 : p0;
                *(uint2*)&hs[eb * 32 + 2 * (lane & 15)] =
                    make_uint2(pack_bf16((xv[0] - pivot) * c1v[0], (xv[1] - pivot) * c1v[1]),
                               pack_bf16((xv[2] - pivot) * c1v[2], (xv[3] - pivot) * c1v[3]));
                __syncwarp();
                float cg[2][4] = {}, cu[2][4] = {};
#pragma unroll
                for (int s = 0; s < 4; s++) {
                    const uint32_t b0 = hs[bb * 32 + 8 * s + t], b1 = hs[bb * 32 + 8 * s + 4 + t];
                    mma16816(cg[s & 1], gf[s], b0, b1);
                    mma16816(cu[s & 1], uf[s], b0, b1);
                }
                const float2 ps = half_warp_sums(xv, pivot);
                if ((lane & 15) == 0) stat[warp * 2 + eb] = ps;
                {
                    const float* bc = (const float*)(sgen + SM_MRG + 4096);
                    mbar_wait(bar_bc, 0);
#pragma unroll
                    for (int w = 0; w < 8; w++) {
                        bg += bc[w * 128 + lane]; cgc += bc[w * 128 + 32 + lane];
                        bu += bc[w * 128 + 64 + lane]; cuc += bc[w * 128 + 96 + lane];
                    }
                }
                if (t < 2) {
                    float v[4];
#pragma unroll
                    for (int i = 0; i < 4; i++) v[i] = t ? cu[0][i] + cu[1][i] : cg[0][i] + cg[1][i];
                    *(float2*)&red[warp * 64 + t * 32 + g * 2] = make_float2(v[0], v[1]);
                    *(float2*)&red[warp * 64 + t * 32 + (g + 8) * 2] = make_float2(v[2], v[3]);
                }
            }
            uint32_t df[4][4];
            mbar_wait(bar_full + 8 * (IDX_WD % NST), (IDX_WD / NST) & 1);
#pragma unroll
            for (int mt = 0; mt < 4; mt++) ldsm4t((sbase + SM_RING + (IDX_WD % NST) * TILE + aoff) ^ (mt << 5), df[mt]);
            cons_sync();
            {
                float gs = 0.f, us = 0.f;
#pragma unroll
                for (int w = 0; w < 8; w++) { gs += red[w * 64 + lane]; us += red[w * 64 + 32 + lane]; }
                float mean_bf, rstd;
                ln_stats(stat, lane & 1, pivot2, mean_bf, rstd);
                const float dm = mean_bf - pivot2;
                gs = bf16r(rstd * (gs - dm * bg) + cgc);
                us = rstd * (us - dm * bu) + cuc;
                const float u2 = gs * (1.0f + 0.044715f * gs * gs) * (2.0f * 0.7978845608028654f * LOG2E);
                const float ge = bf16r(__fdividef(gs, 1.0f + ex2(-u2)));
                const float act = bf16r(ge * bf16r(us));
                const float a0 = __shfl_sync(0xffffffffu, act, 4 * t + bb), a1 = __shfl_sync(0xffffffffu, act, 4 * t + 2 + bb);
                const float a2 = __shfl_sync(0xffffffffu, act, 4 * t + 16 + bb), a3 = __shfl_sync(0xffffffffu, act, 4 * t + 18 + bb);
                const uint32_t b0 = pack_bf16(a0, a1), b1 = pack_bf16(a2, a3);
                float y[4][4] = {};
#pragma unroll
                for (int mt = 0; mt < 4; mt++) mma16816(y[mt], df[mt], b0, b1);
                float v[4];
#pragma unroll
                for (int i = 0; i < 4; i++) v[i] = t == 0 ? y[0][i] : t == 1 ? y[1][i] : t == 2 ? y[2][i] : y[3][i];
            {
                const bool odd = g & 1;
                const float sx = odd ? v[0] : v[2], sy = odd ? v[1] : v[3];
                const float rx = __shfl_xor_sync(0xffffffffu, sx, 4), ry = __shfl_xor_sync(0xffffffffu, sy, 4);
                const int c0 = 64 * warp + 16 * t + (odd ? g + 7 : g);
                const float e0 = odd ? rx : v[0], e1 = odd ? ry : v[1], e2 = odd ? v[2] : rx, e3 = odd ? v[3] : ry;
                st_v4(&sc->inbox[c0 >> 2][cta][(c0 >> 1) & 1], tagf(e0, F_DOWN), tagf(e1, F_DOWN), tagf(e2, F_DOWN), tagf(e3, F_DOWN));
            }
            }
            if (warp == 0) TSTAMP(12);
        }
        {
            float r0;
            {
                const uint4* pin = &sc->inbox[cta][0][0] + tid;
                uint4 v = make_uint4(F_DOWN, F_DOWN, F_DOWN, F_DOWN);
                spin_cycles(DELAY_C);
                bool ok = tid >= NFFN * 2;
                for (int it = 0;; it++) {
                    if (!ok) {
                        v = ld_ll4(pin);
                        ok = ((v.x & v.y & v.z & v.w & 3u) == F_DOWN) && (((v.x | v.y | v.z | v.w) & 3u) == F_DOWN);
                    }
                    if (__all_sync(0xffffffffu, ok) || it > SPIN_LIMIT) break;
                }
                const bool u1 = lane & 2, u2 = lane & 4;
                const float a0 = untag(v.x), a1 = untag(v.y), a2 = untag(v.z), a3 = untag(v.w);
                const float k0 = (u1 ? a1 : a0) + __shfl_xor_sync(0xffffffffu, u1 ? a0 : a1, 2);
                const float k1 = (u1 ? a3 : a2) + __shfl_xor_sync(0xffffffffu, u1 ? a2 : a3, 2);
                r0 = (u2 ? k1 : k0) + __shfl_xor_sync(0xffffffffu, u2 ? k0 : k1, 4);
                r0 += __shfl_xor_sync(0xffffffffu, r0, 8);
                r0 += __shfl_xor_sync(0xffffffffu, r0, 16);
                if (lane < 8) red2[64 + warp * 8 + (2 * (lane & 1) + ((lane >> 2) & 1)) * 2 + ((lane >> 1) & 1)] = r0;
            }
            cons_sync();
            if (warp == 0) {
                float a0 = 0.f, a1 = 0.f;
#pragma unroll
                for (int w = 0; w < 8; w++) { const float2 v = *(const float2*)&red2[64 + w * 8 + (lane & 3) * 2]; a0 += v.x; a1 += v.y; }
                const bool hi = ocol & 1;
                const float gb0 = hi ? bf_hi(m_gb0.x) : bf_lo(m_gb0.x), gb1 = hi ? bf_hi(m_gb1.x) : bf_lo(m_gb1.x);
                if (lane < 4) {
                    p.out[ocol] = __float2bfloat16_rn(xm0 + bf16r(gb0 * bf16r(a0)));
                    p.out[D_MODEL + ocol] = __float2bfloat16_rn(xm1 + bf16r(gb1 * bf16r(a1)));
                }
                if (cta == 0 && lane == 0) *(volatile unsigned*)&sc->epoch = tag;
                TSTAMP(13);
            }
            DRAIN_POLLS()
        }
    }
}

typedef CUresult (*EncodeFn)(CUtensorMap*, CUtensorMapDataType, cuuint32_t, void*, const cuuint64_t*, const cuuint64_t*,
                             const cuuint32_t*, const cuuint32_t*, CUtensorMapInterleave, CUtensorMapSwizzle,
                             CUtensorMapL2promotion, CUtensorMapFloatOOBfill);

struct Maps { CUtensorMap k, v, wq, wmod, wmod8, wo, wg, wu, wd; };

void encode(EncodeFn fn, CUtensorMap* m, const void* ptr, int rank, const cuuint64_t* dims, const cuuint64_t* strides,
            const cuuint32_t* box, CUtensorMapSwizzle sw) {
    const cuuint32_t es[3] = {1, 1, 1};
    fn(m, CU_TENSOR_MAP_DATA_TYPE_BFLOAT16, rank, const_cast<void*>(ptr), dims, strides, box, es,
       CU_TENSOR_MAP_INTERLEAVE_NONE, sw, CU_TENSOR_MAP_L2_PROMOTION_L2_256B, CU_TENSOR_MAP_FLOAT_OOB_FILL_NONE);
}

}

extern "C" void kernel_launch(void* const* d_in, const int* in_sizes, int n_in, void* d_out, int out_size) {
    (void)in_sizes; (void)n_in; (void)out_size;
    static EncodeFn enc = nullptr;
    static Scratch* scratch = nullptr;
    if (!enc) {
        cudaGetSymbolAddress((void**)&scratch, g_scratch);
        void* fn = nullptr;
        cudaDriverEntryPointQueryResult qr;
        cudaGetDriverEntryPoint("cuTensorMapEncodeTiled", &fn, cudaEnableDefault, &qr);
        enc = (EncodeFn)fn;
        cudaFuncSetAttribute(fused_block_kernel, cudaFuncAttributeMaxDynamicSharedMemorySize, SMEM_BYTES);
    }
    Maps m;
    {
        const cuuint64_t dims[3] = {64, (cuuint64_t)16 * SK, 2}, str[2] = {256, 128};
        const cuuint32_t box[3] = {64, 64, 2};
        encode(enc, &m.k, d_in[1], 3, dims, str, box, CU_TENSOR_MAP_SWIZZLE_128B);
        encode(enc, &m.v, d_in[2], 3, dims, str, box, CU_TENSOR_MAP_SWIZZLE_128B);
    }
    {
        const cuuint64_t dims[2] = {4096, 512}, str[1] = {8192};
        const cuuint32_t box[2] = {32, 256};
        encode(enc, &m.wq, d_in[3], 2, dims, str, box, CU_TENSOR_MAP_SWIZZLE_64B);
    }
    {
        const cuuint64_t dims[2] = {N_MOD, 512}, str[1] = {N_MOD * 2};
        const cuuint32_t box[2] = {16, 256};
        encode(enc, &m.wmod, d_in[10], 2, dims, str, box, CU_TENSOR_MAP_SWIZZLE_32B);
        const cuuint32_t box8[2] = {8, 256};
        encode(enc, &m.wmod8, d_in[10], 2, dims, str, box8, CU_TENSOR_MAP_SWIZZLE_NONE);
    }
    {
        const cuuint64_t dims_o[3] = {64, 4096, 8}, dims_d[3] = {64, D_FF, 8}, str[2] = {1024, 128};
        const cuuint32_t box[3] = {64, 16, 8};
        encode(enc, &m.wo, d_in[4], 3, dims_o, str, box, CU_TENSOR_MAP_SWIZZLE_128B);
        encode(enc, &m.wd, d_in[8], 3, dims_d, str, box, CU_TENSOR_MAP_SWIZZLE_128B);
    }
    {
        const cuuint64_t dims[2] = {D_FF, 512}, str[1] = {D_FF * 2};
        const cuuint32_t box[2] = {16, 128};
        encode(enc, &m.wg, d_in[6], 2, dims, str, box, CU_TENSOR_MAP_SWIZZLE_32B);
        encode(enc, &m.wu, d_in[7], 2, dims, str, box, CU_TENSOR_MAP_SWIZZLE_32B);
    }
    Params p;
    p.x = (const __nv_bfloat16*)d_in[0];
    p.c = (const __nv_bfloat16*)d_in[9];
    p.w_mod = (const __nv_bfloat16*)d_in[10];
    p.out = (__nv_bfloat16*)d_out;
    p.sc = scratch;
    p.wo = (const __nv_bfloat16*)d_in[4];
    p.wg = (const __nv_bfloat16*)d_in[6];
    p.wu = (const __nv_bfloat16*)d_in[7];
    p.wd = (const __nv_bfloat16*)d_in[8];
    fused_block_kernel<<<NCTA, NTHREADS, SMEM_BYTES, cudaStreamPerThread>>>(p, m.k, m.v, m.wq, m.wmod, m.wmod8, m.wo, m.wg, m.wu, m.wd);
}
```

```cpp
#include <cuda_runtime.h>
#include <cuda.h>
#include <cuda_bf16.h>
#include <stdint.h>

namespace {

constexpr int D_MODEL = 512;
constexpr int N_HEADS = 32;
constexpr int SK = 32768;
constexpr int DH = 128;
constexpr int D_FF = 1792;
constexpr int N_MOD = 6 * D_MODEL;

constexpr int NCTA = 128;
constexpr int NFFN = D_FF / 16;
constexpr int NTHREADS = 320;
constexpr int NST = 12;
constexpr int TILE = 16384;
#define WINDOW 3
#define WINDOW_TAIL 2
#define GU_WIN 3
#define PACE_THR 96
constexpr int KV_TILES = 64;
#define MOD_AT 8
static_assert(MOD_AT % 2 == 0 && MOD_AT >= 2 && MOD_AT < 56, "schedule");
__host__ __device__ constexpr int kv_idx(int i) { return 2 + 2 * i + (i >= MOD_AT ? 1 : 0); }
constexpr int IDX_MOD = 2 + 2 * MOD_AT;
constexpr int N_STREAM = kv_idx(KV_TILES - 1) + 2;
constexpr int IDX_WO = N_STREAM;
constexpr int IDX_WG = IDX_WO + 2;
constexpr int IDX_WU = IDX_WG + 1;
constexpr int IDX_WD = IDX_WU + 1;
constexpr int SPIN_LIMIT = 1 << 20;

constexpr float LOG2E = 1.4426950408889634f;
constexpr float QK_SCALE = 0.08838834764831845f;

constexpr int SM_RING = 0;
constexpr int SM_MRG = SM_RING + NST * TILE;
constexpr int SM_ML = SM_MRG + 8 * 4 * 136 * 4;
constexpr int SM_RED = SM_ML + 8 * 4 * 8;
constexpr int SM_RED2 = SM_RED + 8 * 64 * 4;
constexpr int SM_QS = SM_RED2 + 8 * 64 * 4;
constexpr int SM_OS = SM_QS + 512 * 2;
constexpr int SM_SC = SM_OS + 2 * 16 * 4;
constexpr int SM_HS = SM_SC + 2 * 512 * 2;
constexpr int SM_STAT = SM_HS + 8 * 2 * 32 * 4;
constexpr int SM_PACE = SM_STAT + 8 * 2 * 8;
constexpr int SM_BAR = SM_PACE + 8;
constexpr int SM_END = SM_BAR + (2 * NST + 1 + 8 + 2) * 8;
constexpr int SMEM_BYTES = SM_END + 1024;

struct Scratch {
    uint4 inbox[NCTA][NCTA][2];
    uint2 x1[NCTA][16];
    uint2 part_o[NCTA][4][64];
    uint2 part_ml[NCTA][4][4];
    uint2 mod[2][N_MOD / 2];
    uint2 q[2][N_HEADS * DH / 2];
    unsigned epoch;
    unsigned pad_[31];
    unsigned cleared;
    unsigned pad2_[31];
    unsigned progress;
};
__device__ Scratch g_scratch;
constexpr uint32_t F_PART = 1, F_WO = 1, F_DOWN = 2, F_X1 = 1;
__device__ __forceinline__ uint32_t tagf(float v, uint32_t f) { return (__float_as_uint(v) & ~3u) | f; }
__device__ __forceinline__ float untag(uint32_t v) { return __uint_as_float(v & ~3u); }

struct Params {
    const __nv_bfloat16* x;
    const __nv_bfloat16* c;
    __nv_bfloat16* out;
    Scratch* sc;
};

#define TSTAMP(i) do { } while (0)

__device__ __forceinline__ uint32_t smem_u32(const void* p) { return (uint32_t)__cvta_generic_to_shared(p); }

__device__ __forceinline__ void mbar_init(uint32_t bar, uint32_t cnt) {
    asm volatile("mbarrier.init.shared::cta.b64 [%0], %1;" ::"r"(bar), "r"(cnt) : "memory");
}
__device__ __forceinline__ void mbar_expect_tx(uint32_t bar, uint32_t bytes) {
    asm volatile("mbarrier.arrive.expect_tx.shared::cta.b64 _, [%0], %1;" ::"r"(bar), "r"(bytes) : "memory");
}
__device__ __forceinline__ void mbar_arrive(uint32_t bar) {
    asm volatile("mbarrier.arrive.shared::cta.b64 _, [%0];" ::"r"(bar) : "memory");
}
__device__ __forceinline__ bool mbar_try(uint32_t bar, uint32_t parity) {
    uint32_t ok;
    asm volatile(
        "{\n\t.reg .pred p;\n\t"
        "mbarrier.try_wait.parity.shared::cta.b64 p, [%1], %2;\n\t"
        "selp.u32 %0, 1, 0, p;\n\t}"
        : "=r"(ok) : "r"(bar), "r"(parity) : "memory");
    return ok != 0;
}
__device__ __forceinline__ void mbar_wait(uint32_t bar, uint32_t parity) {
    if (mbar_try(bar, parity)) return;
    const long long t0 = clock64();
    while (!mbar_try(bar, parity))
        if (clock64() - t0 > (1ll << 31)) return;
}
__device__ __forceinline__ void cons_sync() { asm volatile("bar.sync 1, 256;" ::: "memory"); }

__device__ __forceinline__ void tma_2d(uint32_t dst, const CUtensorMap* m, int c0, int c1, uint32_t bar) {
    asm volatile("cp.async.bulk.tensor.2d.shared::cluster.global.mbarrier::complete_tx::bytes [%0], [%1, {%3, %4}], [%2];"
                 ::"r"(dst), "l"(m), "r"(bar), "r"(c0), "r"(c1) : "memory");
}
__device__ __forceinline__ void tma_3d(uint32_t dst, const CUtensorMap* m, int c0, int c1, int c2, uint32_t bar) {
    asm volatile("cp.async.bulk.tensor.3d.shared::cluster.global.mbarrier::complete_tx::bytes [%0], [%1, {%3, %4, %5}], [%2];"
                 ::"r"(dst), "l"(m), "r"(bar), "r"(c0), "r"(c1), "r"(c2) : "memory");
}
__device__ __forceinline__ void tma_3d_hint(uint32_t dst, const CUtensorMap* m, int c0, int c1, int c2, uint32_t bar, uint64_t pol) {
    asm volatile("cp.async.bulk.tensor.3d.shared::cluster.global.mbarrier::complete_tx::bytes.L2::cache_hint [%0], [%1, {%3, %4, %5}], [%2], %6;"
                 ::"r"(dst), "l"(m), "r"(bar), "r"(c0), "r"(c1), "r"(c2), "l"(pol) : "memory");
}
__device__ __forceinline__ void prefetch_tmap(const CUtensorMap* m) {
    asm volatile("prefetch.tensormap [%0];" ::"l"(m) : "memory");
}

__device__ __forceinline__ void ldsm4(uint32_t addr, uint32_t (&r)[4]) {
    asm volatile("ldmatrix.sync.aligned.m8n8.x4.shared.b16 {%0,%1,%2,%3}, [%4];"
                 : "=r"(r[0]), "=r"(r[1]), "=r"(r[2]), "=r"(r[3]) : "r"(addr) : "memory");
}
__device__ __forceinline__ void ldsm4t(uint32_t addr, uint32_t (&r)[4]) {
    asm volatile("ldmatrix.sync.aligned.m8n8.x4.trans.shared.b16 {%0,%1,%2,%3}, [%4];"
                 : "=r"(r[0]), "=r"(r[1]), "=r"(r[2]), "=r"(r[3]) : "r"(addr) : "memory");
}
__device__ __forceinline__ void mma16816(float (&c)[4], const uint32_t (&a)[4], uint32_t b0, uint32_t b1) {
    asm volatile("mma.sync.aligned.m16n8k16.row.col.f32.bf16.bf16.f32 {%0,%1,%2,%3}, {%4,%5,%6,%7}, {%8,%9}, {%0,%1,%2,%3};"
                 : "+f"(c[0]), "+f"(c[1]), "+f"(c[2]), "+f"(c[3])
                 : "r"(a[0]), "r"(a[1]), "r"(a[2]), "r"(a[3]), "r"(b0), "r"(b1));
}
__device__ __forceinline__ uint32_t movmatrix_t(uint32_t a) {
    uint32_t d;
    asm volatile("movmatrix.sync.aligned.m8n8.trans.b16 %0, %1;" : "=r"(d) : "r"(a));
    return d;
}
__device__ __forceinline__ uint32_t pack_bf16(float a, float b) {
    uint32_t r;
    asm("cvt.rn.bf16x2.f32 %0, %1, %2;" : "=r"(r) : "f"(b), "f"(a));
    return r;
}
__device__ __forceinline__ float bf_lo(uint32_t v) { return __uint_as_float(v << 16); }
__device__ __forceinline__ float bf_hi(uint32_t v) { return __uint_as_float(v & 0xffff0000u); }
__device__ __forceinline__ float bf16r(float a) { return bf_lo(pack_bf16(a, 0.f)); }
__device__ __forceinline__ uint32_t max_bf16x2(uint32_t a, uint32_t b) {
    uint32_t r;
    asm("max.bf16x2 %0, %1, %2;" : "=r"(r) : "r"(a), "r"(b));
    return r;
}
__device__ __forceinline__ float ex2(float x) {
    float r;
    asm("ex2.approx.ftz.f32 %0, %1;" : "=f"(r) : "f"(x));
    return r;
}

__device__ __forceinline__ void st_ll2(uint2* p, uint32_t v, uint32_t tag) {
    asm volatile("st.relaxed.gpu.global.v2.u32 [%0], {%1, %2};" ::"l"(p), "r"(v), "r"(tag) : "memory");
}
__device__ __forceinline__ void st_ll4(uint4* p, uint32_t v0, uint32_t v1, uint32_t tag) {
    asm volatile("st.relaxed.gpu.global.v4.u32 [%0], {%1, %2, %3, %2};" ::"l"(p), "r"(v0), "r"(tag), "r"(v1) : "memory");
}
__device__ __forceinline__ void st_v4(uint4* p, uint32_t a, uint32_t b, uint32_t c, uint32_t d) {
    asm volatile("st.relaxed.gpu.global.v4.u32 [%0], {%1, %2, %3, %4};" ::"l"(p), "r"(a), "r"(b), "r"(c), "r"(d) : "memory");
}
__device__ __forceinline__ uint2 ld_ll2(const uint2* p) {
    uint2 v;
    asm volatile("ld.relaxed.gpu.global.v2.u32 {%0, %1}, [%2];" : "=r"(v.x), "=r"(v.y) : "l"(p) : "memory");
    return v;
}
__device__ __forceinline__ uint4 ld_ll4(const uint4* p) {
    uint4 v;
    asm volatile("ld.relaxed.gpu.global.v4.u32 {%0, %1, %2, %3}, [%4];"
                 : "=r"(v.x), "=r"(v.y), "=r"(v.z), "=r"(v.w) : "l"(p) : "memory");
    return v;
}

#define DELAY_B1 450
#define DELAY_C 450
__device__ __forceinline__ uint32_t clock32() {
    uint32_t c;
    asm volatile("mov.u32 %0, %clock;" : "=r"(c));
    return c;
}
__device__ __forceinline__ void spin_cycles(uint32_t n) {
    if (n > 0) { const uint32_t c0 = clock32(); while (clock32() - c0 < n) {} }
}
__device__ __forceinline__ float rcp_approx(float x) {
    float r;
    asm("rcp.approx.ftz.f32 %0, %1;" : "=f"(r) : "f"(x));
    return r;
}
__device__ __forceinline__ float sqrt_approx(float x) {
    float r;
    asm("sqrt.approx.f32 %0, %1;" : "=f"(r) : "f"(x));
    return r;
}

__device__ __forceinline__ float silu_bf(float v) { return bf16r(v / (1.0f + expf(-v))); }

__device__ __forceinline__ float2 half_warp_sums(const float (&v)[4], float pivot) {
    float s1 = 0.f, s2 = 0.f;
#pragma unroll
    for (int i = 0; i < 4; i++) { const float d = v[i] - pivot; s1 += d; s2 += d * d; }
#pragma unroll
    for (int o = 1; o < 16; o <<= 1) { s1 += __shfl_xor_sync(0xffffffffu, s1, o); s2 += __shfl_xor_sync(0xffffffffu, s2, o); }
    return make_float2(s1, s2);
}
__device__ __forceinline__ void ln_stats(const float2* stat, int b, float pivot, float& mean_bf, float& rstd) {
    float s1 = 0.f, s2 = 0.f;
#pragma unroll
    for (int w = 0; w < 8; w++) { const float2 v = stat[w * 2 + b]; s1 += v.x; s2 += v.y; }
    const float dm = s1 * (1.0f / D_MODEL);
    const float var = fmaxf(s2 * (1.0f / D_MODEL) - dm * dm, 0.f);
    mean_bf = bf16r(pivot + dm);
    rstd = rcp_approx(bf16r(sqrt_approx(bf16r(bf16r(var) + 1e-5f))));
}
__device__ __forceinline__ float ln_norm(float xv, float mean_bf, float rstd) { return bf16r(bf16r(xv - mean_bf) * rstd); }
__device__ __forceinline__ float ln_mod(float n, float cmul, float sadd) { return bf16r(n * bf16r(1.0f + cmul)) + sadd; }

__global__ void __launch_bounds__(NTHREADS, 1)
fused_block_kernel(const Params p, const __grid_constant__ CUtensorMap tm_k, const __grid_constant__ CUtensorMap tm_v,
                   const __grid_constant__ CUtensorMap tm_wq, const __grid_constant__ CUtensorMap tm_wmod,
                   const __grid_constant__ CUtensorMap tm_wmod8,
                   const __grid_constant__ CUtensorMap tm_wo, const __grid_constant__ CUtensorMap tm_wg,
                   const __grid_constant__ CUtensorMap tm_wu, const __grid_constant__ CUtensorMap tm_wd) {
    extern __shared__ unsigned char smem_raw[];
    const uint32_t sbase = (smem_u32(smem_raw) + 1023u) & ~1023u;
    unsigned char* sgen = smem_raw + (sbase - smem_u32(smem_raw));
    const int tid = threadIdx.x, warp = tid >> 5, lane = tid & 31;
    const int cta = blockIdx.x;
    const uint32_t bar_full = sbase + SM_BAR, bar_empty = bar_full + NST * 8;
    const uint32_t bar_clear = bar_empty + NST * 8;
    const uint32_t bar_gu = bar_clear + 8;
    const uint32_t bar_bc = bar_gu + 8 * 8;
    const uint32_t bar_p0w = bar_bc + 8;

    const int key0 = (cta >> 3) * SK + (cta & 7) * 64;
    uint64_t pol = 0;
    if (tid == 256) {
        asm volatile("createpolicy.fractional.L2::evict_first.b64 %0, 1.0;" : "=l"(pol));
        mbar_init(bar_p0w, 1);
#pragma unroll
        for (int i = 0; i < 4; i++) mbar_init(bar_full + 8 * i, 1);
        asm volatile("fence.mbarrier_init.release.cluster;" ::: "memory");
        mbar_expect_tx(bar_p0w, 8192);
        tma_2d(sbase + SM_MRG, &tm_wmod8, cta * 8, 0, bar_p0w);
        tma_2d(sbase + SM_MRG + 4096, &tm_wmod8, cta * 8, 256, bar_p0w);
#pragma unroll
        for (int i = 0; i < 4; i++) mbar_expect_tx(bar_full + 8 * i, TILE);
        tma_2d(sbase + SM_RING, &tm_wq, cta * 32, 0, bar_full);
        tma_2d(sbase + SM_RING + TILE, &tm_wq, cta * 32, 256, bar_full + 8);
        tma_3d_hint(sbase + SM_RING + 2 * TILE, &tm_k, 0, key0, 0, bar_full + 16, pol);
        tma_3d_hint(sbase + SM_RING + 3 * TILE, &tm_v, 0, key0, 0, bar_full + 24, pol);
    }

    if (warp == 8) {
        if (lane == 0) {
            for (int i = 0; i < NST; i++) { if (i >= 4) mbar_init(bar_full + 8 * i, 1); mbar_init(bar_empty + 8 * i, 4); }
            mbar_init(bar_clear, 1);
            for (int k = 0; k < 8; k++) mbar_init(bar_gu + 8 * k, 1);
            mbar_init(bar_bc, 8);
            ((volatile uint32_t*)(sgen + SM_PACE))[0] = 0;
            ((volatile uint32_t*)(sgen + SM_PACE))[1] = WINDOW;
            asm volatile("fence.mbarrier_init.release.cluster;" ::: "memory");
        }
        __syncwarp();
        asm volatile("bar.arrive 2, 320;" ::: "memory");
        asm volatile("bar.arrive 3, 64;" ::: "memory");
        if (lane == 0) {
            int slot = 4; uint32_t ph = 1;
            int landed = 0, wslot = 0; uint32_t wph = 0;
            int kv = 2;
            auto wait_window = [&](int idx, int window) {
                while (landed + window <= idx) {
                    mbar_wait(bar_full + 8 * wslot, wph);
                    if (++wslot == NST) { wslot = 0; wph ^= 1; }
                    landed++;
                }
            };
            volatile uint32_t* pace = (volatile uint32_t*)(sgen + SM_PACE);
            prefetch_tmap(&tm_wmod);
            pace[0] = 4;
            for (int idx = 4; idx < N_STREAM; idx++) {
                if (idx >= NST) mbar_wait(bar_empty + 8 * slot, ph);
                wait_window(idx, (int)pace[1]);
                if (idx == 12) { prefetch_tmap(&tm_wo); prefetch_tmap(&tm_wg); prefetch_tmap(&tm_wu); prefetch_tmap(&tm_wd); }
                const uint32_t fb = bar_full + 8 * slot, dst = sbase + SM_RING + slot * TILE;
                mbar_expect_tx(fb, TILE);
                if (idx == IDX_MOD) {
                    tma_2d(dst, &tm_wmod, 1024 + cta * 16, 0, fb);
                    tma_2d(dst + 8192, &tm_wmod, 1024 + cta * 16, 256, fb);
                } else {
                    tma_3d_hint(dst, (kv & 1) ? &tm_v : &tm_k, 0, key0 + (kv >> 1) * 512, 0, fb, pol);
                    kv++;
                }
                pace[0] = idx + 1;
                if (++slot == NST) { slot = 0; ph ^= 1; }
            }
            auto slot_free = [&](int idx) { mbar_wait(bar_empty + 8 * (idx % NST), ((idx / NST) & 1) ^ 1); };
#pragma unroll
            for (int s = 0; s < 2; s++) {
                const int idx = IDX_WO + s;
                slot_free(idx);
                wait_window(idx, WINDOW_TAIL);
                mbar_expect_tx(bar_full + 8 * (idx % NST), TILE);
                tma_3d(sbase + SM_RING + (idx % NST) * TILE, &tm_wo, 0, cta * 32 + s * 16, 0, bar_full + 8 * (idx % NST));
            }
            if (cta < NFFN) {
                slot_free(IDX_WG); slot_free(IDX_WU);
                mbar_wait(bar_full + 8 * (IDX_WO % NST), (IDX_WO / NST) & 1);
                mbar_wait(bar_full + 8 * ((IDX_WO + 1) % NST), ((IDX_WO + 1) / NST) & 1);
#pragma unroll
                for (int st = 0; st < 8; st++) {
                    if (st >= GU_WIN) mbar_wait(bar_gu + 8 * (st - GU_WIN), 0);
                    mbar_expect_tx(bar_gu + 8 * st, 4096);
                    tma_2d(sbase + SM_RING + (((st & 1) ? IDX_WU : IDX_WG) % NST) * TILE + (st >> 1) * 4096,
                           (st & 1) ? &tm_wu : &tm_wg, cta * 16, (st >> 1) * 128, bar_gu + 8 * st);
                }
                mbar_wait(bar_gu + 8 * 7, 0);
                slot_free(IDX_WD);
                mbar_expect_tx(bar_full + 8 * (IDX_WD % NST), TILE);
                tma_3d(sbase + SM_RING + (IDX_WD % NST) * TILE, &tm_wd, 0, cta * 16, 0, bar_full + 8 * (IDX_WD % NST));
            }
        }
    } else if (warp == 9) {
        Scratch* const sc = p.sc;
        const uint32_t tag = *(volatile unsigned*)&sc->epoch + 1;
        if (lane < 2) {
            st_ll4((uint4*)&sc->mod[lane][cta * 4], 0u, 0u, 0u);
            st_ll4((uint4*)&sc->mod[lane][cta * 4] + 1, 0u, 0u, 0u);
        }
        if (lane < 8) st_ll4((uint4*)&sc->mod[lane >> 2][512 + cta * 8] + (lane & 3), 0u, 0u, 0u);
        if (lane < 16) st_ll4((uint4*)&sc->q[lane >> 3][cta * 16] + (lane & 7), 0u, 0u, 0u);
        __syncwarp();
        asm volatile("bar.arrive 2, 320;" ::: "memory");
        asm volatile("bar.sync 3, 64;" ::: "memory");
#pragma unroll 4
        for (int i = 0; i < 8; i++) st_v4(&sc->inbox[cta][0][0] + i * 32 + lane, 0u, 0u, 0u, 0u);
#pragma unroll 4
        for (int i = 0; i < 4; i++) st_v4((uint4*)&sc->part_o[cta][0][0] + i * 32 + lane, 0u, 0u, 0u, 0u);
        if (lane < 8) st_v4((uint4*)&sc->part_ml[cta][0][0] + lane, 0u, 0u, 0u, 0u);
        if (lane < 2) st_v4((uint4*)&sc->x1[cta][0] + lane, 0u, 0u, 0u, 0u);
        if (cta == 0 && lane == 0) asm volatile("st.relaxed.gpu.global.u32 [%0], %1;" ::"l"(&sc->progress), "r"(0u) : "memory");
        asm volatile("fence.acq_rel.gpu;" ::: "memory");
        __syncwarp();
        if (lane == 0) {
            asm volatile("fence.acq_rel.gpu;" ::: "memory");
            asm volatile("red.relaxed.gpu.global.add.u32 [%0], %1;" ::"l"(&sc->cleared), "r"(1u) : "memory");
            const uint32_t target = tag * NCTA;
            for (int it = 0; it < SPIN_LIMIT; it++) {
                uint32_t v;
                asm volatile("ld.relaxed.gpu.global.u32 %0, [%1];" : "=r"(v) : "l"(&sc->cleared) : "memory");
                if ((int32_t)(v - target) >= 0) break;
                __nanosleep(500);
            }
            asm volatile("fence.acq_rel.gpu;" ::: "memory");
            mbar_arrive(bar_clear);
            volatile uint32_t* pace = (volatile uint32_t*)(sgen + SM_PACE);
            uint32_t posted = 0;
            for (int it = 0; it < SPIN_LIMIT; it++) {
                const uint32_t own = pace[0];
                if (own >= N_STREAM) break;
                if (own > posted) {
                    asm volatile("red.relaxed.gpu.global.add.u32 [%0], %1;" ::"l"(&sc->progress), "r"(own - posted) : "memory");
                    posted = own;
                }
                uint32_t v;
                asm volatile("ld.relaxed.gpu.global.u32 %0, [%1];" : "=r"(v) : "l"(&sc->progress) : "memory");
                const int diff = (int)v - (int)own * NCTA;
                pace[1] = diff > PACE_THR ? WINDOW + 1 : diff < -PACE_THR ? WINDOW - 1 : WINDOW;
                __nanosleep(200);
            }
        }
    } else {
        const int g = lane >> 2, t = lane & 3;
        const int bb = g & 1;
        const int eb = lane >> 4;
        const int ec = 64 * warp + 4 * (lane & 15);
        if (warp == 0) TSTAMP(0);
        Scratch* const sc = p.sc;
        const float c00 = __bfloat162float(p.c[tid]), c01 = __bfloat162float(p.c[tid + 256]);
        const float c10 = __bfloat162float(p.c[D_MODEL + tid]), c11 = __bfloat162float(p.c[D_MODEL + tid + 256]);
        const uint2 xe = __ldg((const uint2*)(p.x + eb * D_MODEL + ec));
        const float xpivot = __bfloat162float(p.x[eb * D_MODEL]);
        const uint32_t tag = *(volatile unsigned*)&sc->epoch + 1;
        const int ocol = cta * 4 + (lane & 3);
        const float xo0 = __bfloat162float(p.x[ocol]), xo1 = __bfloat162float(p.x[D_MODEL + ocol]);

        float* red = (float*)(sgen + SM_RED);
        float* red2 = (float*)(sgen + SM_RED2);
        float2* stat = (float2*)(sgen + SM_STAT);
        uint32_t* hs = (uint32_t*)(sgen + SM_HS) + warp * 64;
        float xn[4];
        {
            float xv[4] = {bf_lo(xe.x), bf_hi(xe.x), bf_lo(xe.y), bf_hi(xe.y)};
            const float2 ps = half_warp_sums(xv, xpivot);
            if ((lane & 15) == 0) stat[warp * 2 + eb] = ps;
            const float s00 = silu_bf(c00), s01 = silu_bf(c01), s10 = silu_bf(c10), s11 = silu_bf(c11);
            __nv_bfloat16* scs = (__nv_bfloat16*)(sgen + SM_SC);
            scs[tid] = __float2bfloat16_rn(s00); scs[tid + 256] = __float2bfloat16_rn(s01);
            scs[512 + tid] = __float2bfloat16_rn(s10); scs[512 + tid + 256] = __float2bfloat16_rn(s11);
            asm volatile("bar.sync 2, 320;" ::: "memory");
            if (warp == 0) TSTAMP(23);
            float cp[4] = {0.f, 0.f, 0.f, 0.f};
            const uint32_t* sc32 = (const uint32_t*)(sgen + SM_SC) + bb * 256 + 32 * warp + t;
            mbar_wait(bar_p0w, 0);
#pragma unroll
            for (int s = 0; s < 4; s++) {
                uint32_t r0, r1;
                asm volatile("ldmatrix.sync.aligned.m8n8.x2.trans.shared.b16 {%0,%1}, [%2];"
                             : "=r"(r0), "=r"(r1) : "r"(sbase + SM_MRG + (64 * warp + 16 * s + (lane & 15)) * 16) : "memory");
                const uint32_t a[4] = {r0, r0, r1, r1};
                mma16816(cp, a, sc32[8 * s], sc32[8 * s + 4]);
            }
            if (t == 0) { red[warp * 16 + g] = cp[0]; red[warp * 16 + 8 + g] = cp[1]; }
            if (warp == 0) TSTAMP(14);
            cons_sync();
            if (warp == 0) {
                float s = 0.f;
#pragma unroll
                for (int w = 0; w < 8; w++) s += red[w * 16 + (lane & 15)];
                const float nx = __shfl_down_sync(0xffffffffu, s, 1);
                if (lane < 16 && !(lane & 1))
                    st_ll2(&sc->mod[lane >> 3][cta * 4 + ((lane & 7) >> 1)], pack_bf16(s, nx), tag);
                TSTAMP(1);
            }
            float mean_bf, rstd;
            ln_stats(stat, eb, xpivot, mean_bf, rstd);
#pragma unroll
            for (int i = 0; i < 4; i++) xn[i] = ln_norm(xv[i], mean_bf, rstd);
        }
        {
            uint4 sa, ca;
            for (int it = 0;; it++) {
                sa = ld_ll4((const uint4*)&sc->mod[eb][ec >> 1]);
                ca = ld_ll4((const uint4*)&sc->mod[eb][256 + (ec >> 1)]);
                const bool ok = sa.y == tag && sa.w == tag && ca.y == tag && ca.w == tag;
                if (__all_sync(0xffffffffu, ok) || it > SPIN_LIMIT) break;
            }
            *(uint2*)&hs[eb * 32 + 2 * (lane & 15)] =
                make_uint2(pack_bf16(ln_mod(xn[0], bf_lo(ca.x), bf_lo(sa.x)), ln_mod(xn[1], bf_hi(ca.x), bf_hi(sa.x))),
                           pack_bf16(ln_mod(xn[2], bf_lo(ca.z), bf_lo(sa.z)), ln_mod(xn[3], bf_hi(ca.z), bf_hi(sa.z))));
            __syncwarp();
            uint32_t hb[8];
#pragma unroll
            for (int i = 0; i < 8; i++) hb[i] = hs[bb * 32 + 8 * (i >> 1) + 4 * (i & 1) + t];
            if (warp == 0) TSTAMP(2);
            float cq[2][4] = {};
            const int ts = warp >> 2;
            mbar_wait(bar_full + 8 * ts, 0);
            const uint32_t tb = sbase + SM_RING + ts * TILE;
#pragma unroll
            for (int s = 0; s < 4; s++) {
                const int row = 64 * (warp & 3) + 16 * s + (lane & 7) + (lane >> 4) * 8;
#pragma unroll
                for (int mt = 0; mt < 2; mt++) {
                    const int ch = 2 * mt + ((lane >> 3) & 1);
                    uint32_t a[4];
                    ldsm4t(tb + row * 64 + ((ch ^ ((row >> 1) & 3)) << 4), a);
                    mma16816(cq[mt], a, hb[2 * s], hb[2 * s + 1]);
                }
            }
            if (t < 2) {
                const float v0 = t == 0 ? cq[0][0] : cq[1][0], v1 = t == 0 ? cq[0][1] : cq[1][1];
                const float v2 = t == 0 ? cq[0][2] : cq[1][2], v3 = t == 0 ? cq[0][3] : cq[1][3];
                *(float2*)&red2[warp * 64 + (16 * t + g) * 2] = make_float2(v0, v1);
                *(float2*)&red2[warp * 64 + (16 * t + g + 8) * 2] = make_float2(v2, v3);
            }
            cons_sync();
            if (warp < 4 && lane == 0) { mbar_arrive(bar_empty); mbar_arrive(bar_empty + 8); }
            if (warp == 0) {
                const int b = lane >> 4, cp = lane & 15;
                float q0 = 0.f, q1 = 0.f;
#pragma unroll
                for (int w = 0; w < 8; w++) {
                    const float4 v = *(const float4*)&red2[w * 64 + cp * 4];
                    q0 += b ? v.y : v.x; q1 += b ? v.w : v.z;
                }
                st_ll2(&sc->q[b][cta * 16 + cp], pack_bf16(q0, q1), tag);
                TSTAMP(3);
            }
        }
        const int pair = cta >> 3;
        uint32_t qf[16];
        {
            uint2* qs = (uint2*)(sgen + SM_QS);
            if (tid < 128) {
                const uint4* src = (const uint4*)&sc->q[pair >> 3][(pair & 7) * 256] + tid;
                uint4 v;
                for (int it = 0;; it++) {
                    v = ld_ll4(src);
                    if ((v.y == tag && v.w == tag) || it > SPIN_LIMIT) break;
                }
                qs[tid] = make_uint2(v.x, v.z);
            }
            cons_sync();
            const uint32_t* q32 = (const uint32_t*)(sgen + SM_QS);
#pragma unroll
            for (int s = 0; s < 8; s++) {
                qf[2 * s] = q32[(g & 3) * 64 + 8 * s + t];
                qf[2 * s + 1] = q32[(g & 3) * 64 + 8 * s + 4 + t];
            }
        }
        if (warp == 0) TSTAMP(4);

        float o[8][4];
#pragma unroll
        for (int i = 0; i < 8; i++) { o[i][0] = o[i][1] = o[i][2] = o[i][3] = 0.f; }
        uint32_t mrun = 0xff80ff80u;
        float ls[4] = {0.f, 0.f, 0.f, 0.f};
        uint4 m_sb, m_cb; uint2 m_ga0, m_ga1, m_gb0, m_gb1;
        {
            const int grp = warp >> 2, wi = warp & 3;
            const int krow = 16 * wi + (lane & 7) + ((lane >> 3) & 1) * 8;
            const uint32_t koff = krow * 128 + ((((lane >> 4) & 1) ^ (lane & 7)) << 4);
            const int vrow = 16 * wi + (lane & 7) + (lane >> 4) * 8;
            const uint32_t voff = vrow * 128 + ((((lane >> 3) & 1) ^ (lane & 7)) << 4);
            const uint32_t ones[4] = {0x3f803f80u, 0x3f803f80u, 0x3f803f80u, 0x3f803f80u};
            for (int i = grp; i < KV_TILES; i += 2) {
                if (i == MOD_AT + grp) {
                    float cm[4] = {};
                    const uint32_t* sc32 = (const uint32_t*)(sgen + SM_SC) + bb * 256 + 32 * warp + t;
                    mbar_wait(bar_full + 8 * (IDX_MOD % NST), (IDX_MOD / NST) & 1);
                    const uint32_t tb = sbase + SM_RING + (IDX_MOD % NST) * TILE;
#pragma unroll
                    for (int s = 0; s < 4; s++) {
                        const int row = 64 * warp + 16 * s + (lane & 7) + (lane >> 4) * 8;
                        const int ch = (lane >> 3) & 1;
                        uint32_t a[4];
                        ldsm4t(tb + row * 32 + ((ch ^ ((row >> 2) & 1)) << 4), a);
                        mma16816(cm, a, sc32[8 * s], sc32[8 * s + 4]);
                    }
                    if (t == 0) {
                        *(float2*)&red[warp * 64 + g * 2] = make_float2(cm[0], cm[1]);
                        *(float2*)&red[warp * 64 + (g + 8) * 2] = make_float2(cm[2], cm[3]);
                    }
                    cons_sync();
                    if (warp < 4 && lane == 0) mbar_arrive(bar_empty + 8 * (IDX_MOD % NST));
                    if (warp == 1 && lane < 16) {
                        const int b = lane >> 3, cp = lane & 7;
                        float q0 = 0.f, q1 = 0.f;
#pragma unroll
                        for (int w = 0; w < 8; w++) {
                            const float4 v = *(const float4*)&red[w * 64 + cp * 4];
                            q0 += b ? v.y : v.x; q1 += b ? v.w : v.z;
                        }
                        st_ll2(&sc->mod[b][512 + cta * 8 + cp], pack_bf16(q0, q1), tag);
                    }
                }
                if (i == 56 + grp) {
                    m_sb = ld_ll4((const uint4*)&sc->mod[eb][768 + (ec >> 1)]);
                    m_cb = ld_ll4((const uint4*)&sc->mod[eb][1024 + (ec >> 1)]);
                    m_ga0 = ld_ll2(&sc->mod[0][512 + (ocol >> 1)]); m_ga1 = ld_ll2(&sc->mod[1][512 + (ocol >> 1)]);
                    m_gb0 = ld_ll2(&sc->mod[0][1280 + (ocol >> 1)]); m_gb1 = ld_ll2(&sc->mod[1][1280 + (ocol >> 1)]);
                }
                if (i == 60 + grp) {
                    for (int it = 0;; it++) {
                        const bool ok = m_sb.y == tag && m_sb.w == tag && m_cb.y == tag && m_cb.w == tag &&
                                        m_ga0.y == tag && m_ga1.y == tag && m_gb0.y == tag && m_gb1.y == tag;
                        if (__all_sync(0xffffffffu, ok) || it > SPIN_LIMIT) break;
                        m_sb = ld_ll4((const uint4*)&sc->mod[eb][768 + (ec >> 1)]);
                        m_cb = ld_ll4((const uint4*)&sc->mod[eb][1024 + (ec >> 1)]);
                        m_ga0 = ld_ll2(&sc->mod[0][512 + (ocol >> 1)]); m_ga1 = ld_ll2(&sc->mod[1][512 + (ocol >> 1)]);
                        m_gb0 = ld_ll2(&sc->mod[0][1280 + (ocol >> 1)]); m_gb1 = ld_ll2(&sc->mod[1][1280 + (ocol >> 1)]);
                    }
                    mbar_wait(bar_clear, 0);
                }
                const int ki = kv_idx(i), ks = ki % NST, vs = (ki + 1) % NST;
                const uint32_t kph = (ki / NST) & 1, vph = ((ki + 1) / NST) & 1;
                mbar_wait(bar_full + 8 * ks, kph);
                const uint32_t kb = sbase + SM_RING + ks * TILE + koff;
                float sa[4] = {0.f, 0.f, 0.f, 0.f}, sb[4] = {0.f, 0.f, 0.f, 0.f};
#pragma unroll
                for (int s = 0; s < 8; s += 2) {
                    uint32_t a0[4], a1[4];
                    ldsm4((kb ^ ((s & 3) << 5)) + (s >> 2) * 8192, a0);
                    ldsm4((kb ^ (((s + 1) & 3) << 5)) + (s >> 2) * 8192, a1);
                    mma16816(sa, a0, qf[2 * s], qf[2 * s + 1]);
                    mma16816(sb, a1, qf[2 * s + 2], qf[2 * s + 3]);
                }
                __syncwarp();
                if (lane == 0) mbar_arrive(bar_empty + 8 * ks);
                uint32_t r01 = pack_bf16(sa[0] + sb[0], sa[1] + sb[1]);
                uint32_t r23 = pack_bf16(sa[2] + sb[2], sa[3] + sb[3]);
                r01 = pack_bf16(bf_lo(r01) * QK_SCALE, bf_hi(r01) * QK_SCALE);
                r23 = pack_bf16(bf_lo(r23) * QK_SCALE, bf_hi(r23) * QK_SCALE);
                uint32_t mx = max_bf16x2(r01, r23);
                mx = max_bf16x2(mx, __shfl_xor_sync(0xffffffffu, mx, 4));
                mx = max_bf16x2(mx, __shfl_xor_sync(0xffffffffu, mx, 8));
                mx = max_bf16x2(mx, __shfl_xor_sync(0xffffffffu, mx, 16));
                const uint32_t mnew = max_bf16x2(mrun, mx);
                const float m0 = bf_lo(mnew), m1 = bf_hi(mnew);
                if (__any_sync(0xffffffffu, mnew != mrun)) {
                    const float al0 = ex2((bf_lo(mrun) - m0) * LOG2E), al1 = ex2((bf_hi(mrun) - m1) * LOG2E);
                    ls[0] *= al0; ls[1] *= al1;
#pragma unroll
                    for (int d = 0; d < 8; d++) { o[d][0] *= al0; o[d][1] *= al1; o[d][2] *= al0; o[d][3] *= al1; }
                    mrun = mnew;
                }
                const float p0 = ex2((bf_lo(r01) - m0) * LOG2E), p1 = ex2((bf_hi(r01) - m1) * LOG2E);
                const float p2 = ex2((bf_lo(r23) - m0) * LOG2E), p3 = ex2((bf_hi(r23) - m1) * LOG2E);
                const uint32_t pb0 = movmatrix_t(pack_bf16(p0, p1)), pb1 = movmatrix_t(pack_bf16(p2, p3));
                mma16816(ls, ones, pb0, pb1);
                mbar_wait(bar_full + 8 * vs, vph);
                const uint32_t vb = sbase + SM_RING + vs * TILE + voff;
#pragma unroll
                for (int d = 0; d < 8; d++) {
                    uint32_t a[4];
                    ldsm4t((vb ^ ((d & 3) << 5)) + (d >> 2) * 8192, a);
                    mma16816(o[d], a, pb0, pb1);
                }
                __syncwarp();
                if (lane == 0) mbar_arrive(bar_empty + 8 * vs);
            }
        }
        if (warp == 7) TSTAMP(5);
        {
            float* mrg = (float*)(sgen + SM_MRG);
            float2* ml = (float2*)(sgen + SM_ML);
            {
                const int hp = (t & 1) * 2, up = t >> 1;
                if (g == 0 && up == 0) { ml[warp * 4 + hp] = make_float2(bf_lo(mrun), ls[0]); ml[warp * 4 + hp + 1] = make_float2(bf_hi(mrun), ls[1]); }
                float* m0p = mrg + (warp * 4 + hp) * 136 + up * 72 + g;
#pragma unroll
                for (int d = 0; d < 4; d++) {
                    m0p[16 * d] = up ? o[d + 4][0] : o[d][0]; m0p[136 + 16 * d] = up ? o[d + 4][1] : o[d][1];
                    m0p[16 * d + 8] = up ? o[d + 4][2] : o[d][2]; m0p[136 + 16 * d + 8] = up ? o[d + 4][3] : o[d][3];
                }
            }
            cons_sync();
            const int hh = tid >> 6, dp = tid & 63;
            float2 mw[8];
            float M = -INFINITY;
#pragma unroll
            for (int w = 0; w < 8; w++) { mw[w] = ml[w * 4 + hh]; M = fmaxf(M, mw[w].x); }
            float L = 0.f, o0 = 0.f, o1 = 0.f;
#pragma unroll
            for (int w = 0; w < 8; w++) {
                const float wt = ex2((mw[w].x - M) * LOG2E);
                const float2 v = *(const float2*)&mrg[(w * 4 + hh) * 136 + 2 * dp + (dp >= 32 ? 8 : 0)];
                L += wt * mw[w].y; o0 += wt * v.x; o1 += wt * v.y;
            }
            st_ll2(&sc->part_o[cta][hh][dp], tagf(o0, F_PART), tagf(o1, F_PART));
            if (dp < 4) st_ll2(&sc->part_ml[cta][hh][dp], tagf(M, F_PART), tagf(L, F_PART));
        }
        if (warp == 0) TSTAMP(6);
        const uint32_t aoff = warp * 2048 + ((lane & 7) + (lane >> 4) * 8) * 128 + ((((lane >> 3) & 1) ^ (lane & 7)) << 4);
        uint32_t wf[8][4];
        {
            const int hq = cta >> 2, kvh = hq >> 2, hh = hq & 3, ds = cta & 3;
            const int b = tid >> 7, dpl = (tid >> 3) & 15, j = tid & 7;
            const int pc = (b * 8 + kvh) * 8 + j;
            const uint2* po = &sc->part_o[pc][hh][ds * 16 + dpl];
            const uint2* pm = &sc->part_ml[pc - j][hh][0];
            uint2 vo, vm[8];
            bool oko = false, okm = false;
            for (int it = 0;; it++) {
                if (!oko) vo = ld_ll2(po);
                if (!okm) {
#pragma unroll
                    for (int jj = 0; jj < 8; jj++) vm[jj] = ld_ll2(pm + jj * 16);
                }
                oko = (vo.x & vo.y & 3u) == F_PART;
                uint32_t all = vm[0].x & vm[0].y;
#pragma unroll
                for (int jj = 1; jj < 8; jj++) all &= vm[jj].x & vm[jj].y;
                okm = (all & 3u) == F_PART;
                if (__all_sync(0xffffffffu, oko && okm) || it > SPIN_LIMIT) break;
            }
            float M = untag(vm[0].x);
#pragma unroll
            for (int jj = 1; jj < 8; jj++) M = fmaxf(M, untag(vm[jj].x));
            float wt = 0.f, L = 0.f;
#pragma unroll
            for (int jj = 0; jj < 8; jj++) {
                const float w_ = ex2((untag(vm[jj].x) - M) * LOG2E);
                L += w_ * untag(vm[jj].y);
                wt = jj == j ? w_ : wt;
            }
            float o0 = wt * untag(vo.x), o1 = wt * untag(vo.y);
#pragma unroll
            for (int o_ = 1; o_ < 8; o_ <<= 1) {
                o0 += __shfl_xor_sync(0xffffffffu, o0, o_);
                o1 += __shfl_xor_sync(0xffffffffu, o1, o_);
            }
            uint32_t* os = (uint32_t*)(sgen + SM_OS);
            const float rl = rcp_approx(L);
            if (j == 0) os[b * 16 + dpl] = pack_bf16(o0 * rl, o1 * rl);
            if (warp == 0) TSTAMP(15);
#pragma unroll
            for (int s = 0; s < 2; s++) {
                const int idx = IDX_WO + s;
                mbar_wait(bar_full + 8 * (idx % NST), (idx / NST) & 1);
                const uint32_t tb = sbase + SM_RING + (idx % NST) * TILE + aoff;
#pragma unroll
                for (int mt = 0; mt < 4; mt++) ldsm4t(tb ^ (mt << 5), wf[s * 4 + mt]);
            }
            cons_sync();
            if (warp == 0) TSTAMP(7);
            float y[4][4] = {};
#pragma unroll
            for (int s = 0; s < 2; s++) {
                const uint32_t b0 = os[bb * 16 + 8 * s + t], b1 = os[bb * 16 + 8 * s + 4 + t];
#pragma unroll
                for (int mt = 0; mt < 4; mt++) mma16816(y[mt], wf[s * 4 + mt], b0, b1);
            }
            float v[4];
#pragma unroll
            for (int i = 0; i < 4; i++) v[i] = t == 0 ? y[0][i] : t == 1 ? y[1][i] : t == 2 ? y[2][i] : y[3][i];
            {
                const bool odd = g & 1;
                const float sx = odd ? v[0] : v[2], sy = odd ? v[1] : v[3];
                const float rx = __shfl_xor_sync(0xffffffffu, sx, 4), ry = __shfl_xor_sync(0xffffffffu, sy, 4);
                const int c0 = 64 * warp + 16 * t + (odd ? g + 7 : g);
                const float e0 = odd ? rx : v[0], e1 = odd ? ry : v[1], e2 = odd ? v[2] : rx, e3 = odd ? v[3] : ry;
                st_v4(&sc->inbox[c0 >> 2][cta][(c0 >> 1) & 1], tagf(e0, F_WO), tagf(e1, F_WO), tagf(e2, F_WO), tagf(e3, F_WO));
            }
        }
        if (warp == 0) TSTAMP(8);
        float xm0 = 0.f, xm1 = 0.f;
        {
            float r0;
            {
                const uint4* pin = &sc->inbox[cta][0][0] + tid;
                uint4 v = make_uint4(F_WO, F_WO, F_WO, F_WO);
                spin_cycles(DELAY_B1);
                bool ok = tid >= NCTA * 2;
                for (int it = 0;; it++) {
                    if (!ok) {
                        v = ld_ll4(pin);
                        ok = ((v.x & v.y & v.z & v.w & 3u) == F_WO) && (((v.x | v.y | v.z | v.w) & 3u) == F_WO);
                    }
                    if (__all_sync(0xffffffffu, ok) || it > SPIN_LIMIT) break;
                }
                const bool u1 = lane & 2, u2 = lane & 4;
                const float a0 = untag(v.x), a1 = untag(v.y), a2 = untag(v.z), a3 = untag(v.w);
                const float k0 = (u1 ? a1 : a0) + __shfl_xor_sync(0xffffffffu, u1 ? a0 : a1, 2);
                const float k1 = (u1 ? a3 : a2) + __shfl_xor_sync(0xffffffffu, u1 ? a2 : a3, 2);
                r0 = (u2 ? k1 : k0) + __shfl_xor_sync(0xffffffffu, u2 ? k0 : k1, 4);
                r0 += __shfl_xor_sync(0xffffffffu, r0, 8);
                r0 += __shfl_xor_sync(0xffffffffu, r0, 16);
                if (lane < 8) red2[warp * 8 + (2 * (lane & 1) + ((lane >> 2) & 1)) * 2 + ((lane >> 1) & 1)] = r0;
            }
            cons_sync();
            if (warp == 0) {
                float a0 = 0.f, a1 = 0.f;
#pragma unroll
                for (int w = 0; w < 8; w++) { const float2 v = *(const float2*)&red2[w * 8 + (lane & 3) * 2]; a0 += v.x; a1 += v.y; }
                const bool hi = ocol & 1;
                const float ga0 = hi ? bf_hi(m_ga0.x) : bf_lo(m_ga0.x), ga1 = hi ? bf_hi(m_ga1.x) : bf_lo(m_ga1.x);
                xm0 = bf16r(xo0 + bf16r(ga0 * bf16r(a0)));
                xm1 = bf16r(xo1 + bf16r(ga1 * bf16r(a1)));
                if (lane < 4) st_ll2(&sc->x1[cta][lane], pack_bf16(xm0, xm1), F_X1);
                TSTAMP(10);
            }
        }
        if (cta < NFFN) {
            const uint4* px = (const uint4*)&sc->x1[ec >> 2][0];
            const uint4* pp = (const uint4*)&sc->x1[0][0];
            uint4 va, vb, pa, pb;
            uint32_t gf[4][4], uf[4][4];
            mbar_wait(bar_gu + 8 * (2 * (warp >> 1)), 0);
            mbar_wait(bar_gu + 8 * (2 * (warp >> 1) + 1), 0);
            {
                const uint32_t tg = sbase + SM_RING + (IDX_WG % NST) * TILE, tu = sbase + SM_RING + (IDX_WU % NST) * TILE;
#pragma unroll
                for (int s = 0; s < 4; s++) {
                    const int row = 64 * warp + 16 * s + (lane & 7) + (lane >> 4) * 8;
                    const uint32_t off = row * 32 + ((((lane >> 3) & 1) ^ ((row >> 2) & 1)) << 4);
                    ldsm4t(tg + off, gf[s]);
                    ldsm4t(tu + off, uf[s]);
                }
            }
            const float c1v[4] = {bf16r(1.0f + bf_lo(m_cb.x)), bf16r(1.0f + bf_hi(m_cb.x)), bf16r(1.0f + bf_lo(m_cb.z)), bf16r(1.0f + bf_hi(m_cb.z))};
            float bg = 0.f, cgc = 0.f, bu = 0.f, cuc = 0.f;
            {
                uint32_t* pre = (uint32_t*)(sgen + SM_MRG) + warp * 128;
                float* bc = (float*)(sgen + SM_MRG + 4096);
                *(uint2*)&pre[eb * 32 + 2 * (lane & 15)] = make_uint2(pack_bf16(c1v[0], c1v[1]), pack_bf16(c1v[2], c1v[3]));
                *(uint2*)&pre[64 + eb * 32 + 2 * (lane & 15)] = make_uint2(m_sb.x, m_sb.z);
                __syncwarp();
                float yg[4] = {}, yu[4] = {};
                const uint32_t* pb = pre + ((g >> 1) & 1) * 64 + bb * 32 + t;
#pragma unroll
                for (int s = 0; s < 4; s++) {
                    const uint32_t b0 = pb[8 * s], b1 = pb[8 * s + 4];
                    mma16816(yg, gf[s], b0, b1);
                    mma16816(yu, uf[s], b0, b1);
                }
                const float y0 = t < 2 ? yg[0] : yu[0], y1 = t < 2 ? yg[1] : yu[1], y2 = t < 2 ? yg[2] : yu[2], y3 = t < 2 ? yg[3] : yu[3];
                float* dstp = bc + warp * 128 + (t >> 1) * 64 + (t & 1) * 32;
                *(float2*)&dstp[g * 2] = make_float2(y0, y1);
                *(float2*)&dstp[(g + 8) * 2] = make_float2(y2, y3);
                __syncwarp();
                if (lane == 0) mbar_arrive(bar_bc);
            }
            if (warp == 0) TSTAMP(11);
            float pivot2;
            {
                bool okx = false, okp = false;
                for (int it = 0;; it++) {
                    if (!okx) { va = ld_ll4(px); vb = ld_ll4(px + 1); }
                    if (!okp) { pa = ld_ll4(pp); pb = ld_ll4(pp + 1); }
                    okx = va.y == F_X1 && va.w == F_X1 && vb.y == F_X1 && vb.w == F_X1;
                    okp = pa.y == F_X1 && pa.w == F_X1 && pb.y == F_X1 && pb.w == F_X1;
                    if (__all_sync(0xffffffffu, okx && okp) || it > SPIN_LIMIT) break;
                }
                if (warp == 0) TSTAMP(9);
                const float xv[4] = {eb ? bf_hi(va.x) : bf_lo(va.x), eb ? bf_hi(va.z) : bf_lo(va.z),
                                     eb ? bf_hi(vb.x) : bf_lo(vb.x), eb ? bf_hi(vb.z) : bf_lo(vb.z)};
                const float p0 = 0.25f * ((bf_lo(pa.x) + bf_lo(pa.z)) + (bf_lo(pb.x) + bf_lo(pb.z)));
                const float p1 = 0.25f * ((bf_hi(pa.x) + bf_hi(pa.z)) + (bf_hi(pb.x) + bf_hi(pb.z)));
                const float pivot = eb ? p1 : p0;
                pivot2 = (lane & 1) ? p1 : p0;
                *(uint2*)&hs[eb * 32 + 2 * (lane & 15)] =
                    make_uint2(pack_bf16((xv[0] - pivot) * c1v[0], (xv[1] - pivot) * c1v[1]),
                               pack_bf16((xv[2] - pivot) * c1v[2], (xv[3] - pivot) * c1v[3]));
                __syncwarp();
                float cg[2][4] = {}, cu[2][4] = {};
#pragma unroll
                for (int s = 0; s < 4; s++) {
                    const uint32_t b0 = hs[bb * 32 + 8 * s + t], b1 = hs[bb * 32 + 8 * s + 4 + t];
                    mma16816(cg[s & 1], gf[s], b0, b1);
                    mma16816(cu[s & 1], uf[s], b0, b1);
                }
                const float2 ps = half_warp_sums(xv, pivot);
                if ((lane & 15) == 0) stat[warp * 2 + eb] = ps;
                {
                    const float* bc = (const float*)(sgen + SM_MRG + 4096);
                    mbar_wait(bar_bc, 0);
#pragma unroll
                    for (int w = 0; w < 8; w++) {
                        bg += bc[w * 128 + lane]; cgc += bc[w * 128 + 32 + lane];
                        bu += bc[w * 128 + 64 + lane]; cuc += bc[w * 128 + 96 + lane];
                    }
                }
                if (t < 2) {
                    float v[4];
#pragma unroll
                    for (int i = 0; i < 4; i++) v[i] = t ? cu[0][i] + cu[1][i] : cg[0][i] + cg[1][i];
                    *(float2*)&red[warp * 64 + t * 32 + g * 2] = make_float2(v[0], v[1]);
                    *(float2*)&red[warp * 64 + t * 32 + (g + 8) * 2] = make_float2(v[2], v[3]);
                }
            }
            uint32_t df[4][4];
            mbar_wait(bar_full + 8 * (IDX_WD % NST), (IDX_WD / NST) & 1);
#pragma unroll
            for (int mt = 0; mt < 4; mt++) ldsm4t((sbase + SM_RING + (IDX_WD % NST) * TILE + aoff) ^ (mt << 5), df[mt]);
            cons_sync();
            {
                float gs = 0.f, us = 0.f;
#pragma unroll
                for (int w = 0; w < 8; w++) { gs += red[w * 64 + lane]; us += red[w * 64 + 32 + lane]; }
                float mean_bf, rstd;
                ln_stats(stat, lane & 1, pivot2, mean_bf, rstd);
                const float dm = mean_bf - pivot2;
                gs = bf16r(rstd * (gs - dm * bg) + cgc);
                us = rstd * (us - dm * bu) + cuc;
                const float u2 = gs * (1.0f + 0.044715f * gs * gs) * (2.0f * 0.7978845608028654f * LOG2E);
                const float ge = bf16r(__fdividef(gs, 1.0f + ex2(-u2)));
                const float act = bf16r(ge * bf16r(us));
                const float a0 = __shfl_sync(0xffffffffu, act, 4 * t + bb), a1 = __shfl_sync(0xffffffffu, act, 4 * t + 2 + bb);
                const float a2 = __shfl_sync(0xffffffffu, act, 4 * t + 16 + bb), a3 = __shfl_sync(0xffffffffu, act, 4 * t + 18 + bb);
                const uint32_t b0 = pack_bf16(a0, a1), b1 = pack_bf16(a2, a3);
                float y[4][4] = {};
#pragma unroll
                for (int mt = 0; mt < 4; mt++) mma16816(y[mt], df[mt], b0, b1);
                float v[4];
#pragma unroll
                for (int i = 0; i < 4; i++) v[i] = t == 0 ? y[0][i] : t == 1 ? y[1][i] : t == 2 ? y[2][i] : y[3][i];
            {
                const bool odd = g & 1;
                const float sx = odd ? v[0] : v[2], sy = odd ? v[1] : v[3];
                const float rx = __shfl_xor_sync(0xffffffffu, sx, 4), ry = __shfl_xor_sync(0xffffffffu, sy, 4);
                const int c0 = 64 * warp + 16 * t + (odd ? g + 7 : g);
                const float e0 = odd ? rx : v[0], e1 = odd ? ry : v[1], e2 = odd ? v[2] : rx, e3 = odd ? v[3] : ry;
                st_v4(&sc->inbox[c0 >> 2][cta][(c0 >> 1) & 1], tagf(e0, F_DOWN), tagf(e1, F_DOWN), tagf(e2, F_DOWN), tagf(e3, F_DOWN));
            }
            }
            if (warp == 0) TSTAMP(12);
        }
        {
            float r0;
            {
                const uint4* pin = &sc->inbox[cta][0][0] + tid;
                uint4 v = make_uint4(F_DOWN, F_DOWN, F_DOWN, F_DOWN);
                spin_cycles(DELAY_C);
                bool ok = tid >= NFFN * 2;
                for (int it = 0;; it++) {
                    if (!ok) {
                        v = ld_ll4(pin);
                        ok = ((v.x & v.y & v.z & v.w & 3u) == F_DOWN) && (((v.x | v.y | v.z | v.w) & 3u) == F_DOWN);
                    }
                    if (__all_sync(0xffffffffu, ok) || it > SPIN_LIMIT) break;
                }
                const bool u1 = lane & 2, u2 = lane & 4;
                const float a0 = untag(v.x), a1 = untag(v.y), a2 = untag(v.z), a3 = untag(v.w);
                const float k0 = (u1 ? a1 : a0) + __shfl_xor_sync(0xffffffffu, u1 ? a0 : a1, 2);
                const float k1 = (u1 ? a3 : a2) + __shfl_xor_sync(0xffffffffu, u1 ? a2 : a3, 2);
                r0 = (u2 ? k1 : k0) + __shfl_xor_sync(0xffffffffu, u2 ? k0 : k1, 4);
                r0 += __shfl_xor_sync(0xffffffffu, r0, 8);
                r0 += __shfl_xor_sync(0xffffffffu, r0, 16);
                if (lane < 8) red2[64 + warp * 8 + (2 * (lane & 1) + ((lane >> 2) & 1)) * 2 + ((lane >> 1) & 1)] = r0;
            }
            cons_sync();
            if (warp == 0) {
                float a0 = 0.f, a1 = 0.f;
#pragma unroll
                for (int w = 0; w < 8; w++) { const float2 v = *(const float2*)&red2[64 + w * 8 + (lane & 3) * 2]; a0 += v.x; a1 += v.y; }
                const bool hi = ocol & 1;
                const float gb0 = hi ? bf_hi(m_gb0.x) : bf_lo(m_gb0.x), gb1 = hi ? bf_hi(m_gb1.x) : bf_lo(m_gb1.x);
                if (lane < 4) {
                    p.out[ocol] = __float2bfloat16_rn(xm0 + bf16r(gb0 * bf16r(a0)));
                    p.out[D_MODEL + ocol] = __float2bfloat16_rn(xm1 + bf16r(gb1 * bf16r(a1)));
                }
                if (cta == 0 && lane == 0) *(volatile unsigned*)&sc->epoch = tag;
                TSTAMP(13);
            }
        }
    }
}

typedef CUresult (*EncodeFn)(CUtensorMap*, CUtensorMapDataType, cuuint32_t, void*, const cuuint64_t*, const cuuint64_t*,
                             const cuuint32_t*, const cuuint32_t*, CUtensorMapInterleave, CUtensorMapSwizzle,
                             CUtensorMapL2promotion, CUtensorMapFloatOOBfill);

struct Maps { CUtensorMap k, v, wq, wmod, wmod8, wo, wg, wu, wd; };

void encode(EncodeFn fn, CUtensorMap* m, const void* ptr, int rank, const cuuint64_t* dims, const cuuint64_t* strides,
            const cuuint32_t* box, CUtensorMapSwizzle sw) {
    const cuuint32_t es[3] = {1, 1, 1};
    fn(m, CU_TENSOR_MAP_DATA_TYPE_BFLOAT16, rank, const_cast<void*>(ptr), dims, strides, box, es,
       CU_TENSOR_MAP_INTERLEAVE_NONE, sw, CU_TENSOR_MAP_L2_PROMOTION_L2_256B, CU_TENSOR_MAP_FLOAT_OOB_FILL_NONE);
}

}

extern "C" void kernel_launch(void* const* d_in, const int* in_sizes, int n_in, void* d_out, int out_size) {
    (void)in_sizes; (void)n_in; (void)out_size;
    static EncodeFn enc = nullptr;
    static Scratch* scratch = nullptr;
    if (!enc) {
        cudaGetSymbolAddress((void**)&scratch, g_scratch);
        void* fn = nullptr;
        cudaDriverEntryPointQueryResult qr;
        cudaGetDriverEntryPoint("cuTensorMapEncodeTiled", &fn, cudaEnableDefault, &qr);
        enc = (EncodeFn)fn;
        cudaFuncSetAttribute(fused_block_kernel, cudaFuncAttributeMaxDynamicSharedMemorySize, SMEM_BYTES);
    }
    Maps m;
    {
        const cuuint64_t dims[3] = {64, (cuuint64_t)16 * SK, 2}, str[2] = {256, 128};
        const cuuint32_t box[3] = {64, 64, 2};
        encode(enc, &m.k, d_in[1], 3, dims, str, box, CU_TENSOR_MAP_SWIZZLE_128B);
        encode(enc, &m.v, d_in[2], 3, dims, str, box, CU_TENSOR_MAP_SWIZZLE_128B);
    }
    {
        const cuuint64_t dims[2] = {4096, 512}, str[1] = {8192};
        const cuuint32_t box[2] = {32, 256};
        encode(enc, &m.wq, d_in[3], 2, dims, str, box, CU_TENSOR_MAP_SWIZZLE_64B);
    }
    {
        const cuuint64_t dims[2] = {N_MOD, 512}, str[1] = {N_MOD * 2};
        const cuuint32_t box[2] = {16, 256};
        encode(enc, &m.wmod, d_in[10], 2, dims, str, box, CU_TENSOR_MAP_SWIZZLE_32B);
        const cuuint32_t box8[2] = {8, 256};
        encode(enc, &m.wmod8, d_in[10], 2, dims, str, box8, CU_TENSOR_MAP_SWIZZLE_NONE);
    }
    {
        const cuuint64_t dims_o[3] = {64, 4096, 8}, dims_d[3] = {64, D_FF, 8}, str[2] = {1024, 128};
        const cuuint32_t box[3] = {64, 16, 8};
        encode(enc, &m.wo, d_in[4], 3, dims_o, str, box, CU_TENSOR_MAP_SWIZZLE_128B);
        encode(enc, &m.wd, d_in[8], 3, dims_d, str, box, CU_TENSOR_MAP_SWIZZLE_128B);
    }
    {
        const cuuint64_t dims[2] = {D_FF, 512}, str[1] = {D_FF * 2};
        const cuuint32_t box[2] = {16, 128};
        encode(enc, &m.wg, d_in[6], 2, dims, str, box, CU_TENSOR_MAP_SWIZZLE_32B);
        encode(enc, &m.wu, d_in[7], 2, dims, str, box, CU_TENSOR_MAP_SWIZZLE_32B);
    }
    Params p;
    p.x = (const __nv_bfloat16*)d_in[0];
    p.c = (const __nv_bfloat16*)d_in[9];
    p.out = (__nv_bfloat16*)d_out;
    p.sc = scratch;
    fused_block_kernel<<<NCTA, NTHREADS, SMEM_BYTES, cudaStreamPerThread>>>(p, m.k, m.v, m.wq, m.wmod, m.wmod8, m.wo, m.wg, m.wu, m.wd);
}
```

```cpp
#include <cuda_runtime.h>
#include <cuda.h>
#include <cuda_bf16.h>
#include <stdint.h>

namespace {

constexpr int D_MODEL = 512;
constexpr int N_HEADS = 32;
constexpr int SK = 32768;
constexpr int DH = 128;
constexpr int D_FF = 1792;
constexpr int N_MOD = 6 * D_MODEL;

constexpr int NCTA = 128;
constexpr int NFFN = D_FF / 16;
constexpr int NOWN = 32;
constexpr int NTHREADS = 320;
constexpr int NST = 12;
constexpr int TILE = 16384;
#define WINDOW 3
#define WINDOW_TAIL 2
#define GU_WIN 3
#define PACE_THR 96
constexpr int KV_TILES = 64;
#define MOD_AT 8
static_assert(MOD_AT % 2 == 0 && MOD_AT >= 2 && MOD_AT < 56, "schedule");
__host__ __device__ constexpr int kv_idx(int i) { return 2 + 2 * i + (i >= MOD_AT ? 1 : 0); }
constexpr int IDX_MOD = 2 + 2 * MOD_AT;
constexpr int N_STREAM = kv_idx(KV_TILES - 1) + 2;
constexpr int IDX_WO = N_STREAM;
constexpr int IDX_WG = IDX_WO + 2;
constexpr int IDX_WU = IDX_WG + 1;
constexpr int IDX_WD = IDX_WU + 1;
constexpr int SPIN_LIMIT = 1 << 20;

constexpr float LOG2E = 1.4426950408889634f;
constexpr float QK_SCALE = 0.08838834764831845f;

constexpr int SM_RING = 0;
constexpr int SM_MRG = SM_RING + NST * TILE;
constexpr int SM_ML = SM_MRG + 8 * 4 * 136 * 4;
constexpr int SM_RED = SM_ML + 8 * 4 * 8;
constexpr int SM_RED2 = SM_RED + 8 * 64 * 4;
constexpr int SM_QS = SM_RED2 + 8 * 64 * 4;
constexpr int SM_OS = SM_QS + 512 * 2;
constexpr int SM_SC = SM_OS + 2 * 128 * 2;
constexpr int SM_HS = SM_SC + 2 * 512 * 2;
constexpr int SM_STAT = SM_HS + 8 * 2 * 32 * 4;
constexpr int SM_PACE = SM_STAT + 8 * 2 * 8;
constexpr int SM_BAR = SM_PACE + 8;
constexpr int SM_END = SM_BAR + (2 * NST + 1 + 8 + 2) * 8;
constexpr int SMEM_BYTES = SM_END + 1024;

struct Scratch {
    uint4 inbox_wo[NOWN][N_HEADS][8];
    uint4 inbox_dn[NCTA][NFFN][2];
    uint2 x1[D_MODEL];
    uint2 part_o[NCTA][4][64];
    uint2 part_ml[NCTA][4][4];
    uint2 mod[2][N_MOD / 2];
    uint2 q[2][N_HEADS * DH / 2];
    unsigned epoch;
    unsigned pad_[31];
    unsigned cleared;
    unsigned pad2_[31];
    unsigned progress;
};
__device__ Scratch g_scratch;
constexpr uint32_t F_PART = 1, F_WO = 1, F_DOWN = 1, F_X1 = 1;
__device__ __forceinline__ uint32_t tagf(float v, uint32_t f) { return (__float_as_uint(v) & ~3u) | f; }
__device__ __forceinline__ float untag(uint32_t v) { return __uint_as_float(v & ~3u); }

struct Params {
    const __nv_bfloat16* x;
    const __nv_bfloat16* c;
    __nv_bfloat16* out;
    Scratch* sc;
};

#define TSTAMP(i) do { } while (0)

__device__ __forceinline__ uint32_t smem_u32(const void* p) { return (uint32_t)__cvta_generic_to_shared(p); }

__device__ __forceinline__ void mbar_init(uint32_t bar, uint32_t cnt) {
    asm volatile("mbarrier.init.shared::cta.b64 [%0], %1;" ::"r"(bar), "r"(cnt) : "memory");
}
__device__ __forceinline__ void mbar_expect_tx(uint32_t bar, uint32_t bytes) {
    asm volatile("mbarrier.arrive.expect_tx.shared::cta.b64 _, [%0], %1;" ::"r"(bar), "r"(bytes) : "memory");
}
__device__ __forceinline__ void mbar_arrive(uint32_t bar) {
    asm volatile("mbarrier.arrive.shared::cta.b64 _, [%0];" ::"r"(bar) : "memory");
}
__device__ __forceinline__ bool mbar_try(uint32_t bar, uint32_t parity) {
    uint32_t ok;
    asm volatile(
        "{\n\t.reg .pred p;\n\t"
        "mbarrier.try_wait.parity.shared::cta.b64 p, [%1], %2;\n\t"
        "selp.u32 %0, 1, 0, p;\n\t}"
        : "=r"(ok) : "r"(bar), "r"(parity) : "memory");
    return ok != 0;
}
__device__ __forceinline__ void mbar_wait(uint32_t bar, uint32_t parity) {
    if (mbar_try(bar, parity)) return;
    const long long t0 = clock64();
    while (!mbar_try(bar, parity))
        if (clock64() - t0 > (1ll << 31)) return;
}
__device__ __forceinline__ void cons_sync() { asm volatile("bar.sync 1, 256;" ::: "memory"); }

__device__ __forceinline__ void tma_2d(uint32_t dst, const CUtensorMap* m, int c0, int c1, uint32_t bar) {
    asm volatile("cp.async.bulk.tensor.2d.shared::cluster.global.mbarrier::complete_tx::bytes [%0], [%1, {%3, %4}], [%2];"
                 ::"r"(dst), "l"(m), "r"(bar), "r"(c0), "r"(c1) : "memory");
}
__device__ __forceinline__ void tma_3d(uint32_t dst, const CUtensorMap* m, int c0, int c1, int c2, uint32_t bar) {
    asm volatile("cp.async.bulk.tensor.3d.shared::cluster.global.mbarrier::complete_tx::bytes [%0], [%1, {%3, %4, %5}], [%2];"
                 ::"r"(dst), "l"(m), "r"(bar), "r"(c0), "r"(c1), "r"(c2) : "memory");
}
__device__ __forceinline__ void tma_3d_hint(uint32_t dst, const CUtensorMap* m, int c0, int c1, int c2, uint32_t bar, uint64_t pol) {
    asm volatile("cp.async.bulk.tensor.3d.shared::cluster.global.mbarrier::complete_tx::bytes.L2::cache_hint [%0], [%1, {%3, %4, %5}], [%2], %6;"
                 ::"r"(dst), "l"(m), "r"(bar), "r"(c0), "r"(c1), "r"(c2), "l"(pol) : "memory");
}
__device__ __forceinline__ void prefetch_tmap(const CUtensorMap* m) {
    asm volatile("prefetch.tensormap [%0];" ::"l"(m) : "memory");
}

__device__ __forceinline__ void ldsm4(uint32_t addr, uint32_t (&r)[4]) {
    asm volatile("ldmatrix.sync.aligned.m8n8.x4.shared.b16 {%0,%1,%2,%3}, [%4];"
                 : "=r"(r[0]), "=r"(r[1]), "=r"(r[2]), "=r"(r[3]) : "r"(addr) : "memory");
}
__device__ __forceinline__ void ldsm4t(uint32_t addr, uint32_t (&r)[4]) {
    asm volatile("ldmatrix.sync.aligned.m8n8.x4.trans.shared.b16 {%0,%1,%2,%3}, [%4];"
                 : "=r"(r[0]), "=r"(r[1]), "=r"(r[2]), "=r"(r[3]) : "r"(addr) : "memory");
}
__device__ __forceinline__ void mma16816(float (&c)[4], const uint32_t (&a)[4], uint32_t b0, uint32_t b1) {
    asm volatile("mma.sync.aligned.m16n8k16.row.col.f32.bf16.bf16.f32 {%0,%1,%2,%3}, {%4,%5,%6,%7}, {%8,%9}, {%0,%1,%2,%3};"
                 : "+f"(c[0]), "+f"(c[1]), "+f"(c[2]), "+f"(c[3])
                 : "r"(a[0]), "r"(a[1]), "r"(a[2]), "r"(a[3]), "r"(b0), "r"(b1));
}
__device__ __forceinline__ uint32_t movmatrix_t(uint32_t a) {
    uint32_t d;
    asm volatile("movmatrix.sync.aligned.m8n8.trans.b16 %0, %1;" : "=r"(d) : "r"(a));
    return d;
}
__device__ __forceinline__ uint32_t pack_bf16(float a, float b) {
    uint32_t r;
    asm("cvt.rn.bf16x2.f32 %0, %1, %2;" : "=r"(r) : "f"(b), "f"(a));
    return r;
}
__device__ __forceinline__ float bf_lo(uint32_t v) { return __uint_as_float(v << 16); }
__device__ __forceinline__ float bf_hi(uint32_t v) { return __uint_as_float(v & 0xffff0000u); }
__device__ __forceinline__ float bf16r(float a) { return bf_lo(pack_bf16(a, 0.f)); }
__device__ __forceinline__ uint32_t max_bf16x2(uint32_t a, uint32_t b) {
    uint32_t r;
    asm("max.bf16x2 %0, %1, %2;" : "=r"(r) : "r"(a), "r"(b));
    return r;
}
__device__ __forceinline__ float ex2(float x) {
    float r;
    asm("ex2.approx.ftz.f32 %0, %1;" : "=f"(r) : "f"(x));
    return r;
}

__device__ __forceinline__ void st_ll2(uint2* p, uint32_t v, uint32_t tag) {
    asm volatile("st.relaxed.gpu.global.v2.u32 [%0], {%1, %2};" ::"l"(p), "r"(v), "r"(tag) : "memory");
}
__device__ __forceinline__ void st_ll4(uint4* p, uint32_t v0, uint32_t v1, uint32_t tag) {
    asm volatile("st.relaxed.gpu.global.v4.u32 [%0], {%1, %2, %3, %2};" ::"l"(p), "r"(v0), "r"(tag), "r"(v1) : "memory");
}
__device__ __forceinline__ void st_v4(uint4* p, uint32_t a, uint32_t b, uint32_t c, uint32_t d) {
    asm volatile("st.relaxed.gpu.global.v4.u32 [%0], {%1, %2, %3, %4};" ::"l"(p), "r"(a), "r"(b), "r"(c), "r"(d) : "memory");
}
__device__ __forceinline__ uint2 ld_ll2(const uint2* p) {
    uint2 v;
    asm volatile("ld.relaxed.gpu.global.v2.u32 {%0, %1}, [%2];" : "=r"(v.x), "=r"(v.y) : "l"(p) : "memory");
    return v;
}
__device__ __forceinline__ uint4 ld_ll4(const uint4* p) {
    uint4 v;
    asm volatile("ld.relaxed.gpu.global.v4.u32 {%0, %1, %2, %3}, [%4];"
                 : "=r"(v.x), "=r"(v.y), "=r"(v.z), "=r"(v.w) : "l"(p) : "memory");
    return v;
}

#define DELAY_B1 450
#define DELAY_C 450
__device__ __forceinline__ uint32_t clock32() {
    uint32_t c;
    asm volatile("mov.u32 %0, %clock;" : "=r"(c));
    return c;
}
__device__ __forceinline__ void spin_cycles(uint32_t n) {
    if (n > 0) { const uint32_t c0 = clock32(); while (clock32() - c0 < n) {} }
}
__device__ __forceinline__ float rcp_approx(float x) {
    float r;
    asm("rcp.approx.ftz.f32 %0, %1;" : "=f"(r) : "f"(x));
    return r;
}
__device__ __forceinline__ float sqrt_approx(float x) {
    float r;
    asm("sqrt.approx.f32 %0, %1;" : "=f"(r) : "f"(x));
    return r;
}

__device__ __forceinline__ float silu_bf(float v) { return bf16r(v / (1.0f + expf(-v))); }

__device__ __forceinline__ float2 half_warp_sums(const float (&v)[4], float pivot) {
    float s1 = 0.f, s2 = 0.f;
#pragma unroll
    for (int i = 0; i < 4; i++) { const float d = v[i] - pivot; s1 += d; s2 += d * d; }
#pragma unroll
    for (int o = 1; o < 16; o <<= 1) { s1 += __shfl_xor_sync(0xffffffffu, s1, o); s2 += __shfl_xor_sync(0xffffffffu, s2, o); }
    return make_float2(s1, s2);
}
__device__ __forceinline__ void ln_stats(const float2* stat, int b, float pivot, float& mean_bf, float& rstd) {
    float s1 = 0.f, s2 = 0.f;
#pragma unroll
    for (int w = 0; w < 8; w++) { const float2 v = stat[w * 2 + b]; s1 += v.x; s2 += v.y; }
    const float dm = s1 * (1.0f / D_MODEL);
    const float var = fmaxf(s2 * (1.0f / D_MODEL) - dm * dm, 0.f);
    mean_bf = bf16r(pivot + dm);
    rstd = rcp_approx(bf16r(sqrt_approx(bf16r(bf16r(var) + 1e-5f))));
}
__device__ __forceinline__ float ln_norm(float xv, float mean_bf, float rstd) { return bf16r(bf16r(xv - mean_bf) * rstd); }
__device__ __forceinline__ float ln_mod(float n, float cmul, float sadd) { return bf16r(n * bf16r(1.0f + cmul)) + sadd; }

__global__ void __launch_bounds__(NTHREADS, 1)
fused_block_kernel(const Params p, const __grid_constant__ CUtensorMap tm_k, const __grid_constant__ CUtensorMap tm_v,
                   const __grid_constant__ CUtensorMap tm_wq, const __grid_constant__ CUtensorMap tm_wmod,
                   const __grid_constant__ CUtensorMap tm_wmod8,
                   const __grid_constant__ CUtensorMap tm_wo, const __grid_constant__ CUtensorMap tm_wg,
                   const __grid_constant__ CUtensorMap tm_wu, const __grid_constant__ CUtensorMap tm_wd) {
    extern __shared__ unsigned char smem_raw[];
    const uint32_t sbase = (smem_u32(smem_raw) + 1023u) & ~1023u;
    unsigned char* sgen = smem_raw + (sbase - smem_u32(smem_raw));
    const int tid = threadIdx.x, warp = tid >> 5, lane = tid & 31;
    const int cta = blockIdx.x;
    const uint32_t bar_full = sbase + SM_BAR, bar_empty = bar_full + NST * 8;
    const uint32_t bar_clear = bar_empty + NST * 8;
    const uint32_t bar_gu = bar_clear + 8;
    const uint32_t bar_bc = bar_gu + 8 * 8;
    const uint32_t bar_p0w = bar_bc + 8;

    const int key0 = (cta >> 3) * SK + (cta & 7) * 64;
    uint64_t pol = 0;
    if (tid == 256) {
        asm volatile("createpolicy.fractional.L2::evict_first.b64 %0, 1.0;" : "=l"(pol));
        mbar_init(bar_p0w, 1);
#pragma unroll
        for (int i = 0; i < 4; i++) mbar_init(bar_full + 8 * i, 1);
        asm volatile("fence.mbarrier_init.release.cluster;" ::: "memory");
        mbar_expect_tx(bar_p0w, 8192);
        tma_2d(sbase + SM_MRG, &tm_wmod8, cta * 8, 0, bar_p0w);
        tma_2d(sbase + SM_MRG + 4096, &tm_wmod8, cta * 8, 256, bar_p0w);
#pragma unroll
        for (int i = 0; i < 4; i++) mbar_expect_tx(bar_full + 8 * i, TILE);
        tma_2d(sbase + SM_RING, &tm_wq, cta * 32, 0, bar_full);
        tma_2d(sbase + SM_RING + TILE, &tm_wq, cta * 32, 256, bar_full + 8);
        tma_3d_hint(sbase + SM_RING + 2 * TILE, &tm_k, 0, key0, 0, bar_full + 16, pol);
        tma_3d_hint(sbase + SM_RING + 3 * TILE, &tm_v, 0, key0, 0, bar_full + 24, pol);
    }

    if (warp == 8) {
        if (lane == 0) {
            for (int i = 0; i < NST; i++) { if (i >= 4) mbar_init(bar_full + 8 * i, 1); mbar_init(bar_empty + 8 * i, 4); }
            mbar_init(bar_clear, 1);
            for (int k = 0; k < 8; k++) mbar_init(bar_gu + 8 * k, 1);
            mbar_init(bar_bc, 8);
            ((volatile uint32_t*)(sgen + SM_PACE))[0] = 0;
            ((volatile uint32_t*)(sgen + SM_PACE))[1] = WINDOW;
            asm volatile("fence.mbarrier_init.release.cluster;" ::: "memory");
        }
        __syncwarp();
        asm volatile("bar.arrive 2, 320;" ::: "memory");
        asm volatile("bar.arrive 3, 64;" ::: "memory");
        if (lane == 0) {
            int slot = 4; uint32_t ph = 1;
            int landed = 0, wslot = 0; uint32_t wph = 0;
            int kv = 2;
            auto wait_window = [&](int idx, int window) {
                while (landed + window <= idx) {
                    mbar_wait(bar_full + 8 * wslot, wph);
                    if (++wslot == NST) { wslot = 0; wph ^= 1; }
                    landed++;
                }
            };
            volatile uint32_t* pace = (volatile uint32_t*)(sgen + SM_PACE);
            prefetch_tmap(&tm_wmod);
            pace[0] = 4;
            for (int idx = 4; idx < N_STREAM; idx++) {
                if (idx >= NST) mbar_wait(bar_empty + 8 * slot, ph);
                wait_window(idx, (int)pace[1]);
                if (idx == 12) { prefetch_tmap(&tm_wo); prefetch_tmap(&tm_wg); prefetch_tmap(&tm_wu); prefetch_tmap(&tm_wd); }
                const uint32_t fb = bar_full + 8 * slot, dst = sbase + SM_RING + slot * TILE;
                mbar_expect_tx(fb, TILE);
                if (idx == IDX_MOD) {
                    tma_2d(dst, &tm_wmod, 1024 + cta * 16, 0, fb);
                    tma_2d(dst + 8192, &tm_wmod, 1024 + cta * 16, 256, fb);
                } else {
                    tma_3d_hint(dst, (kv & 1) ? &tm_v : &tm_k, 0, key0 + (kv >> 1) * 512, 0, fb, pol);
                    kv++;
                }
                pace[0] = idx + 1;
                if (++slot == NST) { slot = 0; ph ^= 1; }
            }
            auto slot_free = [&](int idx) { mbar_wait(bar_empty + 8 * (idx % NST), ((idx / NST) & 1) ^ 1); };
#pragma unroll
            for (int s = 0; s < 2; s++) {
                const int idx = IDX_WO + s;
                slot_free(idx);
                wait_window(idx, WINDOW_TAIL);
                mbar_expect_tx(bar_full + 8 * (idx % NST), TILE);
                tma_3d(sbase + SM_RING + (idx % NST) * TILE, &tm_wo, 0, (cta >> 2) * 128 + s * 64, (cta & 3) * 2, bar_full + 8 * (idx % NST));
            }
            if (cta < NFFN) {
                slot_free(IDX_WG); slot_free(IDX_WU);
                mbar_wait(bar_full + 8 * (IDX_WO % NST), (IDX_WO / NST) & 1);
                mbar_wait(bar_full + 8 * ((IDX_WO + 1) % NST), ((IDX_WO + 1) / NST) & 1);
#pragma unroll
                for (int st = 0; st < 8; st++) {
                    if (st >= GU_WIN) mbar_wait(bar_gu + 8 * (st - GU_WIN), 0);
                    mbar_expect_tx(bar_gu + 8 * st, 4096);
                    tma_2d(sbase + SM_RING + (((st & 1) ? IDX_WU : IDX_WG) % NST) * TILE + (st >> 1) * 4096,
                           (st & 1) ? &tm_wu : &tm_wg, cta * 16, (st >> 1) * 128, bar_gu + 8 * st);
                }
                mbar_wait(bar_gu + 8 * 7, 0);
                slot_free(IDX_WD);
                mbar_expect_tx(bar_full + 8 * (IDX_WD % NST), TILE);
                tma_3d(sbase + SM_RING + (IDX_WD % NST) * TILE, &tm_wd, 0, cta * 16, 0, bar_full + 8 * (IDX_WD % NST));
            }
        }
    } else if (warp == 9) {
        Scratch* const sc = p.sc;
        const uint32_t tag = *(volatile unsigned*)&sc->epoch + 1;
        if (lane < 2) {
            st_ll4((uint4*)&sc->mod[lane][cta * 4], 0u, 0u, 0u);
            st_ll4((uint4*)&sc->mod[lane][cta * 4] + 1, 0u, 0u, 0u);
        }
        if (lane < 8) st_ll4((uint4*)&sc->mod[lane >> 2][512 + cta * 8] + (lane & 3), 0u, 0u, 0u);
        if (lane < 16) st_ll4((uint4*)&sc->q[lane >> 3][cta * 16] + (lane & 7), 0u, 0u, 0u);
        __syncwarp();
        asm volatile("bar.arrive 2, 320;" ::: "memory");
        asm volatile("bar.sync 3, 64;" ::: "memory");
#pragma unroll 4
        for (int i = 0; i < NFFN * 2 / 32; i++) st_v4(&sc->inbox_dn[cta][0][0] + i * 32 + lane, 0u, 0u, 0u, 0u);
        if (cta >= NCTA - NOWN) {
#pragma unroll 4
            for (int i = 0; i < 8; i++) st_v4(&sc->inbox_wo[cta - (NCTA - NOWN)][0][0] + i * 32 + lane, 0u, 0u, 0u, 0u);
            if (lane < 8) st_v4((uint4*)&sc->x1[(cta - (NCTA - NOWN)) * 16] + lane, 0u, 0u, 0u, 0u);
        }
#pragma unroll 4
        for (int i = 0; i < 4; i++) st_v4((uint4*)&sc->part_o[cta][0][0] + i * 32 + lane, 0u, 0u, 0u, 0u);
        if (lane < 8) st_v4((uint4*)&sc->part_ml[cta][0][0] + lane, 0u, 0u, 0u, 0u);
        if (cta == 0 && lane == 0) asm volatile("st.relaxed.gpu.global.u32 [%0], %1;" ::"l"(&sc->progress), "r"(0u) : "memory");
        asm volatile("fence.acq_rel.gpu;" ::: "memory");
        __syncwarp();
        if (lane == 0) {
            asm volatile("fence.acq_rel.gpu;" ::: "memory");
            asm volatile("red.relaxed.gpu.global.add.u32 [%0], %1;" ::"l"(&sc->cleared), "r"(1u) : "memory");
            const uint32_t target = tag * NCTA;
            for (int it = 0; it < SPIN_LIMIT; it++) {
                uint32_t v;
                asm volatile("ld.relaxed.gpu.global.u32 %0, [%1];" : "=r"(v) : "l"(&sc->cleared) : "memory");
                if ((int32_t)(v - target) >= 0) break;
                __nanosleep(500);
            }
            asm volatile("fence.acq_rel.gpu;" ::: "memory");
            mbar_arrive(bar_clear);
            volatile uint32_t* pace = (volatile uint32_t*)(sgen + SM_PACE);
            uint32_t posted = 0;
            for (int it = 0; it < SPIN_LIMIT; it++) {
                const uint32_t own = pace[0];
                if (own >= N_STREAM) break;
                if (own > posted) {
                    asm volatile("red.relaxed.gpu.global.add.u32 [%0], %1;" ::"l"(&sc->progress), "r"(own - posted) : "memory");
                    posted = own;
                }
                uint32_t v;
                asm volatile("ld.relaxed.gpu.global.u32 %0, [%1];" : "=r"(v) : "l"(&sc->progress) : "memory");
                const int diff = (int)v - (int)own * NCTA;
                pace[1] = diff > PACE_THR ? WINDOW + 1 : diff < -PACE_THR ? WINDOW - 1 : WINDOW;
                __nanosleep(200);
            }
        }
    } else {
        const int g = lane >> 2, t = lane & 3;
        const int bb = g & 1;
        const int eb = lane >> 4;
        const int ec = 64 * warp + 4 * (lane & 15);
        if (warp == 0) TSTAMP(0);
        Scratch* const sc = p.sc;
        const float c00 = __bfloat162float(p.c[tid]), c01 = __bfloat162float(p.c[tid + 256]);
        const float c10 = __bfloat162float(p.c[D_MODEL + tid]), c11 = __bfloat162float(p.c[D_MODEL + tid + 256]);
        const uint2 xe = __ldg((const uint2*)(p.x + eb * D_MODEL + ec));
        const float xpivot = __bfloat162float(p.x[eb * D_MODEL]);
        const uint32_t tag = *(volatile unsigned*)&sc->epoch + 1;
        const int ocol = cta * 4 + (lane & 3);
        const int wcol = (cta >= NCTA - NOWN ? cta - (NCTA - NOWN) : 0) * 16 + (lane & 15);
        const float xo = __bfloat162float(p.x[eb * D_MODEL + wcol]);

        float* red = (float*)(sgen + SM_RED);
        float* red2 = (float*)(sgen + SM_RED2);
        float2* stat = (float2*)(sgen + SM_STAT);
        uint32_t* hs = (uint32_t*)(sgen + SM_HS) + warp * 64;
        float xn[4];
        {
            float xv[4] = {bf_lo(xe.x), bf_hi(xe.x), bf_lo(xe.y), bf_hi(xe.y)};
            const float2 ps = half_warp_sums(xv, xpivot);
            if ((lane & 15) == 0) stat[warp * 2 + eb] = ps;
            const float s00 = silu_bf(c00), s01 = silu_bf(c01), s10 = silu_bf(c10), s11 = silu_bf(c11);
            __nv_bfloat16* scs = (__nv_bfloat16*)(sgen + SM_SC);
            scs[tid] = __float2bfloat16_rn(s00); scs[tid + 256] = __float2bfloat16_rn(s01);
            scs[512 + tid] = __float2bfloat16_rn(s10); scs[512 + tid + 256] = __float2bfloat16_rn(s11);
            asm volatile("bar.sync 2, 320;" ::: "memory");
            if (warp == 0) TSTAMP(23);
            float cp[4] = {0.f, 0.f, 0.f, 0.f};
            const uint32_t* sc32 = (const uint32_t*)(sgen + SM_SC) + bb * 256 + 32 * warp + t;
            mbar_wait(bar_p0w, 0);
#pragma unroll
            for (int s = 0; s < 4; s++) {
                uint32_t r0, r1;
                asm volatile("ldmatrix.sync.aligned.m8n8.x2.trans.shared.b16 {%0,%1}, [%2];"
                             : "=r"(r0), "=r"(r1) : "r"(sbase + SM_MRG + (64 * warp + 16 * s + (lane & 15)) * 16) : "memory");
                const uint32_t a[4] = {r0, r0, r1, r1};
                mma16816(cp, a, sc32[8 * s], sc32[8 * s + 4]);
            }
            if (t == 0) { red[warp * 16 + g] = cp[0]; red[warp * 16 + 8 + g] = cp[1]; }
            if (warp == 0) TSTAMP(14);
            cons_sync();
            if (warp == 0) {
                float s = 0.f;
#pragma unroll
                for (int w = 0; w < 8; w++) s += red[w * 16 + (lane & 15)];
                const float nx = __shfl_down_sync(0xffffffffu, s, 1);
                if (lane < 16 && !(lane & 1))
                    st_ll2(&sc->mod[lane >> 3][cta * 4 + ((lane & 7) >> 1)], pack_bf16(s, nx), tag);
                TSTAMP(1);
            }
            float mean_bf, rstd;
            ln_stats(stat, eb, xpivot, mean_bf, rstd);
#pragma unroll
            for (int i = 0; i < 4; i++) xn[i] = ln_norm(xv[i], mean_bf, rstd);
        }
        {
            uint4 sa, ca;
            for (int it = 0;; it++) {
                sa = ld_ll4((const uint4*)&sc->mod[eb][ec >> 1]);
                ca = ld_ll4((const uint4*)&sc->mod[eb][256 + (ec >> 1)]);
                const bool ok = sa.y == tag && sa.w == tag && ca.y == tag && ca.w == tag;
                if (__all_sync(0xffffffffu, ok) || it > SPIN_LIMIT) break;
            }
            *(uint2*)&hs[eb * 32 + 2 * (lane & 15)] =
                make_uint2(pack_bf16(ln_mod(xn[0], bf_lo(ca.x), bf_lo(sa.x)), ln_mod(xn[1], bf_hi(ca.x), bf_hi(sa.x))),
                           pack_bf16(ln_mod(xn[2], bf_lo(ca.z), bf_lo(sa.z)), ln_mod(xn[3], bf_hi(ca.z), bf_hi(sa.z))));
            __syncwarp();
            uint32_t hb[8];
#pragma unroll
            for (int i = 0; i < 8; i++) hb[i] = hs[bb * 32 + 8 * (i >> 1) + 4 * (i & 1) + t];
            if (warp == 0) TSTAMP(2);
            float cq[2][4] = {};
            const int ts = warp >> 2;
            mbar_wait(bar_full + 8 * ts, 0);
            const uint32_t tb = sbase + SM_RING + ts * TILE;
#pragma unroll
            for (int s = 0; s < 4; s++) {
                const int row = 64 * (warp & 3) + 16 * s + (lane & 7) + (lane >> 4) * 8;
#pragma unroll
                for (int mt = 0; mt < 2; mt++) {
                    const int ch = 2 * mt + ((lane >> 3) & 1);
                    uint32_t a[4];
                    ldsm4t(tb + row * 64 + ((ch ^ ((row >> 1) & 3)) << 4), a);
                    mma16816(cq[mt], a, hb[2 * s], hb[2 * s + 1]);
                }
            }
            if (t < 2) {
                const float v0 = t == 0 ? cq[0][0] : cq[1][0], v1 = t == 0 ? cq[0][1] : cq[1][1];
                const float v2 = t == 0 ? cq[0][2] : cq[1][2], v3 = t == 0 ? cq[0][3] : cq[1][3];
                *(float2*)&red2[warp * 64 + (16 * t + g) * 2] = make_float2(v0, v1);
                *(float2*)&red2[warp * 64 + (16 * t + g + 8) * 2] = make_float2(v2, v3);
            }
            cons_sync();
            if (warp < 4 && lane == 0) { mbar_arrive(bar_empty); mbar_arrive(bar_empty + 8); }
            if (warp == 0) {
                const int b = lane >> 4, cp = lane & 15;
                float q0 = 0.f, q1 = 0.f;
#pragma unroll
                for (int w = 0; w < 8; w++) {
                    const float4 v = *(const float4*)&red2[w * 64 + cp * 4];
                    q0 += b ? v.y : v.x; q1 += b ? v.w : v.z;
                }
                st_ll2(&sc->q[b][cta * 16 + cp], pack_bf16(q0, q1), tag);
                TSTAMP(3);
            }
        }
        const int pair = cta >> 3;
        uint32_t qf[16];
        {
            uint2* qs = (uint2*)(sgen + SM_QS);
            if (tid < 128) {
                const uint4* src = (const uint4*)&sc->q[pair >> 3][(pair & 7) * 256] + tid;
                uint4 v;
                for (int it = 0;; it++) {
                    v = ld_ll4(src);
                    if ((v.y == tag && v.w == tag) || it > SPIN_LIMIT) break;
                }
                qs[tid] = make_uint2(v.x, v.z);
            }
            cons_sync();
            const uint32_t* q32 = (const uint32_t*)(sgen + SM_QS);
#pragma unroll
            for (int s = 0; s < 8; s++) {
                qf[2 * s] = q32[(g & 3) * 64 + 8 * s + t];
                qf[2 * s + 1] = q32[(g & 3) * 64 + 8 * s + 4 + t];
            }
        }
        if (warp == 0) TSTAMP(4);

        float o[8][4];
#pragma unroll
        for (int i = 0; i < 8; i++) { o[i][0] = o[i][1] = o[i][2] = o[i][3] = 0.f; }
        uint32_t mrun = 0xff80ff80u;
        float ls[4] = {0.f, 0.f, 0.f, 0.f};
        uint4 m_sb, m_cb; uint2 m_ga, m_gb0, m_gb1;
        {
            const int grp = warp >> 2, wi = warp & 3;
            const int krow = 16 * wi + (lane & 7) + ((lane >> 3) & 1) * 8;
            const uint32_t koff = krow * 128 + ((((lane >> 4) & 1) ^ (lane & 7)) << 4);
            const int vrow = 16 * wi + (lane & 7) + (lane >> 4) * 8;
            const uint32_t voff = vrow * 128 + ((((lane >> 3) & 1) ^ (lane & 7)) << 4);
            const uint32_t ones[4] = {0x3f803f80u, 0x3f803f80u, 0x3f803f80u, 0x3f803f80u};
            for (int i = grp; i < KV_TILES; i += 2) {
                if (i == MOD_AT + grp) {
                    float cm[4] = {};
                    const uint32_t* sc32 = (const uint32_t*)(sgen + SM_SC) + bb * 256 + 32 * warp + t;
                    mbar_wait(bar_full + 8 * (IDX_MOD % NST), (IDX_MOD / NST) & 1);
                    const uint32_t tb = sbase + SM_RING + (IDX_MOD % NST) * TILE;
#pragma unroll
                    for (int s = 0; s < 4; s++) {
                        const int row = 64 * warp + 16 * s + (lane & 7) + (lane >> 4) * 8;
                        const int ch = (lane >> 3) & 1;
                        uint32_t a[4];
                        ldsm4t(tb + row * 32 + ((ch ^ ((row >> 2) & 1)) << 4), a);
                        mma16816(cm, a, sc32[8 * s], sc32[8 * s + 4]);
                    }
                    if (t == 0) {
                        *(float2*)&red[warp * 64 + g * 2] = make_float2(cm[0], cm[1]);
                        *(float2*)&red[warp * 64 + (g + 8) * 2] = make_float2(cm[2], cm[3]);
                    }
                    cons_sync();
                    if (warp < 4 && lane == 0) mbar_arrive(bar_empty + 8 * (IDX_MOD % NST));
                    if (warp == 1 && lane < 16) {
                        const int b = lane >> 3, cp = lane & 7;
                        float q0 = 0.f, q1 = 0.f;
#pragma unroll
                        for (int w = 0; w < 8; w++) {
                            const float4 v = *(const float4*)&red[w * 64 + cp * 4];
                            q0 += b ? v.y : v.x; q1 += b ? v.w : v.z;
                        }
                        st_ll2(&sc->mod[b][512 + cta * 8 + cp], pack_bf16(q0, q1), tag);
                    }
                }
                if (i == 56 + grp) {
                    m_sb = ld_ll4((const uint4*)&sc->mod[eb][768 + (ec >> 1)]);
                    m_cb = ld_ll4((const uint4*)&sc->mod[eb][1024 + (ec >> 1)]);
                    m_ga = ld_ll2(&sc->mod[eb][512 + (wcol >> 1)]);
                    m_gb0 = ld_ll2(&sc->mod[0][1280 + (ocol >> 1)]); m_gb1 = ld_ll2(&sc->mod[1][1280 + (ocol >> 1)]);
                }
                if (i == 60 + grp) {
                    for (int it = 0;; it++) {
                        const bool ok = m_sb.y == tag && m_sb.w == tag && m_cb.y == tag && m_cb.w == tag &&
                                        m_ga.y == tag && m_gb0.y == tag && m_gb1.y == tag;
                        if (__all_sync(0xffffffffu, ok) || it > SPIN_LIMIT) break;
                        m_sb = ld_ll4((const uint4*)&sc->mod[eb][768 + (ec >> 1)]);
                        m_cb = ld_ll4((const uint4*)&sc->mod[eb][1024 + (ec >> 1)]);
                        m_ga = ld_ll2(&sc->mod[eb][512 + (wcol >> 1)]);
                        m_gb0 = ld_ll2(&sc->mod[0][1280 + (ocol >> 1)]); m_gb1 = ld_ll2(&sc->mod[1][1280 + (ocol >> 1)]);
                    }
                    mbar_wait(bar_clear, 0);
                }
                const int ki = kv_idx(i), ks = ki % NST, vs = (ki + 1) % NST;
                const uint32_t kph = (ki / NST) & 1, vph = ((ki + 1) / NST) & 1;
                mbar_wait(bar_full + 8 * ks, kph);
                const uint32_t kb = sbase + SM_RING + ks * TILE + koff;
                float sa[4] = {0.f, 0.f, 0.f, 0.f}, sb[4] = {0.f, 0.f, 0.f, 0.f};
#pragma unroll
                for (int s = 0; s < 8; s += 2) {
                    uint32_t a0[4], a1[4];
                    ldsm4((kb ^ ((s & 3) << 5)) + (s >> 2) * 8192, a0);
                    ldsm4((kb ^ (((s + 1) & 3) << 5)) + (s >> 2) * 8192, a1);
                    mma16816(sa, a0, qf[2 * s], qf[2 * s + 1]);
                    mma16816(sb, a1, qf[2 * s + 2], qf[2 * s + 3]);
                }
                __syncwarp();
                if (lane == 0) mbar_arrive(bar_empty + 8 * ks);
                uint32_t r01 = pack_bf16(sa[0] + sb[0], sa[1] + sb[1]);
                uint32_t r23 = pack_bf16(sa[2] + sb[2], sa[3] + sb[3]);
                r01 = pack_bf16(bf_lo(r01) * QK_SCALE, bf_hi(r01) * QK_SCALE);
                r23 = pack_bf16(bf_lo(r23) * QK_SCALE, bf_hi(r23) * QK_SCALE);
                uint32_t mx = max_bf16x2(r01, r23);
                mx = max_bf16x2(mx, __shfl_xor_sync(0xffffffffu, mx, 4));
                mx = max_bf16x2(mx, __shfl_xor_sync(0xffffffffu, mx, 8));
                mx = max_bf16x2(mx, __shfl_xor_sync(0xffffffffu, mx, 16));
                const uint32_t mnew = max_bf16x2(mrun, mx);
                const float m0 = bf_lo(mnew), m1 = bf_hi(mnew);
                if (__any_sync(0xffffffffu, mnew != mrun)) {
                    const float al0 = ex2((bf_lo(mrun) - m0) * LOG2E), al1 = ex2((bf_hi(mrun) - m1) * LOG2E);
                    ls[0] *= al0; ls[1] *= al1;
#pragma unroll
                    for (int d = 0; d < 8; d++) { o[d][0] *= al0; o[d][1] *= al1; o[d][2] *= al0; o[d][3] *= al1; }
                    mrun = mnew;
                }
                const float p0 = ex2((bf_lo(r01) - m0) * LOG2E), p1 = ex2((bf_hi(r01) - m1) * LOG2E);
                const float p2 = ex2((bf_lo(r23) - m0) * LOG2E), p3 = ex2((bf_hi(r23) - m1) * LOG2E);
                const uint32_t pb0 = movmatrix_t(pack_bf16(p0, p1)), pb1 = movmatrix_t(pack_bf16(p2, p3));
                mma16816(ls, ones, pb0, pb1);
                mbar_wait(bar_full + 8 * vs, vph);
                const uint32_t vb = sbase + SM_RING + vs * TILE + voff;
#pragma unroll
                for (int d = 0; d < 8; d++) {
                    uint32_t a[4];
                    ldsm4t((vb ^ ((d & 3) << 5)) + (d >> 2) * 8192, a);
                    mma16816(o[d], a, pb0, pb1);
                }
                __syncwarp();
                if (lane == 0) mbar_arrive(bar_empty + 8 * vs);
            }
        }
        if (warp == 7) TSTAMP(5);
        {
            float* mrg = (float*)(sgen + SM_MRG);
            float2* ml = (float2*)(sgen + SM_ML);
            {
                const int hp = (t & 1) * 2, up = t >> 1;
                if (g == 0 && up == 0) { ml[warp * 4 + hp] = make_float2(bf_lo(mrun), ls[0]); ml[warp * 4 + hp + 1] = make_float2(bf_hi(mrun), ls[1]); }
                float* m0p = mrg + (warp * 4 + hp) * 136 + up * 72 + g;
#pragma unroll
                for (int d = 0; d < 4; d++) {
                    m0p[16 * d] = up ? o[d + 4][0] : o[d][0]; m0p[136 + 16 * d] = up ? o[d + 4][1] : o[d][1];
                    m0p[16 * d + 8] = up ? o[d + 4][2] : o[d][2]; m0p[136 + 16 * d + 8] = up ? o[d + 4][3] : o[d][3];
                }
            }
            cons_sync();
            const int hh = tid >> 6, dp = tid & 63;
            float2 mw[8];
            float M = -INFINITY;
#pragma unroll
            for (int w = 0; w < 8; w++) { mw[w] = ml[w * 4 + hh]; M = fmaxf(M, mw[w].x); }
            float L = 0.f, o0 = 0.f, o1 = 0.f;
#pragma unroll
            for (int w = 0; w < 8; w++) {
                const float wt = ex2((mw[w].x - M) * LOG2E);
                const float2 v = *(const float2*)&mrg[(w * 4 + hh) * 136 + 2 * dp + (dp >= 32 ? 8 : 0)];
                L += wt * mw[w].y; o0 += wt * v.x; o1 += wt * v.y;
            }
            st_ll2(&sc->part_o[cta][hh][dp], tagf(o0, F_PART), tagf(o1, F_PART));
            if (dp < 4) st_ll2(&sc->part_ml[cta][hh][dp], tagf(M, F_PART), tagf(L, F_PART));
        }
        if (warp == 0) TSTAMP(6);
        {
            const int hq = cta >> 2, kvh = hq >> 2, hh = hq & 3;
            const int b = tid >> 7, dc = (tid >> 3) & 15, j = tid & 7;
            const int pc = (b * 8 + kvh) * 8 + j;
            const uint4* po = (const uint4*)&sc->part_o[pc][hh][0] + dc * 2;
            const uint2* pm = &sc->part_ml[pc - j][hh][0];
            uint4 vo0, vo1; uint2 vm[8];
            bool oko = false, okm = false;
            for (int it = 0;; it++) {
                if (!oko) { vo0 = ld_ll4(po); vo1 = ld_ll4(po + 1); }
                if (!okm) {
#pragma unroll
                    for (int jj = 0; jj < 8; jj++) vm[jj] = ld_ll2(pm + jj * 16);
                }
                oko = (vo0.x & vo0.y & vo0.z & vo0.w & vo1.x & vo1.y & vo1.z & vo1.w & 3u) == F_PART;
                uint32_t all = vm[0].x & vm[0].y;
#pragma unroll
                for (int jj = 1; jj < 8; jj++) all &= vm[jj].x & vm[jj].y;
                okm = (all & 3u) == F_PART;
                if (__all_sync(0xffffffffu, oko && okm) || it > SPIN_LIMIT) break;
            }
            float M = untag(vm[0].x);
#pragma unroll
            for (int jj = 1; jj < 8; jj++) M = fmaxf(M, untag(vm[jj].x));
            float wt = 0.f, L = 0.f;
#pragma unroll
            for (int jj = 0; jj < 8; jj++) {
                const float w_ = ex2((untag(vm[jj].x) - M) * LOG2E);
                L += w_ * untag(vm[jj].y);
                wt = jj == j ? w_ : wt;
            }
            wt *= rcp_approx(L);
            float v[8] = {wt * untag(vo0.x), wt * untag(vo0.y), wt * untag(vo0.z), wt * untag(vo0.w),
                          wt * untag(vo1.x), wt * untag(vo1.y), wt * untag(vo1.z), wt * untag(vo1.w)};
#define XRED(N, O)                                                                       \
            {                                                                            \
                const bool up = lane & (O);                                              \
                _Pragma("unroll") for (int i = 0; i < (N); i++) {                        \
                    const float send = up ? v[i] : v[i + (N)], keep = up ? v[i + (N)] : v[i]; \
                    v[i] = keep + __shfl_xor_sync(0xffffffffu, send, (O));               \
                }                                                                        \
            }
            XRED(4, 1) XRED(2, 2) XRED(1, 4)
#undef XRED
            __nv_bfloat16* os = (__nv_bfloat16*)(sgen + SM_OS);
            os[b * 128 + dc * 8 + 4 * (j & 1) + 2 * ((j >> 1) & 1) + (j >> 2)] = __float2bfloat16_rn(v[0]);
            if (warp == 0) TSTAMP(15);
            uint32_t wf[8][4];
            const uint32_t aoff_o = (warp >> 2) * 8192 + ((lane & 7) + (lane >> 4) * 8) * 128 +
                                    (((((warp & 3) * 2 + ((lane >> 3) & 1)) ^ (lane & 7))) << 4);
#pragma unroll
            for (int s = 0; s < 2; s++) {
                const int idx = IDX_WO + s;
                mbar_wait(bar_full + 8 * (idx % NST), (idx / NST) & 1);
                const uint32_t tb = sbase + SM_RING + (idx % NST) * TILE + aoff_o;
#pragma unroll
                for (int k4 = 0; k4 < 4; k4++) ldsm4t(tb + k4 * 2048, wf[s * 4 + k4]);
            }
            cons_sync();
            if (warp == 0) TSTAMP(7);
            const uint32_t* os32 = (const uint32_t*)(sgen + SM_OS) + bb * 64 + t;
            float y0[4] = {}, y1[4] = {};
#pragma unroll
            for (int ks = 0; ks < 8; ks += 2) {
                mma16816(y0, wf[ks], os32[8 * ks], os32[8 * ks + 4]);
                mma16816(y1, wf[ks + 1], os32[8 * ks + 8], os32[8 * ks + 12]);
            }
            if (t == 0)
                st_v4(&sc->inbox_wo[(cta & 3) * 8 + warp][hq][g], tagf(y0[0] + y1[0], F_WO), tagf(y0[1] + y1[1], F_WO),
                      tagf(y0[2] + y1[2], F_WO), tagf(y0[3] + y1[3], F_WO));
        }
        if (warp == 0) TSTAMP(8);
        if (cta >= NCTA - NOWN) {
            const uint4* pin = &sc->inbox_wo[cta - (NCTA - NOWN)][0][0] + tid;
            uint4 v;
            spin_cycles(DELAY_B1);
            bool ok = false;
            for (int it = 0;; it++) {
                if (!ok) {
                    v = ld_ll4(pin);
                    ok = (v.x & v.y & v.z & v.w & 3u) == F_WO;
                }
                if (__all_sync(0xffffffffu, ok) || it > SPIN_LIMIT) break;
            }
            const bool u1 = lane & 8, u2 = lane & 16;
            const float a0 = untag(v.x), a1 = untag(v.y), a2 = untag(v.z), a3 = untag(v.w);
            const float k0 = (u1 ? a2 : a0) + __shfl_xor_sync(0xffffffffu, u1 ? a0 : a2, 8);
            const float k1 = (u1 ? a3 : a1) + __shfl_xor_sync(0xffffffffu, u1 ? a1 : a3, 8);
            red2[warp * 32 + lane] = (u2 ? k1 : k0) + __shfl_xor_sync(0xffffffffu, u2 ? k0 : k1, 16);
            cons_sync();
            if (warp == 0) {
                float a = 0.f;
#pragma unroll
                for (int w = 0; w < 8; w++) a += red2[w * 32 + lane];
                const float ga = (wcol & 1) ? bf_hi(m_ga.x) : bf_lo(m_ga.x);
                const float xm = bf16r(xo + bf16r(ga * bf16r(a)));
                const float xm_b1 = __shfl_down_sync(0xffffffffu, xm, 16);
                if (lane < 16) st_ll2(&sc->x1[wcol], pack_bf16(xm, xm_b1), F_X1);
                TSTAMP(10);
            }
        }
        const uint32_t aoff = warp * 2048 + ((lane & 7) + (lane >> 4) * 8) * 128 + ((((lane >> 3) & 1) ^ (lane & 7)) << 4);
        if (cta < NFFN) {
            const uint4* px = (const uint4*)&sc->x1[ec];
            const uint4* pp = (const uint4*)&sc->x1[0];
            uint4 va, vb, pa, pb;
            uint32_t gf[4][4], uf[4][4];
            mbar_wait(bar_gu + 8 * (2 * (warp >> 1)), 0);
            mbar_wait(bar_gu + 8 * (2 * (warp >> 1) + 1), 0);
            {
                const uint32_t tg = sbase + SM_RING + (IDX_WG % NST) * TILE, tu = sbase + SM_RING + (IDX_WU % NST) * TILE;
#pragma unroll
                for (int s = 0; s < 4; s++) {
                    const int row = 64 * warp + 16 * s + (lane & 7) + (lane >> 4) * 8;
                    const uint32_t off = row * 32 + ((((lane >> 3) & 1) ^ ((row >> 2) & 1)) << 4);
                    ldsm4t(tg + off, gf[s]);
                    ldsm4t(tu + off, uf[s]);
                }
            }
            const float c1v[4] = {bf16r(1.0f + bf_lo(m_cb.x)), bf16r(1.0f + bf_hi(m_cb.x)), bf16r(1.0f + bf_lo(m_cb.z)), bf16r(1.0f + bf_hi(m_cb.z))};
            float bg = 0.f, cgc = 0.f, bu = 0.f, cuc = 0.f;
            {
                uint32_t* pre = (uint32_t*)(sgen + SM_MRG) + warp * 128;
                float* bc = (float*)(sgen + SM_MRG + 4096);
                *(uint2*)&pre[eb * 32 + 2 * (lane & 15)] = make_uint2(pack_bf16(c1v[0], c1v[1]), pack_bf16(c1v[2], c1v[3]));
                *(uint2*)&pre[64 + eb * 32 + 2 * (lane & 15)] = make_uint2(m_sb.x, m_sb.z);
                __syncwarp();
                float yg[4] = {}, yu[4] = {};
                const uint32_t* pb = pre + ((g >> 1) & 1) * 64 + bb * 32 + t;
#pragma unroll
                for (int s = 0; s < 4; s++) {
                    const uint32_t b0 = pb[8 * s], b1 = pb[8 * s + 4];
                    mma16816(yg, gf[s], b0, b1);
                    mma16816(yu, uf[s], b0, b1);
                }
                const float y0 = t < 2 ? yg[0] : yu[0], y1 = t < 2 ? yg[1] : yu[1], y2 = t < 2 ? yg[2] : yu[2], y3 = t < 2 ? yg[3] : yu[3];
                float* dstp = bc + warp * 128 + (t >> 1) * 64 + (t & 1) * 32;
                *(float2*)&dstp[g * 2] = make_float2(y0, y1);
                *(float2*)&dstp[(g + 8) * 2] = make_float2(y2, y3);
                __syncwarp();
                if (lane == 0) mbar_arrive(bar_bc);
            }
            if (warp == 0) TSTAMP(11);
            float pivot2;
            {
                bool okx = false, okp = false;
                for (int it = 0;; it++) {
                    if (!okx) { va = ld_ll4(px); vb = ld_ll4(px + 1); }
                    if (!okp) { pa = ld_ll4(pp); pb = ld_ll4(pp + 1); }
                    okx = va.y == F_X1 && va.w == F_X1 && vb.y == F_X1 && vb.w == F_X1;
                    okp = pa.y == F_X1 && pa.w == F_X1 && pb.y == F_X1 && pb.w == F_X1;
                    if (__all_sync(0xffffffffu, okx && okp) || it > SPIN_LIMIT) break;
                }
                if (warp == 0) TSTAMP(9);
                const float xv[4] = {eb ? bf_hi(va.x) : bf_lo(va.x), eb ? bf_hi(va.z) : bf_lo(va.z),
                                     eb ? bf_hi(vb.x) : bf_lo(vb.x), eb ? bf_hi(vb.z) : bf_lo(vb.z)};
                const float p0 = 0.25f * ((bf_lo(pa.x) + bf_lo(pa.z)) + (bf_lo(pb.x) + bf_lo(pb.z)));
                const float p1 = 0.25f * ((bf_hi(pa.x) + bf_hi(pa.z)) + (bf_hi(pb.x) + bf_hi(pb.z)));
                const float pivot = eb ? p1 : p0;
                pivot2 = (lane & 1) ? p1 : p0;
                *(uint2*)&hs[eb * 32 + 2 * (lane & 15)] =
                    make_uint2(pack_bf16((xv[0] - pivot) * c1v[0], (xv[1] - pivot) * c1v[1]),
                               pack_bf16((xv[2] - pivot) * c1v[2], (xv[3] - pivot) * c1v[3]));
                __syncwarp();
                float cg[2][4] = {}, cu[2][4] = {};
#pragma unroll
                for (int s = 0; s < 4; s++) {
                    const uint32_t b0 = hs[bb * 32 + 8 * s + t], b1 = hs[bb * 32 + 8 * s + 4 + t];
                    mma16816(cg[s & 1], gf[s], b0, b1);
                    mma16816(cu[s & 1], uf[s], b0, b1);
                }
                const float2 ps = half_warp_sums(xv, pivot);
                if ((lane & 15) == 0) stat[warp * 2 + eb] = ps;
                {
                    const float* bc = (const float*)(sgen + SM_MRG + 4096);
                    mbar_wait(bar_bc, 0);
#pragma unroll
                    for (int w = 0; w < 8; w++) {
                        bg += bc[w * 128 + lane]; cgc += bc[w * 128 + 32 + lane];
                        bu += bc[w * 128 + 64 + lane]; cuc += bc[w * 128 + 96 + lane];
                    }
                }
                if (t < 2) {
                    float v[4];
#pragma unroll
                    for (int i = 0; i < 4; i++) v[i] = t ? cu[0][i] + cu[1][i] : cg[0][i] + cg[1][i];
                    *(float2*)&red[warp * 64 + t * 32 + g * 2] = make_float2(v[0], v[1]);
                    *(float2*)&red[warp * 64 + t * 32 + (g + 8) * 2] = make_float2(v[2], v[3]);
                }
            }
            uint32_t df[4][4];
            mbar_wait(bar_full + 8 * (IDX_WD % NST), (IDX_WD / NST) & 1);
#pragma unroll
            for (int mt = 0; mt < 4; mt++) ldsm4t((sbase + SM_RING + (IDX_WD % NST) * TILE + aoff) ^ (mt << 5), df[mt]);
            cons_sync();
            {
                float gs = 0.f, us = 0.f;
#pragma unroll
                for (int w = 0; w < 8; w++) { gs += red[w * 64 + lane]; us += red[w * 64 + 32 + lane]; }
                float mean_bf, rstd;
                ln_stats(stat, lane & 1, pivot2, mean_bf, rstd);
                const float dm = mean_bf - pivot2;
                gs = bf16r(rstd * (gs - dm * bg) + cgc);
                us = rstd * (us - dm * bu) + cuc;
                const float u2 = gs * (1.0f + 0.044715f * gs * gs) * (2.0f * 0.7978845608028654f * LOG2E);
                const float ge = bf16r(__fdividef(gs, 1.0f + ex2(-u2)));
                const float act = bf16r(ge * bf16r(us));
                const float a0 = __shfl_sync(0xffffffffu, act, 4 * t + bb), a1 = __shfl_sync(0xffffffffu, act, 4 * t + 2 + bb);
                const float a2 = __shfl_sync(0xffffffffu, act, 4 * t + 16 + bb), a3 = __shfl_sync(0xffffffffu, act, 4 * t + 18 + bb);
                const uint32_t b0 = pack_bf16(a0, a1), b1 = pack_bf16(a2, a3);
                float y[4][4] = {};
#pragma unroll
                for (int mt = 0; mt < 4; mt++) mma16816(y[mt], df[mt], b0, b1);
                float v[4];
#pragma unroll
                for (int i = 0; i < 4; i++) v[i] = t == 0 ? y[0][i] : t == 1 ? y[1][i] : t == 2 ? y[2][i] : y[3][i];
            {
                const bool odd = g & 1;
                const float sx = odd ? v[0] : v[2], sy = odd ? v[1] : v[3];
                const float rx = __shfl_xor_sync(0xffffffffu, sx, 4), ry = __shfl_xor_sync(0xffffffffu, sy, 4);
                const int c0 = 64 * warp + 16 * t + (odd ? g + 7 : g);
                const float e0 = odd ? rx : v[0], e1 = odd ? ry : v[1], e2 = odd ? v[2] : rx, e3 = odd ? v[3] : ry;
                st_v4(&sc->inbox_dn[c0 >> 2][cta][(c0 >> 1) & 1], tagf(e0, F_DOWN), tagf(e1, F_DOWN), tagf(e2, F_DOWN), tagf(e3, F_DOWN));
            }
            }
            if (warp == 0) TSTAMP(12);
        }
        {
            uint2 xw;
            float r0;
            {
                const uint4* pin = &sc->inbox_dn[cta][0][0] + tid;
                uint4 v = make_uint4(F_DOWN, F_DOWN, F_DOWN, F_DOWN);
                spin_cycles(DELAY_C);
                xw = ld_ll2(&sc->x1[ocol]);
                bool ok = tid >= NFFN * 2;
                for (int it = 0;; it++) {
                    if (!ok) {
                        v = ld_ll4(pin);
                        ok = (v.x & v.y & v.z & v.w & 3u) == F_DOWN;
                    }
                    if (__all_sync(0xffffffffu, ok) || it > SPIN_LIMIT) break;
                }
                const bool u1 = lane & 2, u2 = lane & 4;
                const float a0 = untag(v.x), a1 = untag(v.y), a2 = untag(v.z), a3 = untag(v.w);
                const float k0 = (u1 ? a1 : a0) + __shfl_xor_sync(0xffffffffu, u1 ? a0 : a1, 2);
                const float k1 = (u1 ? a3 : a2) + __shfl_xor_sync(0xffffffffu, u1 ? a2 : a3, 2);
                r0 = (u2 ? k1 : k0) + __shfl_xor_sync(0xffffffffu, u2 ? k0 : k1, 4);
                r0 += __shfl_xor_sync(0xffffffffu, r0, 8);
                r0 += __shfl_xor_sync(0xffffffffu, r0, 16);
                if (lane < 8) red2[256 + warp * 8 + (2 * (lane & 1) + ((lane >> 2) & 1)) * 2 + ((lane >> 1) & 1)] = r0;
            }
            cons_sync();
            if (warp == 0) {
                float a0 = 0.f, a1 = 0.f;
#pragma unroll
                for (int w = 0; w < 8; w++) { const float2 v = *(const float2*)&red2[256 + w * 8 + (lane & 3) * 2]; a0 += v.x; a1 += v.y; }
                const bool hi = ocol & 1;
                const float gb0 = hi ? bf_hi(m_gb0.x) : bf_lo(m_gb0.x), gb1 = hi ? bf_hi(m_gb1.x) : bf_lo(m_gb1.x);
                for (int it = 0; !__all_sync(0xffffffffu, xw.y == F_X1) && it < SPIN_LIMIT; it++) xw = ld_ll2(&sc->x1[ocol]);
                if (lane < 4) {
                    p.out[ocol] = __float2bfloat16_rn(bf_lo(xw.x) + bf16r(gb0 * bf16r(a0)));
                    p.out[D_MODEL + ocol] = __float2bfloat16_rn(bf_hi(xw.x) + bf16r(gb1 * bf16r(a1)));
                }
                if (cta == 0 && lane == 0) *(volatile unsigned*)&sc->epoch = tag;
                TSTAMP(13);
            }
        }
    }
}

typedef CUresult (*EncodeFn)(CUtensorMap*, CUtensorMapDataType, cuuint32_t, void*, const cuuint64_t*, const cuuint64_t*,
                             const cuuint32_t*, const cuuint32_t*, CUtensorMapInterleave, CUtensorMapSwizzle,
                             CUtensorMapL2promotion, CUtensorMapFloatOOBfill);

struct Maps { CUtensorMap k, v, wq, wmod, wmod8, wo, wg, wu, wd; };

void encode(EncodeFn fn, CUtensorMap* m, const void* ptr, int rank, const cuuint64_t* dims, const cuuint64_t* strides,
            const cuuint32_t* box, CUtensorMapSwizzle sw) {
    const cuuint32_t es[3] = {1, 1, 1};
    fn(m, CU_TENSOR_MAP_DATA_TYPE_BFLOAT16, rank, const_cast<void*>(ptr), dims, strides, box, es,
       CU_TENSOR_MAP_INTERLEAVE_NONE, sw, CU_TENSOR_MAP_L2_PROMOTION_L2_256B, CU_TENSOR_MAP_FLOAT_OOB_FILL_NONE);
}

}

extern "C" void kernel_launch(void* const* d_in, const int* in_sizes, int n_in, void* d_out, int out_size) {
    (void)in_sizes; (void)n_in; (void)out_size;
    static EncodeFn enc = nullptr;
    static Scratch* scratch = nullptr;
    if (!enc) {
        cudaGetSymbolAddress((void**)&scratch, g_scratch);
        void* fn = nullptr;
        cudaDriverEntryPointQueryResult qr;
        cudaGetDriverEntryPoint("cuTensorMapEncodeTiled", &fn, cudaEnableDefault, &qr);
        enc = (EncodeFn)fn;
        cudaFuncSetAttribute(fused_block_kernel, cudaFuncAttributeMaxDynamicSharedMemorySize, SMEM_BYTES);
    }
    Maps m;
    {
        const cuuint64_t dims[3] = {64, (cuuint64_t)16 * SK, 2}, str[2] = {256, 128};
        const cuuint32_t box[3] = {64, 64, 2};
        encode(enc, &m.k, d_in[1], 3, dims, str, box, CU_TENSOR_MAP_SWIZZLE_128B);
        encode(enc, &m.v, d_in[2], 3, dims, str, box, CU_TENSOR_MAP_SWIZZLE_128B);
    }
    {
        const cuuint64_t dims[2] = {4096, 512}, str[1] = {8192};
        const cuuint32_t box[2] = {32, 256};
        encode(enc, &m.wq, d_in[3], 2, dims, str, box, CU_TENSOR_MAP_SWIZZLE_64B);
    }
    {
        const cuuint64_t dims[2] = {N_MOD, 512}, str[1] = {N_MOD * 2};
        const cuuint32_t box[2] = {16, 256};
        encode(enc, &m.wmod, d_in[10], 2, dims, str, box, CU_TENSOR_MAP_SWIZZLE_32B);
        const cuuint32_t box8[2] = {8, 256};
        encode(enc, &m.wmod8, d_in[10], 2, dims, str, box8, CU_TENSOR_MAP_SWIZZLE_NONE);
    }
    {
        const cuuint64_t dims_o[3] = {64, 4096, 8}, dims_d[3] = {64, D_FF, 8}, str[2] = {1024, 128};
        const cuuint32_t box[3] = {64, 16, 8}, box_o[3] = {64, 64, 2};
        encode(enc, &m.wo, d_in[4], 3, dims_o, str, box_o, CU_TENSOR_MAP_SWIZZLE_128B);
        encode(enc, &m.wd, d_in[8], 3, dims_d, str, box, CU_TENSOR_MAP_SWIZZLE_128B);
    }
    {
        const cuuint64_t dims[2] = {D_FF, 512}, str[1] = {D_FF * 2};
        const cuuint32_t box[2] = {16, 128};
        encode(enc, &m.wg, d_in[6], 2, dims, str, box, CU_TENSOR_MAP_SWIZZLE_32B);
        encode(enc, &m.wu, d_in[7], 2, dims, str, box, CU_TENSOR_MAP_SWIZZLE_32B);
    }
    Params p;
    p.x = (const __nv_bfloat16*)d_in[0];
    p.c = (const __nv_bfloat16*)d_in[9];
    p.out = (__nv_bfloat16*)d_out;
    p.sc = scratch;
    fused_block_kernel<<<NCTA, NTHREADS, SMEM_BYTES, cudaStreamPerThread>>>(p, m.k, m.v, m.wq, m.wmod, m.wmod8, m.wo, m.wg, m.wu, m.wd);
}
```

```cpp
#include <cuda_runtime.h>
#include <cuda.h>
#include <cuda_bf16.h>
#include <stdint.h>

namespace {

constexpr int D_MODEL = 512;
constexpr int N_HEADS = 32;
constexpr int SK = 32768;
constexpr int DH = 128;
constexpr int D_FF = 1792;
constexpr int N_MOD = 6 * D_MODEL;

constexpr int NCTA = 128;
constexpr int NFFN = D_FF / 16;
constexpr int NOWN = 32;
constexpr int NTHREADS = 320;
constexpr int NST = 12;
constexpr int TILE = 16384;
#define WINDOW 3
#define WINDOW_TAIL 2
#define GU_WIN 3
#define PACE_THR 96
constexpr int KV_TILES = 64;
#define MOD_AT 8
static_assert(MOD_AT % 2 == 0 && MOD_AT >= 2 && MOD_AT < 56, "schedule");
__host__ __device__ constexpr int kv_idx(int i) { return 2 + 2 * i + (i >= MOD_AT ? 1 : 0); }
constexpr int IDX_MOD = 2 + 2 * MOD_AT;
constexpr int N_STREAM = kv_idx(KV_TILES - 1) + 2;
constexpr int IDX_WO = N_STREAM;
constexpr int IDX_WG = IDX_WO + 2;
constexpr int IDX_WU = IDX_WG + 1;
constexpr int IDX_WD = IDX_WU + 1;
constexpr int SPIN_LIMIT = 1 << 20;

constexpr float LOG2E = 1.4426950408889634f;
constexpr float QK_SCALE = 0.08838834764831845f;

constexpr int SM_RING = 0;
constexpr int SM_MRG = SM_RING + NST * TILE;
constexpr int SM_ML = SM_MRG + 8 * 4 * 136 * 4;
constexpr int SM_RED = SM_ML + 8 * 4 * 8;
constexpr int SM_RED2 = SM_RED + 8 * 64 * 4;
constexpr int SM_QS = SM_RED2 + 8 * 64 * 4;
constexpr int SM_OS = SM_QS + 512 * 2;
constexpr int SM_SC = SM_OS + 2 * 128 * 2;
constexpr int SM_HS = SM_SC + 2 * 512 * 2;
constexpr int SM_STAT = SM_HS + 8 * 2 * 32 * 4;
constexpr int SM_PACE = SM_STAT + 8 * 2 * 8;
constexpr int SM_BAR = SM_PACE + 8;
constexpr int SM_END = SM_BAR + (2 * NST + 1 + 8 + 2) * 8;
constexpr int SMEM_BYTES = SM_END + 1024;

struct Scratch {
    uint4 inbox_wo[NOWN][N_HEADS][8];
    uint4 inbox_dn[NCTA][NFFN][2];
    uint2 x1[D_MODEL];
    uint2 part_o[NCTA][4][64];
    uint2 part_ml[NCTA][4][4];
    uint2 mod[2][N_MOD / 2];
    uint2 q[2][N_HEADS * DH / 2];
    unsigned epoch;
    unsigned pad_[31];
    unsigned cleared;
    unsigned pad2_[31];
    unsigned progress;
};
__device__ Scratch g_scratch;
constexpr uint32_t F_PART = 1, F_WO = 1, F_DOWN = 1, F_X1 = 1;
__device__ __forceinline__ uint32_t tagf(float v, uint32_t f) { return (__float_as_uint(v) & ~3u) | f; }
__device__ __forceinline__ float untag(uint32_t v) { return __uint_as_float(v & ~3u); }

struct Params {
    const __nv_bfloat16* x;
    const __nv_bfloat16* c;
    __nv_bfloat16* out;
    Scratch* sc;
};

#define TSTAMP(i) do { } while (0)

__device__ __forceinline__ uint32_t smem_u32(const void* p) { return (uint32_t)__cvta_generic_to_shared(p); }

__device__ __forceinline__ void mbar_init(uint32_t bar, uint32_t cnt) {
    asm volatile("mbarrier.init.shared::cta.b64 [%0], %1;" ::"r"(bar), "r"(cnt) : "memory");
}
__device__ __forceinline__ void mbar_expect_tx(uint32_t bar, uint32_t bytes) {
    asm volatile("mbarrier.arrive.expect_tx.shared::cta.b64 _, [%0], %1;" ::"r"(bar), "r"(bytes) : "memory");
}
__device__ __forceinline__ void mbar_arrive(uint32_t bar) {
    asm volatile("mbarrier.arrive.shared::cta.b64 _, [%0];" ::"r"(bar) : "memory");
}
__device__ __forceinline__ bool mbar_try(uint32_t bar, uint32_t parity) {
    uint32_t ok;
    asm volatile(
        "{\n\t.reg .pred p;\n\t"
        "mbarrier.try_wait.parity.shared::cta.b64 p, [%1], %2;\n\t"
        "selp.u32 %0, 1, 0, p;\n\t}"
        : "=r"(ok) : "r"(bar), "r"(parity) : "memory");
    return ok != 0;
}
__device__ __forceinline__ void mbar_wait(uint32_t bar, uint32_t parity) {
    if (mbar_try(bar, parity)) return;
    const long long t0 = clock64();
    while (!mbar_try(bar, parity))
        if (clock64() - t0 > (1ll << 31)) return;
}
__device__ __forceinline__ void cons_sync() { asm volatile("bar.sync 1, 256;" ::: "memory"); }

__device__ __forceinline__ void tma_2d(uint32_t dst, const CUtensorMap* m, int c0, int c1, uint32_t bar) {
    asm volatile("cp.async.bulk.tensor.2d.shared::cluster.global.mbarrier::complete_tx::bytes [%0], [%1, {%3, %4}], [%2];"
                 ::"r"(dst), "l"(m), "r"(bar), "r"(c0), "r"(c1) : "memory");
}
__device__ __forceinline__ void tma_3d(uint32_t dst, const CUtensorMap* m, int c0, int c1, int c2, uint32_t bar) {
    asm volatile("cp.async.bulk.tensor.3d.shared::cluster.global.mbarrier::complete_tx::bytes [%0], [%1, {%3, %4, %5}], [%2];"
                 ::"r"(dst), "l"(m), "r"(bar), "r"(c0), "r"(c1), "r"(c2) : "memory");
}
__device__ __forceinline__ void tma_3d_hint(uint32_t dst, const CUtensorMap* m, int c0, int c1, int c2, uint32_t bar, uint64_t pol) {
    asm volatile("cp.async.bulk.tensor.3d.shared::cluster.global.mbarrier::complete_tx::bytes.L2::cache_hint [%0], [%1, {%3, %4, %5}], [%2], %6;"
                 ::"r"(dst), "l"(m), "r"(bar), "r"(c0), "r"(c1), "r"(c2), "l"(pol) : "memory");
}
__device__ __forceinline__ void prefetch_tmap(const CUtensorMap* m) {
    asm volatile("prefetch.tensormap [%0];" ::"l"(m) : "memory");
}

__device__ __forceinline__ void ldsm4(uint32_t addr, uint32_t (&r)[4]) {
    asm volatile("ldmatrix.sync.aligned.m8n8.x4.shared.b16 {%0,%1,%2,%3}, [%4];"
                 : "=r"(r[0]), "=r"(r[1]), "=r"(r[2]), "=r"(r[3]) : "r"(addr) : "memory");
}
__device__ __forceinline__ void ldsm4t(uint32_t addr, uint32_t (&r)[4]) {
    asm volatile("ldmatrix.sync.aligned.m8n8.x4.trans.shared.b16 {%0,%1,%2,%3}, [%4];"
                 : "=r"(r[0]), "=r"(r[1]), "=r"(r[2]), "=r"(r[3]) : "r"(addr) : "memory");
}
__device__ __forceinline__ void mma16816(float (&c)[4], const uint32_t (&a)[4], uint32_t b0, uint32_t b1) {
    asm volatile("mma.sync.aligned.m16n8k16.row.col.f32.bf16.bf16.f32 {%0,%1,%2,%3}, {%4,%5,%6,%7}, {%8,%9}, {%0,%1,%2,%3};"
                 : "+f"(c[0]), "+f"(c[1]), "+f"(c[2]), "+f"(c[3])
                 : "r"(a[0]), "r"(a[1]), "r"(a[2]), "r"(a[3]), "r"(b0), "r"(b1));
}
__device__ __forceinline__ uint32_t movmatrix_t(uint32_t a) {
    uint32_t d;
    asm volatile("movmatrix.sync.aligned.m8n8.trans.b16 %0, %1;" : "=r"(d) : "r"(a));
    return d;
}
__device__ __forceinline__ uint32_t pack_bf16(float a, float b) {
    uint32_t r;
    asm("cvt.rn.bf16x2.f32 %0, %1, %2;" : "=r"(r) : "f"(b), "f"(a));
    return r;
}
__device__ __forceinline__ float bf_lo(uint32_t v) { return __uint_as_float(v << 16); }
__device__ __forceinline__ float bf_hi(uint32_t v) { return __uint_as_float(v & 0xffff0000u); }
__device__ __forceinline__ float bf16r(float a) { return bf_lo(pack_bf16(a, 0.f)); }
__device__ __forceinline__ uint32_t max_bf16x2(uint32_t a, uint32_t b) {
    uint32_t r;
    asm("max.bf16x2 %0, %1, %2;" : "=r"(r) : "r"(a), "r"(b));
    return r;
}
__device__ __forceinline__ float ex2(float x) {
    float r;
    asm("ex2.approx.ftz.f32 %0, %1;" : "=f"(r) : "f"(x));
    return r;
}

__device__ __forceinline__ void st_ll2(uint2* p, uint32_t v, uint32_t tag) {
    asm volatile("st.relaxed.gpu.global.v2.u32 [%0], {%1, %2};" ::"l"(p), "r"(v), "r"(tag) : "memory");
}
__device__ __forceinline__ void st_ll4(uint4* p, uint32_t v0, uint32_t v1, uint32_t tag) {
    asm volatile("st.relaxed.gpu.global.v4.u32 [%0], {%1, %2, %3, %2};" ::"l"(p), "r"(v0), "r"(tag), "r"(v1) : "memory");
}
__device__ __forceinline__ void st_v4(uint4* p, uint32_t a, uint32_t b, uint32_t c, uint32_t d) {
    asm volatile("st.relaxed.gpu.global.v4.u32 [%0], {%1, %2, %3, %4};" ::"l"(p), "r"(a), "r"(b), "r"(c), "r"(d) : "memory");
}
__device__ __forceinline__ uint2 ld_ll2(const uint2* p) {
    uint2 v;
    asm volatile("ld.relaxed.gpu.global.v2.u32 {%0, %1}, [%2];" : "=r"(v.x), "=r"(v.y) : "l"(p) : "memory");
    return v;
}
__device__ __forceinline__ uint4 ld_ll4(const uint4* p) {
    uint4 v;
    asm volatile("ld.relaxed.gpu.global.v4.u32 {%0, %1, %2, %3}, [%4];"
                 : "=r"(v.x), "=r"(v.y), "=r"(v.z), "=r"(v.w) : "l"(p) : "memory");
    return v;
}

#define DELAY_B1 300
#define DELAY_X1 1400
#define DELAY_C 450
__device__ __forceinline__ uint32_t clock32() {
    uint32_t c;
    asm volatile("mov.u32 %0, %clock;" : "=r"(c));
    return c;
}
__device__ __forceinline__ void spin_cycles(uint32_t n) {
    if (n > 0) { const uint32_t c0 = clock32(); while (clock32() - c0 < n) {} }
}
__device__ __forceinline__ float rcp_approx(float x) {
    float r;
    asm("rcp.approx.ftz.f32 %0, %1;" : "=f"(r) : "f"(x));
    return r;
}
__device__ __forceinline__ float sqrt_approx(float x) {
    float r;
    asm("sqrt.approx.f32 %0, %1;" : "=f"(r) : "f"(x));
    return r;
}

__device__ __forceinline__ float silu_bf(float v) { return bf16r(v / (1.0f + expf(-v))); }

__device__ __forceinline__ float2 half_warp_sums(const float (&v)[4], float pivot) {
    float s1 = 0.f, s2 = 0.f;
#pragma unroll
    for (int i = 0; i < 4; i++) { const float d = v[i] - pivot; s1 += d; s2 += d * d; }
#pragma unroll
    for (int o = 1; o < 16; o <<= 1) { s1 += __shfl_xor_sync(0xffffffffu, s1, o); s2 += __shfl_xor_sync(0xffffffffu, s2, o); }
    return make_float2(s1, s2);
}
__device__ __forceinline__ void ln_stats(const float2* stat, int b, float pivot, float& mean_bf, float& rstd) {
    float s1 = 0.f, s2 = 0.f;
#pragma unroll
    for (int w = 0; w < 8; w++) { const float2 v = stat[w * 2 + b]; s1 += v.x; s2 += v.y; }
    const float dm = s1 * (1.0f / D_MODEL);
    const float var = fmaxf(s2 * (1.0f / D_MODEL) - dm * dm, 0.f);
    mean_bf = bf16r(pivot + dm);
    rstd = rcp_approx(bf16r(sqrt_approx(bf16r(bf16r(var) + 1e-5f))));
}
__device__ __forceinline__ float ln_norm(float xv, float mean_bf, float rstd) { return bf16r(bf16r(xv - mean_bf) * rstd); }
__device__ __forceinline__ float ln_mod(float n, float cmul, float sadd) { return bf16r(n * bf16r(1.0f + cmul)) + sadd; }

__global__ void __launch_bounds__(NTHREADS, 1)
fused_block_kernel(const Params p, const __grid_constant__ CUtensorMap tm_k, const __grid_constant__ CUtensorMap tm_v,
                   const __grid_constant__ CUtensorMap tm_wq, const __grid_constant__ CUtensorMap tm_wmod,
                   const __grid_constant__ CUtensorMap tm_wmod8,
                   const __grid_constant__ CUtensorMap tm_wo, const __grid_constant__ CUtensorMap tm_wg,
                   const __grid_constant__ CUtensorMap tm_wu, const __grid_constant__ CUtensorMap tm_wd) {
    extern __shared__ unsigned char smem_raw[];
    const uint32_t sbase = (smem_u32(smem_raw) + 1023u) & ~1023u;
    unsigned char* sgen = smem_raw + (sbase - smem_u32(smem_raw));
    const int tid = threadIdx.x, warp = tid >> 5, lane = tid & 31;
    const int cta = blockIdx.x;
    const uint32_t bar_full = sbase + SM_BAR, bar_empty = bar_full + NST * 8;
    const uint32_t bar_clear = bar_empty + NST * 8;
    const uint32_t bar_gu = bar_clear + 8;
    const uint32_t bar_bc = bar_gu + 8 * 8;
    const uint32_t bar_p0w = bar_bc + 8;

    const int key0 = (cta >> 3) * SK + (cta & 7) * 64;
    uint64_t pol = 0;
    if (tid == 256) {
        asm volatile("createpolicy.fractional.L2::evict_first.b64 %0, 1.0;" : "=l"(pol));
        mbar_init(bar_p0w, 1);
#pragma unroll
        for (int i = 0; i < 4; i++) mbar_init(bar_full + 8 * i, 1);
        asm volatile("fence.mbarrier_init.release.cluster;" ::: "memory");
        mbar_expect_tx(bar_p0w, 8192);
        tma_2d(sbase + SM_MRG, &tm_wmod8, cta * 8, 0, bar_p0w);
        tma_2d(sbase + SM_MRG + 4096, &tm_wmod8, cta * 8, 256, bar_p0w);
#pragma unroll
        for (int i = 0; i < 4; i++) mbar_expect_tx(bar_full + 8 * i, TILE);
        tma_2d(sbase + SM_RING, &tm_wq, cta * 32, 0, bar_full);
        tma_2d(sbase + SM_RING + TILE, &tm_wq, cta * 32, 256, bar_full + 8);
        tma_3d_hint(sbase + SM_RING + 2 * TILE, &tm_k, 0, key0, 0, bar_full + 16, pol);
        tma_3d_hint(sbase + SM_RING + 3 * TILE, &tm_v, 0, key0, 0, bar_full + 24, pol);
    }

    if (warp == 8) {
        if (lane == 0) {
            for (int i = 0; i < NST; i++) { if (i >= 4) mbar_init(bar_full + 8 * i, 1); mbar_init(bar_empty + 8 * i, 4); }
            mbar_init(bar_clear, 1);
            for (int k = 0; k < 8; k++) mbar_init(bar_gu + 8 * k, 1);
            mbar_init(bar_bc, 8);
            ((volatile uint32_t*)(sgen + SM_PACE))[0] = 0;
            ((volatile uint32_t*)(sgen + SM_PACE))[1] = WINDOW;
            asm volatile("fence.mbarrier_init.release.cluster;" ::: "memory");
        }
        __syncwarp();
        asm volatile("bar.arrive 2, 320;" ::: "memory");
        asm volatile("bar.arrive 3, 64;" ::: "memory");
        if (lane == 0) {
            int slot = 4; uint32_t ph = 1;
            int landed = 0, wslot = 0; uint32_t wph = 0;
            int kv = 2;
            auto wait_window = [&](int idx, int window) {
                while (landed + window <= idx) {
                    mbar_wait(bar_full + 8 * wslot, wph);
                    if (++wslot == NST) { wslot = 0; wph ^= 1; }
                    landed++;
                }
            };
            volatile uint32_t* pace = (volatile uint32_t*)(sgen + SM_PACE);
            prefetch_tmap(&tm_wmod);
            pace[0] = 4;
            for (int idx = 4; idx < N_STREAM; idx++) {
                if (idx >= NST) mbar_wait(bar_empty + 8 * slot, ph);
                wait_window(idx, (int)pace[1]);
                if (idx == 12) { prefetch_tmap(&tm_wo); prefetch_tmap(&tm_wg); prefetch_tmap(&tm_wu); prefetch_tmap(&tm_wd); }
                const uint32_t fb = bar_full + 8 * slot, dst = sbase + SM_RING + slot * TILE;
                mbar_expect_tx(fb, TILE);
                if (idx == IDX_MOD) {
                    tma_2d(dst, &tm_wmod, 1024 + cta * 16, 0, fb);
                    tma_2d(dst + 8192, &tm_wmod, 1024 + cta * 16, 256, fb);
                } else {
                    tma_3d_hint(dst, (kv & 1) ? &tm_v : &tm_k, 0, key0 + (kv >> 1) * 512, 0, fb, pol);
                    kv++;
                }
                pace[0] = idx + 1;
                if (++slot == NST) { slot = 0; ph ^= 1; }
            }
            auto slot_free = [&](int idx) { mbar_wait(bar_empty + 8 * (idx % NST), ((idx / NST) & 1) ^ 1); };
#pragma unroll
            for (int s = 0; s < 2; s++) {
                const int idx = IDX_WO + s;
                slot_free(idx);
                wait_window(idx, WINDOW_TAIL);
                mbar_expect_tx(bar_full + 8 * (idx % NST), TILE);
                tma_3d(sbase + SM_RING + (idx % NST) * TILE, &tm_wo, 0, (cta >> 2) * 128 + s * 64, (cta & 3) * 2, bar_full + 8 * (idx % NST));
            }
            if (cta < NFFN) {
                slot_free(IDX_WG); slot_free(IDX_WU);
                mbar_wait(bar_full + 8 * (IDX_WO % NST), (IDX_WO / NST) & 1);
                mbar_wait(bar_full + 8 * ((IDX_WO + 1) % NST), ((IDX_WO + 1) / NST) & 1);
#pragma unroll
                for (int st = 0; st < 8; st++) {
                    if (st >= GU_WIN) mbar_wait(bar_gu + 8 * (st - GU_WIN), 0);
                    mbar_expect_tx(bar_gu + 8 * st, 4096);
                    tma_2d(sbase + SM_RING + (((st & 1) ? IDX_WU : IDX_WG) % NST) * TILE + (st >> 1) * 4096,
                           (st & 1) ? &tm_wu : &tm_wg, cta * 16, (st >> 1) * 128, bar_gu + 8 * st);
                }
                mbar_wait(bar_gu + 8 * 7, 0);
                slot_free(IDX_WD);
                mbar_expect_tx(bar_full + 8 * (IDX_WD % NST), TILE);
                tma_3d(sbase + SM_RING + (IDX_WD % NST) * TILE, &tm_wd, 0, cta * 16, 0, bar_full + 8 * (IDX_WD % NST));
            }
        }
    } else if (warp == 9) {
        Scratch* const sc = p.sc;
        const uint32_t tag = *(volatile unsigned*)&sc->epoch + 1;
        if (lane < 2) {
            st_ll4((uint4*)&sc->mod[lane][cta * 4], 0u, 0u, 0u);
            st_ll4((uint4*)&sc->mod[lane][cta * 4] + 1, 0u, 0u, 0u);
        }
        if (lane < 8) st_ll4((uint4*)&sc->mod[lane >> 2][512 + cta * 8] + (lane & 3), 0u, 0u, 0u);
        if (lane < 16) st_ll4((uint4*)&sc->q[lane >> 3][cta * 16] + (lane & 7), 0u, 0u, 0u);
        __syncwarp();
        asm volatile("bar.arrive 2, 320;" ::: "memory");
        asm volatile("bar.sync 3, 64;" ::: "memory");
#pragma unroll 4
        for (int i = 0; i < NFFN * 2 / 32; i++) st_v4(&sc->inbox_dn[cta][0][0] + i * 32 + lane, 0u, 0u, 0u, 0u);
        if (cta >= NCTA - NOWN) {
#pragma unroll 4
            for (int i = 0; i < 8; i++) st_v4(&sc->inbox_wo[cta - (NCTA - NOWN)][0][0] + i * 32 + lane, 0u, 0u, 0u, 0u);
            if (lane < 8) st_v4((uint4*)&sc->x1[(cta - (NCTA - NOWN)) * 16] + lane, 0u, 0u, 0u, 0u);
        }
#pragma unroll 4
        for (int i = 0; i < 4; i++) st_v4((uint4*)&sc->part_o[cta][0][0] + i * 32 + lane, 0u, 0u, 0u, 0u);
        if (lane < 8) st_v4((uint4*)&sc->part_ml[cta][0][0] + lane, 0u, 0u, 0u, 0u);
        if (cta == 0 && lane == 0) asm volatile("st.relaxed.gpu.global.u32 [%0], %1;" ::"l"(&sc->progress), "r"(0u) : "memory");
        asm volatile("fence.acq_rel.gpu;" ::: "memory");
        __syncwarp();
        if (lane == 0) {
            asm volatile("fence.acq_rel.gpu;" ::: "memory");
            asm volatile("red.relaxed.gpu.global.add.u32 [%0], %1;" ::"l"(&sc->cleared), "r"(1u) : "memory");
            const uint32_t target = tag * NCTA;
            for (int it = 0; it < SPIN_LIMIT; it++) {
                uint32_t v;
                asm volatile("ld.relaxed.gpu.global.u32 %0, [%1];" : "=r"(v) : "l"(&sc->cleared) : "memory");
                if ((int32_t)(v - target) >= 0) break;
                __nanosleep(500);
            }
            asm volatile("fence.acq_rel.gpu;" ::: "memory");
            mbar_arrive(bar_clear);
            volatile uint32_t* pace = (volatile uint32_t*)(sgen + SM_PACE);
            uint32_t posted = 0;
            for (int it = 0; it < SPIN_LIMIT; it++) {
                const uint32_t own = pace[0];
                if (own >= N_STREAM) break;
                if (own > posted) {
                    asm volatile("red.relaxed.gpu.global.add.u32 [%0], %1;" ::"l"(&sc->progress), "r"(own - posted) : "memory");
                    posted = own;
                }
                uint32_t v;
                asm volatile("ld.relaxed.gpu.global.u32 %0, [%1];" : "=r"(v) : "l"(&sc->progress) : "memory");
                const int diff = (int)v - (int)own * NCTA;
                pace[1] = diff > PACE_THR ? WINDOW + 1 : diff < -PACE_THR ? WINDOW - 1 : WINDOW;
                __nanosleep(200);
            }
        }
    } else {
        const int g = lane >> 2, t = lane & 3;
        const int bb = g & 1;
        const int eb = lane >> 4;
        const int ec = 64 * warp + 4 * (lane & 15);
        if (warp == 0) TSTAMP(0);
        Scratch* const sc = p.sc;
        const float c00 = __bfloat162float(p.c[tid]), c01 = __bfloat162float(p.c[tid + 256]);
        const float c10 = __bfloat162float(p.c[D_MODEL + tid]), c11 = __bfloat162float(p.c[D_MODEL + tid + 256]);
        const uint2 xe = __ldg((const uint2*)(p.x + eb * D_MODEL + ec));
        const float xpivot = __bfloat162float(p.x[eb * D_MODEL]);
        const uint32_t tag = *(volatile unsigned*)&sc->epoch + 1;
        const int ocol = cta * 4 + (lane & 3);
        const int wcol = (cta >= NCTA - NOWN ? cta - (NCTA - NOWN) : 0) * 16 + (lane & 15);
        const float xo = __bfloat162float(p.x[eb * D_MODEL + wcol]);

        float* red = (float*)(sgen + SM_RED);
        float* red2 = (float*)(sgen + SM_RED2);
        float2* stat = (float2*)(sgen + SM_STAT);
        uint32_t* hs = (uint32_t*)(sgen + SM_HS) + warp * 64;
        float xn[4];
        {
            float xv[4] = {bf_lo(xe.x), bf_hi(xe.x), bf_lo(xe.y), bf_hi(xe.y)};
            const float2 ps = half_warp_sums(xv, xpivot);
            if ((lane & 15) == 0) stat[warp * 2 + eb] = ps;
            const float s00 = silu_bf(c00), s01 = silu_bf(c01), s10 = silu_bf(c10), s11 = silu_bf(c11);
            __nv_bfloat16* scs = (__nv_bfloat16*)(sgen + SM_SC);
            scs[tid] = __float2bfloat16_rn(s00); scs[tid + 256] = __float2bfloat16_rn(s01);
            scs[512 + tid] = __float2bfloat16_rn(s10); scs[512 + tid + 256] = __float2bfloat16_rn(s11);
            asm volatile("bar.sync 2, 320;" ::: "memory");
            if (warp == 0) TSTAMP(23);
            float cp[4] = {0.f, 0.f, 0.f, 0.f};
            const uint32_t* sc32 = (const uint32_t*)(sgen + SM_SC) + bb * 256 + 32 * warp + t;
            mbar_wait(bar_p0w, 0);
#pragma unroll
            for (int s = 0; s < 4; s++) {
                uint32_t r0, r1;
                asm volatile("ldmatrix.sync.aligned.m8n8.x2.trans.shared.b16 {%0,%1}, [%2];"
                             : "=r"(r0), "=r"(r1) : "r"(sbase + SM_MRG + (64 * warp + 16 * s + (lane & 15)) * 16) : "memory");
                const uint32_t a[4] = {r0, r0, r1, r1};
                mma16816(cp, a, sc32[8 * s], sc32[8 * s + 4]);
            }
            if (t == 0) { red[warp * 16 + g] = cp[0]; red[warp * 16 + 8 + g] = cp[1]; }
            if (warp == 0) TSTAMP(14);
            cons_sync();
            if (warp == 0) {
                float s = 0.f;
#pragma unroll
                for (int w = 0; w < 8; w++) s += red[w * 16 + (lane & 15)];
                const float nx = __shfl_down_sync(0xffffffffu, s, 1);
                if (lane < 16 && !(lane & 1))
                    st_ll2(&sc->mod[lane >> 3][cta * 4 + ((lane & 7) >> 1)], pack_bf16(s, nx), tag);
                TSTAMP(1);
            }
            float mean_bf, rstd;
            ln_stats(stat, eb, xpivot, mean_bf, rstd);
#pragma unroll
            for (int i = 0; i < 4; i++) xn[i] = ln_norm(xv[i], mean_bf, rstd);
        }
        {
            uint4 sa, ca;
            for (int it = 0;; it++) {
                sa = ld_ll4((const uint4*)&sc->mod[eb][ec >> 1]);
                ca = ld_ll4((const uint4*)&sc->mod[eb][256 + (ec >> 1)]);
                const bool ok = sa.y == tag && sa.w == tag && ca.y == tag && ca.w == tag;
                if (__all_sync(0xffffffffu, ok) || it > SPIN_LIMIT) break;
            }
            *(uint2*)&hs[eb * 32 + 2 * (lane & 15)] =
                make_uint2(pack_bf16(ln_mod(xn[0], bf_lo(ca.x), bf_lo(sa.x)), ln_mod(xn[1], bf_hi(ca.x), bf_hi(sa.x))),
                           pack_bf16(ln_mod(xn[2], bf_lo(ca.z), bf_lo(sa.z)), ln_mod(xn[3], bf_hi(ca.z), bf_hi(sa.z))));
            __syncwarp();
            uint32_t hb[8];
#pragma unroll
            for (int i = 0; i < 8; i++) hb[i] = hs[bb * 32 + 8 * (i >> 1) + 4 * (i & 1) + t];
            if (warp == 0) TSTAMP(2);
            float cq[2][4] = {};
            const int ts = warp >> 2;
            mbar_wait(bar_full + 8 * ts, 0);
            const uint32_t tb = sbase + SM_RING + ts * TILE;
#pragma unroll
            for (int s = 0; s < 4; s++) {
                const int row = 64 * (warp & 3) + 16 * s + (lane & 7) + (lane >> 4) * 8;
#pragma unroll
                for (int mt = 0; mt < 2; mt++) {
                    const int ch = 2 * mt + ((lane >> 3) & 1);
                    uint32_t a[4];
                    ldsm4t(tb + row * 64 + ((ch ^ ((row >> 1) & 3)) << 4), a);
                    mma16816(cq[mt], a, hb[2 * s], hb[2 * s + 1]);
                }
            }
            if (t < 2) {
                const float v0 = t == 0 ? cq[0][0] : cq[1][0], v1 = t == 0 ? cq[0][1] : cq[1][1];
                const float v2 = t == 0 ? cq[0][2] : cq[1][2], v3 = t == 0 ? cq[0][3] : cq[1][3];
                *(float2*)&red2[warp * 64 + (16 * t + g) * 2] = make_float2(v0, v1);
                *(float2*)&red2[warp * 64 + (16 * t + g + 8) * 2] = make_float2(v2, v3);
            }
            cons_sync();
            if (warp < 4 && lane == 0) { mbar_arrive(bar_empty); mbar_arrive(bar_empty + 8); }
            if (warp == 0) {
                const int b = lane >> 4, cp = lane & 15;
                float q0 = 0.f, q1 = 0.f;
#pragma unroll
                for (int w = 0; w < 8; w++) {
                    const float4 v = *(const float4*)&red2[w * 64 + cp * 4];
                    q0 += b ? v.y : v.x; q1 += b ? v.w : v.z;
                }
                st_ll2(&sc->q[b][cta * 16 + cp], pack_bf16(q0, q1), tag);
                TSTAMP(3);
            }
        }
        const int pair = cta >> 3;
        uint32_t qf[16];
        {
            uint2* qs = (uint2*)(sgen + SM_QS);
            if (tid < 128) {
                const uint4* src = (const uint4*)&sc->q[pair >> 3][(pair & 7) * 256] + tid;
                uint4 v;
                for (int it = 0;; it++) {
                    v = ld_ll4(src);
                    if ((v.y == tag && v.w == tag) || it > SPIN_LIMIT) break;
                }
                qs[tid] = make_uint2(v.x, v.z);
            }
            cons_sync();
            const uint32_t* q32 = (const uint32_t*)(sgen + SM_QS);
#pragma unroll
            for (int s = 0; s < 8; s++) {
                qf[2 * s] = q32[(g & 3) * 64 + 8 * s + t];
                qf[2 * s + 1] = q32[(g & 3) * 64 + 8 * s + 4 + t];
            }
        }
        if (warp == 0) TSTAMP(4);

        float o[8][4];
#pragma unroll
        for (int i = 0; i < 8; i++) { o[i][0] = o[i][1] = o[i][2] = o[i][3] = 0.f; }
        uint32_t mrun = 0xff80ff80u;
        float ls[4] = {0.f, 0.f, 0.f, 0.f};
        uint4 m_sb, m_cb; uint2 m_ga, m_gb0, m_gb1;
        {
            const int grp = warp >> 2, wi = warp & 3;
            const int krow = 16 * wi + (lane & 7) + ((lane >> 3) & 1) * 8;
            const uint32_t koff = krow * 128 + ((((lane >> 4) & 1) ^ (lane & 7)) << 4);
            const int vrow = 16 * wi + (lane & 7) + (lane >> 4) * 8;
            const uint32_t voff = vrow * 128 + ((((lane >> 3) & 1) ^ (lane & 7)) << 4);
            const uint32_t ones[4] = {0x3f803f80u, 0x3f803f80u, 0x3f803f80u, 0x3f803f80u};
            for (int i = grp; i < KV_TILES; i += 2) {
                if (i == MOD_AT + grp) {
                    float cm[4] = {};
                    const uint32_t* sc32 = (const uint32_t*)(sgen + SM_SC) + bb * 256 + 32 * warp + t;
                    mbar_wait(bar_full + 8 * (IDX_MOD % NST), (IDX_MOD / NST) & 1);
                    const uint32_t tb = sbase + SM_RING + (IDX_MOD % NST) * TILE;
#pragma unroll
                    for (int s = 0; s < 4; s++) {
                        const int row = 64 * warp + 16 * s + (lane & 7) + (lane >> 4) * 8;
                        const int ch = (lane >> 3) & 1;
                        uint32_t a[4];
                        ldsm4t(tb + row * 32 + ((ch ^ ((row >> 2) & 1)) << 4), a);
                        mma16816(cm, a, sc32[8 * s], sc32[8 * s + 4]);
                    }
                    if (t == 0) {
                        *(float2*)&red[warp * 64 + g * 2] = make_float2(cm[0], cm[1]);
                        *(float2*)&red[warp * 64 + (g + 8) * 2] = make_float2(cm[2], cm[3]);
                    }
                    cons_sync();
                    if (warp < 4 && lane == 0) mbar_arrive(bar_empty + 8 * (IDX_MOD % NST));
                    if (warp == 1 && lane < 16) {
                        const int b = lane >> 3, cp = lane & 7;
                        float q0 = 0.f, q1 = 0.f;
#pragma unroll
                        for (int w = 0; w < 8; w++) {
                            const float4 v = *(const float4*)&red[w * 64 + cp * 4];
                            q0 += b ? v.y : v.x; q1 += b ? v.w : v.z;
                        }
                        st_ll2(&sc->mod[b][512 + cta * 8 + cp], pack_bf16(q0, q1), tag);
                    }
                }
                if (i == 56 + grp) {
                    m_sb = ld_ll4((const uint4*)&sc->mod[eb][768 + (ec >> 1)]);
                    m_cb = ld_ll4((const uint4*)&sc->mod[eb][1024 + (ec >> 1)]);
                    m_ga = ld_ll2(&sc->mod[eb][512 + (wcol >> 1)]);
                    m_gb0 = ld_ll2(&sc->mod[0][1280 + (ocol >> 1)]); m_gb1 = ld_ll2(&sc->mod[1][1280 + (ocol >> 1)]);
                }
                if (i == 60 + grp) {
                    for (int it = 0;; it++) {
                        const bool ok = m_sb.y == tag && m_sb.w == tag && m_cb.y == tag && m_cb.w == tag &&
                                        m_ga.y == tag && m_gb0.y == tag && m_gb1.y == tag;
                        if (__all_sync(0xffffffffu, ok) || it > SPIN_LIMIT) break;
                        m_sb = ld_ll4((const uint4*)&sc->mod[eb][768 + (ec >> 1)]);
                        m_cb = ld_ll4((const uint4*)&sc->mod[eb][1024 + (ec >> 1)]);
                        m_ga = ld_ll2(&sc->mod[eb][512 + (wcol >> 1)]);
                        m_gb0 = ld_ll2(&sc->mod[0][1280 + (ocol >> 1)]); m_gb1 = ld_ll2(&sc->mod[1][1280 + (ocol >> 1)]);
                    }
                    mbar_wait(bar_clear, 0);
                }
                const int ki = kv_idx(i), ks = ki % NST, vs = (ki + 1) % NST;
                const uint32_t kph = (ki / NST) & 1, vph = ((ki + 1) / NST) & 1;
                mbar_wait(bar_full + 8 * ks, kph);
                const uint32_t kb = sbase + SM_RING + ks * TILE + koff;
                float sa[4] = {0.f, 0.f, 0.f, 0.f}, sb[4] = {0.f, 0.f, 0.f, 0.f};
#pragma unroll
                for (int s = 0; s < 8; s += 2) {
                    uint32_t a0[4], a1[4];
                    ldsm4((kb ^ ((s & 3) << 5)) + (s >> 2) * 8192, a0);
                    ldsm4((kb ^ (((s + 1) & 3) << 5)) + (s >> 2) * 8192, a1);
                    mma16816(sa, a0, qf[2 * s], qf[2 * s + 1]);
                    mma16816(sb, a1, qf[2 * s + 2], qf[2 * s + 3]);
                }
                __syncwarp();
                if (lane == 0) mbar_arrive(bar_empty + 8 * ks);
                uint32_t r01 = pack_bf16(sa[0] + sb[0], sa[1] + sb[1]);
                uint32_t r23 = pack_bf16(sa[2] + sb[2], sa[3] + sb[3]);
                r01 = pack_bf16(bf_lo(r01) * QK_SCALE, bf_hi(r01) * QK_SCALE);
                r23 = pack_bf16(bf_lo(r23) * QK_SCALE, bf_hi(r23) * QK_SCALE);
                uint32_t mx = max_bf16x2(r01, r23);
                mx = max_bf16x2(mx, __shfl_xor_sync(0xffffffffu, mx, 4));
                mx = max_bf16x2(mx, __shfl_xor_sync(0xffffffffu, mx, 8));
                mx = max_bf16x2(mx, __shfl_xor_sync(0xffffffffu, mx, 16));
                const uint32_t mnew = max_bf16x2(mrun, mx);
                const float m0 = bf_lo(mnew), m1 = bf_hi(mnew);
                if (__any_sync(0xffffffffu, mnew != mrun)) {
                    const float al0 = ex2((bf_lo(mrun) - m0) * LOG2E), al1 = ex2((bf_hi(mrun) - m1) * LOG2E);
                    ls[0] *= al0; ls[1] *= al1;
#pragma unroll
                    for (int d = 0; d < 8; d++) { o[d][0] *= al0; o[d][1] *= al1; o[d][2] *= al0; o[d][3] *= al1; }
                    mrun = mnew;
                }
                const float p0 = ex2((bf_lo(r01) - m0) * LOG2E), p1 = ex2((bf_hi(r01) - m1) * LOG2E);
                const float p2 = ex2((bf_lo(r23) - m0) * LOG2E), p3 = ex2((bf_hi(r23) - m1) * LOG2E);
                const uint32_t pb0 = movmatrix_t(pack_bf16(p0, p1)), pb1 = movmatrix_t(pack_bf16(p2, p3));
                mma16816(ls, ones, pb0, pb1);
                mbar_wait(bar_full + 8 * vs, vph);
                const uint32_t vb = sbase + SM_RING + vs * TILE + voff;
#pragma unroll
                for (int d = 0; d < 8; d++) {
                    uint32_t a[4];
                    ldsm4t((vb ^ ((d & 3) << 5)) + (d >> 2) * 8192, a);
                    mma16816(o[d], a, pb0, pb1);
                }
                __syncwarp();
                if (lane == 0) mbar_arrive(bar_empty + 8 * vs);
            }
        }
        if (warp == 7) TSTAMP(5);
        {
            float* mrg = (float*)(sgen + SM_MRG);
            float2* ml = (float2*)(sgen + SM_ML);
            {
                const int hp = (t & 1) * 2, up = t >> 1;
                if (g == 0 && up == 0) { ml[warp * 4 + hp] = make_float2(bf_lo(mrun), ls[0]); ml[warp * 4 + hp + 1] = make_float2(bf_hi(mrun), ls[1]); }
                float* m0p = mrg + (warp * 4 + hp) * 136 + up * 72 + g;
#pragma unroll
                for (int d = 0; d < 4; d++) {
                    m0p[16 * d] = up ? o[d + 4][0] : o[d][0]; m0p[136 + 16 * d] = up ? o[d + 4][1] : o[d][1];
                    m0p[16 * d + 8] = up ? o[d + 4][2] : o[d][2]; m0p[136 + 16 * d + 8] = up ? o[d + 4][3] : o[d][3];
                }
            }
            cons_sync();
            const int hh = tid >> 6, dp = tid & 63;
            float2 mw[8];
            float M = -INFINITY;
#pragma unroll
            for (int w = 0; w < 8; w++) { mw[w] = ml[w * 4 + hh]; M = fmaxf(M, mw[w].x); }
            float L = 0.f, o0 = 0.f, o1 = 0.f;
#pragma unroll
            for (int w = 0; w < 8; w++) {
                const float wt = ex2((mw[w].x - M) * LOG2E);
                const float2 v = *(const float2*)&mrg[(w * 4 + hh) * 136 + 2 * dp + (dp >= 32 ? 8 : 0)];
                L += wt * mw[w].y; o0 += wt * v.x; o1 += wt * v.y;
            }
            st_ll2(&sc->part_o[cta][hh][dp], tagf(o0, F_PART), tagf(o1, F_PART));
            if (dp < 4) st_ll2(&sc->part_ml[cta][hh][dp], tagf(M, F_PART), tagf(L, F_PART));
        }
        if (warp == 0) TSTAMP(6);
        {
            const int hq = cta >> 2, kvh = hq >> 2, hh = hq & 3;
            const int b = tid >> 7, dc = (tid >> 3) & 15, j = tid & 7;
            const int pc = (b * 8 + kvh) * 8 + j;
            const uint4* po = (const uint4*)&sc->part_o[pc][hh][0] + dc * 2;
            const uint2* pm = &sc->part_ml[pc - j][hh][0];
            uint4 vo0, vo1; uint2 vm[8];
            bool oko = false, okm = false;
            for (int it = 0;; it++) {
                if (!oko) { vo0 = ld_ll4(po); vo1 = ld_ll4(po + 1); }
                if (!okm) {
#pragma unroll
                    for (int jj = 0; jj < 8; jj++) vm[jj] = ld_ll2(pm + jj * 16);
                }
                oko = (vo0.x & vo0.y & vo0.z & vo0.w & vo1.x & vo1.y & vo1.z & vo1.w & 3u) == F_PART;
                uint32_t all = vm[0].x & vm[0].y;
#pragma unroll
                for (int jj = 1; jj < 8; jj++) all &= vm[jj].x & vm[jj].y;
                okm = (all & 3u) == F_PART;
                if (__all_sync(0xffffffffu, oko && okm) || it > SPIN_LIMIT) break;
            }
            float M = untag(vm[0].x);
#pragma unroll
            for (int jj = 1; jj < 8; jj++) M = fmaxf(M, untag(vm[jj].x));
            float wt = 0.f, L = 0.f;
#pragma unroll
            for (int jj = 0; jj < 8; jj++) {
                const float w_ = ex2((untag(vm[jj].x) - M) * LOG2E);
                L += w_ * untag(vm[jj].y);
                wt = jj == j ? w_ : wt;
            }
            wt *= rcp_approx(L);
            float v[8] = {wt * untag(vo0.x), wt * untag(vo0.y), wt * untag(vo0.z), wt * untag(vo0.w),
                          wt * untag(vo1.x), wt * untag(vo1.y), wt * untag(vo1.z), wt * untag(vo1.w)};
#define XRED(N, O)                                                                       \
            {                                                                            \
                const bool up = lane & (O);                                              \
                _Pragma("unroll") for (int i = 0; i < (N); i++) {                        \
                    const float send = up ? v[i] : v[i + (N)], keep = up ? v[i + (N)] : v[i]; \
                    v[i] = keep + __shfl_xor_sync(0xffffffffu, send, (O));               \
                }                                                                        \
            }
            XRED(4, 1) XRED(2, 2) XRED(1, 4)
#undef XRED
            __nv_bfloat16* os = (__nv_bfloat16*)(sgen + SM_OS);
            os[b * 128 + dc * 8 + 4 * (j & 1) + 2 * ((j >> 1) & 1) + (j >> 2)] = __float2bfloat16_rn(v[0]);
            if (warp == 0) TSTAMP(15);
            uint32_t wf[8][4];
            const uint32_t aoff_o = (warp >> 2) * 8192 + ((lane & 7) + (lane >> 4) * 8) * 128 +
                                    (((((warp & 3) * 2 + ((lane >> 3) & 1)) ^ (lane & 7))) << 4);
#pragma unroll
            for (int s = 0; s < 2; s++) {
                const int idx = IDX_WO + s;
                mbar_wait(bar_full + 8 * (idx % NST), (idx / NST) & 1);
                const uint32_t tb = sbase + SM_RING + (idx % NST) * TILE + aoff_o;
#pragma unroll
                for (int k4 = 0; k4 < 4; k4++) ldsm4t(tb + k4 * 2048, wf[s * 4 + k4]);
            }
            cons_sync();
            if (warp == 0) TSTAMP(7);
            const uint32_t* os32 = (const uint32_t*)(sgen + SM_OS) + bb * 64 + t;
            float y0[4] = {}, y1[4] = {};
#pragma unroll
            for (int ks = 0; ks < 8; ks += 2) {
                mma16816(y0, wf[ks], os32[8 * ks], os32[8 * ks + 4]);
                mma16816(y1, wf[ks + 1], os32[8 * ks + 8], os32[8 * ks + 12]);
            }
            if (t == 0)
                st_v4(&sc->inbox_wo[(cta & 3) * 8 + warp][hq][g], tagf(y0[0] + y1[0], F_WO), tagf(y0[1] + y1[1], F_WO),
                      tagf(y0[2] + y1[2], F_WO), tagf(y0[3] + y1[3], F_WO));
        }
        const uint32_t t_wo = clock32();
        if (warp == 0) TSTAMP(8);
        if (cta >= NCTA - NOWN) {
            const uint4* pin = &sc->inbox_wo[cta - (NCTA - NOWN)][0][0] + tid;
            uint4 v;
            spin_cycles(DELAY_B1);
            bool ok = false;
            for (int it = 0;; it++) {
                if (!ok) {
                    v = ld_ll4(pin);
                    ok = (v.x & v.y & v.z & v.w & 3u) == F_WO;
                }
                if (__all_sync(0xffffffffu, ok) || it > SPIN_LIMIT) break;
            }
            const bool u1 = lane & 8, u2 = lane & 16;
            const float a0 = untag(v.x), a1 = untag(v.y), a2 = untag(v.z), a3 = untag(v.w);
            const float k0 = (u1 ? a2 : a0) + __shfl_xor_sync(0xffffffffu, u1 ? a0 : a2, 8);
            const float k1 = (u1 ? a3 : a1) + __shfl_xor_sync(0xffffffffu, u1 ? a1 : a3, 8);
            red2[warp * 32 + lane] = (u2 ? k1 : k0) + __shfl_xor_sync(0xffffffffu, u2 ? k0 : k1, 16);
            cons_sync();
            if (warp == 0) {
                float a = 0.f;
#pragma unroll
                for (int w = 0; w < 8; w++) a += red2[w * 32 + lane];
                const float ga = (wcol & 1) ? bf_hi(m_ga.x) : bf_lo(m_ga.x);
                const float xm = bf16r(xo + bf16r(ga * bf16r(a)));
                const float xm_b1 = __shfl_down_sync(0xffffffffu, xm, 16);
                if (lane < 16) st_ll2(&sc->x1[wcol], pack_bf16(xm, xm_b1), F_X1);
                TSTAMP(10);
            }
        }
        const uint32_t aoff = warp * 2048 + ((lane & 7) + (lane >> 4) * 8) * 128 + ((((lane >> 3) & 1) ^ (lane & 7)) << 4);
        if (cta < NFFN) {
            const uint4* px = (const uint4*)&sc->x1[ec];
            const uint4* pp = (const uint4*)&sc->x1[0];
            uint4 va, vb, pa, pb;
            uint32_t gf[4][4], uf[4][4];
            mbar_wait(bar_gu + 8 * (2 * (warp >> 1)), 0);
            mbar_wait(bar_gu + 8 * (2 * (warp >> 1) + 1), 0);
            {
                const uint32_t tg = sbase + SM_RING + (IDX_WG % NST) * TILE, tu = sbase + SM_RING + (IDX_WU % NST) * TILE;
#pragma unroll
                for (int s = 0; s < 4; s++) {
                    const int row = 64 * warp + 16 * s + (lane & 7) + (lane >> 4) * 8;
                    const uint32_t off = row * 32 + ((((lane >> 3) & 1) ^ ((row >> 2) & 1)) << 4);
                    ldsm4t(tg + off, gf[s]);
                    ldsm4t(tu + off, uf[s]);
                }
            }
            const float c1v[4] = {bf16r(1.0f + bf_lo(m_cb.x)), bf16r(1.0f + bf_hi(m_cb.x)), bf16r(1.0f + bf_lo(m_cb.z)), bf16r(1.0f + bf_hi(m_cb.z))};
            float bg = 0.f, cgc = 0.f, bu = 0.f, cuc = 0.f;
            {
                uint32_t* pre = (uint32_t*)(sgen + SM_MRG) + warp * 128;
                float* bc = (float*)(sgen + SM_MRG + 4096);
                *(uint2*)&pre[eb * 32 + 2 * (lane & 15)] = make_uint2(pack_bf16(c1v[0], c1v[1]), pack_bf16(c1v[2], c1v[3]));
                *(uint2*)&pre[64 + eb * 32 + 2 * (lane & 15)] = make_uint2(m_sb.x, m_sb.z);
                __syncwarp();
                float yg[4] = {}, yu[4] = {};
                const uint32_t* pb = pre + ((g >> 1) & 1) * 64 + bb * 32 + t;
#pragma unroll
                for (int s = 0; s < 4; s++) {
                    const uint32_t b0 = pb[8 * s], b1 = pb[8 * s + 4];
                    mma16816(yg, gf[s], b0, b1);
                    mma16816(yu, uf[s], b0, b1);
                }
                const float y0 = t < 2 ? yg[0] : yu[0], y1 = t < 2 ? yg[1] : yu[1], y2 = t < 2 ? yg[2] : yu[2], y3 = t < 2 ? yg[3] : yu[3];
                float* dstp = bc + warp * 128 + (t >> 1) * 64 + (t & 1) * 32;
                *(float2*)&dstp[g * 2] = make_float2(y0, y1);
                *(float2*)&dstp[(g + 8) * 2] = make_float2(y2, y3);
                __syncwarp();
                if (lane == 0) mbar_arrive(bar_bc);
            }
            if (warp == 0) TSTAMP(11);
            float pivot2;
            {
                while (clock32() - t_wo < DELAY_X1) {}
                bool okx = false, okp = false;
                for (int it = 0;; it++) {
                    if (!okx) { va = ld_ll4(px); vb = ld_ll4(px + 1); }
                    if (!okp) { pa = ld_ll4(pp); pb = ld_ll4(pp + 1); }
                    okx = va.y == F_X1 && va.w == F_X1 && vb.y == F_X1 && vb.w == F_X1;
                    okp = pa.y == F_X1 && pa.w == F_X1 && pb.y == F_X1 && pb.w == F_X1;
                    if (__all_sync(0xffffffffu, okx && okp) || it > SPIN_LIMIT) break;
                }
                if (warp == 0) TSTAMP(9);
                const float xv[4] = {eb ? bf_hi(va.x) : bf_lo(va.x), eb ? bf_hi(va.z) : bf_lo(va.z),
                                     eb ? bf_hi(vb.x) : bf_lo(vb.x), eb ? bf_hi(vb.z) : bf_lo(vb.z)};
                const float p0 = 0.25f * ((bf_lo(pa.x) + bf_lo(pa.z)) + (bf_lo(pb.x) + bf_lo(pb.z)));
                const float p1 = 0.25f * ((bf_hi(pa.x) + bf_hi(pa.z)) + (bf_hi(pb.x) + bf_hi(pb.z)));
                const float pivot = eb ? p1 : p0;
                pivot2 = (lane & 1) ? p1 : p0;
                *(uint2*)&hs[eb * 32 + 2 * (lane & 15)] =
                    make_uint2(pack_bf16((xv[0] - pivot) * c1v[0], (xv[1] - pivot) * c1v[1]),
                               pack_bf16((xv[2] - pivot) * c1v[2], (xv[3] - pivot) * c1v[3]));
                __syncwarp();
                float cg[2][4] = {}, cu[2][4] = {};
#pragma unroll
                for (int s = 0; s < 4; s++) {
                    const uint32_t b0 = hs[bb * 32 + 8 * s + t], b1 = hs[bb * 32 + 8 * s + 4 + t];
                    mma16816(cg[s & 1], gf[s], b0, b1);
                    mma16816(cu[s & 1], uf[s], b0, b1);
                }
                const float2 ps = half_warp_sums(xv, pivot);
                if ((lane & 15) == 0) stat[warp * 2 + eb] = ps;
                {
                    const float* bc = (const float*)(sgen + SM_MRG + 4096);
                    mbar_wait(bar_bc, 0);
#pragma unroll
                    for (int w = 0; w < 8; w++) {
                        bg += bc[w * 128 + lane]; cgc += bc[w * 128 + 32 + lane];
                        bu += bc[w * 128 + 64 + lane]; cuc += bc[w * 128 + 96 + lane];
                    }
                }
                if (t < 2) {
                    float v[4];
#pragma unroll
                    for (int i = 0; i < 4; i++) v[i] = t ? cu[0][i] + cu[1][i] : cg[0][i] + cg[1][i];
                    *(float2*)&red[warp * 64 + t * 32 + g * 2] = make_float2(v[0], v[1]);
                    *(float2*)&red[warp * 64 + t * 32 + (g + 8) * 2] = make_float2(v[2], v[3]);
                }
            }
            uint32_t df[4][4];
            mbar_wait(bar_full + 8 * (IDX_WD % NST), (IDX_WD / NST) & 1);
#pragma unroll
            for (int mt = 0; mt < 4; mt++) ldsm4t((sbase + SM_RING + (IDX_WD % NST) * TILE + aoff) ^ (mt << 5), df[mt]);
            cons_sync();
            {
                float gs = 0.f, us = 0.f;
#pragma unroll
                for (int w = 0; w < 8; w++) { gs += red[w * 64 + lane]; us += red[w * 64 + 32 + lane]; }
                float mean_bf, rstd;
                ln_stats(stat, lane & 1, pivot2, mean_bf, rstd);
                const float dm = mean_bf - pivot2;
                gs = bf16r(rstd * (gs - dm * bg) + cgc);
                us = rstd * (us - dm * bu) + cuc;
                const float u2 = gs * (1.0f + 0.044715f * gs * gs) * (2.0f * 0.7978845608028654f * LOG2E);
                const float ge = bf16r(__fdividef(gs, 1.0f + ex2(-u2)));
                const float act = bf16r(ge * bf16r(us));
                const float a0 = __shfl_sync(0xffffffffu, act, 4 * t + bb), a1 = __shfl_sync(0xffffffffu, act, 4 * t + 2 + bb);
                const float a2 = __shfl_sync(0xffffffffu, act, 4 * t + 16 + bb), a3 = __shfl_sync(0xffffffffu, act, 4 * t + 18 + bb);
                const uint32_t b0 = pack_bf16(a0, a1), b1 = pack_bf16(a2, a3);
                float y[4][4] = {};
#pragma unroll
                for (int mt = 0; mt < 4; mt++) mma16816(y[mt], df[mt], b0, b1);
                float v[4];
#pragma unroll
                for (int i = 0; i < 4; i++) v[i] = t == 0 ? y[0][i] : t == 1 ? y[1][i] : t == 2 ? y[2][i] : y[3][i];
            {
                const bool odd = g & 1;
                const float sx = odd ? v[0] : v[2], sy = odd ? v[1] : v[3];
                const float rx = __shfl_xor_sync(0xffffffffu, sx, 4), ry = __shfl_xor_sync(0xffffffffu, sy, 4);
                const int c0 = 64 * warp + 16 * t + (odd ? g + 7 : g);
                const float e0 = odd ? rx : v[0], e1 = odd ? ry : v[1], e2 = odd ? v[2] : rx, e3 = odd ? v[3] : ry;
                st_v4(&sc->inbox_dn[c0 >> 2][cta][(c0 >> 1) & 1], tagf(e0, F_DOWN), tagf(e1, F_DOWN), tagf(e2, F_DOWN), tagf(e3, F_DOWN));
            }
            }
            if (warp == 0) TSTAMP(12);
        }
        {
            uint2 xw;
            float r0;
            {
                const uint4* pin = &sc->inbox_dn[cta][0][0] + tid;
                uint4 v = make_uint4(F_DOWN, F_DOWN, F_DOWN, F_DOWN);
                spin_cycles(DELAY_C);
                xw = ld_ll2(&sc->x1[ocol]);
                bool ok = tid >= NFFN * 2;
                for (int it = 0;; it++) {
                    if (!ok) {
                        v = ld_ll4(pin);
                        ok = (v.x & v.y & v.z & v.w & 3u) == F_DOWN;
                    }
                    if (__all_sync(0xffffffffu, ok) || it > SPIN_LIMIT) break;
                }
                const bool u1 = lane & 2, u2 = lane & 4;
                const float a0 = untag(v.x), a1 = untag(v.y), a2 = untag(v.z), a3 = untag(v.w);
                const float k0 = (u1 ? a1 : a0) + __shfl_xor_sync(0xffffffffu, u1 ? a0 : a1, 2);
                const float k1 = (u1 ? a3 : a2) + __shfl_xor_sync(0xffffffffu, u1 ? a2 : a3, 2);
                r0 = (u2 ? k1 : k0) + __shfl_xor_sync(0xffffffffu, u2 ? k0 : k1, 4);
                r0 += __shfl_xor_sync(0xffffffffu, r0, 8);
                r0 += __shfl_xor_sync(0xffffffffu, r0, 16);
                if (lane < 8) red2[256 + warp * 8 + (2 * (lane & 1) + ((lane >> 2) & 1)) * 2 + ((lane >> 1) & 1)] = r0;
            }
            cons_sync();
            if (warp == 0) {
                float a0 = 0.f, a1 = 0.f;
#pragma unroll
                for (int w = 0; w < 8; w++) { const float2 v = *(const float2*)&red2[256 + w * 8 + (lane & 3) * 2]; a0 += v.x; a1 += v.y; }
                const bool hi = ocol & 1;
                const float gb0 = hi ? bf_hi(m_gb0.x) : bf_lo(m_gb0.x), gb1 = hi ? bf_hi(m_gb1.x) : bf_lo(m_gb1.x);
                for (int it = 0; !__all_sync(0xffffffffu, xw.y == F_X1) && it < SPIN_LIMIT; it++) xw = ld_ll2(&sc->x1[ocol]);
                if (lane < 4) {
                    p.out[ocol] = __float2bfloat16_rn(bf_lo(xw.x) + bf16r(gb0 * bf16r(a0)));
                    p.out[D_MODEL + ocol] = __float2bfloat16_rn(bf_hi(xw.x) + bf16r(gb1 * bf16r(a1)));
                }
                if (cta == 0 && lane == 0) *(volatile unsigned*)&sc->epoch = tag;
                TSTAMP(13);
            }
        }
    }
}

typedef CUresult (*EncodeFn)(CUtensorMap*, CUtensorMapDataType, cuuint32_t, void*, const cuuint64_t*, const cuuint64_t*,
                             const cuuint32_t*, const cuuint32_t*, CUtensorMapInterleave, CUtensorMapSwizzle,
                             CUtensorMapL2promotion, CUtensorMapFloatOOBfill);

struct Maps { CUtensorMap k, v, wq, wmod, wmod8, wo, wg, wu, wd; };

void encode(EncodeFn fn, CUtensorMap* m, const void* ptr, int rank, const cuuint64_t* dims, const cuuint64_t* strides,
            const cuuint32_t* box, CUtensorMapSwizzle sw) {
    const cuuint32_t es[3] = {1, 1, 1};
    fn(m, CU_TENSOR_MAP_DATA_TYPE_BFLOAT16, rank, const_cast<void*>(ptr), dims, strides, box, es,
       CU_TENSOR_MAP_INTERLEAVE_NONE, sw, CU_TENSOR_MAP_L2_PROMOTION_L2_256B, CU_TENSOR_MAP_FLOAT_OOB_FILL_NONE);
}

}

extern "C" void kernel_launch(void* const* d_in, const int* in_sizes, int n_in, void* d_out, int out_size) {
    (void)in_sizes; (void)n_in; (void)out_size;
    static EncodeFn enc = nullptr;
    static Scratch* scratch = nullptr;
    if (!enc) {
        cudaGetSymbolAddress((void**)&scratch, g_scratch);
        void* fn = nullptr;
        cudaDriverEntryPointQueryResult qr;
        cudaGetDriverEntryPoint("cuTensorMapEncodeTiled", &fn, cudaEnableDefault, &qr);
        enc = (EncodeFn)fn;
        cudaFuncSetAttribute(fused_block_kernel, cudaFuncAttributeMaxDynamicSharedMemorySize, SMEM_BYTES);
    }
    Maps m;
    {
        const cuuint64_t dims[3] = {64, (cuuint64_t)16 * SK, 2}, str[2] = {256, 128};
        const cuuint32_t box[3] = {64, 64, 2};
        encode(enc, &m.k, d_in[1], 3, dims, str, box, CU_TENSOR_MAP_SWIZZLE_128B);
        encode(enc, &m.v, d_in[2], 3, dims, str, box, CU_TENSOR_MAP_SWIZZLE_128B);
    }
    {
        const cuuint64_t dims[2] = {4096, 512}, str[1] = {8192};
        const cuuint32_t box[2] = {32, 256};
        encode(enc, &m.wq, d_in[3], 2, dims, str, box, CU_TENSOR_MAP_SWIZZLE_64B);
    }
    {
        const cuuint64_t dims[2] = {N_MOD, 512}, str[1] = {N_MOD * 2};
        const cuuint32_t box[2] = {16, 256};
        encode(enc, &m.wmod, d_in[10], 2, dims, str, box, CU_TENSOR_MAP_SWIZZLE_32B);
        const cuuint32_t box8[2] = {8, 256};
        encode(enc, &m.wmod8, d_in[10], 2, dims, str, box8, CU_TENSOR_MAP_SWIZZLE_NONE);
    }
    {
        const cuuint64_t dims_o[3] = {64, 4096, 8}, dims_d[3] = {64, D_FF, 8}, str[2] = {1024, 128};
        const cuuint32_t box[3] = {64, 16, 8}, box_o[3] = {64, 64, 2};
        encode(enc, &m.wo, d_in[4], 3, dims_o, str, box_o, CU_TENSOR_MAP_SWIZZLE_128B);
        encode(enc, &m.wd, d_in[8], 3, dims_d, str, box, CU_TENSOR_MAP_SWIZZLE_128B);
    }
    {
        const cuuint64_t dims[2] = {D_FF, 512}, str[1] = {D_FF * 2};
        const cuuint32_t box[2] = {16, 128};
        encode(enc, &m.wg, d_in[6], 2, dims, str, box, CU_TENSOR_MAP_SWIZZLE_32B);
        encode(enc, &m.wu, d_in[7], 2, dims, str, box, CU_TENSOR_MAP_SWIZZLE_32B);
    }
    Params p;
    p.x = (const __nv_bfloat16*)d_in[0];
    p.c = (const __nv_bfloat16*)d_in[9];
    p.out = (__nv_bfloat16*)d_out;
    p.sc = scratch;
    fused_block_kernel<<<NCTA, NTHREADS, SMEM_BYTES, cudaStreamPerThread>>>(p, m.k, m.v, m.wq, m.wmod, m.wmod8, m.wo, m.wg, m.wu, m.wd);
}
```

```cpp
#include <cuda_runtime.h>
#include <cuda.h>
#include <cuda_bf16.h>
#include <stdint.h>

namespace {

constexpr int D_MODEL = 512;
constexpr int N_HEADS = 32;
constexpr int SK = 32768;
constexpr int DH = 128;
constexpr int D_FF = 1792;
constexpr int N_MOD = 6 * D_MODEL;

constexpr int NCTA = 128;
constexpr int NFFN = D_FF / 16;
constexpr int NOWN = 32;
constexpr int NTHREADS = 320;
constexpr int NST = 12;
constexpr int TILE = 16384;
#define WINDOW 3
#define WINDOW_TAIL 1
#define GU_WIN 3
#define WD_WIN 1
#define PACE_THR 96
constexpr int KV_TILES = 64;
#define MOD_AT 8
static_assert(MOD_AT % 2 == 0 && MOD_AT >= 2 && MOD_AT < 56, "schedule");
__host__ __device__ constexpr int kv_idx(int i) { return 2 + 2 * i + (i >= MOD_AT ? 1 : 0); }
constexpr int IDX_MOD = 2 + 2 * MOD_AT;
constexpr int N_STREAM = kv_idx(KV_TILES - 1) + 2;
constexpr int IDX_WO = N_STREAM;
constexpr int IDX_WG = IDX_WO + 2;
constexpr int IDX_WU = IDX_WG + 1;
constexpr int IDX_WD = IDX_WU + 1;
constexpr int SPIN_LIMIT = 1 << 20;

constexpr float LOG2E = 1.4426950408889634f;
constexpr float QK_SCALE = 0.08838834764831845f;

constexpr int SM_RING = 0;
constexpr int SM_MRG = SM_RING + NST * TILE;
constexpr int SM_ML = SM_MRG + 8 * 4 * 136 * 4;
constexpr int SM_RED = SM_ML + 8 * 4 * 8;
constexpr int SM_RED2 = SM_RED + 8 * 64 * 4;
constexpr int SM_QS = SM_RED2 + 8 * 64 * 4;
constexpr int SM_OS = SM_QS + 512 * 2;
constexpr int SM_SC = SM_OS + 2 * 128 * 2;
constexpr int SM_HS = SM_SC + 2 * 512 * 2;
constexpr int SM_STAT = SM_HS + 8 * 2 * 32 * 4;
constexpr int SM_PACE = SM_STAT + 8 * 2 * 8;
constexpr int SM_BAR = SM_PACE + 8;
constexpr int SM_END = SM_BAR + (2 * NST + 1 + 8 + 2) * 8;
constexpr int SMEM_BYTES = SM_END + 1024;

struct Scratch {
    uint4 inbox_wo[NOWN][N_HEADS][8];
    uint4 inbox_dn[NCTA][NFFN][2];
    uint2 x1[D_MODEL];
    uint2 part_o[NCTA][4][64];
    uint2 part_ml[NCTA][4][4];
    uint2 mod[2][N_MOD / 2];
    uint2 q[2][N_HEADS * DH / 2];
    unsigned epoch;
    unsigned pad_[31];
    unsigned cleared;
    unsigned pad2_[31];
    unsigned progress;
};
__device__ Scratch g_scratch;
constexpr uint32_t F_PART = 1, F_WO = 1, F_DOWN = 1, F_X1 = 1;
__device__ __forceinline__ uint32_t tagf(float v, uint32_t f) { return (__float_as_uint(v) & ~3u) | f; }
__device__ __forceinline__ float untag(uint32_t v) { return __uint_as_float(v & ~3u); }

struct Params {
    const __nv_bfloat16* x;
    const __nv_bfloat16* c;
    __nv_bfloat16* out;
    Scratch* sc;
};

#define TSTAMP(i) do { } while (0)

__device__ __forceinline__ uint32_t smem_u32(const void* p) { return (uint32_t)__cvta_generic_to_shared(p); }

__device__ __forceinline__ void mbar_init(uint32_t bar, uint32_t cnt) {
    asm volatile("mbarrier.init.shared::cta.b64 [%0], %1;" ::"r"(bar), "r"(cnt) : "memory");
}
__device__ __forceinline__ void mbar_expect_tx(uint32_t bar, uint32_t bytes) {
    asm volatile("mbarrier.arrive.expect_tx.shared::cta.b64 _, [%0], %1;" ::"r"(bar), "r"(bytes) : "memory");
}
__device__ __forceinline__ void mbar_arrive(uint32_t bar) {
    asm volatile("mbarrier.arrive.shared::cta.b64 _, [%0];" ::"r"(bar) : "memory");
}
__device__ __forceinline__ bool mbar_try(uint32_t bar, uint32_t parity) {
    uint32_t ok;
    asm volatile(
        "{\n\t.reg .pred p;\n\t"
        "mbarrier.try_wait.parity.shared::cta.b64 p, [%1], %2;\n\t"
        "selp.u32 %0, 1, 0, p;\n\t}"
        : "=r"(ok) : "r"(bar), "r"(parity) : "memory");
    return ok != 0;
}
__device__ __forceinline__ void mbar_wait(uint32_t bar, uint32_t parity) {
    if (mbar_try(bar, parity)) return;
    const long long t0 = clock64();
    while (!mbar_try(bar, parity))
        if (clock64() - t0 > (1ll << 31)) return;
}
__device__ __forceinline__ void cons_sync() { asm volatile("bar.sync 1, 256;" ::: "memory"); }

__device__ __forceinline__ void tma_2d(uint32_t dst, const CUtensorMap* m, int c0, int c1, uint32_t bar) {
    asm volatile("cp.async.bulk.tensor.2d.shared::cluster.global.mbarrier::complete_tx::bytes [%0], [%1, {%3, %4}], [%2];"
                 ::"r"(dst), "l"(m), "r"(bar), "r"(c0), "r"(c1) : "memory");
}
__device__ __forceinline__ void tma_3d(uint32_t dst, const CUtensorMap* m, int c0, int c1, int c2, uint32_t bar) {
    asm volatile("cp.async.bulk.tensor.3d.shared::cluster.global.mbarrier::complete_tx::bytes [%0], [%1, {%3, %4, %5}], [%2];"
                 ::"r"(dst), "l"(m), "r"(bar), "r"(c0), "r"(c1), "r"(c2) : "memory");
}
__device__ __forceinline__ void tma_3d_hint(uint32_t dst, const CUtensorMap* m, int c0, int c1, int c2, uint32_t bar, uint64_t pol) {
    asm volatile("cp.async.bulk.tensor.3d.shared::cluster.global.mbarrier::complete_tx::bytes.L2::cache_hint [%0], [%1, {%3, %4, %5}], [%2], %6;"
                 ::"r"(dst), "l"(m), "r"(bar), "r"(c0), "r"(c1), "r"(c2), "l"(pol) : "memory");
}
__device__ __forceinline__ void prefetch_tmap(const CUtensorMap* m) {
    asm volatile("prefetch.tensormap [%0];" ::"l"(m) : "memory");
}

__device__ __forceinline__ void ldsm4(uint32_t addr, uint32_t (&r)[4]) {
    asm volatile("ldmatrix.sync.aligned.m8n8.x4.shared.b16 {%0,%1,%2,%3}, [%4];"
                 : "=r"(r[0]), "=r"(r[1]), "=r"(r[2]), "=r"(r[3]) : "r"(addr) : "memory");
}
__device__ __forceinline__ void ldsm4t(uint32_t addr, uint32_t (&r)[4]) {
    asm volatile("ldmatrix.sync.aligned.m8n8.x4.trans.shared.b16 {%0,%1,%2,%3}, [%4];"
                 : "=r"(r[0]), "=r"(r[1]), "=r"(r[2]), "=r"(r[3]) : "r"(addr) : "memory");
}
__device__ __forceinline__ void mma16816(float (&c)[4], const uint32_t (&a)[4], uint32_t b0, uint32_t b1) {
    asm volatile("mma.sync.aligned.m16n8k16.row.col.f32.bf16.bf16.f32 {%0,%1,%2,%3}, {%4,%5,%6,%7}, {%8,%9}, {%0,%1,%2,%3};"
                 : "+f"(c[0]), "+f"(c[1]), "+f"(c[2]), "+f"(c[3])
                 : "r"(a[0]), "r"(a[1]), "r"(a[2]), "r"(a[3]), "r"(b0), "r"(b1));
}
__device__ __forceinline__ uint32_t movmatrix_t(uint32_t a) {
    uint32_t d;
    asm volatile("movmatrix.sync.aligned.m8n8.trans.b16 %0, %1;" : "=r"(d) : "r"(a));
    return d;
}
__device__ __forceinline__ uint32_t pack_bf16(float a, float b) {
    uint32_t r;
    asm("cvt.rn.bf16x2.f32 %0, %1, %2;" : "=r"(r) : "f"(b), "f"(a));
    return r;
}
__device__ __forceinline__ float bf_lo(uint32_t v) { return __uint_as_float(v << 16); }
__device__ __forceinline__ float bf_hi(uint32_t v) { return __uint_as_float(v & 0xffff0000u); }
__device__ __forceinline__ float bf16r(float a) { return bf_lo(pack_bf16(a, 0.f)); }
__device__ __forceinline__ uint32_t max_bf16x2(uint32_t a, uint32_t b) {
    uint32_t r;
    asm("max.bf16x2 %0, %1, %2;" : "=r"(r) : "r"(a), "r"(b));
    return r;
}
__device__ __forceinline__ float ex2(float x) {
    float r;
    asm("ex2.approx.ftz.f32 %0, %1;" : "=f"(r) : "f"(x));
    return r;
}

__device__ __forceinline__ void st_ll2(uint2* p, uint32_t v, uint32_t tag) {
    asm volatile("st.relaxed.gpu.global.v2.u32 [%0], {%1, %2};" ::"l"(p), "r"(v), "r"(tag) : "memory");
}
__device__ __forceinline__ void st_ll4(uint4* p, uint32_t v0, uint32_t v1, uint32_t tag) {
    asm volatile("st.relaxed.gpu.global.v4.u32 [%0], {%1, %2, %3, %2};" ::"l"(p), "r"(v0), "r"(tag), "r"(v1) : "memory");
}
__device__ __forceinline__ void st_v4(uint4* p, uint32_t a, uint32_t b, uint32_t c, uint32_t d) {
    asm volatile("st.relaxed.gpu.global.v4.u32 [%0], {%1, %2, %3, %4};" ::"l"(p), "r"(a), "r"(b), "r"(c), "r"(d) : "memory");
}
__device__ __forceinline__ uint2 ld_ll2(const uint2* p) {
    uint2 v;
    asm volatile("ld.relaxed.gpu.global.v2.u32 {%0, %1}, [%2];" : "=r"(v.x), "=r"(v.y) : "l"(p) : "memory");
    return v;
}
__device__ __forceinline__ uint4 ld_ll4(const uint4* p) {
    uint4 v;
    asm volatile("ld.relaxed.gpu.global.v4.u32 {%0, %1, %2, %3}, [%4];"
                 : "=r"(v.x), "=r"(v.y), "=r"(v.z), "=r"(v.w) : "l"(p) : "memory");
    return v;
}

#define DELAY_B1 300
#define DELAY_X1 2000
#define DELAY_NOFFN 1500
#define A_BACKOFF 0
#define DELAY_C 600
__device__ __forceinline__ uint32_t clock32() {
    uint32_t c;
    asm volatile("mov.u32 %0, %clock;" : "=r"(c));
    return c;
}
__device__ __forceinline__ void spin_cycles(uint32_t n) {
    if (n > 0) { const uint32_t c0 = clock32(); while (clock32() - c0 < n) {} }
}
__device__ __forceinline__ float rcp_approx(float x) {
    float r;
    asm("rcp.approx.ftz.f32 %0, %1;" : "=f"(r) : "f"(x));
    return r;
}
__device__ __forceinline__ float sqrt_approx(float x) {
    float r;
    asm("sqrt.approx.f32 %0, %1;" : "=f"(r) : "f"(x));
    return r;
}

__device__ __forceinline__ float silu_bf(float v) { return bf16r(v / (1.0f + expf(-v))); }

__device__ __forceinline__ float2 half_warp_sums(const float (&v)[4], float pivot) {
    float s1 = 0.f, s2 = 0.f;
#pragma unroll
    for (int i = 0; i < 4; i++) { const float d = v[i] - pivot; s1 += d; s2 += d * d; }
#pragma unroll
    for (int o = 1; o < 16; o <<= 1) { s1 += __shfl_xor_sync(0xffffffffu, s1, o); s2 += __shfl_xor_sync(0xffffffffu, s2, o); }
    return make_float2(s1, s2);
}
__device__ __forceinline__ void ln_stats(const float2* stat, int b, float pivot, float& mean_bf, float& rstd) {
    float s1 = 0.f, s2 = 0.f;
#pragma unroll
    for (int w = 0; w < 8; w++) { const float2 v = stat[w * 2 + b]; s1 += v.x; s2 += v.y; }
    const float dm = s1 * (1.0f / D_MODEL);
    const float var = fmaxf(s2 * (1.0f / D_MODEL) - dm * dm, 0.f);
    mean_bf = bf16r(pivot + dm);
    rstd = rcp_approx(bf16r(sqrt_approx(bf16r(bf16r(var) + 1e-5f))));
}
__device__ __forceinline__ float ln_norm(float xv, float mean_bf, float rstd) { return bf16r(bf16r(xv - mean_bf) * rstd); }
__device__ __forceinline__ float ln_mod(float n, float cmul, float sadd) { return bf16r(n * bf16r(1.0f + cmul)) + sadd; }

__global__ void __launch_bounds__(NTHREADS, 1)
fused_block_kernel(const Params p, const __grid_constant__ CUtensorMap tm_k, const __grid_constant__ CUtensorMap tm_v,
                   const __grid_constant__ CUtensorMap tm_wq, const __grid_constant__ CUtensorMap tm_wmod,
                   const __grid_constant__ CUtensorMap tm_wmod8,
                   const __grid_constant__ CUtensorMap tm_wo, const __grid_constant__ CUtensorMap tm_wg,
                   const __grid_constant__ CUtensorMap tm_wu, const __grid_constant__ CUtensorMap tm_wd) {
    extern __shared__ unsigned char smem_raw[];
    const uint32_t sbase = (smem_u32(smem_raw) + 1023u) & ~1023u;
    unsigned char* sgen = smem_raw + (sbase - smem_u32(smem_raw));
    const int tid = threadIdx.x, warp = tid >> 5, lane = tid & 31;
    const int cta = blockIdx.x;
    const uint32_t bar_full = sbase + SM_BAR, bar_empty = bar_full + NST * 8;
    const uint32_t bar_clear = bar_empty + NST * 8;
    const uint32_t bar_gu = bar_clear + 8;
    const uint32_t bar_bc = bar_gu + 8 * 8;
    const uint32_t bar_p0w = bar_bc + 8;

    const int key0 = (cta >> 3) * SK + (cta & 7) * 64;
    uint64_t pol = 0;
    if (tid == 256) {
        asm volatile("createpolicy.fractional.L2::evict_first.b64 %0, 1.0;" : "=l"(pol));
        mbar_init(bar_p0w, 1);
#pragma unroll
        for (int i = 0; i < 4; i++) mbar_init(bar_full + 8 * i, 1);
        asm volatile("fence.mbarrier_init.release.cluster;" ::: "memory");
        mbar_expect_tx(bar_p0w, 8192);
        tma_2d(sbase + SM_MRG, &tm_wmod8, cta * 8, 0, bar_p0w);
        tma_2d(sbase + SM_MRG + 4096, &tm_wmod8, cta * 8, 256, bar_p0w);
#pragma unroll
        for (int i = 0; i < 4; i++) mbar_expect_tx(bar_full + 8 * i, TILE);
        tma_2d(sbase + SM_RING, &tm_wq, cta * 32, 0, bar_full);
        tma_2d(sbase + SM_RING + TILE, &tm_wq, cta * 32, 256, bar_full + 8);
        tma_3d_hint(sbase + SM_RING + 2 * TILE, &tm_k, 0, key0, 0, bar_full + 16, pol);
        tma_3d_hint(sbase + SM_RING + 3 * TILE, &tm_v, 0, key0, 0, bar_full + 24, pol);
    }

    if (warp == 8) {
        if (lane == 0) {
            for (int i = 0; i < NST; i++) { if (i >= 4) mbar_init(bar_full + 8 * i, 1); mbar_init(bar_empty + 8 * i, 4); }
            mbar_init(bar_clear, 1);
            for (int k = 0; k < 8; k++) mbar_init(bar_gu + 8 * k, 1);
            mbar_init(bar_bc, 8);
            ((volatile uint32_t*)(sgen + SM_PACE))[0] = 0;
            ((volatile uint32_t*)(sgen + SM_PACE))[1] = WINDOW;
            asm volatile("fence.mbarrier_init.release.cluster;" ::: "memory");
        }
        __syncwarp();
        asm volatile("bar.arrive 2, 320;" ::: "memory");
        asm volatile("bar.arrive 3, 64;" ::: "memory");
        if (lane == 0) {
            int slot = 4; uint32_t ph = 1;
            int landed = 0, wslot = 0; uint32_t wph = 0;
            int kv = 2;
            auto wait_window = [&](int idx, int window) {
                while (landed + window <= idx) {
                    mbar_wait(bar_full + 8 * wslot, wph);
                    if (++wslot == NST) { wslot = 0; wph ^= 1; }
                    landed++;
                }
            };
            volatile uint32_t* pace = (volatile uint32_t*)(sgen + SM_PACE);
            prefetch_tmap(&tm_wmod);
            pace[0] = 4;
            for (int idx = 4; idx < N_STREAM; idx++) {
                if (idx >= NST) mbar_wait(bar_empty + 8 * slot, ph);
                wait_window(idx, (int)pace[1]);
                if (idx == 12) { prefetch_tmap(&tm_wo); prefetch_tmap(&tm_wg); prefetch_tmap(&tm_wu); prefetch_tmap(&tm_wd); }
                const uint32_t fb = bar_full + 8 * slot, dst = sbase + SM_RING + slot * TILE;
                mbar_expect_tx(fb, TILE);
                if (idx == IDX_MOD) {
                    tma_2d(dst, &tm_wmod, 1024 + cta * 16, 0, fb);
                    tma_2d(dst + 8192, &tm_wmod, 1024 + cta * 16, 256, fb);
                } else {
                    tma_3d_hint(dst, (kv & 1) ? &tm_v : &tm_k, 0, key0 + (kv >> 1) * 512, 0, fb, pol);
                    kv++;
                }
                pace[0] = idx + 1;
                if (++slot == NST) { slot = 0; ph ^= 1; }
            }
            auto slot_free = [&](int idx) { mbar_wait(bar_empty + 8 * (idx % NST), ((idx / NST) & 1) ^ 1); };
#pragma unroll
            for (int s = 0; s < 2; s++) {
                const int idx = IDX_WO + s;
                slot_free(idx);
                wait_window(idx, WINDOW_TAIL);
                mbar_expect_tx(bar_full + 8 * (idx % NST), TILE);
                tma_3d(sbase + SM_RING + (idx % NST) * TILE, &tm_wo, 0, (cta >> 2) * 128 + s * 64, (cta & 3) * 2, bar_full + 8 * (idx % NST));
            }
            if (cta < NFFN) {
                slot_free(IDX_WG); slot_free(IDX_WU);
                mbar_wait(bar_full + 8 * (IDX_WO % NST), (IDX_WO / NST) & 1);
                mbar_wait(bar_full + 8 * ((IDX_WO + 1) % NST), ((IDX_WO + 1) / NST) & 1);
#pragma unroll
                for (int st = 0; st < 8; st++) {
                    if (st >= GU_WIN) mbar_wait(bar_gu + 8 * (st - GU_WIN), 0);
                    mbar_expect_tx(bar_gu + 8 * st, 4096);
                    tma_2d(sbase + SM_RING + (((st & 1) ? IDX_WU : IDX_WG) % NST) * TILE + (st >> 1) * 4096,
                           (st & 1) ? &tm_wu : &tm_wg, cta * 16, (st >> 1) * 128, bar_gu + 8 * st);
                }
                mbar_wait(bar_gu + 8 * (8 - WD_WIN), 0);
                slot_free(IDX_WD);
                mbar_expect_tx(bar_full + 8 * (IDX_WD % NST), TILE);
                tma_3d(sbase + SM_RING + (IDX_WD % NST) * TILE, &tm_wd, 0, cta * 16, 0, bar_full + 8 * (IDX_WD % NST));
            }
        }
    } else if (warp == 9) {
        Scratch* const sc = p.sc;
        const uint32_t tag = *(volatile unsigned*)&sc->epoch + 1;
        if (lane < 2) {
            st_ll4((uint4*)&sc->mod[lane][cta * 4], 0u, 0u, 0u);
            st_ll4((uint4*)&sc->mod[lane][cta * 4] + 1, 0u, 0u, 0u);
        }
        if (lane < 8) st_ll4((uint4*)&sc->mod[lane >> 2][512 + cta * 8] + (lane & 3), 0u, 0u, 0u);
        if (lane < 16) st_ll4((uint4*)&sc->q[lane >> 3][cta * 16] + (lane & 7), 0u, 0u, 0u);
        __syncwarp();
        asm volatile("bar.arrive 2, 320;" ::: "memory");
        asm volatile("bar.sync 3, 64;" ::: "memory");
#pragma unroll 4
        for (int i = 0; i < NFFN * 2 / 32; i++) st_v4(&sc->inbox_dn[cta][0][0] + i * 32 + lane, 0u, 0u, 0u, 0u);
        if (cta >= NCTA - NOWN) {
#pragma unroll 4
            for (int i = 0; i < 8; i++) st_v4(&sc->inbox_wo[cta - (NCTA - NOWN)][0][0] + i * 32 + lane, 0u, 0u, 0u, 0u);
            if (lane < 8) st_v4((uint4*)&sc->x1[(cta - (NCTA - NOWN)) * 16] + lane, 0u, 0u, 0u, 0u);
        }
#pragma unroll 4
        for (int i = 0; i < 4; i++) st_v4((uint4*)&sc->part_o[cta][0][0] + i * 32 + lane, 0u, 0u, 0u, 0u);
        if (lane < 8) st_v4((uint4*)&sc->part_ml[cta][0][0] + lane, 0u, 0u, 0u, 0u);
        if (cta == 0 && lane == 0) asm volatile("st.relaxed.gpu.global.u32 [%0], %1;" ::"l"(&sc->progress), "r"(0u) : "memory");
        asm volatile("fence.acq_rel.gpu;" ::: "memory");
        __syncwarp();
        if (lane == 0) {
            asm volatile("fence.acq_rel.gpu;" ::: "memory");
            asm volatile("red.relaxed.gpu.global.add.u32 [%0], %1;" ::"l"(&sc->cleared), "r"(1u) : "memory");
            const uint32_t target = tag * NCTA;
            for (int it = 0; it < SPIN_LIMIT; it++) {
                uint32_t v;
                asm volatile("ld.relaxed.gpu.global.u32 %0, [%1];" : "=r"(v) : "l"(&sc->cleared) : "memory");
                if ((int32_t)(v - target) >= 0) break;
                __nanosleep(500);
            }
            asm volatile("fence.acq_rel.gpu;" ::: "memory");
            mbar_arrive(bar_clear);
            volatile uint32_t* pace = (volatile uint32_t*)(sgen + SM_PACE);
            uint32_t posted = 0;
            for (int it = 0; it < SPIN_LIMIT; it++) {
                const uint32_t own = pace[0];
                if (own >= N_STREAM) break;
                if (own > posted) {
                    asm volatile("red.relaxed.gpu.global.add.u32 [%0], %1;" ::"l"(&sc->progress), "r"(own - posted) : "memory");
                    posted = own;
                }
                uint32_t v;
                asm volatile("ld.relaxed.gpu.global.u32 %0, [%1];" : "=r"(v) : "l"(&sc->progress) : "memory");
                const int diff = (int)v - (int)own * NCTA;
                pace[1] = diff > PACE_THR ? WINDOW + 1 : diff < -PACE_THR ? WINDOW - 1 : WINDOW;
                __nanosleep(200);
            }
        }
    } else {
        const int g = lane >> 2, t = lane & 3;
        const int bb = g & 1;
        const int eb = lane >> 4;
        const int ec = 64 * warp + 4 * (lane & 15);
        if (warp == 0) TSTAMP(0);
        Scratch* const sc = p.sc;
        const float c00 = __bfloat162float(p.c[tid]), c01 = __bfloat162float(p.c[tid + 256]);
        const float c10 = __bfloat162float(p.c[D_MODEL + tid]), c11 = __bfloat162float(p.c[D_MODEL + tid + 256]);
        const uint2 xe = __ldg((const uint2*)(p.x + eb * D_MODEL + ec));
        const float xpivot = __bfloat162float(p.x[eb * D_MODEL]);
        const uint32_t tag = *(volatile unsigned*)&sc->epoch + 1;
        const int ocol = cta * 4 + (lane & 3);
        const int wcol = (cta >= NCTA - NOWN ? cta - (NCTA - NOWN) : 0) * 16 + (lane & 15);
        const float xo = __bfloat162float(p.x[eb * D_MODEL + wcol]);

        float* red = (float*)(sgen + SM_RED);
        float* red2 = (float*)(sgen + SM_RED2);
        float2* stat = (float2*)(sgen + SM_STAT);
        uint32_t* hs = (uint32_t*)(sgen + SM_HS) + warp * 64;
        float xn[4];
        {
            float xv[4] = {bf_lo(xe.x), bf_hi(xe.x), bf_lo(xe.y), bf_hi(xe.y)};
            const float2 ps = half_warp_sums(xv, xpivot);
            if ((lane & 15) == 0) stat[warp * 2 + eb] = ps;
            const float s00 = silu_bf(c00), s01 = silu_bf(c01), s10 = silu_bf(c10), s11 = silu_bf(c11);
            __nv_bfloat16* scs = (__nv_bfloat16*)(sgen + SM_SC);
            scs[tid] = __float2bfloat16_rn(s00); scs[tid + 256] = __float2bfloat16_rn(s01);
            scs[512 + tid] = __float2bfloat16_rn(s10); scs[512 + tid + 256] = __float2bfloat16_rn(s11);
            asm volatile("bar.sync 2, 320;" ::: "memory");
            if (warp == 0) TSTAMP(23);
            float cp[4] = {0.f, 0.f, 0.f, 0.f};
            const uint32_t* sc32 = (const uint32_t*)(sgen + SM_SC) + bb * 256 + 32 * warp + t;
            mbar_wait(bar_p0w, 0);
#pragma unroll
            for (int s = 0; s < 4; s++) {
                uint32_t r0, r1;
                asm volatile("ldmatrix.sync.aligned.m8n8.x2.trans.shared.b16 {%0,%1}, [%2];"
                             : "=r"(r0), "=r"(r1) : "r"(sbase + SM_MRG + (64 * warp + 16 * s + (lane & 15)) * 16) : "memory");
                const uint32_t a[4] = {r0, r0, r1, r1};
                mma16816(cp, a, sc32[8 * s], sc32[8 * s + 4]);
            }
            if (t == 0) { red[warp * 16 + g] = cp[0]; red[warp * 16 + 8 + g] = cp[1]; }
            if (warp == 0) TSTAMP(14);
            cons_sync();
            if (warp == 0) {
                float s = 0.f;
#pragma unroll
                for (int w = 0; w < 8; w++) s += red[w * 16 + (lane & 15)];
                const float nx = __shfl_down_sync(0xffffffffu, s, 1);
                if (lane < 16 && !(lane & 1))
                    st_ll2(&sc->mod[lane >> 3][cta * 4 + ((lane & 7) >> 1)], pack_bf16(s, nx), tag);
                TSTAMP(1);
            }
            float mean_bf, rstd;
            ln_stats(stat, eb, xpivot, mean_bf, rstd);
#pragma unroll
            for (int i = 0; i < 4; i++) xn[i] = ln_norm(xv[i], mean_bf, rstd);
        }
        {
            uint4 sa, ca;
            for (int it = 0;; it++) {
                sa = ld_ll4((const uint4*)&sc->mod[eb][ec >> 1]);
                ca = ld_ll4((const uint4*)&sc->mod[eb][256 + (ec >> 1)]);
                const bool ok = sa.y == tag && sa.w == tag && ca.y == tag && ca.w == tag;
                if (__all_sync(0xffffffffu, ok) || it > SPIN_LIMIT) break;
            }
            *(uint2*)&hs[eb * 32 + 2 * (lane & 15)] =
                make_uint2(pack_bf16(ln_mod(xn[0], bf_lo(ca.x), bf_lo(sa.x)), ln_mod(xn[1], bf_hi(ca.x), bf_hi(sa.x))),
                           pack_bf16(ln_mod(xn[2], bf_lo(ca.z), bf_lo(sa.z)), ln_mod(xn[3], bf_hi(ca.z), bf_hi(sa.z))));
            __syncwarp();
            uint32_t hb[8];
#pragma unroll
            for (int i = 0; i < 8; i++) hb[i] = hs[bb * 32 + 8 * (i >> 1) + 4 * (i & 1) + t];
            if (warp == 0) TSTAMP(2);
            float cq[2][4] = {};
            const int ts = warp >> 2;
            mbar_wait(bar_full + 8 * ts, 0);
            const uint32_t tb = sbase + SM_RING + ts * TILE;
#pragma unroll
            for (int s = 0; s < 4; s++) {
                const int row = 64 * (warp & 3) + 16 * s + (lane & 7) + (lane >> 4) * 8;
#pragma unroll
                for (int mt = 0; mt < 2; mt++) {
                    const int ch = 2 * mt + ((lane >> 3) & 1);
                    uint32_t a[4];
                    ldsm4t(tb + row * 64 + ((ch ^ ((row >> 1) & 3)) << 4), a);
                    mma16816(cq[mt], a, hb[2 * s], hb[2 * s + 1]);
                }
            }
            if (t < 2) {
                const float v0 = t == 0 ? cq[0][0] : cq[1][0], v1 = t == 0 ? cq[0][1] : cq[1][1];
                const float v2 = t == 0 ? cq[0][2] : cq[1][2], v3 = t == 0 ? cq[0][3] : cq[1][3];
                *(float2*)&red2[warp * 64 + (16 * t + g) * 2] = make_float2(v0, v1);
                *(float2*)&red2[warp * 64 + (16 * t + g + 8) * 2] = make_float2(v2, v3);
            }
            cons_sync();
            if (warp < 4 && lane == 0) { mbar_arrive(bar_empty); mbar_arrive(bar_empty + 8); }
            if (warp == 0) {
                const int b = lane >> 4, cp = lane & 15;
                float q0 = 0.f, q1 = 0.f;
#pragma unroll
                for (int w = 0; w < 8; w++) {
                    const float4 v = *(const float4*)&red2[w * 64 + cp * 4];
                    q0 += b ? v.y : v.x; q1 += b ? v.w : v.z;
                }
                st_ll2(&sc->q[b][cta * 16 + cp], pack_bf16(q0, q1), tag);
                TSTAMP(3);
            }
        }
        const int pair = cta >> 3;
        uint32_t qf[16];
        {
            uint2* qs = (uint2*)(sgen + SM_QS);
            if (tid < 128) {
                const uint4* src = (const uint4*)&sc->q[pair >> 3][(pair & 7) * 256] + tid;
                uint4 v;
                for (int it = 0;; it++) {
                    v = ld_ll4(src);
                    if ((v.y == tag && v.w == tag) || it > SPIN_LIMIT) break;
                }
                qs[tid] = make_uint2(v.x, v.z);
            }
            cons_sync();
            const uint32_t* q32 = (const uint32_t*)(sgen + SM_QS);
#pragma unroll
            for (int s = 0; s < 8; s++) {
                qf[2 * s] = q32[(g & 3) * 64 + 8 * s + t];
                qf[2 * s + 1] = q32[(g & 3) * 64 + 8 * s + 4 + t];
            }
        }
        if (warp == 0) TSTAMP(4);

        float o[8][4];
#pragma unroll
        for (int i = 0; i < 8; i++) { o[i][0] = o[i][1] = o[i][2] = o[i][3] = 0.f; }
        uint32_t mrun = 0xff80ff80u;
        float ls[4] = {0.f, 0.f, 0.f, 0.f};
        uint4 m_sb, m_cb; uint2 m_ga, m_gb0, m_gb1;
        {
            const int grp = warp >> 2, wi = warp & 3;
            const int krow = 16 * wi + (lane & 7) + ((lane >> 3) & 1) * 8;
            const uint32_t koff = krow * 128 + ((((lane >> 4) & 1) ^ (lane & 7)) << 4);
            const int vrow = 16 * wi + (lane & 7) + (lane >> 4) * 8;
            const uint32_t voff = vrow * 128 + ((((lane >> 3) & 1) ^ (lane & 7)) << 4);
            const uint32_t ones[4] = {0x3f803f80u, 0x3f803f80u, 0x3f803f80u, 0x3f803f80u};
            for (int i = grp; i < KV_TILES; i += 2) {
                if (i == MOD_AT + grp) {
                    float cm[4] = {};
                    const uint32_t* sc32 = (const uint32_t*)(sgen + SM_SC) + bb * 256 + 32 * warp + t;
                    mbar_wait(bar_full + 8 * (IDX_MOD % NST), (IDX_MOD / NST) & 1);
                    const uint32_t tb = sbase + SM_RING + (IDX_MOD % NST) * TILE;
#pragma unroll
                    for (int s = 0; s < 4; s++) {
                        const int row = 64 * warp + 16 * s + (lane & 7) + (lane >> 4) * 8;
                        const int ch = (lane >> 3) & 1;
                        uint32_t a[4];
                        ldsm4t(tb + row * 32 + ((ch ^ ((row >> 2) & 1)) << 4), a);
                        mma16816(cm, a, sc32[8 * s], sc32[8 * s + 4]);
                    }
                    if (t == 0) {
                        *(float2*)&red[warp * 64 + g * 2] = make_float2(cm[0], cm[1]);
                        *(float2*)&red[warp * 64 + (g + 8) * 2] = make_float2(cm[2], cm[3]);
                    }
                    cons_sync();
                    if (warp < 4 && lane == 0) mbar_arrive(bar_empty + 8 * (IDX_MOD % NST));
                    if (warp == 1 && lane < 16) {
                        const int b = lane >> 3, cp = lane & 7;
                        float q0 = 0.f, q1 = 0.f;
#pragma unroll
                        for (int w = 0; w < 8; w++) {
                            const float4 v = *(const float4*)&red[w * 64 + cp * 4];
                            q0 += b ? v.y : v.x; q1 += b ? v.w : v.z;
                        }
                        st_ll2(&sc->mod[b][512 + cta * 8 + cp], pack_bf16(q0, q1), tag);
                    }
                }
                if (i == 56 + grp) {
                    m_sb = ld_ll4((const uint4*)&sc->mod[eb][768 + (ec >> 1)]);
                    m_cb = ld_ll4((const uint4*)&sc->mod[eb][1024 + (ec >> 1)]);
                    m_ga = ld_ll2(&sc->mod[eb][512 + (wcol >> 1)]);
                    m_gb0 = ld_ll2(&sc->mod[0][1280 + (ocol >> 1)]); m_gb1 = ld_ll2(&sc->mod[1][1280 + (ocol >> 1)]);
                }
                if (i == 60 + grp) {
                    for (int it = 0;; it++) {
                        const bool ok = m_sb.y == tag && m_sb.w == tag && m_cb.y == tag && m_cb.w == tag &&
                                        m_ga.y == tag && m_gb0.y == tag && m_gb1.y == tag;
                        if (__all_sync(0xffffffffu, ok) || it > SPIN_LIMIT) break;
                        m_sb = ld_ll4((const uint4*)&sc->mod[eb][768 + (ec >> 1)]);
                        m_cb = ld_ll4((const uint4*)&sc->mod[eb][1024 + (ec >> 1)]);
                        m_ga = ld_ll2(&sc->mod[eb][512 + (wcol >> 1)]);
                        m_gb0 = ld_ll2(&sc->mod[0][1280 + (ocol >> 1)]); m_gb1 = ld_ll2(&sc->mod[1][1280 + (ocol >> 1)]);
                    }
                    mbar_wait(bar_clear, 0);
                }
                const int ki = kv_idx(i), ks = ki % NST, vs = (ki + 1) % NST;
                const uint32_t kph = (ki / NST) & 1, vph = ((ki + 1) / NST) & 1;
                mbar_wait(bar_full + 8 * ks, kph);
                const uint32_t kb = sbase + SM_RING + ks * TILE + koff;
                float sa[4] = {0.f, 0.f, 0.f, 0.f}, sb[4] = {0.f, 0.f, 0.f, 0.f};
#pragma unroll
                for (int s = 0; s < 8; s += 2) {
                    uint32_t a0[4], a1[4];
                    ldsm4((kb ^ ((s & 3) << 5)) + (s >> 2) * 8192, a0);
                    ldsm4((kb ^ (((s + 1) & 3) << 5)) + (s >> 2) * 8192, a1);
                    mma16816(sa, a0, qf[2 * s], qf[2 * s + 1]);
                    mma16816(sb, a1, qf[2 * s + 2], qf[2 * s + 3]);
                }
                __syncwarp();
                if (lane == 0) mbar_arrive(bar_empty + 8 * ks);
                uint32_t r01 = pack_bf16(sa[0] + sb[0], sa[1] + sb[1]);
                uint32_t r23 = pack_bf16(sa[2] + sb[2], sa[3] + sb[3]);
                r01 = pack_bf16(bf_lo(r01) * QK_SCALE, bf_hi(r01) * QK_SCALE);
                r23 = pack_bf16(bf_lo(r23) * QK_SCALE, bf_hi(r23) * QK_SCALE);
                uint32_t mx = max_bf16x2(r01, r23);
                mx = max_bf16x2(mx, __shfl_xor_sync(0xffffffffu, mx, 4));
                mx = max_bf16x2(mx, __shfl_xor_sync(0xffffffffu, mx, 8));
                mx = max_bf16x2(mx, __shfl_xor_sync(0xffffffffu, mx, 16));
                const uint32_t mnew = max_bf16x2(mrun, mx);
                const float m0 = bf_lo(mnew), m1 = bf_hi(mnew);
                if (__any_sync(0xffffffffu, mnew != mrun)) {
                    const float al0 = ex2((bf_lo(mrun) - m0) * LOG2E), al1 = ex2((bf_hi(mrun) - m1) * LOG2E);
                    ls[0] *= al0; ls[1] *= al1;
#pragma unroll
                    for (int d = 0; d < 8; d++) { o[d][0] *= al0; o[d][1] *= al1; o[d][2] *= al0; o[d][3] *= al1; }
                    mrun = mnew;
                }
                const float p0 = ex2((bf_lo(r01) - m0) * LOG2E), p1 = ex2((bf_hi(r01) - m1) * LOG2E);
                const float p2 = ex2((bf_lo(r23) - m0) * LOG2E), p3 = ex2((bf_hi(r23) - m1) * LOG2E);
                const uint32_t pb0 = movmatrix_t(pack_bf16(p0, p1)), pb1 = movmatrix_t(pack_bf16(p2, p3));
                mma16816(ls, ones, pb0, pb1);
                mbar_wait(bar_full + 8 * vs, vph);
                const uint32_t vb = sbase + SM_RING + vs * TILE + voff;
#pragma unroll
                for (int d = 0; d < 8; d++) {
                    uint32_t a[4];
                    ldsm4t((vb ^ ((d & 3) << 5)) + (d >> 2) * 8192, a);
                    mma16816(o[d], a, pb0, pb1);
                }
                __syncwarp();
                if (lane == 0) mbar_arrive(bar_empty + 8 * vs);
            }
        }
        if (warp == 7) TSTAMP(5);
        {
            float* mrg = (float*)(sgen + SM_MRG);
            float2* ml = (float2*)(sgen + SM_ML);
            {
                const int hp = (t & 1) * 2, up = t >> 1;
                if (g == 0 && up == 0) { ml[warp * 4 + hp] = make_float2(bf_lo(mrun), ls[0]); ml[warp * 4 + hp + 1] = make_float2(bf_hi(mrun), ls[1]); }
                float* m0p = mrg + (warp * 4 + hp) * 136 + up * 72 + g;
#pragma unroll
                for (int d = 0; d < 4; d++) {
                    m0p[16 * d] = up ? o[d + 4][0] : o[d][0]; m0p[136 + 16 * d] = up ? o[d + 4][1] : o[d][1];
                    m0p[16 * d + 8] = up ? o[d + 4][2] : o[d][2]; m0p[136 + 16 * d + 8] = up ? o[d + 4][3] : o[d][3];
                }
            }
            cons_sync();
            const int hh = tid >> 6, dp = tid & 63;
            float2 mw[8];
            float M = -INFINITY;
#pragma unroll
            for (int w = 0; w < 8; w++) { mw[w] = ml[w * 4 + hh]; M = fmaxf(M, mw[w].x); }
            float L = 0.f, o0 = 0.f, o1 = 0.f;
#pragma unroll
            for (int w = 0; w < 8; w++) {
                const float wt = ex2((mw[w].x - M) * LOG2E);
                const float2 v = *(const float2*)&mrg[(w * 4 + hh) * 136 + 2 * dp + (dp >= 32 ? 8 : 0)];
                L += wt * mw[w].y; o0 += wt * v.x; o1 += wt * v.y;
            }
            st_ll2(&sc->part_o[cta][hh][dp], tagf(o0, F_PART), tagf(o1, F_PART));
            if (dp < 4) st_ll2(&sc->part_ml[cta][hh][dp], tagf(M, F_PART), tagf(L, F_PART));
        }
        if (warp == 0) TSTAMP(6);
        {
            const int hq = cta >> 2, kvh = hq >> 2, hh = hq & 3;
            const int b = tid >> 7, dc = (tid >> 3) & 15, j = tid & 7;
            const int pc = (b * 8 + kvh) * 8 + j;
            const uint4* po = (const uint4*)&sc->part_o[pc][hh][0] + dc * 2;
            const uint2* pm = &sc->part_ml[pc - j][hh][0];
            uint4 vo0, vo1; uint2 vm[8];
            bool oko = false, okm = false;
            for (int it = 0;; it++) {
                if (!oko) { vo0 = ld_ll4(po); vo1 = ld_ll4(po + 1); }
                if (!okm) {
#pragma unroll
                    for (int jj = 0; jj < 8; jj++) vm[jj] = ld_ll2(pm + jj * 16);
                }
                oko = (vo0.x & vo0.y & vo0.z & vo0.w & vo1.x & vo1.y & vo1.z & vo1.w & 3u) == F_PART;
                uint32_t all = vm[0].x & vm[0].y;
#pragma unroll
                for (int jj = 1; jj < 8; jj++) all &= vm[jj].x & vm[jj].y;
                okm = (all & 3u) == F_PART;
                if (__all_sync(0xffffffffu, oko && okm) || it > SPIN_LIMIT) break;
                spin_cycles(A_BACKOFF);
            }
            float M = untag(vm[0].x);
#pragma unroll
            for (int jj = 1; jj < 8; jj++) M = fmaxf(M, untag(vm[jj].x));
            float wt = 0.f, L = 0.f;
#pragma unroll
            for (int jj = 0; jj < 8; jj++) {
                const float w_ = ex2((untag(vm[jj].x) - M) * LOG2E);
                L += w_ * untag(vm[jj].y);
                wt = jj == j ? w_ : wt;
            }
            wt *= rcp_approx(L);
            float v[8] = {wt * untag(vo0.x), wt * untag(vo0.y), wt * untag(vo0.z), wt * untag(vo0.w),
                          wt * untag(vo1.x), wt * untag(vo1.y), wt * untag(vo1.z), wt * untag(vo1.w)};
#define XRED(N, O)                                                                       \
            {                                                                            \
                const bool up = lane & (O);                                              \
                _Pragma("unroll") for (int i = 0; i < (N); i++) {                        \
                    const float send = up ? v[i] : v[i + (N)], keep = up ? v[i + (N)] : v[i]; \
                    v[i] = keep + __shfl_xor_sync(0xffffffffu, send, (O));               \
                }                                                                        \
            }
            XRED(4, 1) XRED(2, 2) XRED(1, 4)
#undef XRED
            __nv_bfloat16* os = (__nv_bfloat16*)(sgen + SM_OS);
            os[b * 128 + dc * 8 + 4 * (j & 1) + 2 * ((j >> 1) & 1) + (j >> 2)] = __float2bfloat16_rn(v[0]);
            if (warp == 0) TSTAMP(15);
            uint32_t wf[8][4];
            const uint32_t aoff_o = (warp >> 2) * 8192 + ((lane & 7) + (lane >> 4) * 8) * 128 +
                                    (((((warp & 3) * 2 + ((lane >> 3) & 1)) ^ (lane & 7))) << 4);
#pragma unroll
            for (int s = 0; s < 2; s++) {
                const int idx = IDX_WO + s;
                mbar_wait(bar_full + 8 * (idx % NST), (idx / NST) & 1);
                const uint32_t tb = sbase + SM_RING + (idx % NST) * TILE + aoff_o;
#pragma unroll
                for (int k4 = 0; k4 < 4; k4++) ldsm4t(tb + k4 * 2048, wf[s * 4 + k4]);
            }
            cons_sync();
            if (warp == 0) TSTAMP(7);
            const uint32_t* os32 = (const uint32_t*)(sgen + SM_OS) + bb * 64 + t;
            float y0[4] = {}, y1[4] = {};
#pragma unroll
            for (int ks = 0; ks < 8; ks += 2) {
                mma16816(y0, wf[ks], os32[8 * ks], os32[8 * ks + 4]);
                mma16816(y1, wf[ks + 1], os32[8 * ks + 8], os32[8 * ks + 12]);
            }
            if (t == 0)
                st_v4(&sc->inbox_wo[(cta & 3) * 8 + warp][hq][g], tagf(y0[0] + y1[0], F_WO), tagf(y0[1] + y1[1], F_WO),
                      tagf(y0[2] + y1[2], F_WO), tagf(y0[3] + y1[3], F_WO));
        }
        const uint32_t t_wo = clock32();
        if (warp == 0) TSTAMP(8);
        if (cta >= NCTA - NOWN) {
            const uint4* pin = &sc->inbox_wo[cta - (NCTA - NOWN)][0][0] + tid;
            uint4 v;
            spin_cycles(DELAY_B1);
            bool ok = false;
            for (int it = 0;; it++) {
                if (!ok) {
                    v = ld_ll4(pin);
                    ok = (v.x & v.y & v.z & v.w & 3u) == F_WO;
                }
                if (__all_sync(0xffffffffu, ok) || it > SPIN_LIMIT) break;
            }
            const bool u1 = lane & 8, u2 = lane & 16;
            const float a0 = untag(v.x), a1 = untag(v.y), a2 = untag(v.z), a3 = untag(v.w);
            const float k0 = (u1 ? a2 : a0) + __shfl_xor_sync(0xffffffffu, u1 ? a0 : a2, 8);
            const float k1 = (u1 ? a3 : a1) + __shfl_xor_sync(0xffffffffu, u1 ? a1 : a3, 8);
            red2[warp * 32 + lane] = (u2 ? k1 : k0) + __shfl_xor_sync(0xffffffffu, u2 ? k0 : k1, 16);
            cons_sync();
            if (warp == 0) {
                float a = 0.f;
#pragma unroll
                for (int w = 0; w < 8; w++) a += red2[w * 32 + lane];
                const float ga = (wcol & 1) ? bf_hi(m_ga.x) : bf_lo(m_ga.x);
                const float xm = bf16r(xo + bf16r(ga * bf16r(a)));
                const float xm_b1 = __shfl_down_sync(0xffffffffu, xm, 16);
                if (lane < 16) st_ll2(&sc->x1[wcol], pack_bf16(xm, xm_b1), F_X1);
                TSTAMP(10);
            }
        }
        const uint32_t aoff = warp * 2048 + ((lane & 7) + (lane >> 4) * 8) * 128 + ((((lane >> 3) & 1) ^ (lane & 7)) << 4);
        if (cta < NFFN) {
            const uint4* px = (const uint4*)&sc->x1[ec];
            const uint4* pp = (const uint4*)&sc->x1[0];
            uint4 va, vb, pa, pb;
            uint32_t gf[4][4], uf[4][4];
            mbar_wait(bar_gu + 8 * (2 * (warp >> 1)), 0);
            mbar_wait(bar_gu + 8 * (2 * (warp >> 1) + 1), 0);
            {
                const uint32_t tg = sbase + SM_RING + (IDX_WG % NST) * TILE, tu = sbase + SM_RING + (IDX_WU % NST) * TILE;
#pragma unroll
                for (int s = 0; s < 4; s++) {
                    const int row = 64 * warp + 16 * s + (lane & 7) + (lane >> 4) * 8;
                    const uint32_t off = row * 32 + ((((lane >> 3) & 1) ^ ((row >> 2) & 1)) << 4);
                    ldsm4t(tg + off, gf[s]);
                    ldsm4t(tu + off, uf[s]);
                }
            }
            const float c1v[4] = {bf16r(1.0f + bf_lo(m_cb.x)), bf16r(1.0f + bf_hi(m_cb.x)), bf16r(1.0f + bf_lo(m_cb.z)), bf16r(1.0f + bf_hi(m_cb.z))};
            float bg = 0.f, cgc = 0.f, bu = 0.f, cuc = 0.f;
            {
                uint32_t* pre = (uint32_t*)(sgen + SM_MRG) + warp * 128;
                float* bc = (float*)(sgen + SM_MRG + 4096);
                *(uint2*)&pre[eb * 32 + 2 * (lane & 15)] = make_uint2(pack_bf16(c1v[0], c1v[1]), pack_bf16(c1v[2], c1v[3]));
                *(uint2*)&pre[64 + eb * 32 + 2 * (lane & 15)] = make_uint2(m_sb.x, m_sb.z);
                __syncwarp();
                float yg[4] = {}, yu[4] = {};
                const uint32_t* pb = pre + ((g >> 1) & 1) * 64 + bb * 32 + t;
#pragma unroll
                for (int s = 0; s < 4; s++) {
                    const uint32_t b0 = pb[8 * s], b1 = pb[8 * s + 4];
                    mma16816(yg, gf[s], b0, b1);
                    mma16816(yu, uf[s], b0, b1);
                }
                const float y0 = t < 2 ? yg[0] : yu[0], y1 = t < 2 ? yg[1] : yu[1], y2 = t < 2 ? yg[2] : yu[2], y3 = t < 2 ? yg[3] : yu[3];
                float* dstp = bc + warp * 128 + (t >> 1) * 64 + (t & 1) * 32;
                *(float2*)&dstp[g * 2] = make_float2(y0, y1);
                *(float2*)&dstp[(g + 8) * 2] = make_float2(y2, y3);
                __syncwarp();
                if (lane == 0) mbar_arrive(bar_bc);
            }
            if (warp == 0) TSTAMP(11);
            float pivot2;
            {
                while (clock32() - t_wo < DELAY_X1) {}
                bool okx = false, okp = false;
                for (int it = 0;; it++) {
                    if (!okx) { va = ld_ll4(px); vb = ld_ll4(px + 1); }
                    if (!okp) { pa = ld_ll4(pp); pb = ld_ll4(pp + 1); }
                    okx = va.y == F_X1 && va.w == F_X1 && vb.y == F_X1 && vb.w == F_X1;
                    okp = pa.y == F_X1 && pa.w == F_X1 && pb.y == F_X1 && pb.w == F_X1;
                    if (__all_sync(0xffffffffu, okx && okp) || it > SPIN_LIMIT) break;
                }
                if (warp == 0) TSTAMP(9);
                const float xv[4] = {eb ? bf_hi(va.x) : bf_lo(va.x), eb ? bf_hi(va.z) : bf_lo(va.z),
                                     eb ? bf_hi(vb.x) : bf_lo(vb.x), eb ? bf_hi(vb.z) : bf_lo(vb.z)};
                const float p0 = 0.25f * ((bf_lo(pa.x) + bf_lo(pa.z)) + (bf_lo(pb.x) + bf_lo(pb.z)));
                const float p1 = 0.25f * ((bf_hi(pa.x) + bf_hi(pa.z)) + (bf_hi(pb.x) + bf_hi(pb.z)));
                const float pivot = eb ? p1 : p0;
                pivot2 = (lane & 1) ? p1 : p0;
                *(uint2*)&hs[eb * 32 + 2 * (lane & 15)] =
                    make_uint2(pack_bf16((xv[0] - pivot) * c1v[0], (xv[1] - pivot) * c1v[1]),
                               pack_bf16((xv[2] - pivot) * c1v[2], (xv[3] - pivot) * c1v[3]));
                __syncwarp();
                float cg[2][4] = {}, cu[2][4] = {};
#pragma unroll
                for (int s = 0; s < 4; s++) {
                    const uint32_t b0 = hs[bb * 32 + 8 * s + t], b1 = hs[bb * 32 + 8 * s + 4 + t];
                    mma16816(cg[s & 1], gf[s], b0, b1);
                    mma16816(cu[s & 1], uf[s], b0, b1);
                }
                const float2 ps = half_warp_sums(xv, pivot);
                if ((lane & 15) == 0) stat[warp * 2 + eb] = ps;
                {
                    const float* bc = (const float*)(sgen + SM_MRG + 4096);
                    mbar_wait(bar_bc, 0);
#pragma unroll
                    for (int w = 0; w < 8; w++) {
                        bg += bc[w * 128 + lane]; cgc += bc[w * 128 + 32 + lane];
                        bu += bc[w * 128 + 64 + lane]; cuc += bc[w * 128 + 96 + lane];
                    }
                }
                if (t < 2) {
                    float v[4];
#pragma unroll
                    for (int i = 0; i < 4; i++) v[i] = t ? cu[0][i] + cu[1][i] : cg[0][i] + cg[1][i];
                    *(float2*)&red[warp * 64 + t * 32 + g * 2] = make_float2(v[0], v[1]);
                    *(float2*)&red[warp * 64 + t * 32 + (g + 8) * 2] = make_float2(v[2], v[3]);
                }
            }
            uint32_t df[4][4];
            mbar_wait(bar_full + 8 * (IDX_WD % NST), (IDX_WD / NST) & 1);
#pragma unroll
            for (int mt = 0; mt < 4; mt++) ldsm4t((sbase + SM_RING + (IDX_WD % NST) * TILE + aoff) ^ (mt << 5), df[mt]);
            cons_sync();
            {
                float gs = 0.f, us = 0.f;
#pragma unroll
                for (int w = 0; w < 8; w++) { gs += red[w * 64 + lane]; us += red[w * 64 + 32 + lane]; }
                float mean_bf, rstd;
                ln_stats(stat, lane & 1, pivot2, mean_bf, rstd);
                const float dm = mean_bf - pivot2;
                gs = bf16r(rstd * (gs - dm * bg) + cgc);
                us = rstd * (us - dm * bu) + cuc;
                const float u2 = gs * (1.0f + 0.044715f * gs * gs) * (2.0f * 0.7978845608028654f * LOG2E);
                const float ge = bf16r(__fdividef(gs, 1.0f + ex2(-u2)));
                const float act = bf16r(ge * bf16r(us));
                const float a0 = __shfl_sync(0xffffffffu, act, 4 * t + bb), a1 = __shfl_sync(0xffffffffu, act, 4 * t + 2 + bb);
                const float a2 = __shfl_sync(0xffffffffu, act, 4 * t + 16 + bb), a3 = __shfl_sync(0xffffffffu, act, 4 * t + 18 + bb);
                const uint32_t b0 = pack_bf16(a0, a1), b1 = pack_bf16(a2, a3);
                float y[4][4] = {};
#pragma unroll
                for (int mt = 0; mt < 4; mt++) mma16816(y[mt], df[mt], b0, b1);
                float v[4];
#pragma unroll
                for (int i = 0; i < 4; i++) v[i] = t == 0 ? y[0][i] : t == 1 ? y[1][i] : t == 2 ? y[2][i] : y[3][i];
            {
                const bool odd = g & 1;
                const float sx = odd ? v[0] : v[2], sy = odd ? v[1] : v[3];
                const float rx = __shfl_xor_sync(0xffffffffu, sx, 4), ry = __shfl_xor_sync(0xffffffffu, sy, 4);
                const int c0 = 64 * warp + 16 * t + (odd ? g + 7 : g);
                const float e0 = odd ? rx : v[0], e1 = odd ? ry : v[1], e2 = odd ? v[2] : rx, e3 = odd ? v[3] : ry;
                st_v4(&sc->inbox_dn[c0 >> 2][cta][(c0 >> 1) & 1], tagf(e0, F_DOWN), tagf(e1, F_DOWN), tagf(e2, F_DOWN), tagf(e3, F_DOWN));
            }
            }
            if (warp == 0) TSTAMP(12);
        }
        {
            uint2 xw;
            float r0;
            {
                const uint4* pin = &sc->inbox_dn[cta][0][0] + tid;
                uint4 v = make_uint4(F_DOWN, F_DOWN, F_DOWN, F_DOWN);
                if (cta < NFFN) spin_cycles(DELAY_C);
                else while (clock32() - t_wo < DELAY_X1 + DELAY_NOFFN) {}
                xw = ld_ll2(&sc->x1[ocol]);
                bool ok = tid >= NFFN * 2;
                for (int it = 0;; it++) {
                    if (!ok) {
                        v = ld_ll4(pin);
                        ok = (v.x & v.y & v.z & v.w & 3u) == F_DOWN;
                    }
                    if (__all_sync(0xffffffffu, ok) || it > SPIN_LIMIT) break;
                }
                const bool u1 = lane & 2, u2 = lane & 4;
                const float a0 = untag(v.x), a1 = untag(v.y), a2 = untag(v.z), a3 = untag(v.w);
                const float k0 = (u1 ? a1 : a0) + __shfl_xor_sync(0xffffffffu, u1 ? a0 : a1, 2);
                const float k1 = (u1 ? a3 : a2) + __shfl_xor_sync(0xffffffffu, u1 ? a2 : a3, 2);
                r0 = (u2 ? k1 : k0) + __shfl_xor_sync(0xffffffffu, u2 ? k0 : k1, 4);
                r0 += __shfl_xor_sync(0xffffffffu, r0, 8);
                r0 += __shfl_xor_sync(0xffffffffu, r0, 16);
                if (lane < 8) red2[256 + warp * 8 + (2 * (lane & 1) + ((lane >> 2) & 1)) * 2 + ((lane >> 1) & 1)] = r0;
            }
            cons_sync();
            if (warp == 0) {
                float a0 = 0.f, a1 = 0.f;
#pragma unroll
                for (int w = 0; w < 8; w++) { const float2 v = *(const float2*)&red2[256 + w * 8 + (lane & 3) * 2]; a0 += v.x; a1 += v.y; }
                const bool hi = ocol & 1;
                const float gb0 = hi ? bf_hi(m_gb0.x) : bf_lo(m_gb0.x), gb1 = hi ? bf_hi(m_gb1.x) : bf_lo(m_gb1.x);
                for (int it = 0; !__all_sync(0xffffffffu, xw.y == F_X1) && it < SPIN_LIMIT; it++) xw = ld_ll2(&sc->x1[ocol]);
                if (lane < 4) {
                    p.out[ocol] = __float2bfloat16_rn(bf_lo(xw.x) + bf16r(gb0 * bf16r(a0)));
                    p.out[D_MODEL + ocol] = __float2bfloat16_rn(bf_hi(xw.x) + bf16r(gb1 * bf16r(a1)));
                }
                if (cta == 0 && lane == 0) *(volatile unsigned*)&sc->epoch = tag;
                TSTAMP(13);
            }
        }
    }
}

typedef CUresult (*EncodeFn)(CUtensorMap*, CUtensorMapDataType, cuuint32_t, void*, const cuuint64_t*, const cuuint64_t*,
                             const cuuint32_t*, const cuuint32_t*, CUtensorMapInterleave, CUtensorMapSwizzle,
                             CUtensorMapL2promotion, CUtensorMapFloatOOBfill);

struct Maps { CUtensorMap k, v, wq, wmod, wmod8, wo, wg, wu, wd; };

void encode(EncodeFn fn, CUtensorMap* m, const void* ptr, int rank, const cuuint64_t* dims, const cuuint64_t* strides,
            const cuuint32_t* box, CUtensorMapSwizzle sw) {
    const cuuint32_t es[3] = {1, 1, 1};
    fn(m, CU_TENSOR_MAP_DATA_TYPE_BFLOAT16, rank, const_cast<void*>(ptr), dims, strides, box, es,
       CU_TENSOR_MAP_INTERLEAVE_NONE, sw, CU_TENSOR_MAP_L2_PROMOTION_L2_256B, CU_TENSOR_MAP_FLOAT_OOB_FILL_NONE);
}

}

extern "C" void kernel_launch(void* const* d_in, const int* in_sizes, int n_in, void* d_out, int out_size) {
    (void)in_sizes; (void)n_in; (void)out_size;
    static EncodeFn enc = nullptr;
    static Scratch* scratch = nullptr;
    if (!enc) {
        cudaGetSymbolAddress((void**)&scratch, g_scratch);
        void* fn = nullptr;
        cudaDriverEntryPointQueryResult qr;
        cudaGetDriverEntryPoint("cuTensorMapEncodeTiled", &fn, cudaEnableDefault, &qr);
        enc = (EncodeFn)fn;
        cudaFuncSetAttribute(fused_block_kernel, cudaFuncAttributeMaxDynamicSharedMemorySize, SMEM_BYTES);
    }
    Maps m;
    {
        const cuuint64_t dims[3] = {64, (cuuint64_t)16 * SK, 2}, str[2] = {256, 128};
        const cuuint32_t box[3] = {64, 64, 2};
        encode(enc, &m.k, d_in[1], 3, dims, str, box, CU_TENSOR_MAP_SWIZZLE_128B);
        encode(enc, &m.v, d_in[2], 3, dims, str, box, CU_TENSOR_MAP_SWIZZLE_128B);
    }
    {
        const cuuint64_t dims[2] = {4096, 512}, str[1] = {8192};
        const cuuint32_t box[2] = {32, 256};
        encode(enc, &m.wq, d_in[3], 2, dims, str, box, CU_TENSOR_MAP_SWIZZLE_64B);
    }
    {
        const cuuint64_t dims[2] = {N_MOD, 512}, str[1] = {N_MOD * 2};
        const cuuint32_t box[2] = {16, 256};
        encode(enc, &m.wmod, d_in[10], 2, dims, str, box, CU_TENSOR_MAP_SWIZZLE_32B);
        const cuuint32_t box8[2] = {8, 256};
        encode(enc, &m.wmod8, d_in[10], 2, dims, str, box8, CU_TENSOR_MAP_SWIZZLE_NONE);
    }
    {
        const cuuint64_t dims_o[3] = {64, 4096, 8}, dims_d[3] = {64, D_FF, 8}, str[2] = {1024, 128};
        const cuuint32_t box[3] = {64, 16, 8}, box_o[3] = {64, 64, 2};
        encode(enc, &m.wo, d_in[4], 3, dims_o, str, box_o, CU_TENSOR_MAP_SWIZZLE_128B);
        encode(enc, &m.wd, d_in[8], 3, dims_d, str, box, CU_TENSOR_MAP_SWIZZLE_128B);
    }
    {
        const cuuint64_t dims[2] = {D_FF, 512}, str[1] = {D_FF * 2};
        const cuuint32_t box[2] = {16, 128};
        encode(enc, &m.wg, d_in[6], 2, dims, str, box, CU_TENSOR_MAP_SWIZZLE_32B);
        encode(enc, &m.wu, d_in[7], 2, dims, str, box, CU_TENSOR_MAP_SWIZZLE_32B);
    }
    Params p;
    p.x = (const __nv_bfloat16*)d_in[0];
    p.c = (const __nv_bfloat16*)d_in[9];
    p.out = (__nv_bfloat16*)d_out;
    p.sc = scratch;
    fused_block_kernel<<<NCTA, NTHREADS, SMEM_BYTES, cudaStreamPerThread>>>(p, m.k, m.v, m.wq, m.wmod, m.wmod8, m.wo, m.wg, m.wu, m.wd);
}
```

```cpp
#include <cuda_runtime.h>
#include <cuda.h>
#include <cuda_bf16.h>
#include <stdint.h>

namespace {

constexpr int D_MODEL = 512;
constexpr int N_HEADS = 32;
constexpr int SK = 32768;
constexpr int DH = 128;
constexpr int D_FF = 1792;
constexpr int N_MOD = 6 * D_MODEL;

constexpr int NCTA = 128;
constexpr int NFFN = D_FF / 16;
constexpr int NOWN = 32;
constexpr int NTHREADS = 320;
constexpr int NST = 12;
constexpr int TILE = 16384;
#define WINDOW 3
#define WINDOW_TAIL 1
#define GU_WIN 3
#define GU_EARLY 0
#define WD_WIN 2
#define PACE_THR 96
constexpr int KV_TILES = 64;
#define MOD_AT 8
static_assert(MOD_AT % 2 == 0 && MOD_AT >= 2 && MOD_AT < 56, "schedule");
__host__ __device__ constexpr int kv_idx(int i) { return 2 + 2 * i + (i >= MOD_AT ? 1 : 0); }
constexpr int IDX_MOD = 2 + 2 * MOD_AT;
constexpr int N_STREAM = kv_idx(KV_TILES - 1) + 2;
constexpr int IDX_WO = N_STREAM;
constexpr int IDX_WG = IDX_WO + 2;
constexpr int IDX_WU = IDX_WG + 1;
constexpr int IDX_WD = IDX_WU + 1;
constexpr int SPIN_LIMIT = 1 << 20;

constexpr float LOG2E = 1.4426950408889634f;
constexpr float QK_SCALE = 0.08838834764831845f;

constexpr int SM_RING = 0;
constexpr int SM_MRG = SM_RING + NST * TILE;
constexpr int SM_ML = SM_MRG + 8 * 4 * 136 * 4;
constexpr int SM_RED = SM_ML + 8 * 4 * 8;
constexpr int SM_RED2 = SM_RED + 8 * 64 * 4;
constexpr int SM_QS = SM_RED2 + 8 * 64 * 4;
constexpr int SM_OS = SM_QS + 512 * 2;
constexpr int SM_SC = SM_OS + 2 * 128 * 2;
constexpr int SM_HS = SM_SC + 2 * 512 * 2;
constexpr int SM_STAT = SM_HS + 8 * 2 * 32 * 4;
constexpr int SM_PACE = SM_STAT + 8 * 2 * 8;
constexpr int SM_BAR = SM_PACE + 8;
constexpr int SM_END = SM_BAR + (2 * NST + 1 + 8 + 2) * 8;
constexpr int SMEM_BYTES = SM_END + 1024;

struct Scratch {
    uint4 inbox_wo[NOWN][N_HEADS][8];
    uint4 inbox_dn[NCTA][NFFN][2];
    uint2 x1[D_MODEL];
    uint2 part_o[NCTA][4][64];
    uint2 part_ml[NCTA][4][4];
    uint2 mod[2][N_MOD / 2];
    uint2 q[2][N_HEADS * DH / 2];
    unsigned epoch;
    unsigned pad_[31];
    unsigned cleared;
    unsigned pad2_[31];
    unsigned progress;
};
__device__ Scratch g_scratch;
constexpr uint32_t F_PART = 1, F_WO = 1, F_DOWN = 1, F_X1 = 1;
__device__ __forceinline__ uint32_t tagf(float v, uint32_t f) { return (__float_as_uint(v) & ~3u) | f; }
__device__ __forceinline__ float untag(uint32_t v) { return __uint_as_float(v & ~3u); }

struct Params {
    const __nv_bfloat16* x;
    const __nv_bfloat16* c;
    __nv_bfloat16* out;
    Scratch* sc;
};

#define TSTAMP(i) do { } while (0)

__device__ __forceinline__ uint32_t smem_u32(const void* p) { return (uint32_t)__cvta_generic_to_shared(p); }

__device__ __forceinline__ void mbar_init(uint32_t bar, uint32_t cnt) {
    asm volatile("mbarrier.init.shared::cta.b64 [%0], %1;" ::"r"(bar), "r"(cnt) : "memory");
}
__device__ __forceinline__ void mbar_expect_tx(uint32_t bar, uint32_t bytes) {
    asm volatile("mbarrier.arrive.expect_tx.shared::cta.b64 _, [%0], %1;" ::"r"(bar), "r"(bytes) : "memory");
}
__device__ __forceinline__ void mbar_arrive(uint32_t bar) {
    asm volatile("mbarrier.arrive.shared::cta.b64 _, [%0];" ::"r"(bar) : "memory");
}
__device__ __forceinline__ bool mbar_try(uint32_t bar, uint32_t parity) {
    uint32_t ok;
    asm volatile(
        "{\n\t.reg .pred p;\n\t"
        "mbarrier.try_wait.parity.shared::cta.b64 p, [%1], %2;\n\t"
        "selp.u32 %0, 1, 0, p;\n\t}"
        : "=r"(ok) : "r"(bar), "r"(parity) : "memory");
    return ok != 0;
}
__device__ __forceinline__ void mbar_wait(uint32_t bar, uint32_t parity) {
    if (mbar_try(bar, parity)) return;
    const long long t0 = clock64();
    while (!mbar_try(bar, parity))
        if (clock64() - t0 > (1ll << 31)) return;
}
__device__ __forceinline__ void cons_sync() { asm volatile("bar.sync 1, 256;" ::: "memory"); }

__device__ __forceinline__ void tma_2d(uint32_t dst, const CUtensorMap* m, int c0, int c1, uint32_t bar) {
    asm volatile("cp.async.bulk.tensor.2d.shared::cluster.global.mbarrier::complete_tx::bytes [%0], [%1, {%3, %4}], [%2];"
                 ::"r"(dst), "l"(m), "r"(bar), "r"(c0), "r"(c1) : "memory");
}
__device__ __forceinline__ void tma_3d(uint32_t dst, const CUtensorMap* m, int c0, int c1, int c2, uint32_t bar) {
    asm volatile("cp.async.bulk.tensor.3d.shared::cluster.global.mbarrier::complete_tx::bytes [%0], [%1, {%3, %4, %5}], [%2];"
                 ::"r"(dst), "l"(m), "r"(bar), "r"(c0), "r"(c1), "r"(c2) : "memory");
}
__device__ __forceinline__ void tma_3d_hint(uint32_t dst, const CUtensorMap* m, int c0, int c1, int c2, uint32_t bar, uint64_t pol) {
    asm volatile("cp.async.bulk.tensor.3d.shared::cluster.global.mbarrier::complete_tx::bytes.L2::cache_hint [%0], [%1, {%3, %4, %5}], [%2], %6;"
                 ::"r"(dst), "l"(m), "r"(bar), "r"(c0), "r"(c1), "r"(c2), "l"(pol) : "memory");
}
__device__ __forceinline__ void prefetch_tmap(const CUtensorMap* m) {
    asm volatile("prefetch.tensormap [%0];" ::"l"(m) : "memory");
}

__device__ __forceinline__ void ldsm4(uint32_t addr, uint32_t (&r)[4]) {
    asm volatile("ldmatrix.sync.aligned.m8n8.x4.shared.b16 {%0,%1,%2,%3}, [%4];"
                 : "=r"(r[0]), "=r"(r[1]), "=r"(r[2]), "=r"(r[3]) : "r"(addr) : "memory");
}
__device__ __forceinline__ void ldsm4t(uint32_t addr, uint32_t (&r)[4]) {
    asm volatile("ldmatrix.sync.aligned.m8n8.x4.trans.shared.b16 {%0,%1,%2,%3}, [%4];"
                 : "=r"(r[0]), "=r"(r[1]), "=r"(r[2]), "=r"(r[3]) : "r"(addr) : "memory");
}
__device__ __forceinline__ void mma16816(float (&c)[4], const uint32_t (&a)[4], uint32_t b0, uint32_t b1) {
    asm volatile("mma.sync.aligned.m16n8k16.row.col.f32.bf16.bf16.f32 {%0,%1,%2,%3}, {%4,%5,%6,%7}, {%8,%9}, {%0,%1,%2,%3};"
                 : "+f"(c[0]), "+f"(c[1]), "+f"(c[2]), "+f"(c[3])
                 : "r"(a[0]), "r"(a[1]), "r"(a[2]), "r"(a[3]), "r"(b0), "r"(b1));
}
__device__ __forceinline__ uint32_t movmatrix_t(uint32_t a) {
    uint32_t d;
    asm volatile("movmatrix.sync.aligned.m8n8.trans.b16 %0, %1;" : "=r"(d) : "r"(a));
    return d;
}
__device__ __forceinline__ uint32_t pack_bf16(float a, float b) {
    uint32_t r;
    asm("cvt.rn.bf16x2.f32 %0, %1, %2;" : "=r"(r) : "f"(b), "f"(a));
    return r;
}
__device__ __forceinline__ float bf_lo(uint32_t v) { return __uint_as_float(v << 16); }
__device__ __forceinline__ float bf_hi(uint32_t v) { return __uint_as_float(v & 0xffff0000u); }
__device__ __forceinline__ float bf16r(float a) { return bf_lo(pack_bf16(a, 0.f)); }
__device__ __forceinline__ uint32_t max_bf16x2(uint32_t a, uint32_t b) {
    uint32_t r;
    asm("max.bf16x2 %0, %1, %2;" : "=r"(r) : "r"(a), "r"(b));
    return r;
}
__device__ __forceinline__ float ex2(float x) {
    float r;
    asm("ex2.approx.ftz.f32 %0, %1;" : "=f"(r) : "f"(x));
    return r;
}

__device__ __forceinline__ void st_ll2(uint2* p, uint32_t v, uint32_t tag) {
    asm volatile("st.relaxed.gpu.global.v2.u32 [%0], {%1, %2};" ::"l"(p), "r"(v), "r"(tag) : "memory");
}
__device__ __forceinline__ void st_ll4(uint4* p, uint32_t v0, uint32_t v1, uint32_t tag) {
    asm volatile("st.relaxed.gpu.global.v4.u32 [%0], {%1, %2, %3, %2};" ::"l"(p), "r"(v0), "r"(tag), "r"(v1) : "memory");
}
__device__ __forceinline__ void st_v4(uint4* p, uint32_t a, uint32_t b, uint32_t c, uint32_t d) {
    asm volatile("st.relaxed.gpu.global.v4.u32 [%0], {%1, %2, %3, %4};" ::"l"(p), "r"(a), "r"(b), "r"(c), "r"(d) : "memory");
}
__device__ __forceinline__ uint2 ld_ll2(const uint2* p) {
    uint2 v;
    asm volatile("ld.relaxed.gpu.global.v2.u32 {%0, %1}, [%2];" : "=r"(v.x), "=r"(v.y) : "l"(p) : "memory");
    return v;
}
__device__ __forceinline__ uint4 ld_ll4(const uint4* p) {
    uint4 v;
    asm volatile("ld.relaxed.gpu.global.v4.u32 {%0, %1, %2, %3}, [%4];"
                 : "=r"(v.x), "=r"(v.y), "=r"(v.z), "=r"(v.w) : "l"(p) : "memory");
    return v;
}

#define DELAY_B1 300
#define DELAY_X1 2000
#define DELAY_NOFFN 1500
#define A_BACKOFF 0
#define DELAY_C 600
__device__ __forceinline__ uint32_t clock32() {
    uint32_t c;
    asm volatile("mov.u32 %0, %clock;" : "=r"(c));
    return c;
}
__device__ __forceinline__ void spin_cycles(uint32_t n) {
    if (n > 0) { const uint32_t c0 = clock32(); while (clock32() - c0 < n) {} }
}
__device__ __forceinline__ float rcp_approx(float x) {
    float r;
    asm("rcp.approx.ftz.f32 %0, %1;" : "=f"(r) : "f"(x));
    return r;
}
__device__ __forceinline__ float sqrt_approx(float x) {
    float r;
    asm("sqrt.approx.f32 %0, %1;" : "=f"(r) : "f"(x));
    return r;
}

__device__ __forceinline__ float silu_bf(float v) { return bf16r(v / (1.0f + expf(-v))); }

__device__ __forceinline__ float2 half_warp_sums(const float (&v)[4], float pivot) {
    float s1 = 0.f, s2 = 0.f;
#pragma unroll
    for (int i = 0; i < 4; i++) { const float d = v[i] - pivot; s1 += d; s2 += d * d; }
#pragma unroll
    for (int o = 1; o < 16; o <<= 1) { s1 += __shfl_xor_sync(0xffffffffu, s1, o); s2 += __shfl_xor_sync(0xffffffffu, s2, o); }
    return make_float2(s1, s2);
}
__device__ __forceinline__ void ln_stats(const float2* stat, int b, float pivot, float& mean_bf, float& rstd) {
    float s1 = 0.f, s2 = 0.f;
#pragma unroll
    for (int w = 0; w < 8; w++) { const float2 v = stat[w * 2 + b]; s1 += v.x; s2 += v.y; }
    const float dm = s1 * (1.0f / D_MODEL);
    const float var = fmaxf(s2 * (1.0f / D_MODEL) - dm * dm, 0.f);
    mean_bf = bf16r(pivot + dm);
    rstd = rcp_approx(bf16r(sqrt_approx(bf16r(bf16r(var) + 1e-5f))));
}
__device__ __forceinline__ float ln_norm(float xv, float mean_bf, float rstd) { return bf16r(bf16r(xv - mean_bf) * rstd); }
__device__ __forceinline__ float ln_mod(float n, float cmul, float sadd) { return bf16r(n * bf16r(1.0f + cmul)) + sadd; }

__global__ void __launch_bounds__(NTHREADS, 1)
fused_block_kernel(const Params p, const __grid_constant__ CUtensorMap tm_k, const __grid_constant__ CUtensorMap tm_v,
                   const __grid_constant__ CUtensorMap tm_wq, const __grid_constant__ CUtensorMap tm_wmod,
                   const __grid_constant__ CUtensorMap tm_wmod8,
                   const __grid_constant__ CUtensorMap tm_wo, const __grid_constant__ CUtensorMap tm_wg,
                   const __grid_constant__ CUtensorMap tm_wu, const __grid_constant__ CUtensorMap tm_wd) {
    extern __shared__ unsigned char smem_raw[];
    const uint32_t sbase = (smem_u32(smem_raw) + 1023u) & ~1023u;
    unsigned char* sgen = smem_raw + (sbase - smem_u32(smem_raw));
    const int tid = threadIdx.x, warp = tid >> 5, lane = tid & 31;
    const int cta = blockIdx.x;
    const uint32_t bar_full = sbase + SM_BAR, bar_empty = bar_full + NST * 8;
    const uint32_t bar_clear = bar_empty + NST * 8;
    const uint32_t bar_gu = bar_clear + 8;
    const uint32_t bar_bc = bar_gu + 8 * 8;
    const uint32_t bar_p0w = bar_bc + 8;

    const int key0 = (cta >> 3) * SK + (cta & 7) * 64;
    uint64_t pol = 0;
    if (tid == 256) {
        asm volatile("createpolicy.fractional.L2::evict_first.b64 %0, 1.0;" : "=l"(pol));
        mbar_init(bar_p0w, 1);
#pragma unroll
        for (int i = 0; i < 4; i++) mbar_init(bar_full + 8 * i, 1);
        asm volatile("fence.mbarrier_init.release.cluster;" ::: "memory");
        mbar_expect_tx(bar_p0w, 8192);
        tma_2d(sbase + SM_MRG, &tm_wmod8, cta * 8, 0, bar_p0w);
        tma_2d(sbase + SM_MRG + 4096, &tm_wmod8, cta * 8, 256, bar_p0w);
#pragma unroll
        for (int i = 0; i < 4; i++) mbar_expect_tx(bar_full + 8 * i, TILE);
        tma_2d(sbase + SM_RING, &tm_wq, cta * 32, 0, bar_full);
        tma_2d(sbase + SM_RING + TILE, &tm_wq, cta * 32, 256, bar_full + 8);
        tma_3d_hint(sbase + SM_RING + 2 * TILE, &tm_k, 0, key0, 0, bar_full + 16, pol);
        tma_3d_hint(sbase + SM_RING + 3 * TILE, &tm_v, 0, key0, 0, bar_full + 24, pol);
    }

    if (warp == 8) {
        if (lane == 0) {
            for (int i = 0; i < NST; i++) { if (i >= 4) mbar_init(bar_full + 8 * i, 1); mbar_init(bar_empty + 8 * i, 4); }
            mbar_init(bar_clear, 1);
            for (int k = 0; k < 8; k++) mbar_init(bar_gu + 8 * k, 1);
            mbar_init(bar_bc, 8);
            ((volatile uint32_t*)(sgen + SM_PACE))[0] = 0;
            ((volatile uint32_t*)(sgen + SM_PACE))[1] = WINDOW;
            asm volatile("fence.mbarrier_init.release.cluster;" ::: "memory");
        }
        __syncwarp();
        asm volatile("bar.arrive 2, 320;" ::: "memory");
        asm volatile("bar.arrive 3, 64;" ::: "memory");
        if (lane == 0) {
            int slot = 4; uint32_t ph = 1;
            int landed = 0, wslot = 0; uint32_t wph = 0;
            int kv = 2;
            auto wait_window = [&](int idx, int window) {
                while (landed + window <= idx) {
                    mbar_wait(bar_full + 8 * wslot, wph);
                    if (++wslot == NST) { wslot = 0; wph ^= 1; }
                    landed++;
                }
            };
            volatile uint32_t* pace = (volatile uint32_t*)(sgen + SM_PACE);
            prefetch_tmap(&tm_wmod);
            pace[0] = 4;
            for (int idx = 4; idx < N_STREAM; idx++) {
                if (idx >= NST) mbar_wait(bar_empty + 8 * slot, ph);
                wait_window(idx, (int)pace[1]);
                if (idx == 12) { prefetch_tmap(&tm_wo); prefetch_tmap(&tm_wg); prefetch_tmap(&tm_wu); prefetch_tmap(&tm_wd); }
                const uint32_t fb = bar_full + 8 * slot, dst = sbase + SM_RING + slot * TILE;
                mbar_expect_tx(fb, TILE);
                if (idx == IDX_MOD) {
                    tma_2d(dst, &tm_wmod, 1024 + cta * 16, 0, fb);
                    tma_2d(dst + 8192, &tm_wmod, 1024 + cta * 16, 256, fb);
                } else {
                    tma_3d_hint(dst, (kv & 1) ? &tm_v : &tm_k, 0, key0 + (kv >> 1) * 512, 0, fb, pol);
                    kv++;
                }
                pace[0] = idx + 1;
                if (++slot == NST) { slot = 0; ph ^= 1; }
            }
            auto slot_free = [&](int idx) { mbar_wait(bar_empty + 8 * (idx % NST), ((idx / NST) & 1) ^ 1); };
#pragma unroll
            for (int s = 0; s < 2; s++) {
                const int idx = IDX_WO + s;
                slot_free(idx);
                wait_window(idx, WINDOW_TAIL);
                mbar_expect_tx(bar_full + 8 * (idx % NST), TILE);
                tma_3d(sbase + SM_RING + (idx % NST) * TILE, &tm_wo, 0, (cta >> 2) * 128 + s * 64, (cta & 3) * 2, bar_full + 8 * (idx % NST));
            }
            if (cta < NFFN) {
                slot_free(IDX_WG); slot_free(IDX_WU);
#pragma unroll
                for (int st = 0; st < 8; st++) {
                    if (st == GU_EARLY) {
                        mbar_wait(bar_full + 8 * (IDX_WO % NST), (IDX_WO / NST) & 1);
                        mbar_wait(bar_full + 8 * ((IDX_WO + 1) % NST), ((IDX_WO + 1) / NST) & 1);
                    }
                    if (st >= GU_WIN) mbar_wait(bar_gu + 8 * (st - GU_WIN), 0);
                    mbar_expect_tx(bar_gu + 8 * st, 4096);
                    tma_2d(sbase + SM_RING + (((st & 1) ? IDX_WU : IDX_WG) % NST) * TILE + (st >> 1) * 4096,
                           (st & 1) ? &tm_wu : &tm_wg, cta * 16, (st >> 1) * 128, bar_gu + 8 * st);
                }
                mbar_wait(bar_gu + 8 * (8 - WD_WIN), 0);
                slot_free(IDX_WD);
                mbar_expect_tx(bar_full + 8 * (IDX_WD % NST), TILE);
                tma_3d(sbase + SM_RING + (IDX_WD % NST) * TILE, &tm_wd, 0, cta * 16, 0, bar_full + 8 * (IDX_WD % NST));
            }
        }
    } else if (warp == 9) {
        Scratch* const sc = p.sc;
        const uint32_t tag = *(volatile unsigned*)&sc->epoch + 1;
        if (lane < 2) {
            st_ll4((uint4*)&sc->mod[lane][cta * 4], 0u, 0u, 0u);
            st_ll4((uint4*)&sc->mod[lane][cta * 4] + 1, 0u, 0u, 0u);
        }
        if (lane < 8) st_ll4((uint4*)&sc->mod[lane >> 2][512 + cta * 8] + (lane & 3), 0u, 0u, 0u);
        if (lane < 16) st_ll4((uint4*)&sc->q[lane >> 3][cta * 16] + (lane & 7), 0u, 0u, 0u);
        __syncwarp();
        asm volatile("bar.arrive 2, 320;" ::: "memory");
        asm volatile("bar.sync 3, 64;" ::: "memory");
#pragma unroll 4
        for (int i = 0; i < NFFN * 2 / 32; i++) st_v4(&sc->inbox_dn[cta][0][0] + i * 32 + lane, 0u, 0u, 0u, 0u);
        if (cta >= NCTA - NOWN) {
#pragma unroll 4
            for (int i = 0; i < 8; i++) st_v4(&sc->inbox_wo[cta - (NCTA - NOWN)][0][0] + i * 32 + lane, 0u, 0u, 0u, 0u);
            if (lane < 8) st_v4((uint4*)&sc->x1[(cta - (NCTA - NOWN)) * 16] + lane, 0u, 0u, 0u, 0u);
        }
#pragma unroll 4
        for (int i = 0; i < 4; i++) st_v4((uint4*)&sc->part_o[cta][0][0] + i * 32 + lane, 0u, 0u, 0u, 0u);
        if (lane < 8) st_v4((uint4*)&sc->part_ml[cta][0][0] + lane, 0u, 0u, 0u, 0u);
        if (cta == 0 && lane == 0) asm volatile("st.relaxed.gpu.global.u32 [%0], %1;" ::"l"(&sc->progress), "r"(0u) : "memory");
        asm volatile("fence.acq_rel.gpu;" ::: "memory");
        __syncwarp();
        if (lane == 0) {
            asm volatile("fence.acq_rel.gpu;" ::: "memory");
            asm volatile("red.relaxed.gpu.global.add.u32 [%0], %1;" ::"l"(&sc->cleared), "r"(1u) : "memory");
            const uint32_t target = tag * NCTA;
            for (int it = 0; it < SPIN_LIMIT; it++) {
                uint32_t v;
                asm volatile("ld.relaxed.gpu.global.u32 %0, [%1];" : "=r"(v) : "l"(&sc->cleared) : "memory");
                if ((int32_t)(v - target) >= 0) break;
                __nanosleep(500);
            }
            asm volatile("fence.acq_rel.gpu;" ::: "memory");
            mbar_arrive(bar_clear);
            volatile uint32_t* pace = (volatile uint32_t*)(sgen + SM_PACE);
            uint32_t posted = 0;
            for (int it = 0; it < SPIN_LIMIT; it++) {
                const uint32_t own = pace[0];
                if (own >= N_STREAM) break;
                if (own > posted) {
                    asm volatile("red.relaxed.gpu.global.add.u32 [%0], %1;" ::"l"(&sc->progress), "r"(own - posted) : "memory");
                    posted = own;
                }
                uint32_t v;
                asm volatile("ld.relaxed.gpu.global.u32 %0, [%1];" : "=r"(v) : "l"(&sc->progress) : "memory");
                const int diff = (int)v - (int)own * NCTA;
                pace[1] = diff > PACE_THR ? WINDOW + 1 : diff < -PACE_THR ? WINDOW - 1 : WINDOW;
                __nanosleep(200);
            }
        }
    } else {
        const int g = lane >> 2, t = lane & 3;
        const int bb = g & 1;
        const int eb = lane >> 4;
        const int ec = 64 * warp + 4 * (lane & 15);
        if (warp == 0) TSTAMP(0);
        Scratch* const sc = p.sc;
        const float c00 = __bfloat162float(p.c[tid]), c01 = __bfloat162float(p.c[tid + 256]);
        const float c10 = __bfloat162float(p.c[D_MODEL + tid]), c11 = __bfloat162float(p.c[D_MODEL + tid + 256]);
        const uint2 xe = __ldg((const uint2*)(p.x + eb * D_MODEL + ec));
        const float xpivot = __bfloat162float(p.x[eb * D_MODEL]);
        const uint32_t tag = *(volatile unsigned*)&sc->epoch + 1;
        const int ocol = cta * 4 + (lane & 3);
        const int wcol = (cta >= NCTA - NOWN ? cta - (NCTA - NOWN) : 0) * 16 + (lane & 15);
        const float xo = __bfloat162float(p.x[eb * D_MODEL + wcol]);

        float* red = (float*)(sgen + SM_RED);
        float* red2 = (float*)(sgen + SM_RED2);
        float2* stat = (float2*)(sgen + SM_STAT);
        uint32_t* hs = (uint32_t*)(sgen + SM_HS) + warp * 64;
        float xn[4];
        {
            float xv[4] = {bf_lo(xe.x), bf_hi(xe.x), bf_lo(xe.y), bf_hi(xe.y)};
            const float2 ps = half_warp_sums(xv, xpivot);
            if ((lane & 15) == 0) stat[warp * 2 + eb] = ps;
            const float s00 = silu_bf(c00), s01 = silu_bf(c01), s10 = silu_bf(c10), s11 = silu_bf(c11);
            __nv_bfloat16* scs = (__nv_bfloat16*)(sgen + SM_SC);
            scs[tid] = __float2bfloat16_rn(s00); scs[tid + 256] = __float2bfloat16_rn(s01);
            scs[512 + tid] = __float2bfloat16_rn(s10); scs[512 + tid + 256] = __float2bfloat16_rn(s11);
            asm volatile("bar.sync 2, 320;" ::: "memory");
            if (warp == 0) TSTAMP(23);
            float cp[4] = {0.f, 0.f, 0.f, 0.f};
            const uint32_t* sc32 = (const uint32_t*)(sgen + SM_SC) + bb * 256 + 32 * warp + t;
            mbar_wait(bar_p0w, 0);
#pragma unroll
            for (int s = 0; s < 4; s++) {
                uint32_t r0, r1;
                asm volatile("ldmatrix.sync.aligned.m8n8.x2.trans.shared.b16 {%0,%1}, [%2];"
                             : "=r"(r0), "=r"(r1) : "r"(sbase + SM_MRG + (64 * warp + 16 * s + (lane & 15)) * 16) : "memory");
                const uint32_t a[4] = {r0, r0, r1, r1};
                mma16816(cp, a, sc32[8 * s], sc32[8 * s + 4]);
            }
            if (t == 0) { red[warp * 16 + g] = cp[0]; red[warp * 16 + 8 + g] = cp[1]; }
            if (warp == 0) TSTAMP(14);
            cons_sync();
            if (warp == 0) {
                float s = 0.f;
#pragma unroll
                for (int w = 0; w < 8; w++) s += red[w * 16 + (lane & 15)];
                const float nx = __shfl_down_sync(0xffffffffu, s, 1);
                if (lane < 16 && !(lane & 1))
                    st_ll2(&sc->mod[lane >> 3][cta * 4 + ((lane & 7) >> 1)], pack_bf16(s, nx), tag);
                TSTAMP(1);
            }
            float mean_bf, rstd;
            ln_stats(stat, eb, xpivot, mean_bf, rstd);
#pragma unroll
            for (int i = 0; i < 4; i++) xn[i] = ln_norm(xv[i], mean_bf, rstd);
        }
        {
            uint4 sa, ca;
            for (int it = 0;; it++) {
                sa = ld_ll4((const uint4*)&sc->mod[eb][ec >> 1]);
                ca = ld_ll4((const uint4*)&sc->mod[eb][256 + (ec >> 1)]);
                const bool ok = sa.y == tag && sa.w == tag && ca.y == tag && ca.w == tag;
                if (__all_sync(0xffffffffu, ok) || it > SPIN_LIMIT) break;
            }
            *(uint2*)&hs[eb * 32 + 2 * (lane & 15)] =
                make_uint2(pack_bf16(ln_mod(xn[0], bf_lo(ca.x), bf_lo(sa.x)), ln_mod(xn[1], bf_hi(ca.x), bf_hi(sa.x))),
                           pack_bf16(ln_mod(xn[2], bf_lo(ca.z), bf_lo(sa.z)), ln_mod(xn[3], bf_hi(ca.z), bf_hi(sa.z))));
            __syncwarp();
            uint32_t hb[8];
#pragma unroll
            for (int i = 0; i < 8; i++) hb[i] = hs[bb * 32 + 8 * (i >> 1) + 4 * (i & 1) + t];
            if (warp == 0) TSTAMP(2);
            float cq[2][4] = {};
            const int ts = warp >> 2;
            mbar_wait(bar_full + 8 * ts, 0);
            const uint32_t tb = sbase + SM_RING + ts * TILE;
#pragma unroll
            for (int s = 0; s < 4; s++) {
                const int row = 64 * (warp & 3) + 16 * s + (lane & 7) + (lane >> 4) * 8;
#pragma unroll
                for (int mt = 0; mt < 2; mt++) {
                    const int ch = 2 * mt + ((lane >> 3) & 1);
                    uint32_t a[4];
                    ldsm4t(tb + row * 64 + ((ch ^ ((row >> 1) & 3)) << 4), a);
                    mma16816(cq[mt], a, hb[2 * s], hb[2 * s + 1]);
                }
            }
            if (t < 2) {
                const float v0 = t == 0 ? cq[0][0] : cq[1][0], v1 = t == 0 ? cq[0][1] : cq[1][1];
                const float v2 = t == 0 ? cq[0][2] : cq[1][2], v3 = t == 0 ? cq[0][3] : cq[1][3];
                *(float2*)&red2[warp * 64 + (16 * t + g) * 2] = make_float2(v0, v1);
                *(float2*)&red2[warp * 64 + (16 * t + g + 8) * 2] = make_float2(v2, v3);
            }
            cons_sync();
            if (warp < 4 && lane == 0) { mbar_arrive(bar_empty); mbar_arrive(bar_empty + 8); }
            if (warp == 0) {
                const int b = lane >> 4, cp = lane & 15;
                float q0 = 0.f, q1 = 0.f;
#pragma unroll
                for (int w = 0; w < 8; w++) {
                    const float4 v = *(const float4*)&red2[w * 64 + cp * 4];
                    q0 += b ? v.y : v.x; q1 += b ? v.w : v.z;
                }
                st_ll2(&sc->q[b][cta * 16 + cp], pack_bf16(q0, q1), tag);
                TSTAMP(3);
            }
        }
        const int pair = cta >> 3;
        uint32_t qf[16];
        {
            uint2* qs = (uint2*)(sgen + SM_QS);
            if (tid < 128) {
                const uint4* src = (const uint4*)&sc->q[pair >> 3][(pair & 7) * 256] + tid;
                uint4 v;
                for (int it = 0;; it++) {
                    v = ld_ll4(src);
                    if ((v.y == tag && v.w == tag) || it > SPIN_LIMIT) break;
                }
                qs[tid] = make_uint2(v.x, v.z);
            }
            cons_sync();
            const uint32_t* q32 = (const uint32_t*)(sgen + SM_QS);
#pragma unroll
            for (int s = 0; s < 8; s++) {
                qf[2 * s] = q32[(g & 3) * 64 + 8 * s + t];
                qf[2 * s + 1] = q32[(g & 3) * 64 + 8 * s + 4 + t];
            }
        }
        if (warp == 0) TSTAMP(4);

        float o[8][4];
#pragma unroll
        for (int i = 0; i < 8; i++) { o[i][0] = o[i][1] = o[i][2] = o[i][3] = 0.f; }
        uint32_t mrun = 0xff80ff80u;
        float ls[4] = {0.f, 0.f, 0.f, 0.f};
        uint4 m_sb, m_cb; uint2 m_ga, m_gb0, m_gb1;
        {
            const int grp = warp >> 2, wi = warp & 3;
            const int krow = 16 * wi + (lane & 7) + ((lane >> 3) & 1) * 8;
            const uint32_t koff = krow * 128 + ((((lane >> 4) & 1) ^ (lane & 7)) << 4);
            const int vrow = 16 * wi + (lane & 7) + (lane >> 4) * 8;
            const uint32_t voff = vrow * 128 + ((((lane >> 3) & 1) ^ (lane & 7)) << 4);
            const uint32_t ones[4] = {0x3f803f80u, 0x3f803f80u, 0x3f803f80u, 0x3f803f80u};
            for (int i = grp; i < KV_TILES; i += 2) {
                if (i == MOD_AT + grp) {
                    float cm[4] = {};
                    const uint32_t* sc32 = (const uint32_t*)(sgen + SM_SC) + bb * 256 + 32 * warp + t;
                    mbar_wait(bar_full + 8 * (IDX_MOD % NST), (IDX_MOD / NST) & 1);
                    const uint32_t tb = sbase + SM_RING + (IDX_MOD % NST) * TILE;
#pragma unroll
                    for (int s = 0; s < 4; s++) {
                        const int row = 64 * warp + 16 * s + (lane & 7) + (lane >> 4) * 8;
                        const int ch = (lane >> 3) & 1;
                        uint32_t a[4];
                        ldsm4t(tb + row * 32 + ((ch ^ ((row >> 2) & 1)) << 4), a);
                        mma16816(cm, a, sc32[8 * s], sc32[8 * s + 4]);
                    }
                    if (t == 0) {
                        *(float2*)&red[warp * 64 + g * 2] = make_float2(cm[0], cm[1]);
                        *(float2*)&red[warp * 64 + (g + 8) * 2] = make_float2(cm[2], cm[3]);
                    }
                    cons_sync();
                    if (warp < 4 && lane == 0) mbar_arrive(bar_empty + 8 * (IDX_MOD % NST));
                    if (warp == 1 && lane < 16) {
                        const int b = lane >> 3, cp = lane & 7;
                        float q0 = 0.f, q1 = 0.f;
#pragma unroll
                        for (int w = 0; w < 8; w++) {
                            const float4 v = *(const float4*)&red[w * 64 + cp * 4];
                            q0 += b ? v.y : v.x; q1 += b ? v.w : v.z;
                        }
                        st_ll2(&sc->mod[b][512 + cta * 8 + cp], pack_bf16(q0, q1), tag);
                    }
                }
                if (i == 56 + grp) {
                    m_sb = ld_ll4((const uint4*)&sc->mod[eb][768 + (ec >> 1)]);
                    m_cb = ld_ll4((const uint4*)&sc->mod[eb][1024 + (ec >> 1)]);
                    m_ga = ld_ll2(&sc->mod[eb][512 + (wcol >> 1)]);
                    m_gb0 = ld_ll2(&sc->mod[0][1280 + (ocol >> 1)]); m_gb1 = ld_ll2(&sc->mod[1][1280 + (ocol >> 1)]);
                }
                if (i == 60 + grp) {
                    for (int it = 0;; it++) {
                        const bool ok = m_sb.y == tag && m_sb.w == tag && m_cb.y == tag && m_cb.w == tag &&
                                        m_ga.y == tag && m_gb0.y == tag && m_gb1.y == tag;
                        if (__all_sync(0xffffffffu, ok) || it > SPIN_LIMIT) break;
                        m_sb = ld_ll4((const uint4*)&sc->mod[eb][768 + (ec >> 1)]);
                        m_cb = ld_ll4((const uint4*)&sc->mod[eb][1024 + (ec >> 1)]);
                        m_ga = ld_ll2(&sc->mod[eb][512 + (wcol >> 1)]);
                        m_gb0 = ld_ll2(&sc->mod[0][1280 + (ocol >> 1)]); m_gb1 = ld_ll2(&sc->mod[1][1280 + (ocol >> 1)]);
                    }
                    mbar_wait(bar_clear, 0);
                }
                const int ki = kv_idx(i), ks = ki % NST, vs = (ki + 1) % NST;
                const uint32_t kph = (ki / NST) & 1, vph = ((ki + 1) / NST) & 1;
                mbar_wait(bar_full + 8 * ks, kph);
                const uint32_t kb = sbase + SM_RING + ks * TILE + koff;
                float sa[4] = {0.f, 0.f, 0.f, 0.f}, sb[4] = {0.f, 0.f, 0.f, 0.f};
#pragma unroll
                for (int s = 0; s < 8; s += 2) {
                    uint32_t a0[4], a1[4];
                    ldsm4((kb ^ ((s & 3) << 5)) + (s >> 2) * 8192, a0);
                    ldsm4((kb ^ (((s + 1) & 3) << 5)) + (s >> 2) * 8192, a1);
                    mma16816(sa, a0, qf[2 * s], qf[2 * s + 1]);
                    mma16816(sb, a1, qf[2 * s + 2], qf[2 * s + 3]);
                }
                __syncwarp();
                if (lane == 0) mbar_arrive(bar_empty + 8 * ks);
                uint32_t r01 = pack_bf16(sa[0] + sb[0], sa[1] + sb[1]);
                uint32_t r23 = pack_bf16(sa[2] + sb[2], sa[3] + sb[3]);
                r01 = pack_bf16(bf_lo(r01) * QK_SCALE, bf_hi(r01) * QK_SCALE);
                r23 = pack_bf16(bf_lo(r23) * QK_SCALE, bf_hi(r23) * QK_SCALE);
                uint32_t mx = max_bf16x2(r01, r23);
                mx = max_bf16x2(mx, __shfl_xor_sync(0xffffffffu, mx, 4));
                mx = max_bf16x2(mx, __shfl_xor_sync(0xffffffffu, mx, 8));
                mx = max_bf16x2(mx, __shfl_xor_sync(0xffffffffu, mx, 16));
                const uint32_t mnew = max_bf16x2(mrun, mx);
                const float m0 = bf_lo(mnew), m1 = bf_hi(mnew);
                if (__any_sync(0xffffffffu, mnew != mrun)) {
                    const float al0 = ex2((bf_lo(mrun) - m0) * LOG2E), al1 = ex2((bf_hi(mrun) - m1) * LOG2E);
                    ls[0] *= al0; ls[1] *= al1;
#pragma unroll
                    for (int d = 0; d < 8; d++) { o[d][0] *= al0; o[d][1] *= al1; o[d][2] *= al0; o[d][3] *= al1; }
                    mrun = mnew;
                }
                const float p0 = ex2((bf_lo(r01) - m0) * LOG2E), p1 = ex2((bf_hi(r01) - m1) * LOG2E);
                const float p2 = ex2((bf_lo(r23) - m0) * LOG2E), p3 = ex2((bf_hi(r23) - m1) * LOG2E);
                const uint32_t pb0 = movmatrix_t(pack_bf16(p0, p1)), pb1 = movmatrix_t(pack_bf16(p2, p3));
                mma16816(ls, ones, pb0, pb1);
                mbar_wait(bar_full + 8 * vs, vph);
                const uint32_t vb = sbase + SM_RING + vs * TILE + voff;
#pragma unroll
                for (int d = 0; d < 8; d++) {
                    uint32_t a[4];
                    ldsm4t((vb ^ ((d & 3) << 5)) + (d >> 2) * 8192, a);
                    mma16816(o[d], a, pb0, pb1);
                }
                __syncwarp();
                if (lane == 0) mbar_arrive(bar_empty + 8 * vs);
            }
        }
        if (warp == 7) TSTAMP(5);
        {
            float* mrg = (float*)(sgen + SM_MRG);
            float2* ml = (float2*)(sgen + SM_ML);
            {
                const int hp = (t & 1) * 2, up = t >> 1;
                if (g == 0 && up == 0) { ml[warp * 4 + hp] = make_float2(bf_lo(mrun), ls[0]); ml[warp * 4 + hp + 1] = make_float2(bf_hi(mrun), ls[1]); }
                float* m0p = mrg + (warp * 4 + hp) * 136 + up * 72 + g;
#pragma unroll
                for (int d = 0; d < 4; d++) {
                    m0p[16 * d] = up ? o[d + 4][0] : o[d][0]; m0p[136 + 16 * d] = up ? o[d + 4][1] : o[d][1];
                    m0p[16 * d + 8] = up ? o[d + 4][2] : o[d][2]; m0p[136 + 16 * d + 8] = up ? o[d + 4][3] : o[d][3];
                }
            }
            cons_sync();
            const int hh = tid >> 6, dp = tid & 63;
            float2 mw[8];
            float M = -INFINITY;
#pragma unroll
            for (int w = 0; w < 8; w++) { mw[w] = ml[w * 4 + hh]; M = fmaxf(M, mw[w].x); }
            float L = 0.f, o0 = 0.f, o1 = 0.f;
#pragma unroll
            for (int w = 0; w < 8; w++) {
                const float wt = ex2((mw[w].x - M) * LOG2E);
                const float2 v = *(const float2*)&mrg[(w * 4 + hh) * 136 + 2 * dp + (dp >= 32 ? 8 : 0)];
                L += wt * mw[w].y; o0 += wt * v.x; o1 += wt * v.y;
            }
            st_ll2(&sc->part_o[cta][hh][dp], tagf(o0, F_PART), tagf(o1, F_PART));
            if (dp < 4) st_ll2(&sc->part_ml[cta][hh][dp], tagf(M, F_PART), tagf(L, F_PART));
        }
        if (warp == 0) TSTAMP(6);
        {
            const int hq = cta >> 2, kvh = hq >> 2, hh = hq & 3;
            const int b = tid >> 7, dc = (tid >> 3) & 15, j = tid & 7;
            const int pc = (b * 8 + kvh) * 8 + j;
            const uint4* po = (const uint4*)&sc->part_o[pc][hh][0] + dc * 2;
            const uint2* pm = &sc->part_ml[pc - j][hh][0];
            uint4 vo0, vo1; uint2 vm[8];
            bool oko = false, okm = false;
            for (int it = 0;; it++) {
                if (!oko) { vo0 = ld_ll4(po); vo1 = ld_ll4(po + 1); }
                if (!okm) {
#pragma unroll
                    for (int jj = 0; jj < 8; jj++) vm[jj] = ld_ll2(pm + jj * 16);
                }
                oko = (vo0.x & vo0.y & vo0.z & vo0.w & vo1.x & vo1.y & vo1.z & vo1.w & 3u) == F_PART;
                uint32_t all = vm[0].x & vm[0].y;
#pragma unroll
                for (int jj = 1; jj < 8; jj++) all &= vm[jj].x & vm[jj].y;
                okm = (all & 3u) == F_PART;
                if (__all_sync(0xffffffffu, oko && okm) || it > SPIN_LIMIT) break;
                spin_cycles(A_BACKOFF);
            }
            float M = untag(vm[0].x);
#pragma unroll
            for (int jj = 1; jj < 8; jj++) M = fmaxf(M, untag(vm[jj].x));
            float wt = 0.f, L = 0.f;
#pragma unroll
            for (int jj = 0; jj < 8; jj++) {
                const float w_ = ex2((untag(vm[jj].x) - M) * LOG2E);
                L += w_ * untag(vm[jj].y);
                wt = jj == j ? w_ : wt;
            }
            wt *= rcp_approx(L);
            float v[8] = {wt * untag(vo0.x), wt * untag(vo0.y), wt * untag(vo0.z), wt * untag(vo0.w),
                          wt * untag(vo1.x), wt * untag(vo1.y), wt * untag(vo1.z), wt * untag(vo1.w)};
#define XRED(N, O)                                                                       \
            {                                                                            \
                const bool up = lane & (O);                                              \
                _Pragma("unroll") for (int i = 0; i < (N); i++) {                        \
                    const float send = up ? v[i] : v[i + (N)], keep = up ? v[i + (N)] : v[i]; \
                    v[i] = keep + __shfl_xor_sync(0xffffffffu, send, (O));               \
                }                                                                        \
            }
            XRED(4, 1) XRED(2, 2) XRED(1, 4)
#undef XRED
            __nv_bfloat16* os = (__nv_bfloat16*)(sgen + SM_OS);
            os[b * 128 + dc * 8 + 4 * (j & 1) + 2 * ((j >> 1) & 1) + (j >> 2)] = __float2bfloat16_rn(v[0]);
            if (warp == 0) TSTAMP(15);
            uint32_t wf[8][4];
            const uint32_t aoff_o = (warp >> 2) * 8192 + ((lane & 7) + (lane >> 4) * 8) * 128 +
                                    (((((warp & 3) * 2 + ((lane >> 3) & 1)) ^ (lane & 7))) << 4);
#pragma unroll
            for (int s = 0; s < 2; s++) {
                const int idx = IDX_WO + s;
                mbar_wait(bar_full + 8 * (idx % NST), (idx / NST) & 1);
                const uint32_t tb = sbase + SM_RING + (idx % NST) * TILE + aoff_o;
#pragma unroll
                for (int k4 = 0; k4 < 4; k4++) ldsm4t(tb + k4 * 2048, wf[s * 4 + k4]);
            }
            cons_sync();
            if (warp == 0) TSTAMP(7);
            const uint32_t* os32 = (const uint32_t*)(sgen + SM_OS) + bb * 64 + t;
            float y0[4] = {}, y1[4] = {};
#pragma unroll
            for (int ks = 0; ks < 8; ks += 2) {
                mma16816(y0, wf[ks], os32[8 * ks], os32[8 * ks + 4]);
                mma16816(y1, wf[ks + 1], os32[8 * ks + 8], os32[8 * ks + 12]);
            }
            if (t == 0)
                st_v4(&sc->inbox_wo[(cta & 3) * 8 + warp][hq][g], tagf(y0[0] + y1[0], F_WO), tagf(y0[1] + y1[1], F_WO),
                      tagf(y0[2] + y1[2], F_WO), tagf(y0[3] + y1[3], F_WO));
        }
        const uint32_t t_wo = clock32();
        if (warp == 0) TSTAMP(8);
        if (cta >= NCTA - NOWN) {
            const uint4* pin = &sc->inbox_wo[cta - (NCTA - NOWN)][0][0] + tid;
            uint4 v;
            spin_cycles(DELAY_B1);
            bool ok = false;
            for (int it = 0;; it++) {
                if (!ok) {
                    v = ld_ll4(pin);
                    ok = (v.x & v.y & v.z & v.w & 3u) == F_WO;
                }
                if (__all_sync(0xffffffffu, ok) || it > SPIN_LIMIT) break;
            }
            const bool u1 = lane & 8, u2 = lane & 16;
            const float a0 = untag(v.x), a1 = untag(v.y), a2 = untag(v.z), a3 = untag(v.w);
            const float k0 = (u1 ? a2 : a0) + __shfl_xor_sync(0xffffffffu, u1 ? a0 : a2, 8);
            const float k1 = (u1 ? a3 : a1) + __shfl_xor_sync(0xffffffffu, u1 ? a1 : a3, 8);
            red2[warp * 32 + lane] = (u2 ? k1 : k0) + __shfl_xor_sync(0xffffffffu, u2 ? k0 : k1, 16);
            cons_sync();
            if (warp == 0) {
                float a = 0.f;
#pragma unroll
                for (int w = 0; w < 8; w++) a += red2[w * 32 + lane];
                const float ga = (wcol & 1) ? bf_hi(m_ga.x) : bf_lo(m_ga.x);
                const float xm = bf16r(xo + bf16r(ga * bf16r(a)));
                const float xm_b1 = __shfl_down_sync(0xffffffffu, xm, 16);
                if (lane < 16) st_ll2(&sc->x1[wcol], pack_bf16(xm, xm_b1), F_X1);
                TSTAMP(10);
            }
        }
        const uint32_t aoff = warp * 2048 + ((lane & 7) + (lane >> 4) * 8) * 128 + ((((lane >> 3) & 1) ^ (lane & 7)) << 4);
        if (cta < NFFN) {
            const uint4* px = (const uint4*)&sc->x1[ec];
            const uint4* pp = (const uint4*)&sc->x1[0];
            uint4 va, vb, pa, pb;
            uint32_t gf[4][4], uf[4][4];
            mbar_wait(bar_gu + 8 * (2 * (warp >> 1)), 0);
            mbar_wait(bar_gu + 8 * (2 * (warp >> 1) + 1), 0);
            {
                const uint32_t tg = sbase + SM_RING + (IDX_WG % NST) * TILE, tu = sbase + SM_RING + (IDX_WU % NST) * TILE;
#pragma unroll
                for (int s = 0; s < 4; s++) {
                    const int row = 64 * warp + 16 * s + (lane & 7) + (lane >> 4) * 8;
                    const uint32_t off = row * 32 + ((((lane >> 3) & 1) ^ ((row >> 2) & 1)) << 4);
                    ldsm4t(tg + off, gf[s]);
                    ldsm4t(tu + off, uf[s]);
                }
            }
            const float c1v[4] = {bf16r(1.0f + bf_lo(m_cb.x)), bf16r(1.0f + bf_hi(m_cb.x)), bf16r(1.0f + bf_lo(m_cb.z)), bf16r(1.0f + bf_hi(m_cb.z))};
            float bg = 0.f, cgc = 0.f, bu = 0.f, cuc = 0.f;
            {
                uint32_t* pre = (uint32_t*)(sgen + SM_MRG) + warp * 128;
                float* bc = (float*)(sgen + SM_MRG + 4096);
                *(uint2*)&pre[eb * 32 + 2 * (lane & 15)] = make_uint2(pack_bf16(c1v[0], c1v[1]), pack_bf16(c1v[2], c1v[3]));
                *(uint2*)&pre[64 + eb * 32 + 2 * (lane & 15)] = make_uint2(m_sb.x, m_sb.z);
                __syncwarp();
                float yg[4] = {}, yu[4] = {};
                const uint32_t* pb = pre + ((g >> 1) & 1) * 64 + bb * 32 + t;
#pragma unroll
                for (int s = 0; s < 4; s++) {
                    const uint32_t b0 = pb[8 * s], b1 = pb[8 * s + 4];
                    mma16816(yg, gf[s], b0, b1);
                    mma16816(yu, uf[s], b0, b1);
                }
                const float y0 = t < 2 ? yg[0] : yu[0], y1 = t < 2 ? yg[1] : yu[1], y2 = t < 2 ? yg[2] : yu[2], y3 = t < 2 ? yg[3] : yu[3];
                float* dstp = bc + warp * 128 + (t >> 1) * 64 + (t & 1) * 32;
                *(float2*)&dstp[g * 2] = make_float2(y0, y1);
                *(float2*)&dstp[(g + 8) * 2] = make_float2(y2, y3);
                __syncwarp();
                if (lane == 0) mbar_arrive(bar_bc);
            }
            if (warp == 0) TSTAMP(11);
            float pivot2;
            {
                while (clock32() - t_wo < DELAY_X1) {}
                bool okx = false, okp = false;
                for (int it = 0;; it++) {
                    if (!okx) { va = ld_ll4(px); vb = ld_ll4(px + 1); }
                    if (!okp) { pa = ld_ll4(pp); pb = ld_ll4(pp + 1); }
                    okx = va.y == F_X1 && va.w == F_X1 && vb.y == F_X1 && vb.w == F_X1;
                    okp = pa.y == F_X1 && pa.w == F_X1 && pb.y == F_X1 && pb.w == F_X1;
                    if (__all_sync(0xffffffffu, okx && okp) || it > SPIN_LIMIT) break;
                }
                if (warp == 0) TSTAMP(9);
                const float xv[4] = {eb ? bf_hi(va.x) : bf_lo(va.x), eb ? bf_hi(va.z) : bf_lo(va.z),
                                     eb ? bf_hi(vb.x) : bf_lo(vb.x), eb ? bf_hi(vb.z) : bf_lo(vb.z)};
                const float p0 = 0.25f * ((bf_lo(pa.x) + bf_lo(pa.z)) + (bf_lo(pb.x) + bf_lo(pb.z)));
                const float p1 = 0.25f * ((bf_hi(pa.x) + bf_hi(pa.z)) + (bf_hi(pb.x) + bf_hi(pb.z)));
                const float pivot = eb ? p1 : p0;
                pivot2 = (lane & 1) ? p1 : p0;
                *(uint2*)&hs[eb * 32 + 2 * (lane & 15)] =
                    make_uint2(pack_bf16((xv[0] - pivot) * c1v[0], (xv[1] - pivot) * c1v[1]),
                               pack_bf16((xv[2] - pivot) * c1v[2], (xv[3] - pivot) * c1v[3]));
                __syncwarp();
                float cg[2][4] = {}, cu[2][4] = {};
#pragma unroll
                for (int s = 0; s < 4; s++) {
                    const uint32_t b0 = hs[bb * 32 + 8 * s + t], b1 = hs[bb * 32 + 8 * s + 4 + t];
                    mma16816(cg[s & 1], gf[s], b0, b1);
                    mma16816(cu[s & 1], uf[s], b0, b1);
                }
                const float2 ps = half_warp_sums(xv, pivot);
                if ((lane & 15) == 0) stat[warp * 2 + eb] = ps;
                {
                    const float* bc = (const float*)(sgen + SM_MRG + 4096);
                    mbar_wait(bar_bc, 0);
#pragma unroll
                    for (int w = 0; w < 8; w++) {
                        bg += bc[w * 128 + lane]; cgc += bc[w * 128 + 32 + lane];
                        bu += bc[w * 128 + 64 + lane]; cuc += bc[w * 128 + 96 + lane];
                    }
                }
                if (t < 2) {
                    float v[4];
#pragma unroll
                    for (int i = 0; i < 4; i++) v[i] = t ? cu[0][i] + cu[1][i] : cg[0][i] + cg[1][i];
                    *(float2*)&red[warp * 64 + t * 32 + g * 2] = make_float2(v[0], v[1]);
                    *(float2*)&red[warp * 64 + t * 32 + (g + 8) * 2] = make_float2(v[2], v[3]);
                }
            }
            uint32_t df[4][4];
            mbar_wait(bar_full + 8 * (IDX_WD % NST), (IDX_WD / NST) & 1);
#pragma unroll
            for (int mt = 0; mt < 4; mt++) ldsm4t((sbase + SM_RING + (IDX_WD % NST) * TILE + aoff) ^ (mt << 5), df[mt]);
            cons_sync();
            {
                float gs = 0.f, us = 0.f;
#pragma unroll
                for (int w = 0; w < 8; w++) { gs += red[w * 64 + lane]; us += red[w * 64 + 32 + lane]; }
                float mean_bf, rstd;
                ln_stats(stat, lane & 1, pivot2, mean_bf, rstd);
                const float dm = mean_bf - pivot2;
                gs = bf16r(rstd * (gs - dm * bg) + cgc);
                us = rstd * (us - dm * bu) + cuc;
                const float u2 = gs * (1.0f + 0.044715f * gs * gs) * (2.0f * 0.7978845608028654f * LOG2E);
                const float ge = bf16r(__fdividef(gs, 1.0f + ex2(-u2)));
                const float act = bf16r(ge * bf16r(us));
                const float a0 = __shfl_sync(0xffffffffu, act, 4 * t + bb), a1 = __shfl_sync(0xffffffffu, act, 4 * t + 2 + bb);
                const float a2 = __shfl_sync(0xffffffffu, act, 4 * t + 16 + bb), a3 = __shfl_sync(0xffffffffu, act, 4 * t + 18 + bb);
                const uint32_t b0 = pack_bf16(a0, a1), b1 = pack_bf16(a2, a3);
                float y[4][4] = {};
#pragma unroll
                for (int mt = 0; mt < 4; mt++) mma16816(y[mt], df[mt], b0, b1);
                float v[4];
#pragma unroll
                for (int i = 0; i < 4; i++) v[i] = t == 0 ? y[0][i] : t == 1 ? y[1][i] : t == 2 ? y[2][i] : y[3][i];
            {
                const bool odd = g & 1;
                const float sx = odd ? v[0] : v[2], sy = odd ? v[1] : v[3];
                const float rx = __shfl_xor_sync(0xffffffffu, sx, 4), ry = __shfl_xor_sync(0xffffffffu, sy, 4);
                const int c0 = 64 * warp + 16 * t + (odd ? g + 7 : g);
                const float e0 = odd ? rx : v[0], e1 = odd ? ry : v[1], e2 = odd ? v[2] : rx, e3 = odd ? v[3] : ry;
                st_v4(&sc->inbox_dn[c0 >> 2][cta][(c0 >> 1) & 1], tagf(e0, F_DOWN), tagf(e1, F_DOWN), tagf(e2, F_DOWN), tagf(e3, F_DOWN));
            }
            }
            if (warp == 0) TSTAMP(12);
        }
        {
            uint2 xw;
            float r0;
            {
                const uint4* pin = &sc->inbox_dn[cta][0][0] + tid;
                uint4 v = make_uint4(F_DOWN, F_DOWN, F_DOWN, F_DOWN);
                if (cta < NFFN) spin_cycles(DELAY_C);
                else while (clock32() - t_wo < DELAY_X1 + DELAY_NOFFN) {}
                xw = ld_ll2(&sc->x1[ocol]);
                bool ok = tid >= NFFN * 2;
                for (int it = 0;; it++) {
                    if (!ok) {
                        v = ld_ll4(pin);
                        ok = (v.x & v.y & v.z & v.w & 3u) == F_DOWN;
                    }
                    if (__all_sync(0xffffffffu, ok) || it > SPIN_LIMIT) break;
                }
                const bool u1 = lane & 2, u2 = lane & 4;
                const float a0 = untag(v.x), a1 = untag(v.y), a2 = untag(v.z), a3 = untag(v.w);
                const float k0 = (u1 ? a1 : a0) + __shfl_xor_sync(0xffffffffu, u1 ? a0 : a1, 2);
                const float k1 = (u1 ? a3 : a2) + __shfl_xor_sync(0xffffffffu, u1 ? a2 : a3, 2);
                r0 = (u2 ? k1 : k0) + __shfl_xor_sync(0xffffffffu, u2 ? k0 : k1, 4);
                r0 += __shfl_xor_sync(0xffffffffu, r0, 8);
                r0 += __shfl_xor_sync(0xffffffffu, r0, 16);
                if (lane < 8) red2[256 + warp * 8 + (2 * (lane & 1) + ((lane >> 2) & 1)) * 2 + ((lane >> 1) & 1)] = r0;
            }
            cons_sync();
            if (warp == 0) {
                float a0 = 0.f, a1 = 0.f;
#pragma unroll
                for (int w = 0; w < 8; w++) { const float2 v = *(const float2*)&red2[256 + w * 8 + (lane & 3) * 2]; a0 += v.x; a1 += v.y; }
                const bool hi = ocol & 1;
                const float gb0 = hi ? bf_hi(m_gb0.x) : bf_lo(m_gb0.x), gb1 = hi ? bf_hi(m_gb1.x) : bf_lo(m_gb1.x);
                for (int it = 0; !__all_sync(0xffffffffu, xw.y == F_X1) && it < SPIN_LIMIT; it++) xw = ld_ll2(&sc->x1[ocol]);
                if (lane < 4) {
                    p.out[ocol] = __float2bfloat16_rn(bf_lo(xw.x) + bf16r(gb0 * bf16r(a0)));
                    p.out[D_MODEL + ocol] = __float2bfloat16_rn(bf_hi(xw.x) + bf16r(gb1 * bf16r(a1)));
                }
                if (cta == 0 && lane == 0) *(volatile unsigned*)&sc->epoch = tag;
                TSTAMP(13);
            }
        }
    }
}

typedef CUresult (*EncodeFn)(CUtensorMap*, CUtensorMapDataType, cuuint32_t, void*, const cuuint64_t*, const cuuint64_t*,
                             const cuuint32_t*, const cuuint32_t*, CUtensorMapInterleave, CUtensorMapSwizzle,
                             CUtensorMapL2promotion, CUtensorMapFloatOOBfill);

struct Maps { CUtensorMap k, v, wq, wmod, wmod8, wo, wg, wu, wd; };

void encode(EncodeFn fn, CUtensorMap* m, const void* ptr, int rank, const cuuint64_t* dims, const cuuint64_t* strides,
            const cuuint32_t* box, CUtensorMapSwizzle sw) {
    const cuuint32_t es[3] = {1, 1, 1};
    fn(m, CU_TENSOR_MAP_DATA_TYPE_BFLOAT16, rank, const_cast<void*>(ptr), dims, strides, box, es,
       CU_TENSOR_MAP_INTERLEAVE_NONE, sw, CU_TENSOR_MAP_L2_PROMOTION_L2_256B, CU_TENSOR_MAP_FLOAT_OOB_FILL_NONE);
}

}

extern "C" void kernel_launch(void* const* d_in, const int* in_sizes, int n_in, void* d_out, int out_size) {
    (void)in_sizes; (void)n_in; (void)out_size;
    static EncodeFn enc = nullptr;
    static Scratch* scratch = nullptr;
    if (!enc) {
        cudaGetSymbolAddress((void**)&scratch, g_scratch);
        void* fn = nullptr;
        cudaDriverEntryPointQueryResult qr;
        cudaGetDriverEntryPoint("cuTensorMapEncodeTiled", &fn, cudaEnableDefault, &qr);
        enc = (EncodeFn)fn;
        cudaFuncSetAttribute(fused_block_kernel, cudaFuncAttributeMaxDynamicSharedMemorySize, SMEM_BYTES);
    }
    Maps m;
    {
        const cuuint64_t dims[3] = {64, (cuuint64_t)16 * SK, 2}, str[2] = {256, 128};
        const cuuint32_t box[3] = {64, 64, 2};
        encode(enc, &m.k, d_in[1], 3, dims, str, box, CU_TENSOR_MAP_SWIZZLE_128B);
        encode(enc, &m.v, d_in[2], 3, dims, str, box, CU_TENSOR_MAP_SWIZZLE_128B);
    }
    {
        const cuuint64_t dims[2] = {4096, 512}, str[1] = {8192};
        const cuuint32_t box[2] = {32, 256};
        encode(enc, &m.wq, d_in[3], 2, dims, str, box, CU_TENSOR_MAP_SWIZZLE_64B);
    }
    {
        const cuuint64_t dims[2] = {N_MOD, 512}, str[1] = {N_MOD * 2};
        const cuuint32_t box[2] = {16, 256};
        encode(enc, &m.wmod, d_in[10], 2, dims, str, box, CU_TENSOR_MAP_SWIZZLE_32B);
        const cuuint32_t box8[2] = {8, 256};
        encode(enc, &m.wmod8, d_in[10], 2, dims, str, box8, CU_TENSOR_MAP_SWIZZLE_NONE);
    }
    {
        const cuuint64_t dims_o[3] = {64, 4096, 8}, dims_d[3] = {64, D_FF, 8}, str[2] = {1024, 128};
        const cuuint32_t box[3] = {64, 16, 8}, box_o[3] = {64, 64, 2};
        encode(enc, &m.wo, d_in[4], 3, dims_o, str, box_o, CU_TENSOR_MAP_SWIZZLE_128B);
        encode(enc, &m.wd, d_in[8], 3, dims_d, str, box, CU_TENSOR_MAP_SWIZZLE_128B);
    }
    {
        const cuuint64_t dims[2] = {D_FF, 512}, str[1] = {D_FF * 2};
        const cuuint32_t box[2] = {16, 128};
        encode(enc, &m.wg, d_in[6], 2, dims, str, box, CU_TENSOR_MAP_SWIZZLE_32B);
        encode(enc, &m.wu, d_in[7], 2, dims, str, box, CU_TENSOR_MAP_SWIZZLE_32B);
    }
    Params p;
    p.x = (const __nv_bfloat16*)d_in[0];
    p.c = (const __nv_bfloat16*)d_in[9];
    p.out = (__nv_bfloat16*)d_out;
    p.sc = scratch;
    fused_block_kernel<<<NCTA, NTHREADS, SMEM_BYTES, cudaStreamPerThread>>>(p, m.k, m.v, m.wq, m.wmod, m.wmod8, m.wo, m.wg, m.wu, m.wd);
}
```

```cpp
#include <cuda_runtime.h>
#include <cuda.h>
#include <cuda_bf16.h>
#include <stdint.h>

namespace {

constexpr int D_MODEL = 512;
constexpr int N_HEADS = 32;
constexpr int SK = 32768;
constexpr int DH = 128;
constexpr int D_FF = 1792;
constexpr int N_MOD = 6 * D_MODEL;

constexpr int NCTA = 128;
constexpr int NFFN = D_FF / 16;
constexpr int NOWN = 32;
constexpr int NTHREADS = 320;
constexpr int NST = 12;
constexpr int TILE = 16384;
#define WINDOW 3
#define WINDOW_TAIL 1
#define GU_WIN 3
#define GU_EARLY 0
#define WD_WIN 2
#define PACE_THR 96
constexpr int KV_TILES = 64;
#define MOD_AT 8
static_assert(MOD_AT % 2 == 0 && MOD_AT >= 2 && MOD_AT < 56, "schedule");
__host__ __device__ constexpr int kv_idx(int i) { return 2 + 2 * i + (i >= MOD_AT ? 1 : 0); }
constexpr int IDX_MOD = 2 + 2 * MOD_AT;
constexpr int N_STREAM = kv_idx(KV_TILES - 1) + 2;
constexpr int IDX_WO = N_STREAM;
constexpr int IDX_WG = IDX_WO + 2;
constexpr int IDX_WU = IDX_WG + 1;
constexpr int IDX_WD = IDX_WU + 1;
constexpr int SPIN_LIMIT = 1 << 20;

constexpr float LOG2E = 1.4426950408889634f;
constexpr float QK_SCALE = 0.08838834764831845f;

constexpr int SM_RING = 0;
constexpr int SM_MRG = SM_RING + NST * TILE;
constexpr int SM_ML = SM_MRG + 8 * 4 * 136 * 4;
constexpr int SM_RED = SM_ML + 8 * 4 * 8;
constexpr int SM_RED2 = SM_RED + 8 * 64 * 4;
constexpr int SM_QS = SM_RED2 + 8 * 64 * 4;
constexpr int SM_OS = SM_QS + 512 * 2;
constexpr int SM_SC = SM_OS + 2 * 128 * 2;
constexpr int SM_HS = SM_SC + 2 * 512 * 2;
constexpr int SM_STAT = SM_HS + 8 * 2 * 32 * 4;
constexpr int SM_PACE = SM_STAT + 8 * 2 * 8;
constexpr int SM_BAR = SM_PACE + 8;
constexpr int SM_END = SM_BAR + (2 * NST + 1 + 8 + 1) * 8;
constexpr int SMEM_BYTES = SM_END + 1024;

struct Scratch {
    uint4 inbox_wo[NOWN][N_HEADS][8];
    uint4 inbox_dn[NCTA][NFFN][2];
    uint2 x1[D_MODEL];
    uint2 part_o[NCTA][4][64];
    uint2 part_ml[NCTA][4][4];
    uint2 mod[2][N_MOD / 2];
    uint2 q[2][N_HEADS * DH / 2];
    unsigned epoch;
    unsigned pad_[31];
    unsigned cleared;
    unsigned pad2_[31];
    unsigned progress;
};
__device__ Scratch g_scratch;
constexpr uint32_t F_PART = 1, F_WO = 1, F_DOWN = 1, F_X1 = 1;
__device__ __forceinline__ uint32_t tagf(float v, uint32_t f) { return (__float_as_uint(v) & ~3u) | f; }
__device__ __forceinline__ float untag(uint32_t v) { return __uint_as_float(v & ~3u); }

struct Params {
    const __nv_bfloat16* x;
    const __nv_bfloat16* c;
    __nv_bfloat16* out;
    Scratch* sc;
};

#define TSTAMP(i) do { } while (0)

__device__ __forceinline__ uint32_t smem_u32(const void* p) { return (uint32_t)__cvta_generic_to_shared(p); }

__device__ __forceinline__ void mbar_init(uint32_t bar, uint32_t cnt) {
    asm volatile("mbarrier.init.shared::cta.b64 [%0], %1;" ::"r"(bar), "r"(cnt) : "memory");
}
__device__ __forceinline__ void mbar_expect_tx(uint32_t bar, uint32_t bytes) {
    asm volatile("mbarrier.arrive.expect_tx.shared::cta.b64 _, [%0], %1;" ::"r"(bar), "r"(bytes) : "memory");
}
__device__ __forceinline__ void mbar_arrive(uint32_t bar) {
    asm volatile("mbarrier.arrive.shared::cta.b64 _, [%0];" ::"r"(bar) : "memory");
}
__device__ __forceinline__ bool mbar_try(uint32_t bar, uint32_t parity) {
    uint32_t ok;
    asm volatile(
        "{\n\t.reg .pred p;\n\t"
        "mbarrier.try_wait.parity.shared::cta.b64 p, [%1], %2;\n\t"
        "selp.u32 %0, 1, 0, p;\n\t}"
        : "=r"(ok) : "r"(bar), "r"(parity) : "memory");
    return ok != 0;
}
__device__ __forceinline__ void mbar_wait(uint32_t bar, uint32_t parity) {
    if (mbar_try(bar, parity)) return;
    const long long t0 = clock64();
    while (!mbar_try(bar, parity))
        if (clock64() - t0 > (1ll << 31)) return;
}
__device__ __forceinline__ void cons_sync() { asm volatile("bar.sync 1, 256;" ::: "memory"); }

__device__ __forceinline__ void tma_2d(uint32_t dst, const CUtensorMap* m, int c0, int c1, uint32_t bar) {
    asm volatile("cp.async.bulk.tensor.2d.shared::cluster.global.mbarrier::complete_tx::bytes [%0], [%1, {%3, %4}], [%2];"
                 ::"r"(dst), "l"(m), "r"(bar), "r"(c0), "r"(c1) : "memory");
}
__device__ __forceinline__ void tma_3d(uint32_t dst, const CUtensorMap* m, int c0, int c1, int c2, uint32_t bar) {
    asm volatile("cp.async.bulk.tensor.3d.shared::cluster.global.mbarrier::complete_tx::bytes [%0], [%1, {%3, %4, %5}], [%2];"
                 ::"r"(dst), "l"(m), "r"(bar), "r"(c0), "r"(c1), "r"(c2) : "memory");
}
__device__ __forceinline__ void tma_3d_hint(uint32_t dst, const CUtensorMap* m, int c0, int c1, int c2, uint32_t bar, uint64_t pol) {
    asm volatile("cp.async.bulk.tensor.3d.shared::cluster.global.mbarrier::complete_tx::bytes.L2::cache_hint [%0], [%1, {%3, %4, %5}], [%2], %6;"
                 ::"r"(dst), "l"(m), "r"(bar), "r"(c0), "r"(c1), "r"(c2), "l"(pol) : "memory");
}
__device__ __forceinline__ void prefetch_tmap(const CUtensorMap* m) {
    asm volatile("prefetch.tensormap [%0];" ::"l"(m) : "memory");
}

__device__ __forceinline__ void ldsm4(uint32_t addr, uint32_t (&r)[4]) {
    asm volatile("ldmatrix.sync.aligned.m8n8.x4.shared.b16 {%0,%1,%2,%3}, [%4];"
                 : "=r"(r[0]), "=r"(r[1]), "=r"(r[2]), "=r"(r[3]) : "r"(addr) : "memory");
}
__device__ __forceinline__ void ldsm4t(uint32_t addr, uint32_t (&r)[4]) {
    asm volatile("ldmatrix.sync.aligned.m8n8.x4.trans.shared.b16 {%0,%1,%2,%3}, [%4];"
                 : "=r"(r[0]), "=r"(r[1]), "=r"(r[2]), "=r"(r[3]) : "r"(addr) : "memory");
}
__device__ __forceinline__ void mma16816(float (&c)[4], const uint32_t (&a)[4], uint32_t b0, uint32_t b1) {
    asm volatile("mma.sync.aligned.m16n8k16.row.col.f32.bf16.bf16.f32 {%0,%1,%2,%3}, {%4,%5,%6,%7}, {%8,%9}, {%0,%1,%2,%3};"
                 : "+f"(c[0]), "+f"(c[1]), "+f"(c[2]), "+f"(c[3])
                 : "r"(a[0]), "r"(a[1]), "r"(a[2]), "r"(a[3]), "r"(b0), "r"(b1));
}
__device__ __forceinline__ uint32_t movmatrix_t(uint32_t a) {
    uint32_t d;
    asm volatile("movmatrix.sync.aligned.m8n8.trans.b16 %0, %1;" : "=r"(d) : "r"(a));
    return d;
}
__device__ __forceinline__ uint32_t pack_bf16(float a, float b) {
    uint32_t r;
    asm("cvt.rn.bf16x2.f32 %0, %1, %2;" : "=r"(r) : "f"(b), "f"(a));
    return r;
}
__device__ __forceinline__ float bf_lo(uint32_t v) { return __uint_as_float(v << 16); }
__device__ __forceinline__ float bf_hi(uint32_t v) { return __uint_as_float(v & 0xffff0000u); }
__device__ __forceinline__ float bf16r(float a) { return bf_lo(pack_bf16(a, 0.f)); }
__device__ __forceinline__ uint32_t max_bf16x2(uint32_t a, uint32_t b) {
    uint32_t r;
    asm("max.bf16x2 %0, %1, %2;" : "=r"(r) : "r"(a), "r"(b));
    return r;
}
__device__ __forceinline__ float ex2(float x) {
    float r;
    asm("ex2.approx.ftz.f32 %0, %1;" : "=f"(r) : "f"(x));
    return r;
}

__device__ __forceinline__ void st_ll2(uint2* p, uint32_t v, uint32_t tag) {
    asm volatile("st.relaxed.gpu.global.v2.u32 [%0], {%1, %2};" ::"l"(p), "r"(v), "r"(tag) : "memory");
}
__device__ __forceinline__ void st_ll4(uint4* p, uint32_t v0, uint32_t v1, uint32_t tag) {
    asm volatile("st.relaxed.gpu.global.v4.u32 [%0], {%1, %2, %3, %2};" ::"l"(p), "r"(v0), "r"(tag), "r"(v1) : "memory");
}
__device__ __forceinline__ void st_v4(uint4* p, uint32_t a, uint32_t b, uint32_t c, uint32_t d) {
    asm volatile("st.relaxed.gpu.global.v4.u32 [%0], {%1, %2, %3, %4};" ::"l"(p), "r"(a), "r"(b), "r"(c), "r"(d) : "memory");
}
__device__ __forceinline__ uint2 ld_ll2(const uint2* p) {
    uint2 v;
    asm volatile("ld.relaxed.gpu.global.v2.u32 {%0, %1}, [%2];" : "=r"(v.x), "=r"(v.y) : "l"(p) : "memory");
    return v;
}
__device__ __forceinline__ uint4 ld_ll4(const uint4* p) {
    uint4 v;
    asm volatile("ld.relaxed.gpu.global.v4.u32 {%0, %1, %2, %3}, [%4];"
                 : "=r"(v.x), "=r"(v.y), "=r"(v.z), "=r"(v.w) : "l"(p) : "memory");
    return v;
}

#define DELAY_B1 300
#define DELAY_X1 2000
#define DELAY_NOFFN 1500
#define A_BACKOFF 0
#define DELAY_C 600
__device__ __forceinline__ uint32_t clock32() {
    uint32_t c;
    asm volatile("mov.u32 %0, %clock;" : "=r"(c));
    return c;
}
__device__ __forceinline__ void spin_cycles(uint32_t n) {
    if (n > 0) { const uint32_t c0 = clock32(); while (clock32() - c0 < n) {} }
}
__device__ __forceinline__ float rcp_approx(float x) {
    float r;
    asm("rcp.approx.ftz.f32 %0, %1;" : "=f"(r) : "f"(x));
    return r;
}
__device__ __forceinline__ float sqrt_approx(float x) {
    float r;
    asm("sqrt.approx.f32 %0, %1;" : "=f"(r) : "f"(x));
    return r;
}

__device__ __forceinline__ float silu_bf(float v) { return bf16r(v / (1.0f + expf(-v))); }

__device__ __forceinline__ float2 half_warp_sums(const float (&v)[4], float pivot) {
    float s1 = 0.f, s2 = 0.f;
#pragma unroll
    for (int i = 0; i < 4; i++) { const float d = v[i] - pivot; s1 += d; s2 += d * d; }
#pragma unroll
    for (int o = 1; o < 16; o <<= 1) { s1 += __shfl_xor_sync(0xffffffffu, s1, o); s2 += __shfl_xor_sync(0xffffffffu, s2, o); }
    return make_float2(s1, s2);
}
__device__ __forceinline__ void ln_stats(const float2* stat, int b, float pivot, float& mean_bf, float& rstd) {
    float s1 = 0.f, s2 = 0.f;
#pragma unroll
    for (int w = 0; w < 8; w++) { const float2 v = stat[w * 2 + b]; s1 += v.x; s2 += v.y; }
    const float dm = s1 * (1.0f / D_MODEL);
    const float var = fmaxf(s2 * (1.0f / D_MODEL) - dm * dm, 0.f);
    mean_bf = bf16r(pivot + dm);
    rstd = rcp_approx(bf16r(sqrt_approx(bf16r(bf16r(var) + 1e-5f))));
}
__device__ __forceinline__ float ln_norm(float xv, float mean_bf, float rstd) { return bf16r(bf16r(xv - mean_bf) * rstd); }
__device__ __forceinline__ float ln_mod(float n, float cmul, float sadd) { return bf16r(n * bf16r(1.0f + cmul)) + sadd; }

__global__ void __launch_bounds__(NTHREADS, 1)
fused_block_kernel(const Params p, const __grid_constant__ CUtensorMap tm_k, const __grid_constant__ CUtensorMap tm_v,
                   const __grid_constant__ CUtensorMap tm_wq, const __grid_constant__ CUtensorMap tm_wmod,
                   const __grid_constant__ CUtensorMap tm_wmod8,
                   const __grid_constant__ CUtensorMap tm_wo, const __grid_constant__ CUtensorMap tm_wg,
                   const __grid_constant__ CUtensorMap tm_wu, const __grid_constant__ CUtensorMap tm_wd) {
    extern __shared__ unsigned char smem_raw[];
    const uint32_t sbase = (smem_u32(smem_raw) + 1023u) & ~1023u;
    unsigned char* sgen = smem_raw + (sbase - smem_u32(smem_raw));
    const int tid = threadIdx.x, warp = tid >> 5, lane = tid & 31;
    const int cta = blockIdx.x;
    const uint32_t bar_full = sbase + SM_BAR, bar_empty = bar_full + NST * 8;
    const uint32_t bar_clear = bar_empty + NST * 8;
    const uint32_t bar_gu = bar_clear + 8;
    const uint32_t bar_p0w = bar_gu + 8 * 8;

    const int key0 = (cta >> 3) * SK + (cta & 7) * 64;
    uint64_t pol = 0;
    if (tid == 256) {
        asm volatile("createpolicy.fractional.L2::evict_first.b64 %0, 1.0;" : "=l"(pol));
        mbar_init(bar_p0w, 1);
#pragma unroll
        for (int i = 0; i < 4; i++) mbar_init(bar_full + 8 * i, 1);
        asm volatile("fence.mbarrier_init.release.cluster;" ::: "memory");
        mbar_expect_tx(bar_p0w, 8192);
        tma_2d(sbase + SM_MRG, &tm_wmod8, cta * 8, 0, bar_p0w);
        tma_2d(sbase + SM_MRG + 4096, &tm_wmod8, cta * 8, 256, bar_p0w);
#pragma unroll
        for (int i = 0; i < 4; i++) mbar_expect_tx(bar_full + 8 * i, TILE);
        tma_2d(sbase + SM_RING, &tm_wq, cta * 32, 0, bar_full);
        tma_2d(sbase + SM_RING + TILE, &tm_wq, cta * 32, 256, bar_full + 8);
        tma_3d_hint(sbase + SM_RING + 2 * TILE, &tm_k, 0, key0, 0, bar_full + 16, pol);
        tma_3d_hint(sbase + SM_RING + 3 * TILE, &tm_v, 0, key0, 0, bar_full + 24, pol);
    }

    if (warp == 8) {
        if (lane == 0) {
            for (int i = 0; i < NST; i++) { if (i >= 4) mbar_init(bar_full + 8 * i, 1); mbar_init(bar_empty + 8 * i, 4); }
            mbar_init(bar_clear, 1);
            for (int k = 0; k < 8; k++) mbar_init(bar_gu + 8 * k, 1);
            ((volatile uint32_t*)(sgen + SM_PACE))[0] = 0;
            ((volatile uint32_t*)(sgen + SM_PACE))[1] = WINDOW;
            asm volatile("fence.mbarrier_init.release.cluster;" ::: "memory");
        }
        __syncwarp();
        asm volatile("bar.arrive 2, 320;" ::: "memory");
        asm volatile("bar.arrive 3, 64;" ::: "memory");
        if (lane == 0) {
            int slot = 4; uint32_t ph = 1;
            int landed = 0, wslot = 0; uint32_t wph = 0;
            int kv = 2;
            auto wait_window = [&](int idx, int window) {
                while (landed + window <= idx) {
                    mbar_wait(bar_full + 8 * wslot, wph);
                    if (++wslot == NST) { wslot = 0; wph ^= 1; }
                    landed++;
                }
            };
            volatile uint32_t* pace = (volatile uint32_t*)(sgen + SM_PACE);
            prefetch_tmap(&tm_wmod);
            pace[0] = 4;
            for (int idx = 4; idx < N_STREAM; idx++) {
                if (idx >= NST) mbar_wait(bar_empty + 8 * slot, ph);
                wait_window(idx, (int)pace[1]);
                if (idx == 12) { prefetch_tmap(&tm_wo); prefetch_tmap(&tm_wg); prefetch_tmap(&tm_wu); prefetch_tmap(&tm_wd); }
                const uint32_t fb = bar_full + 8 * slot, dst = sbase + SM_RING + slot * TILE;
                mbar_expect_tx(fb, TILE);
                if (idx == IDX_MOD) {
                    tma_2d(dst, &tm_wmod, 1024 + cta * 16, 0, fb);
                    tma_2d(dst + 8192, &tm_wmod, 1024 + cta * 16, 256, fb);
                } else {
                    tma_3d_hint(dst, (kv & 1) ? &tm_v : &tm_k, 0, key0 + (kv >> 1) * 512, 0, fb, pol);
                    kv++;
                }
                pace[0] = idx + 1;
                if (++slot == NST) { slot = 0; ph ^= 1; }
            }
            auto slot_free = [&](int idx) { mbar_wait(bar_empty + 8 * (idx % NST), ((idx / NST) & 1) ^ 1); };
#pragma unroll
            for (int s = 0; s < 2; s++) {
                const int idx = IDX_WO + s;
                slot_free(idx);
                wait_window(idx, WINDOW_TAIL);
                mbar_expect_tx(bar_full + 8 * (idx % NST), TILE);
                tma_3d(sbase + SM_RING + (idx % NST) * TILE, &tm_wo, 0, (cta >> 2) * 128 + s * 64, (cta & 3) * 2, bar_full + 8 * (idx % NST));
            }
            if (cta < NFFN) {
                slot_free(IDX_WG); slot_free(IDX_WU);
#pragma unroll
                for (int st = 0; st < 8; st++) {
                    if (st == GU_EARLY) {
                        mbar_wait(bar_full + 8 * (IDX_WO % NST), (IDX_WO / NST) & 1);
                        mbar_wait(bar_full + 8 * ((IDX_WO + 1) % NST), ((IDX_WO + 1) / NST) & 1);
                    }
                    if (st >= GU_WIN) mbar_wait(bar_gu + 8 * (st - GU_WIN), 0);
                    mbar_expect_tx(bar_gu + 8 * st, 4096);
                    tma_2d(sbase + SM_RING + (((st & 1) ? IDX_WU : IDX_WG) % NST) * TILE + (st >> 1) * 4096,
                           (st & 1) ? &tm_wu : &tm_wg, cta * 16, (st >> 1) * 128, bar_gu + 8 * st);
                }
                mbar_wait(bar_gu + 8 * (8 - WD_WIN), 0);
                slot_free(IDX_WD);
                mbar_expect_tx(bar_full + 8 * (IDX_WD % NST), TILE);
                tma_3d(sbase + SM_RING + (IDX_WD % NST) * TILE, &tm_wd, 0, cta * 16, 0, bar_full + 8 * (IDX_WD % NST));
            }
        }
    } else if (warp == 9) {
        Scratch* const sc = p.sc;
        const uint32_t tag = *(volatile unsigned*)&sc->epoch + 1;
        if (lane < 2) {
            st_ll4((uint4*)&sc->mod[lane][cta * 4], 0u, 0u, 0u);
            st_ll4((uint4*)&sc->mod[lane][cta * 4] + 1, 0u, 0u, 0u);
        }
        if (lane < 8) st_ll4((uint4*)&sc->mod[lane >> 2][512 + cta * 8] + (lane & 3), 0u, 0u, 0u);
        if (lane < 16) st_ll4((uint4*)&sc->q[lane >> 3][cta * 16] + (lane & 7), 0u, 0u, 0u);
        __syncwarp();
        asm volatile("bar.arrive 2, 320;" ::: "memory");
        asm volatile("bar.sync 3, 64;" ::: "memory");
#pragma unroll 4
        for (int i = 0; i < NFFN * 2 / 32; i++) st_v4(&sc->inbox_dn[cta][0][0] + i * 32 + lane, 0u, 0u, 0u, 0u);
        if (cta >= NCTA - NOWN) {
#pragma unroll 4
            for (int i = 0; i < 8; i++) st_v4(&sc->inbox_wo[cta - (NCTA - NOWN)][0][0] + i * 32 + lane, 0u, 0u, 0u, 0u);
            if (lane < 8) st_v4((uint4*)&sc->x1[(cta - (NCTA - NOWN)) * 16] + lane, 0u, 0u, 0u, 0u);
        }
#pragma unroll 4
        for (int i = 0; i < 4; i++) st_v4((uint4*)&sc->part_o[cta][0][0] + i * 32 + lane, 0u, 0u, 0u, 0u);
        if (lane < 8) st_v4((uint4*)&sc->part_ml[cta][0][0] + lane, 0u, 0u, 0u, 0u);
        if (cta == 0 && lane == 0) asm volatile("st.relaxed.gpu.global.u32 [%0], %1;" ::"l"(&sc->progress), "r"(0u) : "memory");
        asm volatile("fence.acq_rel.gpu;" ::: "memory");
        __syncwarp();
        if (lane == 0) {
            asm volatile("fence.acq_rel.gpu;" ::: "memory");
            asm volatile("red.relaxed.gpu.global.add.u32 [%0], %1;" ::"l"(&sc->cleared), "r"(1u) : "memory");
            const uint32_t target = tag * NCTA;
            for (int it = 0; it < SPIN_LIMIT; it++) {
                uint32_t v;
                asm volatile("ld.relaxed.gpu.global.u32 %0, [%1];" : "=r"(v) : "l"(&sc->cleared) : "memory");
                if ((int32_t)(v - target) >= 0) break;
                __nanosleep(500);
            }
            asm volatile("fence.acq_rel.gpu;" ::: "memory");
            mbar_arrive(bar_clear);
            volatile uint32_t* pace = (volatile uint32_t*)(sgen + SM_PACE);
            uint32_t posted = 0;
            for (int it = 0; it < SPIN_LIMIT; it++) {
                const uint32_t own = pace[0];
                if (own >= N_STREAM) break;
                if (own > posted) {
                    asm volatile("red.relaxed.gpu.global.add.u32 [%0], %1;" ::"l"(&sc->progress), "r"(own - posted) : "memory");
                    posted = own;
                }
                uint32_t v;
                asm volatile("ld.relaxed.gpu.global.u32 %0, [%1];" : "=r"(v) : "l"(&sc->progress) : "memory");
                const int diff = (int)v - (int)own * NCTA;
                pace[1] = diff > PACE_THR ? WINDOW + 1 : diff < -PACE_THR ? WINDOW - 1 : WINDOW;
                __nanosleep(200);
            }
        }
    } else {
        const int g = lane >> 2, t = lane & 3;
        const int bb = g & 1;
        const int eb = lane >> 4;
        const int ec = 64 * warp + 4 * (lane & 15);
        if (warp == 0) TSTAMP(0);
        Scratch* const sc = p.sc;
        const float c00 = __bfloat162float(p.c[tid]), c01 = __bfloat162float(p.c[tid + 256]);
        const float c10 = __bfloat162float(p.c[D_MODEL + tid]), c11 = __bfloat162float(p.c[D_MODEL + tid + 256]);
        const uint2 xe = __ldg((const uint2*)(p.x + eb * D_MODEL + ec));
        const float xpivot = __bfloat162float(p.x[eb * D_MODEL]);
        const uint32_t tag = *(volatile unsigned*)&sc->epoch + 1;
        const int ocol = cta * 4 + (lane & 3);
        const int wcol = (cta >= NCTA - NOWN ? cta - (NCTA - NOWN) : 0) * 16 + (lane & 15);
        const float xo = __bfloat162float(p.x[eb * D_MODEL + wcol]);

        float* red = (float*)(sgen + SM_RED);
        float* red2 = (float*)(sgen + SM_RED2);
        float2* stat = (float2*)(sgen + SM_STAT);
        uint32_t* hs = (uint32_t*)(sgen + SM_HS) + warp * 64;
        float xn[4];
        {
            float xv[4] = {bf_lo(xe.x), bf_hi(xe.x), bf_lo(xe.y), bf_hi(xe.y)};
            const float2 ps = half_warp_sums(xv, xpivot);
            if ((lane & 15) == 0) stat[warp * 2 + eb] = ps;
            const float s00 = silu_bf(c00), s01 = silu_bf(c01), s10 = silu_bf(c10), s11 = silu_bf(c11);
            __nv_bfloat16* scs = (__nv_bfloat16*)(sgen + SM_SC);
            scs[tid] = __float2bfloat16_rn(s00); scs[tid + 256] = __float2bfloat16_rn(s01);
            scs[512 + tid] = __float2bfloat16_rn(s10); scs[512 + tid + 256] = __float2bfloat16_rn(s11);
            asm volatile("bar.sync 2, 320;" ::: "memory");
            if (warp == 0) TSTAMP(23);
            float cp[4] = {0.f, 0.f, 0.f, 0.f};
            const uint32_t* sc32 = (const uint32_t*)(sgen + SM_SC) + bb * 256 + 32 * warp + t;
            mbar_wait(bar_p0w, 0);
#pragma unroll
            for (int s = 0; s < 4; s++) {
                uint32_t r0, r1;
                asm volatile("ldmatrix.sync.aligned.m8n8.x2.trans.shared.b16 {%0,%1}, [%2];"
                             : "=r"(r0), "=r"(r1) : "r"(sbase + SM_MRG + (64 * warp + 16 * s + (lane & 15)) * 16) : "memory");
                const uint32_t a[4] = {r0, r0, r1, r1};
                mma16816(cp, a, sc32[8 * s], sc32[8 * s + 4]);
            }
            if (t == 0) { red[warp * 16 + g] = cp[0]; red[warp * 16 + 8 + g] = cp[1]; }
            if (warp == 0) TSTAMP(14);
            cons_sync();
            if (warp == 0) {
                float s = 0.f;
#pragma unroll
                for (int w = 0; w < 8; w++) s += red[w * 16 + (lane & 15)];
                const float nx = __shfl_down_sync(0xffffffffu, s, 1);
                if (lane < 16 && !(lane & 1))
                    st_ll2(&sc->mod[lane >> 3][cta * 4 + ((lane & 7) >> 1)], pack_bf16(s, nx), tag);
                TSTAMP(1);
            }
            float mean_bf, rstd;
            ln_stats(stat, eb, xpivot, mean_bf, rstd);
#pragma unroll
            for (int i = 0; i < 4; i++) xn[i] = ln_norm(xv[i], mean_bf, rstd);
        }
        {
            uint4 sa, ca;
            for (int it = 0;; it++) {
                sa = ld_ll4((const uint4*)&sc->mod[eb][ec >> 1]);
                ca = ld_ll4((const uint4*)&sc->mod[eb][256 + (ec >> 1)]);
                const bool ok = sa.y == tag && sa.w == tag && ca.y == tag && ca.w == tag;
                if (__all_sync(0xffffffffu, ok) || it > SPIN_LIMIT) break;
            }
            *(uint2*)&hs[eb * 32 + 2 * (lane & 15)] =
                make_uint2(pack_bf16(ln_mod(xn[0], bf_lo(ca.x), bf_lo(sa.x)), ln_mod(xn[1], bf_hi(ca.x), bf_hi(sa.x))),
                           pack_bf16(ln_mod(xn[2], bf_lo(ca.z), bf_lo(sa.z)), ln_mod(xn[3], bf_hi(ca.z), bf_hi(sa.z))));
            __syncwarp();
            uint32_t hb[8];
#pragma unroll
            for (int i = 0; i < 8; i++) hb[i] = hs[bb * 32 + 8 * (i >> 1) + 4 * (i & 1) + t];
            if (warp == 0) TSTAMP(2);
            float cq[2][4] = {};
            const int ts = warp >> 2;
            mbar_wait(bar_full + 8 * ts, 0);
            const uint32_t tb = sbase + SM_RING + ts * TILE;
#pragma unroll
            for (int s = 0; s < 4; s++) {
                const int row = 64 * (warp & 3) + 16 * s + (lane & 7) + (lane >> 4) * 8;
#pragma unroll
                for (int mt = 0; mt < 2; mt++) {
                    const int ch = 2 * mt + ((lane >> 3) & 1);
                    uint32_t a[4];
                    ldsm4t(tb + row * 64 + ((ch ^ ((row >> 1) & 3)) << 4), a);
                    mma16816(cq[mt], a, hb[2 * s], hb[2 * s + 1]);
                }
            }
            if (t < 2) {
                const float v0 = t == 0 ? cq[0][0] : cq[1][0], v1 = t == 0 ? cq[0][1] : cq[1][1];
                const float v2 = t == 0 ? cq[0][2] : cq[1][2], v3 = t == 0 ? cq[0][3] : cq[1][3];
                *(float2*)&red2[warp * 64 + (16 * t + g) * 2] = make_float2(v0, v1);
                *(float2*)&red2[warp * 64 + (16 * t + g + 8) * 2] = make_float2(v2, v3);
            }
            cons_sync();
            if (warp < 4 && lane == 0) { mbar_arrive(bar_empty); mbar_arrive(bar_empty + 8); }
            if (warp == 0) {
                const int b = lane >> 4, cp = lane & 15;
                float q0 = 0.f, q1 = 0.f;
#pragma unroll
                for (int w = 0; w < 8; w++) {
                    const float4 v = *(const float4*)&red2[w * 64 + cp * 4];
                    q0 += b ? v.y : v.x; q1 += b ? v.w : v.z;
                }
                st_ll2(&sc->q[b][cta * 16 + cp], pack_bf16(q0, q1), tag);
                TSTAMP(3);
            }
        }
        const int pair = cta >> 3;
        uint32_t qf[16];
        {
            uint2* qs = (uint2*)(sgen + SM_QS);
            if (tid < 128) {
                const uint4* src = (const uint4*)&sc->q[pair >> 3][(pair & 7) * 256] + tid;
                uint4 v;
                for (int it = 0;; it++) {
                    v = ld_ll4(src);
                    if ((v.y == tag && v.w == tag) || it > SPIN_LIMIT) break;
                }
                qs[tid] = make_uint2(v.x, v.z);
            }
            cons_sync();
            const uint32_t* q32 = (const uint32_t*)(sgen + SM_QS);
#pragma unroll
            for (int s = 0; s < 8; s++) {
                qf[2 * s] = q32[(g & 3) * 64 + 8 * s + t];
                qf[2 * s + 1] = q32[(g & 3) * 64 + 8 * s + 4 + t];
            }
        }
        if (warp == 0) TSTAMP(4);

        float o[8][4];
#pragma unroll
        for (int i = 0; i < 8; i++) { o[i][0] = o[i][1] = o[i][2] = o[i][3] = 0.f; }
        uint32_t mrun = 0xff80ff80u;
        float ls[4] = {0.f, 0.f, 0.f, 0.f};
        uint4 m_sb, m_cb; uint2 m_ga, m_gb0, m_gb1;
        {
            const int grp = warp >> 2, wi = warp & 3;
            const int krow = 16 * wi + (lane & 7) + ((lane >> 3) & 1) * 8;
            const uint32_t koff = krow * 128 + ((((lane >> 4) & 1) ^ (lane & 7)) << 4);
            const int vrow = 16 * wi + (lane & 7) + (lane >> 4) * 8;
            const uint32_t voff = vrow * 128 + ((((lane >> 3) & 1) ^ (lane & 7)) << 4);
            const uint32_t ones[4] = {0x3f803f80u, 0x3f803f80u, 0x3f803f80u, 0x3f803f80u};
            for (int i = grp; i < KV_TILES; i += 2) {
                if (i == MOD_AT + grp) {
                    float cm[4] = {};
                    const uint32_t* sc32 = (const uint32_t*)(sgen + SM_SC) + bb * 256 + 32 * warp + t;
                    mbar_wait(bar_full + 8 * (IDX_MOD % NST), (IDX_MOD / NST) & 1);
                    const uint32_t tb = sbase + SM_RING + (IDX_MOD % NST) * TILE;
#pragma unroll
                    for (int s = 0; s < 4; s++) {
                        const int row = 64 * warp + 16 * s + (lane & 7) + (lane >> 4) * 8;
                        const int ch = (lane >> 3) & 1;
                        uint32_t a[4];
                        ldsm4t(tb + row * 32 + ((ch ^ ((row >> 2) & 1)) << 4), a);
                        mma16816(cm, a, sc32[8 * s], sc32[8 * s + 4]);
                    }
                    if (t == 0) {
                        *(float2*)&red[warp * 64 + g * 2] = make_float2(cm[0], cm[1]);
                        *(float2*)&red[warp * 64 + (g + 8) * 2] = make_float2(cm[2], cm[3]);
                    }
                    cons_sync();
                    if (warp < 4 && lane == 0) mbar_arrive(bar_empty + 8 * (IDX_MOD % NST));
                    if (warp == 1 && lane < 16) {
                        const int b = lane >> 3, cp = lane & 7;
                        float q0 = 0.f, q1 = 0.f;
#pragma unroll
                        for (int w = 0; w < 8; w++) {
                            const float4 v = *(const float4*)&red[w * 64 + cp * 4];
                            q0 += b ? v.y : v.x; q1 += b ? v.w : v.z;
                        }
                        st_ll2(&sc->mod[b][512 + cta * 8 + cp], pack_bf16(q0, q1), tag);
                    }
                }
                if (i == 56 + grp) {
                    m_sb = ld_ll4((const uint4*)&sc->mod[eb][768 + (ec >> 1)]);
                    m_cb = ld_ll4((const uint4*)&sc->mod[eb][1024 + (ec >> 1)]);
                    m_ga = ld_ll2(&sc->mod[eb][512 + (wcol >> 1)]);
                    m_gb0 = ld_ll2(&sc->mod[0][1280 + (ocol >> 1)]); m_gb1 = ld_ll2(&sc->mod[1][1280 + (ocol >> 1)]);
                }
                if (i == 60 + grp) {
                    for (int it = 0;; it++) {
                        const bool ok = m_sb.y == tag && m_sb.w == tag && m_cb.y == tag && m_cb.w == tag &&
                                        m_ga.y == tag && m_gb0.y == tag && m_gb1.y == tag;
                        if (__all_sync(0xffffffffu, ok) || it > SPIN_LIMIT) break;
                        m_sb = ld_ll4((const uint4*)&sc->mod[eb][768 + (ec >> 1)]);
                        m_cb = ld_ll4((const uint4*)&sc->mod[eb][1024 + (ec >> 1)]);
                        m_ga = ld_ll2(&sc->mod[eb][512 + (wcol >> 1)]);
                        m_gb0 = ld_ll2(&sc->mod[0][1280 + (ocol >> 1)]); m_gb1 = ld_ll2(&sc->mod[1][1280 + (ocol >> 1)]);
                    }
                    mbar_wait(bar_clear, 0);
                }
                const int ki = kv_idx(i), ks = ki % NST, vs = (ki + 1) % NST;
                const uint32_t kph = (ki / NST) & 1, vph = ((ki + 1) / NST) & 1;
                mbar_wait(bar_full + 8 * ks, kph);
                const uint32_t kb = sbase + SM_RING + ks * TILE + koff;
                float sa[4] = {0.f, 0.f, 0.f, 0.f}, sb[4] = {0.f, 0.f, 0.f, 0.f};
#pragma unroll
                for (int s = 0; s < 8; s += 2) {
                    uint32_t a0[4], a1[4];
                    ldsm4((kb ^ ((s & 3) << 5)) + (s >> 2) * 8192, a0);
                    ldsm4((kb ^ (((s + 1) & 3) << 5)) + (s >> 2) * 8192, a1);
                    mma16816(sa, a0, qf[2 * s], qf[2 * s + 1]);
                    mma16816(sb, a1, qf[2 * s + 2], qf[2 * s + 3]);
                }
                __syncwarp();
                if (lane == 0) mbar_arrive(bar_empty + 8 * ks);
                uint32_t r01 = pack_bf16(sa[0] + sb[0], sa[1] + sb[1]);
                uint32_t r23 = pack_bf16(sa[2] + sb[2], sa[3] + sb[3]);
                r01 = pack_bf16(bf_lo(r01) * QK_SCALE, bf_hi(r01) * QK_SCALE);
                r23 = pack_bf16(bf_lo(r23) * QK_SCALE, bf_hi(r23) * QK_SCALE);
                uint32_t mx = max_bf16x2(r01, r23);
                mx = max_bf16x2(mx, __shfl_xor_sync(0xffffffffu, mx, 4));
                mx = max_bf16x2(mx, __shfl_xor_sync(0xffffffffu, mx, 8));
                mx = max_bf16x2(mx, __shfl_xor_sync(0xffffffffu, mx, 16));
                const uint32_t mnew = max_bf16x2(mrun, mx);
                const float m0 = bf_lo(mnew), m1 = bf_hi(mnew);
                if (__any_sync(0xffffffffu, mnew != mrun)) {
                    const float al0 = ex2((bf_lo(mrun) - m0) * LOG2E), al1 = ex2((bf_hi(mrun) - m1) * LOG2E);
                    ls[0] *= al0; ls[1] *= al1;
#pragma unroll
                    for (int d = 0; d < 8; d++) { o[d][0] *= al0; o[d][1] *= al1; o[d][2] *= al0; o[d][3] *= al1; }
                    mrun = mnew;
                }
                const float p0 = ex2((bf_lo(r01) - m0) * LOG2E), p1 = ex2((bf_hi(r01) - m1) * LOG2E);
                const float p2 = ex2((bf_lo(r23) - m0) * LOG2E), p3 = ex2((bf_hi(r23) - m1) * LOG2E);
                const uint32_t pb0 = movmatrix_t(pack_bf16(p0, p1)), pb1 = movmatrix_t(pack_bf16(p2, p3));
                mma16816(ls, ones, pb0, pb1);
                mbar_wait(bar_full + 8 * vs, vph);
                const uint32_t vb = sbase + SM_RING + vs * TILE + voff;
#pragma unroll
                for (int d = 0; d < 8; d++) {
                    uint32_t a[4];
                    ldsm4t((vb ^ ((d & 3) << 5)) + (d >> 2) * 8192, a);
                    mma16816(o[d], a, pb0, pb1);
                }
                __syncwarp();
                if (lane == 0) mbar_arrive(bar_empty + 8 * vs);
            }
        }
        if (warp == 7) TSTAMP(5);
        {
            float* mrg = (float*)(sgen + SM_MRG);
            float2* ml = (float2*)(sgen + SM_ML);
            {
                const int hp = (t & 1) * 2, up = t >> 1;
                if (g == 0 && up == 0) { ml[warp * 4 + hp] = make_float2(bf_lo(mrun), ls[0]); ml[warp * 4 + hp + 1] = make_float2(bf_hi(mrun), ls[1]); }
                float* m0p = mrg + (warp * 4 + hp) * 136 + up * 72 + g;
#pragma unroll
                for (int d = 0; d < 4; d++) {
                    m0p[16 * d] = up ? o[d + 4][0] : o[d][0]; m0p[136 + 16 * d] = up ? o[d + 4][1] : o[d][1];
                    m0p[16 * d + 8] = up ? o[d + 4][2] : o[d][2]; m0p[136 + 16 * d + 8] = up ? o[d + 4][3] : o[d][3];
                }
            }
            cons_sync();
            const int hh = tid >> 6, dp = tid & 63;
            float2 mw[8];
            float M = -INFINITY;
#pragma unroll
            for (int w = 0; w < 8; w++) { mw[w] = ml[w * 4 + hh]; M = fmaxf(M, mw[w].x); }
            float L = 0.f, o0 = 0.f, o1 = 0.f;
#pragma unroll
            for (int w = 0; w < 8; w++) {
                const float wt = ex2((mw[w].x - M) * LOG2E);
                const float2 v = *(const float2*)&mrg[(w * 4 + hh) * 136 + 2 * dp + (dp >= 32 ? 8 : 0)];
                L += wt * mw[w].y; o0 += wt * v.x; o1 += wt * v.y;
            }
            st_ll2(&sc->part_o[cta][hh][dp], tagf(o0, F_PART), tagf(o1, F_PART));
            if (dp < 4) st_ll2(&sc->part_ml[cta][hh][dp], tagf(M, F_PART), tagf(L, F_PART));
        }
        if (warp == 0) TSTAMP(6);
        {
            const int hq = cta >> 2, kvh = hq >> 2, hh = hq & 3;
            const int b = tid >> 7, dc = (tid >> 3) & 15, j = tid & 7;
            const int pc = (b * 8 + kvh) * 8 + j;
            const uint4* po = (const uint4*)&sc->part_o[pc][hh][0] + dc * 2;
            const uint2* pm = &sc->part_ml[pc - j][hh][0];
            uint4 vo0, vo1; uint2 vm[8];
            bool oko = false, okm = false;
            for (int it = 0;; it++) {
                if (!oko) { vo0 = ld_ll4(po); vo1 = ld_ll4(po + 1); }
                if (!okm) {
#pragma unroll
                    for (int jj = 0; jj < 8; jj++) vm[jj] = ld_ll2(pm + jj * 16);
                }
                oko = (vo0.x & vo0.y & vo0.z & vo0.w & vo1.x & vo1.y & vo1.z & vo1.w & 3u) == F_PART;
                uint32_t all = vm[0].x & vm[0].y;
#pragma unroll
                for (int jj = 1; jj < 8; jj++) all &= vm[jj].x & vm[jj].y;
                okm = (all & 3u) == F_PART;
                if (__all_sync(0xffffffffu, oko && okm) || it > SPIN_LIMIT) break;
                spin_cycles(A_BACKOFF);
            }
            float M = untag(vm[0].x);
#pragma unroll
            for (int jj = 1; jj < 8; jj++) M = fmaxf(M, untag(vm[jj].x));
            float wt = 0.f, L = 0.f;
#pragma unroll
            for (int jj = 0; jj < 8; jj++) {
                const float w_ = ex2((untag(vm[jj].x) - M) * LOG2E);
                L += w_ * untag(vm[jj].y);
                wt = jj == j ? w_ : wt;
            }
            wt *= rcp_approx(L);
            float v[8] = {wt * untag(vo0.x), wt * untag(vo0.y), wt * untag(vo0.z), wt * untag(vo0.w),
                          wt * untag(vo1.x), wt * untag(vo1.y), wt * untag(vo1.z), wt * untag(vo1.w)};
#define XRED(N, O)                                                                       \
            {                                                                            \
                const bool up = lane & (O);                                              \
                _Pragma("unroll") for (int i = 0; i < (N); i++) {                        \
                    const float send = up ? v[i] : v[i + (N)], keep = up ? v[i + (N)] : v[i]; \
                    v[i] = keep + __shfl_xor_sync(0xffffffffu, send, (O));               \
                }                                                                        \
            }
            XRED(4, 1) XRED(2, 2) XRED(1, 4)
#undef XRED
            __nv_bfloat16* os = (__nv_bfloat16*)(sgen + SM_OS);
            os[b * 128 + dc * 8 + 4 * (j & 1) + 2 * ((j >> 1) & 1) + (j >> 2)] = __float2bfloat16_rn(v[0]);
            if (warp == 0) TSTAMP(15);
            uint32_t wf[8][4];
            const uint32_t aoff_o = (warp >> 2) * 8192 + ((lane & 7) + (lane >> 4) * 8) * 128 +
                                    (((((warp & 3) * 2 + ((lane >> 3) & 1)) ^ (lane & 7))) << 4);
#pragma unroll
            for (int s = 0; s < 2; s++) {
                const int idx = IDX_WO + s;
                mbar_wait(bar_full + 8 * (idx % NST), (idx / NST) & 1);
                const uint32_t tb = sbase + SM_RING + (idx % NST) * TILE + aoff_o;
#pragma unroll
                for (int k4 = 0; k4 < 4; k4++) ldsm4t(tb + k4 * 2048, wf[s * 4 + k4]);
            }
            cons_sync();
            if (warp == 0) TSTAMP(7);
            const uint32_t* os32 = (const uint32_t*)(sgen + SM_OS) + bb * 64 + t;
            float y0[4] = {}, y1[4] = {};
#pragma unroll
            for (int ks = 0; ks < 8; ks += 2) {
                mma16816(y0, wf[ks], os32[8 * ks], os32[8 * ks + 4]);
                mma16816(y1, wf[ks + 1], os32[8 * ks + 8], os32[8 * ks + 12]);
            }
            if (t == 0)
                st_v4(&sc->inbox_wo[(cta & 3) * 8 + warp][hq][g], tagf(y0[0] + y1[0], F_WO), tagf(y0[1] + y1[1], F_WO),
                      tagf(y0[2] + y1[2], F_WO), tagf(y0[3] + y1[3], F_WO));
        }
        const uint32_t t_wo = clock32();
        if (warp == 0) TSTAMP(8);
        if (cta >= NCTA - NOWN) {
            const uint4* pin = &sc->inbox_wo[cta - (NCTA - NOWN)][0][0] + tid;
            uint4 v;
            spin_cycles(DELAY_B1);
            bool ok = false;
            for (int it = 0;; it++) {
                if (!ok) {
                    v = ld_ll4(pin);
                    ok = (v.x & v.y & v.z & v.w & 3u) == F_WO;
                }
                if (__all_sync(0xffffffffu, ok) || it > SPIN_LIMIT) break;
            }
            const bool u1 = lane & 8, u2 = lane & 16;
            const float a0 = untag(v.x), a1 = untag(v.y), a2 = untag(v.z), a3 = untag(v.w);
            const float k0 = (u1 ? a2 : a0) + __shfl_xor_sync(0xffffffffu, u1 ? a0 : a2, 8);
            const float k1 = (u1 ? a3 : a1) + __shfl_xor_sync(0xffffffffu, u1 ? a1 : a3, 8);
            red2[warp * 32 + lane] = (u2 ? k1 : k0) + __shfl_xor_sync(0xffffffffu, u2 ? k0 : k1, 16);
            cons_sync();
            if (warp == 0) {
                float a = 0.f;
#pragma unroll
                for (int w = 0; w < 8; w++) a += red2[w * 32 + lane];
                const float ga = (wcol & 1) ? bf_hi(m_ga.x) : bf_lo(m_ga.x);
                const float xm = bf16r(xo + bf16r(ga * bf16r(a)));
                const float xm_b1 = __shfl_down_sync(0xffffffffu, xm, 16);
                if (lane < 16) st_ll2(&sc->x1[wcol], pack_bf16(xm, xm_b1), F_X1);
                TSTAMP(10);
            }
        }
        const uint32_t aoff = warp * 2048 + ((lane & 7) + (lane >> 4) * 8) * 128 + ((((lane >> 3) & 1) ^ (lane & 7)) << 4);
        if (cta < NFFN) {
            uint32_t* pre = (uint32_t*)(sgen + SM_MRG) + warp * 192;
            float* abc = (float*)(sgen + SM_MRG + 8 * 192 * 4);
            const float c1v[4] = {bf16r(1.0f + bf_lo(m_cb.x)), bf16r(1.0f + bf_hi(m_cb.x)), bf16r(1.0f + bf_lo(m_cb.z)), bf16r(1.0f + bf_hi(m_cb.z))};
            *(uint2*)&pre[64 + eb * 32 + 2 * (lane & 15)] = make_uint2(pack_bf16(c1v[0], c1v[1]), pack_bf16(c1v[2], c1v[3]));
            *(uint2*)&pre[128 + eb * 32 + 2 * (lane & 15)] = make_uint2(m_sb.x, m_sb.z);
            float pivot2, xd[4];
            {
                const uint4* px = (const uint4*)&sc->x1[ec];
                const uint4* pp = (const uint4*)&sc->x1[0];
                uint4 va, vb, pa, pb;
                while (clock32() - t_wo < DELAY_X1) {}
                bool okx = false, okp = false;
                for (int it = 0;; it++) {
                    if (!okx) { va = ld_ll4(px); vb = ld_ll4(px + 1); }
                    if (!okp) { pa = ld_ll4(pp); pb = ld_ll4(pp + 1); }
                    okx = va.y == F_X1 && va.w == F_X1 && vb.y == F_X1 && vb.w == F_X1;
                    okp = pa.y == F_X1 && pa.w == F_X1 && pb.y == F_X1 && pb.w == F_X1;
                    if (__all_sync(0xffffffffu, okx && okp) || it > SPIN_LIMIT) break;
                }
                if (warp == 0) TSTAMP(9);
                const float xv[4] = {eb ? bf_hi(va.x) : bf_lo(va.x), eb ? bf_hi(va.z) : bf_lo(va.z),
                                     eb ? bf_hi(vb.x) : bf_lo(vb.x), eb ? bf_hi(vb.z) : bf_lo(vb.z)};
                const float p0 = 0.25f * ((bf_lo(pa.x) + bf_lo(pa.z)) + (bf_lo(pb.x) + bf_lo(pb.z)));
                const float p1 = 0.25f * ((bf_hi(pa.x) + bf_hi(pa.z)) + (bf_hi(pb.x) + bf_hi(pb.z)));
                const float pivot = eb ? p1 : p0;
                pivot2 = (lane & 1) ? p1 : p0;
                *(uint2*)&pre[eb * 32 + 2 * (lane & 15)] =
                    make_uint2(pack_bf16((xv[0] - pivot) * c1v[0], (xv[1] - pivot) * c1v[1]),
                               pack_bf16((xv[2] - pivot) * c1v[2], (xv[3] - pivot) * c1v[3]));
                __syncwarp();
#pragma unroll
                for (int i = 0; i < 4; i++) xd[i] = xv[i] - pivot;
            }
            {
                uint32_t bf[8];
                const uint32_t* pb = pre + (g >> 1 < 2 ? g >> 1 : 2) * 64 + bb * 32 + t;
#pragma unroll
                for (int i = 0; i < 8; i++) bf[i] = pb[8 * (i >> 1) + 4 * (i & 1)];
                mbar_wait(bar_gu + 8 * (2 * (warp >> 1)), 0);
                mbar_wait(bar_gu + 8 * (2 * (warp >> 1) + 1), 0);
                if (warp == 0) TSTAMP(11);
                const uint32_t tg = sbase + SM_RING + (IDX_WG % NST) * TILE, tu = sbase + SM_RING + (IDX_WU % NST) * TILE;
                float cg[2][4] = {}, cu[2][4] = {};
#pragma unroll
                for (int s = 0; s < 4; s++) {
                    const int row = 64 * warp + 16 * s + (lane & 7) + (lane >> 4) * 8;
                    const uint32_t off = row * 32 + ((((lane >> 3) & 1) ^ ((row >> 2) & 1)) << 4);
                    uint32_t ga_[4], ua_[4];
                    ldsm4t(tg + off, ga_);
                    ldsm4t(tu + off, ua_);
                    mma16816(cg[s & 1], ga_, bf[2 * s], bf[2 * s + 1]);
                    mma16816(cu[s & 1], ua_, bf[2 * s], bf[2 * s + 1]);
                }
                const float2 ps = half_warp_sums(xd, 0.f);
                if ((lane & 15) == 0) stat[warp * 2 + eb] = ps;
                if (t < 3) {
                    float* dg = abc + warp * 192 + t * 32;
                    *(float2*)&dg[g * 2] = make_float2(cg[0][0] + cg[1][0], cg[0][1] + cg[1][1]);
                    *(float2*)&dg[(g + 8) * 2] = make_float2(cg[0][2] + cg[1][2], cg[0][3] + cg[1][3]);
                    *(float2*)&dg[96 + g * 2] = make_float2(cu[0][0] + cu[1][0], cu[0][1] + cu[1][1]);
                    *(float2*)&dg[96 + (g + 8) * 2] = make_float2(cu[0][2] + cu[1][2], cu[0][3] + cu[1][3]);
                }
            }
            uint32_t df[4][4];
            mbar_wait(bar_full + 8 * (IDX_WD % NST), (IDX_WD / NST) & 1);
#pragma unroll
            for (int mt = 0; mt < 4; mt++) ldsm4t((sbase + SM_RING + (IDX_WD % NST) * TILE + aoff) ^ (mt << 5), df[mt]);
            cons_sync();
            {
                float sm6[6] = {0.f, 0.f, 0.f, 0.f, 0.f, 0.f};
#pragma unroll
                for (int w = 0; w < 8; w++)
#pragma unroll
                    for (int k = 0; k < 6; k++) sm6[k] += abc[w * 192 + k * 32 + lane];
                float mean_bf, rstd;
                ln_stats(stat, lane & 1, pivot2, mean_bf, rstd);
                const float dm = mean_bf - pivot2;
                const float gs = bf16r(rstd * (sm6[0] - dm * sm6[1]) + sm6[2]);
                const float us = rstd * (sm6[3] - dm * sm6[4]) + sm6[5];
                const float u2 = gs * (1.0f + 0.044715f * gs * gs) * (2.0f * 0.7978845608028654f * LOG2E);
                const float ge = bf16r(__fdividef(gs, 1.0f + ex2(-u2)));
                const float act = bf16r(ge * bf16r(us));
                const float a0 = __shfl_sync(0xffffffffu, act, 4 * t + bb), a1 = __shfl_sync(0xffffffffu, act, 4 * t + 2 + bb);
                const float a2 = __shfl_sync(0xffffffffu, act, 4 * t + 16 + bb), a3 = __shfl_sync(0xffffffffu, act, 4 * t + 18 + bb);
                const uint32_t b0 = pack_bf16(a0, a1), b1 = pack_bf16(a2, a3);
                float y[4][4] = {};
#pragma unroll
                for (int mt = 0; mt < 4; mt++) mma16816(y[mt], df[mt], b0, b1);
                float v[4];
#pragma unroll
                for (int i = 0; i < 4; i++) v[i] = t == 0 ? y[0][i] : t == 1 ? y[1][i] : t == 2 ? y[2][i] : y[3][i];
            {
                const bool odd = g & 1;
                const float sx = odd ? v[0] : v[2], sy = odd ? v[1] : v[3];
                const float rx = __shfl_xor_sync(0xffffffffu, sx, 4), ry = __shfl_xor_sync(0xffffffffu, sy, 4);
                const int c0 = 64 * warp + 16 * t + (odd ? g + 7 : g);
                const float e0 = odd ? rx : v[0], e1 = odd ? ry : v[1], e2 = odd ? v[2] : rx, e3 = odd ? v[3] : ry;
                st_v4(&sc->inbox_dn[c0 >> 2][cta][(c0 >> 1) & 1], tagf(e0, F_DOWN), tagf(e1, F_DOWN), tagf(e2, F_DOWN), tagf(e3, F_DOWN));
            }
            }
            if (warp == 0) TSTAMP(12);
        }
        {
            uint2 xw;
            float r0;
            {
                const uint4* pin = &sc->inbox_dn[cta][0][0] + tid;
                uint4 v = make_uint4(F_DOWN, F_DOWN, F_DOWN, F_DOWN);
                if (cta < NFFN) spin_cycles(DELAY_C);
                else while (clock32() - t_wo < DELAY_X1 + DELAY_NOFFN) {}
                xw = ld_ll2(&sc->x1[ocol]);
                bool ok = tid >= NFFN * 2;
                for (int it = 0;; it++) {
                    if (!ok) {
                        v = ld_ll4(pin);
                        ok = (v.x & v.y & v.z & v.w & 3u) == F_DOWN;
                    }
                    if (__all_sync(0xffffffffu, ok) || it > SPIN_LIMIT) break;
                }
                const bool u1 = lane & 2, u2 = lane & 4;
                const float a0 = untag(v.x), a1 = untag(v.y), a2 = untag(v.z), a3 = untag(v.w);
                const float k0 = (u1 ? a1 : a0) + __shfl_xor_sync(0xffffffffu, u1 ? a0 : a1, 2);
                const float k1 = (u1 ? a3 : a2) + __shfl_xor_sync(0xffffffffu, u1 ? a2 : a3, 2);
                r0 = (u2 ? k1 : k0) + __shfl_xor_sync(0xffffffffu, u2 ? k0 : k1, 4);
                r0 += __shfl_xor_sync(0xffffffffu, r0, 8);
                r0 += __shfl_xor_sync(0xffffffffu, r0, 16);
                if (lane < 8) red2[256 + warp * 8 + (2 * (lane & 1) + ((lane >> 2) & 1)) * 2 + ((lane >> 1) & 1)] = r0;
            }
            cons_sync();
            if (warp == 0) {
                float a0 = 0.f, a1 = 0.f;
#pragma unroll
                for (int w = 0; w < 8; w++) { const float2 v = *(const float2*)&red2[256 + w * 8 + (lane & 3) * 2]; a0 += v.x; a1 += v.y; }
                const bool hi = ocol & 1;
                const float gb0 = hi ? bf_hi(m_gb0.x) : bf_lo(m_gb0.x), gb1 = hi ? bf_hi(m_gb1.x) : bf_lo(m_gb1.x);
                for (int it = 0; !__all_sync(0xffffffffu, xw.y == F_X1) && it < SPIN_LIMIT; it++) xw = ld_ll2(&sc->x1[ocol]);
                if (lane < 4) {
                    p.out[ocol] = __float2bfloat16_rn(bf_lo(xw.x) + bf16r(gb0 * bf16r(a0)));
                    p.out[D_MODEL + ocol] = __float2bfloat16_rn(bf_hi(xw.x) + bf16r(gb1 * bf16r(a1)));
                }
                if (cta == 0 && lane == 0) *(volatile unsigned*)&sc->epoch = tag;
                TSTAMP(13);
            }
        }
    }
}

typedef CUresult (*EncodeFn)(CUtensorMap*, CUtensorMapDataType, cuuint32_t, void*, const cuuint64_t*, const cuuint64_t*,
                             const cuuint32_t*, const cuuint32_t*, CUtensorMapInterleave, CUtensorMapSwizzle,
                             CUtensorMapL2promotion, CUtensorMapFloatOOBfill);

struct Maps { CUtensorMap k, v, wq, wmod, wmod8, wo, wg, wu, wd; };

void encode(EncodeFn fn, CUtensorMap* m, const void* ptr, int rank, const cuuint64_t* dims, const cuuint64_t* strides,
            const cuuint32_t* box, CUtensorMapSwizzle sw) {
    const cuuint32_t es[3] = {1, 1, 1};
    fn(m, CU_TENSOR_MAP_DATA_TYPE_BFLOAT16, rank, const_cast<void*>(ptr), dims, strides, box, es,
       CU_TENSOR_MAP_INTERLEAVE_NONE, sw, CU_TENSOR_MAP_L2_PROMOTION_L2_256B, CU_TENSOR_MAP_FLOAT_OOB_FILL_NONE);
}

}

extern "C" void kernel_launch(void* const* d_in, const int* in_sizes, int n_in, void* d_out, int out_size) {
    (void)in_sizes; (void)n_in; (void)out_size;
    static EncodeFn enc = nullptr;
    static Scratch* scratch = nullptr;
    if (!enc) {
        cudaGetSymbolAddress((void**)&scratch, g_scratch);
        void* fn = nullptr;
        cudaDriverEntryPointQueryResult qr;
        cudaGetDriverEntryPoint("cuTensorMapEncodeTiled", &fn, cudaEnableDefault, &qr);
        enc = (EncodeFn)fn;
        cudaFuncSetAttribute(fused_block_kernel, cudaFuncAttributeMaxDynamicSharedMemorySize, SMEM_BYTES);
    }
    Maps m;
    {
        const cuuint64_t dims[3] = {64, (cuuint64_t)16 * SK, 2}, str[2] = {256, 128};
        const cuuint32_t box[3] = {64, 64, 2};
        encode(enc, &m.k, d_in[1], 3, dims, str, box, CU_TENSOR_MAP_SWIZZLE_128B);
        encode(enc, &m.v, d_in[2], 3, dims, str, box, CU_TENSOR_MAP_SWIZZLE_128B);
    }
    {
        const cuuint64_t dims[2] = {4096, 512}, str[1] = {8192};
        const cuuint32_t box[2] = {32, 256};
        encode(enc, &m.wq, d_in[3], 2, dims, str, box, CU_TENSOR_MAP_SWIZZLE_64B);
    }
    {
        const cuuint64_t dims[2] = {N_MOD, 512}, str[1] = {N_MOD * 2};
        const cuuint32_t box[2] = {16, 256};
        encode(enc, &m.wmod, d_in[10], 2, dims, str, box, CU_TENSOR_MAP_SWIZZLE_32B);
        const cuuint32_t box8[2] = {8, 256};
        encode(enc, &m.wmod8, d_in[10], 2, dims, str, box8, CU_TENSOR_MAP_SWIZZLE_NONE);
    }
    {
        const cuuint64_t dims_o[3] = {64, 4096, 8}, dims_d[3] = {64, D_FF, 8}, str[2] = {1024, 128};
        const cuuint32_t box[3] = {64, 16, 8}, box_o[3] = {64, 64, 2};
        encode(enc, &m.wo, d_in[4], 3, dims_o, str, box_o, CU_TENSOR_MAP_SWIZZLE_128B);
        encode(enc, &m.wd, d_in[8], 3, dims_d, str, box, CU_TENSOR_MAP_SWIZZLE_128B);
    }
    {
        const cuuint64_t dims[2] = {D_FF, 512}, str[1] = {D_FF * 2};
        const cuuint32_t box[2] = {16, 128};
        encode(enc, &m.wg, d_in[6], 2, dims, str, box, CU_TENSOR_MAP_SWIZZLE_32B);
        encode(enc, &m.wu, d_in[7], 2, dims, str, box, CU_TENSOR_MAP_SWIZZLE_32B);
    }
    Params p;
    p.x = (const __nv_bfloat16*)d_in[0];
    p.c = (const __nv_bfloat16*)d_in[9];
    p.out = (__nv_bfloat16*)d_out;
    p.sc = scratch;
    fused_block_kernel<<<NCTA, NTHREADS, SMEM_BYTES, cudaStreamPerThread>>>(p, m.k, m.v, m.wq, m.wmod, m.wmod8, m.wo, m.wg, m.wu, m.wd);
}
```

```cpp
#include <cuda_runtime.h>
#include <cuda.h>
#include <cuda_bf16.h>
#include <stdint.h>

namespace {

constexpr int D_MODEL = 512;
constexpr int N_HEADS = 32;
constexpr int SK = 32768;
constexpr int DH = 128;
constexpr int D_FF = 1792;
constexpr int N_MOD = 6 * D_MODEL;

constexpr int NCTA = 128;
constexpr int NFFN = D_FF / 16;
constexpr int NOWN = 32;
constexpr int NTHREADS = 320;
constexpr int NST = 12;
constexpr int TILE = 16384;
#define WINDOW 3
#define WINDOW_TAIL 1
#define GU_WIN 3
#define GU_EARLY 0
#define WD_WIN 2
#define PACE_THR 96
constexpr int KV_TILES = 64;
#define MOD_AT 8
static_assert(MOD_AT % 2 == 0 && MOD_AT >= 2 && MOD_AT < 56, "schedule");
__host__ __device__ constexpr int kv_idx(int i) { return 2 + 2 * i + (i >= MOD_AT ? 1 : 0); }
constexpr int IDX_MOD = 2 + 2 * MOD_AT;
constexpr int N_STREAM = kv_idx(KV_TILES - 1) + 2;
constexpr int IDX_WO = N_STREAM;
constexpr int IDX_WG = IDX_WO + 2;
constexpr int IDX_WU = IDX_WG + 1;
constexpr int IDX_WD = IDX_WU + 1;
constexpr int SPIN_LIMIT = 1 << 20;

constexpr float LOG2E = 1.4426950408889634f;
constexpr float QK_SCALE = 0.08838834764831845f;

constexpr int SM_RING = 0;
constexpr int SM_MRG = SM_RING + NST * TILE;
constexpr int SM_ML = SM_MRG + 8 * 4 * 136 * 4;
constexpr int SM_RED = SM_ML + 8 * 4 * 8;
constexpr int SM_RED2 = SM_RED + 8 * 64 * 4;
constexpr int SM_QS = SM_RED2 + 8 * 64 * 4;
constexpr int SM_OS = SM_QS + 512 * 2;
constexpr int SM_SC = SM_OS + 2 * 128 * 2;
constexpr int SM_HS = SM_SC + 2 * 512 * 2;
constexpr int SM_STAT = SM_HS + 8 * 2 * 32 * 4;
constexpr int SM_PACE = SM_STAT + 8 * 2 * 8;
constexpr int SM_BAR = SM_PACE + 8;
constexpr int SM_END = SM_BAR + (2 * NST + 1 + 8 + 2) * 8;
constexpr int SMEM_BYTES = SM_END + 1024;

struct Scratch {
    uint4 inbox_wo[NOWN][N_HEADS][8];
    uint4 inbox_dn[NCTA][NFFN][2];
    uint2 x1[D_MODEL];
    uint2 part_o[NCTA][4][64];
    uint2 part_ml[NCTA][4][4];
    uint2 mod[2][N_MOD / 2];
    uint2 q[2][N_HEADS * DH / 2];
    unsigned epoch;
    unsigned pad_[31];
    unsigned cleared;
    unsigned pad2_[31];
    unsigned progress;
};
__device__ Scratch g_scratch;
constexpr uint32_t F_PART = 1, F_WO = 1, F_DOWN = 1, F_X1 = 1;
__device__ __forceinline__ uint32_t tagf(float v, uint32_t f) { return (__float_as_uint(v) & ~3u) | f; }
__device__ __forceinline__ float untag(uint32_t v) { return __uint_as_float(v & ~3u); }

struct Params {
    const __nv_bfloat16* x;
    const __nv_bfloat16* c;
    __nv_bfloat16* out;
    Scratch* sc;
};

#define TSTAMP(i) do { } while (0)

__device__ __forceinline__ uint32_t smem_u32(const void* p) { return (uint32_t)__cvta_generic_to_shared(p); }

__device__ __forceinline__ void mbar_init(uint32_t bar, uint32_t cnt) {
    asm volatile("mbarrier.init.shared::cta.b64 [%0], %1;" ::"r"(bar), "r"(cnt) : "memory");
}
__device__ __forceinline__ void mbar_expect_tx(uint32_t bar, uint32_t bytes) {
    asm volatile("mbarrier.arrive.expect_tx.shared::cta.b64 _, [%0], %1;" ::"r"(bar), "r"(bytes) : "memory");
}
__device__ __forceinline__ void mbar_arrive(uint32_t bar) {
    asm volatile("mbarrier.arrive.shared::cta.b64 _, [%0];" ::"r"(bar) : "memory");
}
__device__ __forceinline__ bool mbar_try(uint32_t bar, uint32_t parity) {
    uint32_t ok;
    asm volatile(
        "{\n\t.reg .pred p;\n\t"
        "mbarrier.try_wait.parity.shared::cta.b64 p, [%1], %2;\n\t"
        "selp.u32 %0, 1, 0, p;\n\t}"
        : "=r"(ok) : "r"(bar), "r"(parity) : "memory");
    return ok != 0;
}
__device__ __forceinline__ bool mbar_test(uint32_t bar, uint32_t parity) {
    uint32_t ok;
    asm volatile(
        "{\n\t.reg .pred p;\n\t"
        "mbarrier.test_wait.parity.shared::cta.b64 p, [%1], %2;\n\t"
        "selp.u32 %0, 1, 0, p;\n\t}"
        : "=r"(ok) : "r"(bar), "r"(parity) : "memory");
    return ok != 0;
}
__device__ __forceinline__ void mbar_wait(uint32_t bar, uint32_t parity) {
    if (mbar_try(bar, parity)) return;
    const long long t0 = clock64();
    while (!mbar_try(bar, parity))
        if (clock64() - t0 > (1ll << 31)) return;
}
__device__ __forceinline__ void cons_sync() { asm volatile("bar.sync 1, 256;" ::: "memory"); }

__device__ __forceinline__ void tma_2d(uint32_t dst, const CUtensorMap* m, int c0, int c1, uint32_t bar) {
    asm volatile("cp.async.bulk.tensor.2d.shared::cluster.global.mbarrier::complete_tx::bytes [%0], [%1, {%3, %4}], [%2];"
                 ::"r"(dst), "l"(m), "r"(bar), "r"(c0), "r"(c1) : "memory");
}
__device__ __forceinline__ void tma_3d(uint32_t dst, const CUtensorMap* m, int c0, int c1, int c2, uint32_t bar) {
    asm volatile("cp.async.bulk.tensor.3d.shared::cluster.global.mbarrier::complete_tx::bytes [%0], [%1, {%3, %4, %5}], [%2];"
                 ::"r"(dst), "l"(m), "r"(bar), "r"(c0), "r"(c1), "r"(c2) : "memory");
}
__device__ __forceinline__ void tma_3d_hint(uint32_t dst, const CUtensorMap* m, int c0, int c1, int c2, uint32_t bar, uint64_t pol) {
    asm volatile("cp.async.bulk.tensor.3d.shared::cluster.global.mbarrier::complete_tx::bytes.L2::cache_hint [%0], [%1, {%3, %4, %5}], [%2], %6;"
                 ::"r"(dst), "l"(m), "r"(bar), "r"(c0), "r"(c1), "r"(c2), "l"(pol) : "memory");
}
__device__ __forceinline__ void prefetch_tmap(const CUtensorMap* m) {
    asm volatile("prefetch.tensormap [%0];" ::"l"(m) : "memory");
}

__device__ __forceinline__ void ldsm4(uint32_t addr, uint32_t (&r)[4]) {
    asm volatile("ldmatrix.sync.aligned.m8n8.x4.shared.b16 {%0,%1,%2,%3}, [%4];"
                 : "=r"(r[0]), "=r"(r[1]), "=r"(r[2]), "=r"(r[3]) : "r"(addr) : "memory");
}
__device__ __forceinline__ void ldsm4t(uint32_t addr, uint32_t (&r)[4]) {
    asm volatile("ldmatrix.sync.aligned.m8n8.x4.trans.shared.b16 {%0,%1,%2,%3}, [%4];"
                 : "=r"(r[0]), "=r"(r[1]), "=r"(r[2]), "=r"(r[3]) : "r"(addr) : "memory");
}
__device__ __forceinline__ void mma16816(float (&c)[4], const uint32_t (&a)[4], uint32_t b0, uint32_t b1) {
    asm volatile("mma.sync.aligned.m16n8k16.row.col.f32.bf16.bf16.f32 {%0,%1,%2,%3}, {%4,%5,%6,%7}, {%8,%9}, {%0,%1,%2,%3};"
                 : "+f"(c[0]), "+f"(c[1]), "+f"(c[2]), "+f"(c[3])
                 : "r"(a[0]), "r"(a[1]), "r"(a[2]), "r"(a[3]), "r"(b0), "r"(b1));
}
__device__ __forceinline__ uint32_t movmatrix_t(uint32_t a) {
    uint32_t d;
    asm volatile("movmatrix.sync.aligned.m8n8.trans.b16 %0, %1;" : "=r"(d) : "r"(a));
    return d;
}
__device__ __forceinline__ uint32_t pack_bf16(float a, float b) {
    uint32_t r;
    asm("cvt.rn.bf16x2.f32 %0, %1, %2;" : "=r"(r) : "f"(b), "f"(a));
    return r;
}
__device__ __forceinline__ float bf_lo(uint32_t v) { return __uint_as_float(v << 16); }
__device__ __forceinline__ float bf_hi(uint32_t v) { return __uint_as_float(v & 0xffff0000u); }
__device__ __forceinline__ float bf16r(float a) { return bf_lo(pack_bf16(a, 0.f)); }
__device__ __forceinline__ uint32_t max_bf16x2(uint32_t a, uint32_t b) {
    uint32_t r;
    asm("max.bf16x2 %0, %1, %2;" : "=r"(r) : "r"(a), "r"(b));
    return r;
}
__device__ __forceinline__ float ex2(float x) {
    float r;
    asm("ex2.approx.ftz.f32 %0, %1;" : "=f"(r) : "f"(x));
    return r;
}

__device__ __forceinline__ void st_ll2(uint2* p, uint32_t v, uint32_t tag) {
    asm volatile("st.relaxed.gpu.global.v2.u32 [%0], {%1, %2};" ::"l"(p), "r"(v), "r"(tag) : "memory");
}
__device__ __forceinline__ void st_ll4(uint4* p, uint32_t v0, uint32_t v1, uint32_t tag) {
    asm volatile("st.relaxed.gpu.global.v4.u32 [%0], {%1, %2, %3, %2};" ::"l"(p), "r"(v0), "r"(tag), "r"(v1) : "memory");
}
__device__ __forceinline__ void st_v4(uint4* p, uint32_t a, uint32_t b, uint32_t c, uint32_t d) {
    asm volatile("st.relaxed.gpu.global.v4.u32 [%0], {%1, %2, %3, %4};" ::"l"(p), "r"(a), "r"(b), "r"(c), "r"(d) : "memory");
}
__device__ __forceinline__ uint2 ld_ll2(const uint2* p) {
    uint2 v;
    asm volatile("ld.relaxed.gpu.global.v2.u32 {%0, %1}, [%2];" : "=r"(v.x), "=r"(v.y) : "l"(p) : "memory");
    return v;
}
__device__ __forceinline__ uint4 ld_ll4(const uint4* p) {
    uint4 v;
    asm volatile("ld.relaxed.gpu.global.v4.u32 {%0, %1, %2, %3}, [%4];"
                 : "=r"(v.x), "=r"(v.y), "=r"(v.z), "=r"(v.w) : "l"(p) : "memory");
    return v;
}

#define DELAY_B1 300
#define DELAY_X1 2000
#define DELAY_NOFFN 1500
#define A_BACKOFF 0
#define DELAY_C 600
__device__ __forceinline__ uint32_t clock32() {
    uint32_t c;
    asm volatile("mov.u32 %0, %clock;" : "=r"(c));
    return c;
}
__device__ __forceinline__ void spin_cycles(uint32_t n) {
    if (n > 0) { const uint32_t c0 = clock32(); while (clock32() - c0 < n) {} }
}
__device__ __forceinline__ float rcp_approx(float x) {
    float r;
    asm("rcp.approx.ftz.f32 %0, %1;" : "=f"(r) : "f"(x));
    return r;
}
__device__ __forceinline__ float sqrt_approx(float x) {
    float r;
    asm("sqrt.approx.f32 %0, %1;" : "=f"(r) : "f"(x));
    return r;
}

__device__ __forceinline__ float silu_bf(float v) { return bf16r(v / (1.0f + expf(-v))); }

__device__ __forceinline__ float2 half_warp_sums(const float (&v)[4], float pivot) {
    float s1 = 0.f, s2 = 0.f;
#pragma unroll
    for (int i = 0; i < 4; i++) { const float d = v[i] - pivot; s1 += d; s2 += d * d; }
#pragma unroll
    for (int o = 1; o < 16; o <<= 1) { s1 += __shfl_xor_sync(0xffffffffu, s1, o); s2 += __shfl_xor_sync(0xffffffffu, s2, o); }
    return make_float2(s1, s2);
}
__device__ __forceinline__ void ln_stats(const float2* stat, int b, float pivot, float& mean_bf, float& rstd) {
    float s1 = 0.f, s2 = 0.f;
#pragma unroll
    for (int w = 0; w < 8; w++) { const float2 v = stat[w * 2 + b]; s1 += v.x; s2 += v.y; }
    const float dm = s1 * (1.0f / D_MODEL);
    const float var = fmaxf(s2 * (1.0f / D_MODEL) - dm * dm, 0.f);
    mean_bf = bf16r(pivot + dm);
    rstd = rcp_approx(bf16r(sqrt_approx(bf16r(bf16r(var) + 1e-5f))));
}
__device__ __forceinline__ float ln_norm(float xv, float mean_bf, float rstd) { return bf16r(bf16r(xv - mean_bf) * rstd); }
__device__ __forceinline__ float ln_mod(float n, float cmul, float sadd) { return bf16r(n * bf16r(1.0f + cmul)) + sadd; }

__global__ void __launch_bounds__(NTHREADS, 1)
fused_block_kernel(const Params p, const __grid_constant__ CUtensorMap tm_k, const __grid_constant__ CUtensorMap tm_v,
                   const __grid_constant__ CUtensorMap tm_wq, const __grid_constant__ CUtensorMap tm_wmod,
                   const __grid_constant__ CUtensorMap tm_wmod8,
                   const __grid_constant__ CUtensorMap tm_wo, const __grid_constant__ CUtensorMap tm_wg,
                   const __grid_constant__ CUtensorMap tm_wu, const __grid_constant__ CUtensorMap tm_wd) {
    extern __shared__ unsigned char smem_raw[];
    const uint32_t sbase = (smem_u32(smem_raw) + 1023u) & ~1023u;
    unsigned char* sgen = smem_raw + (sbase - smem_u32(smem_raw));
    const int tid = threadIdx.x, warp = tid >> 5, lane = tid & 31;
    const int cta = blockIdx.x;
    const uint32_t bar_full = sbase + SM_BAR, bar_empty = bar_full + NST * 8;
    const uint32_t bar_clear = bar_empty + NST * 8;
    const uint32_t bar_gu = bar_clear + 8;
    const uint32_t bar_bc = bar_gu + 8 * 8;
    const uint32_t bar_p0w = bar_bc + 8;

    const int key0 = (cta >> 3) * SK + (cta & 7) * 64;
    uint64_t pol = 0;
    if (tid == 256) {
        asm volatile("createpolicy.fractional.L2::evict_first.b64 %0, 1.0;" : "=l"(pol));
        mbar_init(bar_p0w, 1);
#pragma unroll
        for (int i = 0; i < 4; i++) mbar_init(bar_full + 8 * i, 1);
        asm volatile("fence.mbarrier_init.release.cluster;" ::: "memory");
        mbar_expect_tx(bar_p0w, 8192);
        tma_2d(sbase + SM_MRG, &tm_wmod8, cta * 8, 0, bar_p0w);
        tma_2d(sbase + SM_MRG + 4096, &tm_wmod8, cta * 8, 256, bar_p0w);
#pragma unroll
        for (int i = 0; i < 4; i++) mbar_expect_tx(bar_full + 8 * i, TILE);
        tma_2d(sbase + SM_RING, &tm_wq, cta * 32, 0, bar_full);
        tma_2d(sbase + SM_RING + TILE, &tm_wq, cta * 32, 256, bar_full + 8);
        tma_3d_hint(sbase + SM_RING + 2 * TILE, &tm_k, 0, key0, 0, bar_full + 16, pol);
        tma_3d_hint(sbase + SM_RING + 3 * TILE, &tm_v, 0, key0, 0, bar_full + 24, pol);
    }

    if (warp == 8) {
        if (lane == 0) {
            for (int i = 0; i < NST; i++) { if (i >= 4) mbar_init(bar_full + 8 * i, 1); mbar_init(bar_empty + 8 * i, 4); }
            mbar_init(bar_clear, 1);
            for (int k = 0; k < 8; k++) mbar_init(bar_gu + 8 * k, 1);
            mbar_init(bar_bc, 8);
            ((volatile uint32_t*)(sgen + SM_PACE))[0] = 0;
            ((volatile uint32_t*)(sgen + SM_PACE))[1] = WINDOW;
            asm volatile("fence.mbarrier_init.release.cluster;" ::: "memory");
        }
        __syncwarp();
        asm volatile("bar.arrive 2, 320;" ::: "memory");
        asm volatile("bar.arrive 3, 64;" ::: "memory");
        if (lane == 0) {
            int slot = 4; uint32_t ph = 1;
            int landed = 0, wslot = 0; uint32_t wph = 0;
            int kv = 2;
            auto wait_window = [&](int idx, int window) {
                while (landed + window <= idx) {
                    mbar_wait(bar_full + 8 * wslot, wph);
                    if (++wslot == NST) { wslot = 0; wph ^= 1; }
                    landed++;
                }
            };
            volatile uint32_t* pace = (volatile uint32_t*)(sgen + SM_PACE);
            prefetch_tmap(&tm_wmod);
            pace[0] = 4;
            for (int idx = 4; idx < N_STREAM; idx++) {
                if (idx >= NST) mbar_wait(bar_empty + 8 * slot, ph);
                wait_window(idx, (int)pace[1]);
                if (idx == 12) { prefetch_tmap(&tm_wo); prefetch_tmap(&tm_wg); prefetch_tmap(&tm_wu); prefetch_tmap(&tm_wd); }
                const uint32_t fb = bar_full + 8 * slot, dst = sbase + SM_RING + slot * TILE;
                mbar_expect_tx(fb, TILE);
                if (idx == IDX_MOD) {
                    tma_2d(dst, &tm_wmod, 1024 + cta * 16, 0, fb);
                    tma_2d(dst + 8192, &tm_wmod, 1024 + cta * 16, 256, fb);
                } else {
                    tma_3d_hint(dst, (kv & 1) ? &tm_v : &tm_k, 0, key0 + (kv >> 1) * 512, 0, fb, pol);
                    kv++;
                }
                pace[0] = idx + 1;
                if (++slot == NST) { slot = 0; ph ^= 1; }
            }
            auto slot_free = [&](int idx) { mbar_wait(bar_empty + 8 * (idx % NST), ((idx / NST) & 1) ^ 1); };
#pragma unroll
            for (int s = 0; s < 2; s++) {
                const int idx = IDX_WO + s;
                slot_free(idx);
                wait_window(idx, WINDOW_TAIL);
                mbar_expect_tx(bar_full + 8 * (idx % NST), TILE);
                tma_3d(sbase + SM_RING + (idx % NST) * TILE, &tm_wo, 0, (cta >> 2) * 128 + s * 64, (cta & 3) * 2, bar_full + 8 * (idx % NST));
            }
            if (cta < NFFN) {
                slot_free(IDX_WG); slot_free(IDX_WU);
#pragma unroll
                for (int st = 0; st < 8; st++) {
                    if (st == GU_EARLY) {
                        mbar_wait(bar_full + 8 * (IDX_WO % NST), (IDX_WO / NST) & 1);
                        mbar_wait(bar_full + 8 * ((IDX_WO + 1) % NST), ((IDX_WO + 1) / NST) & 1);
                    }
                    if (st >= GU_WIN) mbar_wait(bar_gu + 8 * (st - GU_WIN), 0);
                    mbar_expect_tx(bar_gu + 8 * st, 4096);
                    tma_2d(sbase + SM_RING + (((st & 1) ? IDX_WU : IDX_WG) % NST) * TILE + (st >> 1) * 4096,
                           (st & 1) ? &tm_wu : &tm_wg, cta * 16, (st >> 1) * 128, bar_gu + 8 * st);
                }
                mbar_wait(bar_gu + 8 * (8 - WD_WIN), 0);
                slot_free(IDX_WD);
                mbar_expect_tx(bar_full + 8 * (IDX_WD % NST), TILE);
                tma_3d(sbase + SM_RING + (IDX_WD % NST) * TILE, &tm_wd, 0, cta * 16, 0, bar_full + 8 * (IDX_WD % NST));
            }
        }
    } else if (warp == 9) {
        Scratch* const sc = p.sc;
        const uint32_t tag = *(volatile unsigned*)&sc->epoch + 1;
        if (lane < 2) {
            st_ll4((uint4*)&sc->mod[lane][cta * 4], 0u, 0u, 0u);
            st_ll4((uint4*)&sc->mod[lane][cta * 4] + 1, 0u, 0u, 0u);
        }
        if (lane < 8) st_ll4((uint4*)&sc->mod[lane >> 2][512 + cta * 8] + (lane & 3), 0u, 0u, 0u);
        if (lane < 16) st_ll4((uint4*)&sc->q[lane >> 3][cta * 16] + (lane & 7), 0u, 0u, 0u);
        __syncwarp();
        asm volatile("bar.arrive 2, 320;" ::: "memory");
        asm volatile("bar.sync 3, 64;" ::: "memory");
#pragma unroll 4
        for (int i = 0; i < NFFN * 2 / 32; i++) st_v4(&sc->inbox_dn[cta][0][0] + i * 32 + lane, 0u, 0u, 0u, 0u);
        if (cta >= NCTA - NOWN) {
#pragma unroll 4
            for (int i = 0; i < 8; i++) st_v4(&sc->inbox_wo[cta - (NCTA - NOWN)][0][0] + i * 32 + lane, 0u, 0u, 0u, 0u);
            if (lane < 8) st_v4((uint4*)&sc->x1[(cta - (NCTA - NOWN)) * 16] + lane, 0u, 0u, 0u, 0u);
        }
#pragma unroll 4
        for (int i = 0; i < 4; i++) st_v4((uint4*)&sc->part_o[cta][0][0] + i * 32 + lane, 0u, 0u, 0u, 0u);
        if (lane < 8) st_v4((uint4*)&sc->part_ml[cta][0][0] + lane, 0u, 0u, 0u, 0u);
        if (cta == 0 && lane == 0) asm volatile("st.relaxed.gpu.global.u32 [%0], %1;" ::"l"(&sc->progress), "r"(0u) : "memory");
        asm volatile("fence.acq_rel.gpu;" ::: "memory");
        __syncwarp();
        if (lane == 0) {
            asm volatile("fence.acq_rel.gpu;" ::: "memory");
            asm volatile("red.relaxed.gpu.global.add.u32 [%0], %1;" ::"l"(&sc->cleared), "r"(1u) : "memory");
            const uint32_t target = tag * NCTA;
            for (int it = 0; it < SPIN_LIMIT; it++) {
                uint32_t v;
                asm volatile("ld.relaxed.gpu.global.u32 %0, [%1];" : "=r"(v) : "l"(&sc->cleared) : "memory");
                if ((int32_t)(v - target) >= 0) break;
                __nanosleep(500);
            }
            asm volatile("fence.acq_rel.gpu;" ::: "memory");
            mbar_arrive(bar_clear);
            volatile uint32_t* pace = (volatile uint32_t*)(sgen + SM_PACE);
            uint32_t posted = 0;
            for (int it = 0; it < SPIN_LIMIT; it++) {
                const uint32_t own = pace[0];
                if (own >= N_STREAM) break;
                if (own > posted) {
                    asm volatile("red.relaxed.gpu.global.add.u32 [%0], %1;" ::"l"(&sc->progress), "r"(own - posted) : "memory");
                    posted = own;
                }
                uint32_t v;
                asm volatile("ld.relaxed.gpu.global.u32 %0, [%1];" : "=r"(v) : "l"(&sc->progress) : "memory");
                const int diff = (int)v - (int)own * NCTA;
                pace[1] = diff > PACE_THR ? WINDOW + 1 : diff < -PACE_THR ? WINDOW - 1 : WINDOW;
                __nanosleep(200);
            }
        }
    } else {
        const int g = lane >> 2, t = lane & 3;
        const int bb = g & 1;
        const int eb = lane >> 4;
        const int ec = 64 * warp + 4 * (lane & 15);
        if (warp == 0) TSTAMP(0);
        Scratch* const sc = p.sc;
        const float c00 = __bfloat162float(p.c[tid]), c01 = __bfloat162float(p.c[tid + 256]);
        const float c10 = __bfloat162float(p.c[D_MODEL + tid]), c11 = __bfloat162float(p.c[D_MODEL + tid + 256]);
        const uint2 xe = __ldg((const uint2*)(p.x + eb * D_MODEL + ec));
        const float xpivot = __bfloat162float(p.x[eb * D_MODEL]);
        const uint32_t tag = *(volatile unsigned*)&sc->epoch + 1;
        const int ocol = cta * 4 + (lane & 3);
        const int wcol = (cta >= NCTA - NOWN ? cta - (NCTA - NOWN) : 0) * 16 + (lane & 15);
        const float xo = __bfloat162float(p.x[eb * D_MODEL + wcol]);

        float* red = (float*)(sgen + SM_RED);
        float* red2 = (float*)(sgen + SM_RED2);
        float2* stat = (float2*)(sgen + SM_STAT);
        uint32_t* hs = (uint32_t*)(sgen + SM_HS) + warp * 64;
        float xn[4];
        {
            float xv[4] = {bf_lo(xe.x), bf_hi(xe.x), bf_lo(xe.y), bf_hi(xe.y)};
            const float2 ps = half_warp_sums(xv, xpivot);
            if ((lane & 15) == 0) stat[warp * 2 + eb] = ps;
            const float s00 = silu_bf(c00), s01 = silu_bf(c01), s10 = silu_bf(c10), s11 = silu_bf(c11);
            __nv_bfloat16* scs = (__nv_bfloat16*)(sgen + SM_SC);
            scs[tid] = __float2bfloat16_rn(s00); scs[tid + 256] = __float2bfloat16_rn(s01);
            scs[512 + tid] = __float2bfloat16_rn(s10); scs[512 + tid + 256] = __float2bfloat16_rn(s11);
            asm volatile("bar.sync 2, 320;" ::: "memory");
            if (warp == 0) TSTAMP(23);
            float cp[4] = {0.f, 0.f, 0.f, 0.f};
            const uint32_t* sc32 = (const uint32_t*)(sgen + SM_SC) + bb * 256 + 32 * warp + t;
            mbar_wait(bar_p0w, 0);
#pragma unroll
            for (int s = 0; s < 4; s++) {
                uint32_t r0, r1;
                asm volatile("ldmatrix.sync.aligned.m8n8.x2.trans.shared.b16 {%0,%1}, [%2];"
                             : "=r"(r0), "=r"(r1) : "r"(sbase + SM_MRG + (64 * warp + 16 * s + (lane & 15)) * 16) : "memory");
                const uint32_t a[4] = {r0, r0, r1, r1};
                mma16816(cp, a, sc32[8 * s], sc32[8 * s + 4]);
            }
            if (t == 0) { red[warp * 16 + g] = cp[0]; red[warp * 16 + 8 + g] = cp[1]; }
            if (warp == 0) TSTAMP(14);
            cons_sync();
            if (warp == 0) {
                float s = 0.f;
#pragma unroll
                for (int w = 0; w < 8; w++) s += red[w * 16 + (lane & 15)];
                const float nx = __shfl_down_sync(0xffffffffu, s, 1);
                if (lane < 16 && !(lane & 1))
                    st_ll2(&sc->mod[lane >> 3][cta * 4 + ((lane & 7) >> 1)], pack_bf16(s, nx), tag);
                TSTAMP(1);
            }
            float mean_bf, rstd;
            ln_stats(stat, eb, xpivot, mean_bf, rstd);
#pragma unroll
            for (int i = 0; i < 4; i++) xn[i] = ln_norm(xv[i], mean_bf, rstd);
        }
        {
            uint4 sa, ca;
            for (int it = 0;; it++) {
                sa = ld_ll4((const uint4*)&sc->mod[eb][ec >> 1]);
                ca = ld_ll4((const uint4*)&sc->mod[eb][256 + (ec >> 1)]);
                const bool ok = sa.y == tag && sa.w == tag && ca.y == tag && ca.w == tag;
                if (__all_sync(0xffffffffu, ok) || it > SPIN_LIMIT) break;
            }
            *(uint2*)&hs[eb * 32 + 2 * (lane & 15)] =
                make_uint2(pack_bf16(ln_mod(xn[0], bf_lo(ca.x), bf_lo(sa.x)), ln_mod(xn[1], bf_hi(ca.x), bf_hi(sa.x))),
                           pack_bf16(ln_mod(xn[2], bf_lo(ca.z), bf_lo(sa.z)), ln_mod(xn[3], bf_hi(ca.z), bf_hi(sa.z))));
            __syncwarp();
            uint32_t hb[8];
#pragma unroll
            for (int i = 0; i < 8; i++) hb[i] = hs[bb * 32 + 8 * (i >> 1) + 4 * (i & 1) + t];
            if (warp == 0) TSTAMP(2);
            float cq[2][4] = {};
            const int ts = warp >> 2;
            mbar_wait(bar_full + 8 * ts, 0);
            const uint32_t tb = sbase + SM_RING + ts * TILE;
#pragma unroll
            for (int s = 0; s < 4; s++) {
                const int row = 64 * (warp & 3) + 16 * s + (lane & 7) + (lane >> 4) * 8;
#pragma unroll
                for (int mt = 0; mt < 2; mt++) {
                    const int ch = 2 * mt + ((lane >> 3) & 1);
                    uint32_t a[4];
                    ldsm4t(tb + row * 64 + ((ch ^ ((row >> 1) & 3)) << 4), a);
                    mma16816(cq[mt], a, hb[2 * s], hb[2 * s + 1]);
                }
            }
            if (t < 2) {
                const float v0 = t == 0 ? cq[0][0] : cq[1][0], v1 = t == 0 ? cq[0][1] : cq[1][1];
                const float v2 = t == 0 ? cq[0][2] : cq[1][2], v3 = t == 0 ? cq[0][3] : cq[1][3];
                *(float2*)&red2[warp * 64 + (16 * t + g) * 2] = make_float2(v0, v1);
                *(float2*)&red2[warp * 64 + (16 * t + g + 8) * 2] = make_float2(v2, v3);
            }
            cons_sync();
            if (warp < 4 && lane == 0) { mbar_arrive(bar_empty); mbar_arrive(bar_empty + 8); }
            if (warp == 0) {
                const int b = lane >> 4, cp = lane & 15;
                float q0 = 0.f, q1 = 0.f;
#pragma unroll
                for (int w = 0; w < 8; w++) {
                    const float4 v = *(const float4*)&red2[w * 64 + cp * 4];
                    q0 += b ? v.y : v.x; q1 += b ? v.w : v.z;
                }
                st_ll2(&sc->q[b][cta * 16 + cp], pack_bf16(q0, q1), tag);
                TSTAMP(3);
            }
        }
        const int pair = cta >> 3;
        uint32_t qf[16];
        {
            uint2* qs = (uint2*)(sgen + SM_QS);
            if (tid < 128) {
                const uint4* src = (const uint4*)&sc->q[pair >> 3][(pair & 7) * 256] + tid;
                uint4 v;
                for (int it = 0;; it++) {
                    v = ld_ll4(src);
                    if ((v.y == tag && v.w == tag) || it > SPIN_LIMIT) break;
                }
                qs[tid] = make_uint2(v.x, v.z);
            }
            cons_sync();
            const uint32_t* q32 = (const uint32_t*)(sgen + SM_QS);
#pragma unroll
            for (int s = 0; s < 8; s++) {
                qf[2 * s] = q32[(g & 3) * 64 + 8 * s + t];
                qf[2 * s + 1] = q32[(g & 3) * 64 + 8 * s + 4 + t];
            }
        }
        if (warp == 0) TSTAMP(4);

        float o[8][4];
#pragma unroll
        for (int i = 0; i < 8; i++) { o[i][0] = o[i][1] = o[i][2] = o[i][3] = 0.f; }
        uint32_t mrun = 0xff80ff80u;
        float ls[4] = {0.f, 0.f, 0.f, 0.f};
        uint4 m_sb, m_cb; uint2 m_ga, m_gb0, m_gb1;
        {
            const int grp = warp >> 2, wi = warp & 3;
            const int krow = 16 * wi + (lane & 7) + ((lane >> 3) & 1) * 8;
            const uint32_t koff = krow * 128 + ((((lane >> 4) & 1) ^ (lane & 7)) << 4);
            const int vrow = 16 * wi + (lane & 7) + (lane >> 4) * 8;
            const uint32_t voff = vrow * 128 + ((((lane >> 3) & 1) ^ (lane & 7)) << 4);
            const uint32_t ones[4] = {0x3f803f80u, 0x3f803f80u, 0x3f803f80u, 0x3f803f80u};
            for (int i = grp; i < KV_TILES; i += 2) {
                if (i == MOD_AT + grp) {
                    float cm[4] = {};
                    const uint32_t* sc32 = (const uint32_t*)(sgen + SM_SC) + bb * 256 + 32 * warp + t;
                    mbar_wait(bar_full + 8 * (IDX_MOD % NST), (IDX_MOD / NST) & 1);
                    const uint32_t tb = sbase + SM_RING + (IDX_MOD % NST) * TILE;
#pragma unroll
                    for (int s = 0; s < 4; s++) {
                        const int row = 64 * warp + 16 * s + (lane & 7) + (lane >> 4) * 8;
                        const int ch = (lane >> 3) & 1;
                        uint32_t a[4];
                        ldsm4t(tb + row * 32 + ((ch ^ ((row >> 2) & 1)) << 4), a);
                        mma16816(cm, a, sc32[8 * s], sc32[8 * s + 4]);
                    }
                    if (t == 0) {
                        *(float2*)&red[warp * 64 + g * 2] = make_float2(cm[0], cm[1]);
                        *(float2*)&red[warp * 64 + (g + 8) * 2] = make_float2(cm[2], cm[3]);
                    }
                    cons_sync();
                    if (warp < 4 && lane == 0) mbar_arrive(bar_empty + 8 * (IDX_MOD % NST));
                    if (warp == 1 && lane < 16) {
                        const int b = lane >> 3, cp = lane & 7;
                        float q0 = 0.f, q1 = 0.f;
#pragma unroll
                        for (int w = 0; w < 8; w++) {
                            const float4 v = *(const float4*)&red[w * 64 + cp * 4];
                            q0 += b ? v.y : v.x; q1 += b ? v.w : v.z;
                        }
                        st_ll2(&sc->mod[b][512 + cta * 8 + cp], pack_bf16(q0, q1), tag);
                    }
                }
                if (i == 56 + grp) {
                    m_sb = ld_ll4((const uint4*)&sc->mod[eb][768 + (ec >> 1)]);
                    m_cb = ld_ll4((const uint4*)&sc->mod[eb][1024 + (ec >> 1)]);
                    m_ga = ld_ll2(&sc->mod[eb][512 + (wcol >> 1)]);
                    m_gb0 = ld_ll2(&sc->mod[0][1280 + (ocol >> 1)]); m_gb1 = ld_ll2(&sc->mod[1][1280 + (ocol >> 1)]);
                }
                if (i == 60 + grp) {
                    for (int it = 0;; it++) {
                        const bool ok = m_sb.y == tag && m_sb.w == tag && m_cb.y == tag && m_cb.w == tag &&
                                        m_ga.y == tag && m_gb0.y == tag && m_gb1.y == tag;
                        if (__all_sync(0xffffffffu, ok) || it > SPIN_LIMIT) break;
                        m_sb = ld_ll4((const uint4*)&sc->mod[eb][768 + (ec >> 1)]);
                        m_cb = ld_ll4((const uint4*)&sc->mod[eb][1024 + (ec >> 1)]);
                        m_ga = ld_ll2(&sc->mod[eb][512 + (wcol >> 1)]);
                        m_gb0 = ld_ll2(&sc->mod[0][1280 + (ocol >> 1)]); m_gb1 = ld_ll2(&sc->mod[1][1280 + (ocol >> 1)]);
                    }
                    mbar_wait(bar_clear, 0);
                }
                const int ki = kv_idx(i), ks = ki % NST, vs = (ki + 1) % NST;
                const uint32_t kph = (ki / NST) & 1, vph = ((ki + 1) / NST) & 1;
                mbar_wait(bar_full + 8 * ks, kph);
                const uint32_t kb = sbase + SM_RING + ks * TILE + koff;
                float sa[4] = {0.f, 0.f, 0.f, 0.f}, sb[4] = {0.f, 0.f, 0.f, 0.f};
#pragma unroll
                for (int s = 0; s < 8; s += 2) {
                    uint32_t a0[4], a1[4];
                    ldsm4((kb ^ ((s & 3) << 5)) + (s >> 2) * 8192, a0);
                    ldsm4((kb ^ (((s + 1) & 3) << 5)) + (s >> 2) * 8192, a1);
                    mma16816(sa, a0, qf[2 * s], qf[2 * s + 1]);
                    mma16816(sb, a1, qf[2 * s + 2], qf[2 * s + 3]);
                }
                __syncwarp();
                if (lane == 0) mbar_arrive(bar_empty + 8 * ks);
                uint32_t r01 = pack_bf16(sa[0] + sb[0], sa[1] + sb[1]);
                uint32_t r23 = pack_bf16(sa[2] + sb[2], sa[3] + sb[3]);
                r01 = pack_bf16(bf_lo(r01) * QK_SCALE, bf_hi(r01) * QK_SCALE);
                r23 = pack_bf16(bf_lo(r23) * QK_SCALE, bf_hi(r23) * QK_SCALE);
                uint32_t mx = max_bf16x2(r01, r23);
                mx = max_bf16x2(mx, __shfl_xor_sync(0xffffffffu, mx, 4));
                mx = max_bf16x2(mx, __shfl_xor_sync(0xffffffffu, mx, 8));
                mx = max_bf16x2(mx, __shfl_xor_sync(0xffffffffu, mx, 16));
                const uint32_t mnew = max_bf16x2(mrun, mx);
                const float m0 = bf_lo(mnew), m1 = bf_hi(mnew);
                if (__any_sync(0xffffffffu, mnew != mrun)) {
                    const float al0 = ex2((bf_lo(mrun) - m0) * LOG2E), al1 = ex2((bf_hi(mrun) - m1) * LOG2E);
                    ls[0] *= al0; ls[1] *= al1;
#pragma unroll
                    for (int d = 0; d < 8; d++) { o[d][0] *= al0; o[d][1] *= al1; o[d][2] *= al0; o[d][3] *= al1; }
                    mrun = mnew;
                }
                const float p0 = ex2((bf_lo(r01) - m0) * LOG2E), p1 = ex2((bf_hi(r01) - m1) * LOG2E);
                const float p2 = ex2((bf_lo(r23) - m0) * LOG2E), p3 = ex2((bf_hi(r23) - m1) * LOG2E);
                const uint32_t pb0 = movmatrix_t(pack_bf16(p0, p1)), pb1 = movmatrix_t(pack_bf16(p2, p3));
                mma16816(ls, ones, pb0, pb1);
                mbar_wait(bar_full + 8 * vs, vph);
                const uint32_t vb = sbase + SM_RING + vs * TILE + voff;
#pragma unroll
                for (int d = 0; d < 8; d++) {
                    uint32_t a[4];
                    ldsm4t((vb ^ ((d & 3) << 5)) + (d >> 2) * 8192, a);
                    mma16816(o[d], a, pb0, pb1);
                }
                __syncwarp();
                if (lane == 0) mbar_arrive(bar_empty + 8 * vs);
            }
        }
        if (warp == 7) TSTAMP(5);
        {
            float* mrg = (float*)(sgen + SM_MRG);
            float2* ml = (float2*)(sgen + SM_ML);
            {
                const int hp = (t & 1) * 2, up = t >> 1;
                if (g == 0 && up == 0) { ml[warp * 4 + hp] = make_float2(bf_lo(mrun), ls[0]); ml[warp * 4 + hp + 1] = make_float2(bf_hi(mrun), ls[1]); }
                float* m0p = mrg + (warp * 4 + hp) * 136 + up * 72 + g;
#pragma unroll
                for (int d = 0; d < 4; d++) {
                    m0p[16 * d] = up ? o[d + 4][0] : o[d][0]; m0p[136 + 16 * d] = up ? o[d + 4][1] : o[d][1];
                    m0p[16 * d + 8] = up ? o[d + 4][2] : o[d][2]; m0p[136 + 16 * d + 8] = up ? o[d + 4][3] : o[d][3];
                }
            }
            cons_sync();
            const int hh = tid >> 6, dp = tid & 63;
            float2 mw[8];
            float M = -INFINITY;
#pragma unroll
            for (int w = 0; w < 8; w++) { mw[w] = ml[w * 4 + hh]; M = fmaxf(M, mw[w].x); }
            float L = 0.f, o0 = 0.f, o1 = 0.f;
#pragma unroll
            for (int w = 0; w < 8; w++) {
                const float wt = ex2((mw[w].x - M) * LOG2E);
                const float2 v = *(const float2*)&mrg[(w * 4 + hh) * 136 + 2 * dp + (dp >= 32 ? 8 : 0)];
                L += wt * mw[w].y; o0 += wt * v.x; o1 += wt * v.y;
            }
            st_ll2(&sc->part_o[cta][hh][dp], tagf(o0, F_PART), tagf(o1, F_PART));
            if (dp < 4) st_ll2(&sc->part_ml[cta][hh][dp], tagf(M, F_PART), tagf(L, F_PART));
        }
        if (warp == 0) TSTAMP(6);
        {
            const int hq = cta >> 2, kvh = hq >> 2, hh = hq & 3;
            const int b = tid >> 7, dc = (tid >> 3) & 15, j = tid & 7;
            const int pc = (b * 8 + kvh) * 8 + j;
            const uint4* po = (const uint4*)&sc->part_o[pc][hh][0] + dc * 2;
            const uint2* pm = &sc->part_ml[pc - j][hh][0];
            uint4 vo0, vo1; uint2 vm[8];
            bool oko = false, okm = false;
            for (int it = 0;; it++) {
                if (!oko) { vo0 = ld_ll4(po); vo1 = ld_ll4(po + 1); }
                if (!okm) {
#pragma unroll
                    for (int jj = 0; jj < 8; jj++) vm[jj] = ld_ll2(pm + jj * 16);
                }
                oko = (vo0.x & vo0.y & vo0.z & vo0.w & vo1.x & vo1.y & vo1.z & vo1.w & 3u) == F_PART;
                uint32_t all = vm[0].x & vm[0].y;
#pragma unroll
                for (int jj = 1; jj < 8; jj++) all &= vm[jj].x & vm[jj].y;
                okm = (all & 3u) == F_PART;
                if (__all_sync(0xffffffffu, oko && okm) || it > SPIN_LIMIT) break;
                spin_cycles(A_BACKOFF);
            }
            float M = untag(vm[0].x);
#pragma unroll
            for (int jj = 1; jj < 8; jj++) M = fmaxf(M, untag(vm[jj].x));
            float wt = 0.f, L = 0.f;
#pragma unroll
            for (int jj = 0; jj < 8; jj++) {
                const float w_ = ex2((untag(vm[jj].x) - M) * LOG2E);
                L += w_ * untag(vm[jj].y);
                wt = jj == j ? w_ : wt;
            }
            wt *= rcp_approx(L);
            float v[8] = {wt * untag(vo0.x), wt * untag(vo0.y), wt * untag(vo0.z), wt * untag(vo0.w),
                          wt * untag(vo1.x), wt * untag(vo1.y), wt * untag(vo1.z), wt * untag(vo1.w)};
#define XRED(N, O)                                                                       \
            {                                                                            \
                const bool up = lane & (O);                                              \
                _Pragma("unroll") for (int i = 0; i < (N); i++) {                        \
                    const float send = up ? v[i] : v[i + (N)], keep = up ? v[i + (N)] : v[i]; \
                    v[i] = keep + __shfl_xor_sync(0xffffffffu, send, (O));               \
                }                                                                        \
            }
            XRED(4, 1) XRED(2, 2) XRED(1, 4)
#undef XRED
            __nv_bfloat16* os = (__nv_bfloat16*)(sgen + SM_OS);
            os[b * 128 + dc * 8 + 4 * (j & 1) + 2 * ((j >> 1) & 1) + (j >> 2)] = __float2bfloat16_rn(v[0]);
            if (warp == 0) TSTAMP(15);
            uint32_t wf[8][4];
            const uint32_t aoff_o = (warp >> 2) * 8192 + ((lane & 7) + (lane >> 4) * 8) * 128 +
                                    (((((warp & 3) * 2 + ((lane >> 3) & 1)) ^ (lane & 7))) << 4);
#pragma unroll
            for (int s = 0; s < 2; s++) {
                const int idx = IDX_WO + s;
                mbar_wait(bar_full + 8 * (idx % NST), (idx / NST) & 1);
                const uint32_t tb = sbase + SM_RING + (idx % NST) * TILE + aoff_o;
#pragma unroll
                for (int k4 = 0; k4 < 4; k4++) ldsm4t(tb + k4 * 2048, wf[s * 4 + k4]);
            }
            cons_sync();
            if (warp == 0) TSTAMP(7);
            const uint32_t* os32 = (const uint32_t*)(sgen + SM_OS) + bb * 64 + t;
            float y0[4] = {}, y1[4] = {};
#pragma unroll
            for (int ks = 0; ks < 8; ks += 2) {
                mma16816(y0, wf[ks], os32[8 * ks], os32[8 * ks + 4]);
                mma16816(y1, wf[ks + 1], os32[8 * ks + 8], os32[8 * ks + 12]);
            }
            if (t == 0)
                st_v4(&sc->inbox_wo[(cta & 3) * 8 + warp][hq][g], tagf(y0[0] + y1[0], F_WO), tagf(y0[1] + y1[1], F_WO),
                      tagf(y0[2] + y1[2], F_WO), tagf(y0[3] + y1[3], F_WO));
        }
        const uint32_t t_wo = clock32();
        if (warp == 0) TSTAMP(8);
        if (cta >= NCTA - NOWN) {
            const uint4* pin = &sc->inbox_wo[cta - (NCTA - NOWN)][0][0] + tid;
            uint4 v;
            spin_cycles(DELAY_B1);
            bool ok = false;
            for (int it = 0;; it++) {
                if (!ok) {
                    v = ld_ll4(pin);
                    ok = (v.x & v.y & v.z & v.w & 3u) == F_WO;
                }
                if (__all_sync(0xffffffffu, ok) || it > SPIN_LIMIT) break;
            }
            const bool u1 = lane & 8, u2 = lane & 16;
            const float a0 = untag(v.x), a1 = untag(v.y), a2 = untag(v.z), a3 = untag(v.w);
            const float k0 = (u1 ? a2 : a0) + __shfl_xor_sync(0xffffffffu, u1 ? a0 : a2, 8);
            const float k1 = (u1 ? a3 : a1) + __shfl_xor_sync(0xffffffffu, u1 ? a1 : a3, 8);
            red2[warp * 32 + lane] = (u2 ? k1 : k0) + __shfl_xor_sync(0xffffffffu, u2 ? k0 : k1, 16);
            cons_sync();
            if (warp == 0) {
                float a = 0.f;
#pragma unroll
                for (int w = 0; w < 8; w++) a += red2[w * 32 + lane];
                const float ga = (wcol & 1) ? bf_hi(m_ga.x) : bf_lo(m_ga.x);
                const float xm = bf16r(xo + bf16r(ga * bf16r(a)));
                const float xm_b1 = __shfl_down_sync(0xffffffffu, xm, 16);
                if (lane < 16) st_ll2(&sc->x1[wcol], pack_bf16(xm, xm_b1), F_X1);
                TSTAMP(10);
            }
        }
        const uint32_t aoff = warp * 2048 + ((lane & 7) + (lane >> 4) * 8) * 128 + ((((lane >> 3) & 1) ^ (lane & 7)) << 4);
        if (cta < NFFN) {
            const uint4* px = (const uint4*)&sc->x1[ec];
            const uint4* pp = (const uint4*)&sc->x1[0];
            uint4 va, vb, pa, pb;
            const float c1v[4] = {bf16r(1.0f + bf_lo(m_cb.x)), bf16r(1.0f + bf_hi(m_cb.x)), bf16r(1.0f + bf_lo(m_cb.z)), bf16r(1.0f + bf_hi(m_cb.z))};
            float bg = 0.f, cgc = 0.f, bu = 0.f, cuc = 0.f;
            uint32_t gf[4][4], uf[4][4];
            const uint32_t bar_g = bar_gu + 8 * (2 * (warp >> 1));
            uint32_t* pre = (uint32_t*)(sgen + SM_MRG) + warp * 128;
            *(uint2*)&pre[eb * 32 + 2 * (lane & 15)] = make_uint2(pack_bf16(c1v[0], c1v[1]), pack_bf16(c1v[2], c1v[3]));
            *(uint2*)&pre[64 + eb * 32 + 2 * (lane & 15)] = make_uint2(m_sb.x, m_sb.z);
            __syncwarp();
            auto weights_and_bc = [&]() {
                mbar_wait(bar_g, 0);
                mbar_wait(bar_g + 8, 0);
                const uint32_t tg = sbase + SM_RING + (IDX_WG % NST) * TILE, tu = sbase + SM_RING + (IDX_WU % NST) * TILE;
#pragma unroll
                for (int s = 0; s < 4; s++) {
                    const int row = 64 * warp + 16 * s + (lane & 7) + (lane >> 4) * 8;
                    const uint32_t off = row * 32 + ((((lane >> 3) & 1) ^ ((row >> 2) & 1)) << 4);
                    ldsm4t(tg + off, gf[s]);
                    ldsm4t(tu + off, uf[s]);
                }
                float* bc = (float*)(sgen + SM_MRG + 4096);
                float yg[4] = {}, yu[4] = {};
                const uint32_t* pb = pre + ((g >> 1) & 1) * 64 + bb * 32 + t;
#pragma unroll
                for (int s = 0; s < 4; s++) {
                    const uint32_t b0 = pb[8 * s], b1 = pb[8 * s + 4];
                    mma16816(yg, gf[s], b0, b1);
                    mma16816(yu, uf[s], b0, b1);
                }
                const float y0 = t < 2 ? yg[0] : yu[0], y1 = t < 2 ? yg[1] : yu[1], y2 = t < 2 ? yg[2] : yu[2], y3 = t < 2 ? yg[3] : yu[3];
                float* dstp = bc + warp * 128 + (t >> 1) * 64 + (t & 1) * 32;
                *(float2*)&dstp[g * 2] = make_float2(y0, y1);
                *(float2*)&dstp[(g + 8) * 2] = make_float2(y2, y3);
                __syncwarp();
                if (lane == 0) mbar_arrive(bar_bc);
            };
            const bool gu_early = __all_sync(0xffffffffu, mbar_test(bar_g, 0) && mbar_test(bar_g + 8, 0));
            if (gu_early) weights_and_bc();
            if (warp == 0) TSTAMP(11);
            float pivot2;
            {
                while (clock32() - t_wo < DELAY_X1) {}
                bool okx = false, okp = false;
                for (int it = 0;; it++) {
                    if (!okx) { va = ld_ll4(px); vb = ld_ll4(px + 1); }
                    if (!okp) { pa = ld_ll4(pp); pb = ld_ll4(pp + 1); }
                    okx = va.y == F_X1 && va.w == F_X1 && vb.y == F_X1 && vb.w == F_X1;
                    okp = pa.y == F_X1 && pa.w == F_X1 && pb.y == F_X1 && pb.w == F_X1;
                    if (__all_sync(0xffffffffu, okx && okp) || it > SPIN_LIMIT) break;
                }
                if (warp == 0) TSTAMP(9);
                const float xv[4] = {eb ? bf_hi(va.x) : bf_lo(va.x), eb ? bf_hi(va.z) : bf_lo(va.z),
                                     eb ? bf_hi(vb.x) : bf_lo(vb.x), eb ? bf_hi(vb.z) : bf_lo(vb.z)};
                const float p0 = 0.25f * ((bf_lo(pa.x) + bf_lo(pa.z)) + (bf_lo(pb.x) + bf_lo(pb.z)));
                const float p1 = 0.25f * ((bf_hi(pa.x) + bf_hi(pa.z)) + (bf_hi(pb.x) + bf_hi(pb.z)));
                const float pivot = eb ? p1 : p0;
                pivot2 = (lane & 1) ? p1 : p0;
                *(uint2*)&hs[eb * 32 + 2 * (lane & 15)] =
                    make_uint2(pack_bf16((xv[0] - pivot) * c1v[0], (xv[1] - pivot) * c1v[1]),
                               pack_bf16((xv[2] - pivot) * c1v[2], (xv[3] - pivot) * c1v[3]));
                __syncwarp();
                if (!gu_early) weights_and_bc();
                float cg[2][4] = {}, cu[2][4] = {};
#pragma unroll
                for (int s = 0; s < 4; s++) {
                    const uint32_t b0 = hs[bb * 32 + 8 * s + t], b1 = hs[bb * 32 + 8 * s + 4 + t];
                    mma16816(cg[s & 1], gf[s], b0, b1);
                    mma16816(cu[s & 1], uf[s], b0, b1);
                }
                const float2 ps = half_warp_sums(xv, pivot);
                if ((lane & 15) == 0) stat[warp * 2 + eb] = ps;
                {
                    const float* bc = (const float*)(sgen + SM_MRG + 4096);
                    mbar_wait(bar_bc, 0);
#pragma unroll
                    for (int w = 0; w < 8; w++) {
                        bg += bc[w * 128 + lane]; cgc += bc[w * 128 + 32 + lane];
                        bu += bc[w * 128 + 64 + lane]; cuc += bc[w * 128 + 96 + lane];
                    }
                }
                if (t < 2) {
                    float v[4];
#pragma unroll
                    for (int i = 0; i < 4; i++) v[i] = t ? cu[0][i] + cu[1][i] : cg[0][i] + cg[1][i];
                    *(float2*)&red[warp * 64 + t * 32 + g * 2] = make_float2(v[0], v[1]);
                    *(float2*)&red[warp * 64 + t * 32 + (g + 8) * 2] = make_float2(v[2], v[3]);
                }
            }
            uint32_t df[4][4];
            mbar_wait(bar_full + 8 * (IDX_WD % NST), (IDX_WD / NST) & 1);
#pragma unroll
            for (int mt = 0; mt < 4; mt++) ldsm4t((sbase + SM_RING + (IDX_WD % NST) * TILE + aoff) ^ (mt << 5), df[mt]);
            cons_sync();
            {
                float gs = 0.f, us = 0.f;
#pragma unroll
                for (int w = 0; w < 8; w++) { gs += red[w * 64 + lane]; us += red[w * 64 + 32 + lane]; }
                float mean_bf, rstd;
                ln_stats(stat, lane & 1, pivot2, mean_bf, rstd);
                const float dm = mean_bf - pivot2;
                gs = bf16r(rstd * (gs - dm * bg) + cgc);
                us = rstd * (us - dm * bu) + cuc;
                const float u2 = gs * (1.0f + 0.044715f * gs * gs) * (2.0f * 0.7978845608028654f * LOG2E);
                const float ge = bf16r(__fdividef(gs, 1.0f + ex2(-u2)));
                const float act = bf16r(ge * bf16r(us));
                const float a0 = __shfl_sync(0xffffffffu, act, 4 * t + bb), a1 = __shfl_sync(0xffffffffu, act, 4 * t + 2 + bb);
                const float a2 = __shfl_sync(0xffffffffu, act, 4 * t + 16 + bb), a3 = __shfl_sync(0xffffffffu, act, 4 * t + 18 + bb);
                const uint32_t b0 = pack_bf16(a0, a1), b1 = pack_bf16(a2, a3);
                float y[4][4] = {};
#pragma unroll
                for (int mt = 0; mt < 4; mt++) mma16816(y[mt], df[mt], b0, b1);
                float v[4];
#pragma unroll
                for (int i = 0; i < 4; i++) v[i] = t == 0 ? y[0][i] : t == 1 ? y[1][i] : t == 2 ? y[2][i] : y[3][i];
            {
                const bool odd = g & 1;
                const float sx = odd ? v[0] : v[2], sy = odd ? v[1] : v[3];
                const float rx = __shfl_xor_sync(0xffffffffu, sx, 4), ry = __shfl_xor_sync(0xffffffffu, sy, 4);
                const int c0 = 64 * warp + 16 * t + (odd ? g + 7 : g);
                const float e0 = odd ? rx : v[0], e1 = odd ? ry : v[1], e2 = odd ? v[2] : rx, e3 = odd ? v[3] : ry;
                st_v4(&sc->inbox_dn[c0 >> 2][cta][(c0 >> 1) & 1], tagf(e0, F_DOWN), tagf(e1, F_DOWN), tagf(e2, F_DOWN), tagf(e3, F_DOWN));
            }
            }
            if (warp == 0) TSTAMP(12);
        }
        {
            uint2 xw;
            float r0;
            {
                const uint4* pin = &sc->inbox_dn[cta][0][0] + tid;
                uint4 v = make_uint4(F_DOWN, F_DOWN, F_DOWN, F_DOWN);
                if (cta < NFFN) spin_cycles(DELAY_C);
                else while (clock32() - t_wo < DELAY_X1 + DELAY_NOFFN) {}
                xw = ld_ll2(&sc->x1[ocol]);
                bool ok = tid >= NFFN * 2;
                for (int it = 0;; it++) {
                    if (!ok) {
                        v = ld_ll4(pin);
                        ok = (v.x & v.y & v.z & v.w & 3u) == F_DOWN;
                    }
                    if (__all_sync(0xffffffffu, ok) || it > SPIN_LIMIT) break;
                }
                const bool u1 = lane & 2, u2 = lane & 4;
                const float a0 = untag(v.x), a1 = untag(v.y), a2 = untag(v.z), a3 = untag(v.w);
                const float k0 = (u1 ? a1 : a0) + __shfl_xor_sync(0xffffffffu, u1 ? a0 : a1, 2);
                const float k1 = (u1 ? a3 : a2) + __shfl_xor_sync(0xffffffffu, u1 ? a2 : a3, 2);
                r0 = (u2 ? k1 : k0) + __shfl_xor_sync(0xffffffffu, u2 ? k0 : k1, 4);
                r0 += __shfl_xor_sync(0xffffffffu, r0, 8);
                r0 += __shfl_xor_sync(0xffffffffu, r0, 16);
                if (lane < 8) red2[256 + warp * 8 + (2 * (lane & 1) + ((lane >> 2) & 1)) * 2 + ((lane >> 1) & 1)] = r0;
            }
            cons_sync();
            if (warp == 0) {
                float a0 = 0.f, a1 = 0.f;
#pragma unroll
                for (int w = 0; w < 8; w++) { const float2 v = *(const float2*)&red2[256 + w * 8 + (lane & 3) * 2]; a0 += v.x; a1 += v.y; }
                const bool hi = ocol & 1;
                const float gb0 = hi ? bf_hi(m_gb0.x) : bf_lo(m_gb0.x), gb1 = hi ? bf_hi(m_gb1.x) : bf_lo(m_gb1.x);
                for (int it = 0; !__all_sync(0xffffffffu, xw.y == F_X1) && it < SPIN_LIMIT; it++) xw = ld_ll2(&sc->x1[ocol]);
                if (lane < 4) {
                    p.out[ocol] = __float2bfloat16_rn(bf_lo(xw.x) + bf16r(gb0 * bf16r(a0)));
                    p.out[D_MODEL + ocol] = __float2bfloat16_rn(bf_hi(xw.x) + bf16r(gb1 * bf16r(a1)));
                }
                if (cta == 0 && lane == 0) *(volatile unsigned*)&sc->epoch = tag;
                TSTAMP(13);
            }
        }
    }
}

typedef CUresult (*EncodeFn)(CUtensorMap*, CUtensorMapDataType, cuuint32_t, void*, const cuuint64_t*, const cuuint64_t*,
                             const cuuint32_t*, const cuuint32_t*, CUtensorMapInterleave, CUtensorMapSwizzle,
                             CUtensorMapL2promotion, CUtensorMapFloatOOBfill);

struct Maps { CUtensorMap k, v, wq, wmod, wmod8, wo, wg, wu, wd; };

void encode(EncodeFn fn, CUtensorMap* m, const void* ptr, int rank, const cuuint64_t* dims, const cuuint64_t* strides,
            const cuuint32_t* box, CUtensorMapSwizzle sw) {
    const cuuint32_t es[3] = {1, 1, 1};
    fn(m, CU_TENSOR_MAP_DATA_TYPE_BFLOAT16, rank, const_cast<void*>(ptr), dims, strides, box, es,
       CU_TENSOR_MAP_INTERLEAVE_NONE, sw, CU_TENSOR_MAP_L2_PROMOTION_L2_256B, CU_TENSOR_MAP_FLOAT_OOB_FILL_NONE);
}

}

extern "C" void kernel_launch(void* const* d_in, const int* in_sizes, int n_in, void* d_out, int out_size) {
    (void)in_sizes; (void)n_in; (void)out_size;
    static EncodeFn enc = nullptr;
    static Scratch* scratch = nullptr;
    if (!enc) {
        cudaGetSymbolAddress((void**)&scratch, g_scratch);
        void* fn = nullptr;
        cudaDriverEntryPointQueryResult qr;
        cudaGetDriverEntryPoint("cuTensorMapEncodeTiled", &fn, cudaEnableDefault, &qr);
        enc = (EncodeFn)fn;
        cudaFuncSetAttribute(fused_block_kernel, cudaFuncAttributeMaxDynamicSharedMemorySize, SMEM_BYTES);
    }
    Maps m;
    {
        const cuuint64_t dims[3] = {64, (cuuint64_t)16 * SK, 2}, str[2] = {256, 128};
        const cuuint32_t box[3] = {64, 64, 2};
        encode(enc, &m.k, d_in[1], 3, dims, str, box, CU_TENSOR_MAP_SWIZZLE_128B);
        encode(enc, &m.v, d_in[2], 3, dims, str, box, CU_TENSOR_MAP_SWIZZLE_128B);
    }
    {
        const cuuint64_t dims[2] = {4096, 512}, str[1] = {8192};
        const cuuint32_t box[2] = {32, 256};
        encode(enc, &m.wq, d_in[3], 2, dims, str, box, CU_TENSOR_MAP_SWIZZLE_64B);
    }
    {
        const cuuint64_t dims[2] = {N_MOD, 512}, str[1] = {N_MOD * 2};
        const cuuint32_t box[2] = {16, 256};
        encode(enc, &m.wmod, d_in[10], 2, dims, str, box, CU_TENSOR_MAP_SWIZZLE_32B);
        const cuuint32_t box8[2] = {8, 256};
        encode(enc, &m.wmod8, d_in[10], 2, dims, str, box8, CU_TENSOR_MAP_SWIZZLE_NONE);
    }
    {
        const cuuint64_t dims_o[3] = {64, 4096, 8}, dims_d[3] = {64, D_FF, 8}, str[2] = {1024, 128};
        const cuuint32_t box[3] = {64, 16, 8}, box_o[3] = {64, 64, 2};
        encode(enc, &m.wo, d_in[4], 3, dims_o, str, box_o, CU_TENSOR_MAP_SWIZZLE_128B);
        encode(enc, &m.wd, d_in[8], 3, dims_d, str, box, CU_TENSOR_MAP_SWIZZLE_128B);
    }
    {
        const cuuint64_t dims[2] = {D_FF, 512}, str[1] = {D_FF * 2};
        const cuuint32_t box[2] = {16, 128};
        encode(enc, &m.wg, d_in[6], 2, dims, str, box, CU_TENSOR_MAP_SWIZZLE_32B);
        encode(enc, &m.wu, d_in[7], 2, dims, str, box, CU_TENSOR_MAP_SWIZZLE_32B);
    }
    Params p;
    p.x = (const __nv_bfloat16*)d_in[0];
    p.c = (const __nv_bfloat16*)d_in[9];
    p.out = (__nv_bfloat16*)d_out;
    p.sc = scratch;
    fused_block_kernel<<<NCTA, NTHREADS, SMEM_BYTES, cudaStreamPerThread>>>(p, m.k, m.v, m.wq, m.wmod, m.wmod8, m.wo, m.wg, m.wu, m.wd);
}
```

```cpp
#include <cuda_runtime.h>
#include <cuda.h>
#include <cuda_bf16.h>
#include <stdint.h>

namespace {

constexpr int D_MODEL = 512;
constexpr int N_HEADS = 32;
constexpr int SK = 32768;
constexpr int DH = 128;
constexpr int D_FF = 1792;
constexpr int N_MOD = 6 * D_MODEL;

constexpr int NCTA = 128;
constexpr int NFFN = D_FF / 16;
constexpr int NOWN = 32;
constexpr int NTHREADS = 320;
constexpr int NST = 12;
constexpr int TILE = 16384;
#define WINDOW 3
#define WINDOW_TAIL 1
#define GU_WIN 3
#define GU_EARLY 0
#define WD_WIN 2
#define PACE_THR 96
constexpr int KV_TILES = 64;
#define MOD_AT 8
static_assert(MOD_AT % 2 == 0 && MOD_AT >= 2 && MOD_AT < 56, "schedule");
__host__ __device__ constexpr int kv_idx(int i) { return 2 + 2 * i + (i >= MOD_AT ? 1 : 0); }
constexpr int IDX_MOD = 2 + 2 * MOD_AT;
constexpr int N_STREAM = kv_idx(KV_TILES - 1) + 2;
constexpr int IDX_WO = N_STREAM;
constexpr int IDX_WG = IDX_WO + 2;
constexpr int IDX_WU = IDX_WG + 1;
constexpr int IDX_WD = IDX_WU + 1;
constexpr int SPIN_LIMIT = 1 << 20;

constexpr float LOG2E = 1.4426950408889634f;
constexpr float QK_SCALE = 0.08838834764831845f;

constexpr int SM_RING = 0;
constexpr int SM_MRG = SM_RING + NST * TILE;
constexpr int SM_ML = SM_MRG + 8 * 4 * 136 * 4;
constexpr int SM_RED = SM_ML + 8 * 4 * 8;
constexpr int SM_RED2 = SM_RED + 8 * 64 * 4;
constexpr int SM_QS = SM_RED2 + 8 * 64 * 4;
constexpr int SM_OS = SM_QS + 512 * 2;
constexpr int SM_SC = SM_OS + 2 * 128 * 2;
constexpr int SM_HS = SM_SC + 2 * 512 * 2;
constexpr int SM_STAT = SM_HS + 8 * 2 * 32 * 4;
constexpr int SM_PACE = SM_STAT + 8 * 2 * 8;
constexpr int SM_BAR = SM_PACE + 8;
constexpr int SM_END = SM_BAR + (2 * NST + 1 + 8 + 2) * 8;
constexpr int SMEM_BYTES = SM_END + 1024;

struct Scratch {
    uint4 inbox_wo[NOWN][N_HEADS][8];
    uint4 inbox_dn[NCTA][NFFN][2];
    uint2 x1[D_MODEL];
    uint2 part_o[NCTA][4][64];
    uint2 part_ml[NCTA][4][4];
    uint2 mod[2][N_MOD / 2];
    uint2 q[2][N_HEADS * DH / 2];
    unsigned epoch;
    unsigned pad_[31];
    unsigned cleared;
    unsigned pad2_[31];
    unsigned progress;
};
__device__ Scratch g_scratch;
constexpr uint32_t F_PART = 1, F_WO = 1, F_DOWN = 1, F_X1 = 1;
__device__ __forceinline__ uint32_t tagf(float v, uint32_t f) { return (__float_as_uint(v) & ~3u) | f; }
__device__ __forceinline__ float untag(uint32_t v) { return __uint_as_float(v & ~3u); }

struct Params {
    const __nv_bfloat16* x;
    const __nv_bfloat16* c;
    __nv_bfloat16* out;
    Scratch* sc;
};

#define TSTAMP(i) do { } while (0)

__device__ __forceinline__ uint32_t smem_u32(const void* p) { return (uint32_t)__cvta_generic_to_shared(p); }

__device__ __forceinline__ void mbar_init(uint32_t bar, uint32_t cnt) {
    asm volatile("mbarrier.init.shared::cta.b64 [%0], %1;" ::"r"(bar), "r"(cnt) : "memory");
}
__device__ __forceinline__ void mbar_expect_tx(uint32_t bar, uint32_t bytes) {
    asm volatile("mbarrier.arrive.expect_tx.shared::cta.b64 _, [%0], %1;" ::"r"(bar), "r"(bytes) : "memory");
}
__device__ __forceinline__ void mbar_arrive(uint32_t bar) {
    asm volatile("mbarrier.arrive.shared::cta.b64 _, [%0];" ::"r"(bar) : "memory");
}
__device__ __forceinline__ bool mbar_try(uint32_t bar, uint32_t parity) {
    uint32_t ok;
    asm volatile(
        "{\n\t.reg .pred p;\n\t"
        "mbarrier.try_wait.parity.shared::cta.b64 p, [%1], %2;\n\t"
        "selp.u32 %0, 1, 0, p;\n\t}"
        : "=r"(ok) : "r"(bar), "r"(parity) : "memory");
    return ok != 0;
}
__device__ __forceinline__ bool mbar_test(uint32_t bar, uint32_t parity) {
    uint32_t ok;
    asm volatile(
        "{\n\t.reg .pred p;\n\t"
        "mbarrier.test_wait.parity.shared::cta.b64 p, [%1], %2;\n\t"
        "selp.u32 %0, 1, 0, p;\n\t}"
        : "=r"(ok) : "r"(bar), "r"(parity) : "memory");
    return ok != 0;
}
__device__ __forceinline__ void mbar_wait(uint32_t bar, uint32_t parity) {
    if (mbar_try(bar, parity)) return;
    const long long t0 = clock64();
    while (!mbar_try(bar, parity))
        if (clock64() - t0 > (1ll << 31)) return;
}
__device__ __forceinline__ void cons_sync() { asm volatile("bar.sync 1, 256;" ::: "memory"); }

__device__ __forceinline__ void tma_2d(uint32_t dst, const CUtensorMap* m, int c0, int c1, uint32_t bar) {
    asm volatile("cp.async.bulk.tensor.2d.shared::cluster.global.mbarrier::complete_tx::bytes [%0], [%1, {%3, %4}], [%2];"
                 ::"r"(dst), "l"(m), "r"(bar), "r"(c0), "r"(c1) : "memory");
}
__device__ __forceinline__ void tma_3d(uint32_t dst, const CUtensorMap* m, int c0, int c1, int c2, uint32_t bar) {
    asm volatile("cp.async.bulk.tensor.3d.shared::cluster.global.mbarrier::complete_tx::bytes [%0], [%1, {%3, %4, %5}], [%2];"
                 ::"r"(dst), "l"(m), "r"(bar), "r"(c0), "r"(c1), "r"(c2) : "memory");
}
__device__ __forceinline__ void tma_3d_hint(uint32_t dst, const CUtensorMap* m, int c0, int c1, int c2, uint32_t bar, uint64_t pol) {
    asm volatile("cp.async.bulk.tensor.3d.shared::cluster.global.mbarrier::complete_tx::bytes.L2::cache_hint [%0], [%1, {%3, %4, %5}], [%2], %6;"
                 ::"r"(dst), "l"(m), "r"(bar), "r"(c0), "r"(c1), "r"(c2), "l"(pol) : "memory");
}
__device__ __forceinline__ void prefetch_tmap(const CUtensorMap* m) {
    asm volatile("prefetch.tensormap [%0];" ::"l"(m) : "memory");
}

__device__ __forceinline__ void ldsm4(uint32_t addr, uint32_t (&r)[4]) {
    asm volatile("ldmatrix.sync.aligned.m8n8.x4.shared.b16 {%0,%1,%2,%3}, [%4];"
                 : "=r"(r[0]), "=r"(r[1]), "=r"(r[2]), "=r"(r[3]) : "r"(addr) : "memory");
}
__device__ __forceinline__ void ldsm4t(uint32_t addr, uint32_t (&r)[4]) {
    asm volatile("ldmatrix.sync.aligned.m8n8.x4.trans.shared.b16 {%0,%1,%2,%3}, [%4];"
                 : "=r"(r[0]), "=r"(r[1]), "=r"(r[2]), "=r"(r[3]) : "r"(addr) : "memory");
}
__device__ __forceinline__ void mma16816(float (&c)[4], const uint32_t (&a)[4], uint32_t b0, uint32_t b1) {
    asm volatile("mma.sync.aligned.m16n8k16.row.col.f32.bf16.bf16.f32 {%0,%1,%2,%3}, {%4,%5,%6,%7}, {%8,%9}, {%0,%1,%2,%3};"
                 : "+f"(c[0]), "+f"(c[1]), "+f"(c[2]), "+f"(c[3])
                 : "r"(a[0]), "r"(a[1]), "r"(a[2]), "r"(a[3]), "r"(b0), "r"(b1));
}
__device__ __forceinline__ uint32_t movmatrix_t(uint32_t a) {
    uint32_t d;
    asm volatile("movmatrix.sync.aligned.m8n8.trans.b16 %0, %1;" : "=r"(d) : "r"(a));
    return d;
}
__device__ __forceinline__ uint32_t pack_bf16(float a, float b) {
    uint32_t r;
    asm("cvt.rn.bf16x2.f32 %0, %1, %2;" : "=r"(r) : "f"(b), "f"(a));
    return r;
}
__device__ __forceinline__ float bf_lo(uint32_t v) { return __uint_as_float(v << 16); }
__device__ __forceinline__ float bf_hi(uint32_t v) { return __uint_as_float(v & 0xffff0000u); }
__device__ __forceinline__ float bf16r(float a) { return bf_lo(pack_bf16(a, 0.f)); }
__device__ __forceinline__ uint32_t max_bf16x2(uint32_t a, uint32_t b) {
    uint32_t r;
    asm("max.bf16x2 %0, %1, %2;" : "=r"(r) : "r"(a), "r"(b));
    return r;
}
__device__ __forceinline__ float ex2(float x) {
    float r;
    asm("ex2.approx.ftz.f32 %0, %1;" : "=f"(r) : "f"(x));
    return r;
}

__device__ __forceinline__ void st_ll2(uint2* p, uint32_t v, uint32_t tag) {
    asm volatile("st.relaxed.gpu.global.v2.u32 [%0], {%1, %2};" ::"l"(p), "r"(v), "r"(tag) : "memory");
}
__device__ __forceinline__ void st_ll4(uint4* p, uint32_t v0, uint32_t v1, uint32_t tag) {
    asm volatile("st.relaxed.gpu.global.v4.u32 [%0], {%1, %2, %3, %2};" ::"l"(p), "r"(v0), "r"(tag), "r"(v1) : "memory");
}
__device__ __forceinline__ void st_v4(uint4* p, uint32_t a, uint32_t b, uint32_t c, uint32_t d) {
    asm volatile("st.relaxed.gpu.global.v4.u32 [%0], {%1, %2, %3, %4};" ::"l"(p), "r"(a), "r"(b), "r"(c), "r"(d) : "memory");
}
__device__ __forceinline__ uint2 ld_ll2(const uint2* p) {
    uint2 v;
    asm volatile("ld.relaxed.gpu.global.v2.u32 {%0, %1}, [%2];" : "=r"(v.x), "=r"(v.y) : "l"(p) : "memory");
    return v;
}
__device__ __forceinline__ uint4 ld_ll4(const uint4* p) {
    uint4 v;
    asm volatile("ld.relaxed.gpu.global.v4.u32 {%0, %1, %2, %3}, [%4];"
                 : "=r"(v.x), "=r"(v.y), "=r"(v.z), "=r"(v.w) : "l"(p) : "memory");
    return v;
}

#define DELAY_B1 300
#define DELAY_X1 2000
#define DELAY_NOFFN 1500
#define A_BACKOFF 0
#define DELAY_C 600
__device__ __forceinline__ uint32_t clock32() {
    uint32_t c;
    asm volatile("mov.u32 %0, %clock;" : "=r"(c));
    return c;
}
__device__ __forceinline__ void spin_cycles(uint32_t n) {
    if (n > 0) { const uint32_t c0 = clock32(); while (clock32() - c0 < n) {} }
}
__device__ __forceinline__ float rcp_approx(float x) {
    float r;
    asm("rcp.approx.ftz.f32 %0, %1;" : "=f"(r) : "f"(x));
    return r;
}
__device__ __forceinline__ float sqrt_approx(float x) {
    float r;
    asm("sqrt.approx.f32 %0, %1;" : "=f"(r) : "f"(x));
    return r;
}

__device__ __forceinline__ float silu_bf(float v) { return bf16r(v / (1.0f + expf(-v))); }

__device__ __forceinline__ float2 half_warp_sums(const float (&v)[4], float pivot) {
    float s1 = 0.f, s2 = 0.f;
#pragma unroll
    for (int i = 0; i < 4; i++) { const float d = v[i] - pivot; s1 += d; s2 += d * d; }
#pragma unroll
    for (int o = 1; o < 16; o <<= 1) { s1 += __shfl_xor_sync(0xffffffffu, s1, o); s2 += __shfl_xor_sync(0xffffffffu, s2, o); }
    return make_float2(s1, s2);
}
__device__ __forceinline__ void ln_stats(const float2* stat, int b, float pivot, float& mean_bf, float& rstd) {
    float s1 = 0.f, s2 = 0.f;
#pragma unroll
    for (int w = 0; w < 8; w++) { const float2 v = stat[w * 2 + b]; s1 += v.x; s2 += v.y; }
    const float dm = s1 * (1.0f / D_MODEL);
    const float var = fmaxf(s2 * (1.0f / D_MODEL) - dm * dm, 0.f);
    mean_bf = bf16r(pivot + dm);
    rstd = rcp_approx(bf16r(sqrt_approx(bf16r(bf16r(var) + 1e-5f))));
}
__device__ __forceinline__ float ln_norm(float xv, float mean_bf, float rstd) { return bf16r(bf16r(xv - mean_bf) * rstd); }
__device__ __forceinline__ float ln_mod(float n, float cmul, float sadd) { return bf16r(n * bf16r(1.0f + cmul)) + sadd; }

__global__ void __launch_bounds__(NTHREADS, 1)
fused_block_kernel(const Params p, const __grid_constant__ CUtensorMap tm_k, const __grid_constant__ CUtensorMap tm_v,
                   const __grid_constant__ CUtensorMap tm_wq, const __grid_constant__ CUtensorMap tm_wmod,
                   const __grid_constant__ CUtensorMap tm_wmod8,
                   const __grid_constant__ CUtensorMap tm_wo, const __grid_constant__ CUtensorMap tm_wg,
                   const __grid_constant__ CUtensorMap tm_wu, const __grid_constant__ CUtensorMap tm_wd) {
    extern __shared__ unsigned char smem_raw[];
    const uint32_t sbase = (smem_u32(smem_raw) + 1023u) & ~1023u;
    unsigned char* sgen = smem_raw + (sbase - smem_u32(smem_raw));
    const int tid = threadIdx.x, warp = tid >> 5, lane = tid & 31;
    const int cta = blockIdx.x;
    const uint32_t bar_full = sbase + SM_BAR, bar_empty = bar_full + NST * 8;
    const uint32_t bar_clear = bar_empty + NST * 8;
    const uint32_t bar_gu = bar_clear + 8;
    const uint32_t bar_bc = bar_gu + 8 * 8;
    const uint32_t bar_p0w = bar_bc + 8;

    const int key0 = (cta >> 3) * SK + (cta & 7) * 64;
    uint64_t pol = 0;
    if (tid == 256) {
        asm volatile("createpolicy.fractional.L2::evict_first.b64 %0, 1.0;" : "=l"(pol));
        mbar_init(bar_p0w, 1);
#pragma unroll
        for (int i = 0; i < 4; i++) mbar_init(bar_full + 8 * i, 1);
        asm volatile("fence.mbarrier_init.release.cluster;" ::: "memory");
        mbar_expect_tx(bar_p0w, 8192);
        tma_2d(sbase + SM_MRG, &tm_wmod8, cta * 8, 0, bar_p0w);
        tma_2d(sbase + SM_MRG + 4096, &tm_wmod8, cta * 8, 256, bar_p0w);
#pragma unroll
        for (int i = 0; i < 4; i++) mbar_expect_tx(bar_full + 8 * i, TILE);
        tma_2d(sbase + SM_RING, &tm_wq, cta * 32, 0, bar_full);
        tma_2d(sbase + SM_RING + TILE, &tm_wq, cta * 32, 256, bar_full + 8);
        tma_3d_hint(sbase + SM_RING + 2 * TILE, &tm_k, 0, key0, 0, bar_full + 16, pol);
        tma_3d_hint(sbase + SM_RING + 3 * TILE, &tm_v, 0, key0, 0, bar_full + 24, pol);
    }

    if (warp == 8) {
        if (lane == 0) {
            for (int i = 0; i < NST; i++) { if (i >= 4) mbar_init(bar_full + 8 * i, 1); mbar_init(bar_empty + 8 * i, 4); }
            mbar_init(bar_clear, 1);
            for (int k = 0; k < 8; k++) mbar_init(bar_gu + 8 * k, 1);
            mbar_init(bar_bc, 8);
            ((volatile uint32_t*)(sgen + SM_PACE))[0] = 0;
            ((volatile uint32_t*)(sgen + SM_PACE))[1] = WINDOW;
            asm volatile("fence.mbarrier_init.release.cluster;" ::: "memory");
        }
        __syncwarp();
        asm volatile("bar.arrive 2, 320;" ::: "memory");
        asm volatile("bar.arrive 3, 64;" ::: "memory");
        if (lane == 0) {
            int slot = 4; uint32_t ph = 1;
            int landed = 0, wslot = 0; uint32_t wph = 0;
            int kv = 2;
            auto wait_window = [&](int idx, int window) {
                while (landed + window <= idx) {
                    mbar_wait(bar_full + 8 * wslot, wph);
                    if (++wslot == NST) { wslot = 0; wph ^= 1; }
                    landed++;
                }
            };
            volatile uint32_t* pace = (volatile uint32_t*)(sgen + SM_PACE);
            prefetch_tmap(&tm_wmod);
            pace[0] = 4;
            for (int idx = 4; idx < N_STREAM; idx++) {
                if (idx >= NST) mbar_wait(bar_empty + 8 * slot, ph);
                wait_window(idx, (int)pace[1]);
                if (idx == 12) { prefetch_tmap(&tm_wo); prefetch_tmap(&tm_wg); prefetch_tmap(&tm_wu); prefetch_tmap(&tm_wd); }
                const uint32_t fb = bar_full + 8 * slot, dst = sbase + SM_RING + slot * TILE;
                mbar_expect_tx(fb, TILE);
                if (idx == IDX_MOD) {
                    tma_2d(dst, &tm_wmod, 1024 + cta * 16, 0, fb);
                    tma_2d(dst + 8192, &tm_wmod, 1024 + cta * 16, 256, fb);
                } else {
                    tma_3d_hint(dst, (kv & 1) ? &tm_v : &tm_k, 0, key0 + (kv >> 1) * 512, 0, fb, pol);
                    kv++;
                }
                pace[0] = idx + 1;
                if (++slot == NST) { slot = 0; ph ^= 1; }
            }
            auto slot_free = [&](int idx) { mbar_wait(bar_empty + 8 * (idx % NST), ((idx / NST) & 1) ^ 1); };
#pragma unroll
            for (int s = 0; s < 2; s++) {
                const int idx = IDX_WO + s;
                slot_free(idx);
                wait_window(idx, WINDOW_TAIL);
                mbar_expect_tx(bar_full + 8 * (idx % NST), TILE);
                tma_3d(sbase + SM_RING + (idx % NST) * TILE, &tm_wo, 0, (cta >> 2) * 128 + s * 64, (cta & 3) * 2, bar_full + 8 * (idx % NST));
            }
            if (cta < NFFN) {
                slot_free(IDX_WG); slot_free(IDX_WU);
#pragma unroll
                for (int st = 0; st < 8; st++) {
                    if (st == GU_EARLY) {
                        mbar_wait(bar_full + 8 * (IDX_WO % NST), (IDX_WO / NST) & 1);
                        mbar_wait(bar_full + 8 * ((IDX_WO + 1) % NST), ((IDX_WO + 1) / NST) & 1);
                    }
                    if (st >= GU_WIN) mbar_wait(bar_gu + 8 * (st - GU_WIN), 0);
                    mbar_expect_tx(bar_gu + 8 * st, 4096);
                    tma_2d(sbase + SM_RING + (((st & 1) ? IDX_WU : IDX_WG) % NST) * TILE + (st >> 1) * 4096,
                           (st & 1) ? &tm_wu : &tm_wg, cta * 16, (st >> 1) * 128, bar_gu + 8 * st);
                }
                mbar_wait(bar_gu + 8 * (8 - WD_WIN), 0);
                slot_free(IDX_WD);
                mbar_expect_tx(bar_full + 8 * (IDX_WD % NST), TILE);
                tma_3d(sbase + SM_RING + (IDX_WD % NST) * TILE, &tm_wd, 0, cta * 16, 0, bar_full + 8 * (IDX_WD % NST));
            }
        }
    } else if (warp == 9) {
        Scratch* const sc = p.sc;
        const uint32_t tag = *(volatile unsigned*)&sc->epoch + 1;
        if (lane < 2) {
            st_ll4((uint4*)&sc->mod[lane][cta * 4], 0u, 0u, 0u);
            st_ll4((uint4*)&sc->mod[lane][cta * 4] + 1, 0u, 0u, 0u);
        }
        if (lane < 8) st_ll4((uint4*)&sc->mod[lane >> 2][512 + cta * 8] + (lane & 3), 0u, 0u, 0u);
        if (lane < 16) st_ll4((uint4*)&sc->q[lane >> 3][cta * 16] + (lane & 7), 0u, 0u, 0u);
        __syncwarp();
        asm volatile("bar.arrive 2, 320;" ::: "memory");
        asm volatile("bar.sync 3, 64;" ::: "memory");
#pragma unroll 4
        for (int i = 0; i < NFFN * 2 / 32; i++) st_v4(&sc->inbox_dn[cta][0][0] + i * 32 + lane, 0u, 0u, 0u, 0u);
        if (cta >= NCTA - NOWN) {
#pragma unroll 4
            for (int i = 0; i < 8; i++) st_v4(&sc->inbox_wo[cta - (NCTA - NOWN)][0][0] + i * 32 + lane, 0u, 0u, 0u, 0u);
            if (lane < 8) st_v4((uint4*)&sc->x1[(cta - (NCTA - NOWN)) * 16] + lane, 0u, 0u, 0u, 0u);
        }
#pragma unroll 4
        for (int i = 0; i < 4; i++) st_v4((uint4*)&sc->part_o[cta][0][0] + i * 32 + lane, 0u, 0u, 0u, 0u);
        if (lane < 8) st_v4((uint4*)&sc->part_ml[cta][0][0] + lane, 0u, 0u, 0u, 0u);
        if (cta == 0 && lane == 0) asm volatile("st.relaxed.gpu.global.u32 [%0], %1;" ::"l"(&sc->progress), "r"(0u) : "memory");
        asm volatile("fence.acq_rel.gpu;" ::: "memory");
        __syncwarp();
        if (lane == 0) {
            asm volatile("fence.acq_rel.gpu;" ::: "memory");
            asm volatile("red.relaxed.gpu.global.add.u32 [%0], %1;" ::"l"(&sc->cleared), "r"(1u) : "memory");
            const uint32_t target = tag * NCTA;
            for (int it = 0; it < SPIN_LIMIT; it++) {
                uint32_t v;
                asm volatile("ld.relaxed.gpu.global.u32 %0, [%1];" : "=r"(v) : "l"(&sc->cleared) : "memory");
                if ((int32_t)(v - target) >= 0) break;
                __nanosleep(500);
            }
            asm volatile("fence.acq_rel.gpu;" ::: "memory");
            mbar_arrive(bar_clear);
            volatile uint32_t* pace = (volatile uint32_t*)(sgen + SM_PACE);
            uint32_t posted = 0;
            for (int it = 0; it < SPIN_LIMIT; it++) {
                const uint32_t own = pace[0];
                if (own >= N_STREAM) break;
                if (own > posted) {
                    asm volatile("red.relaxed.gpu.global.add.u32 [%0], %1;" ::"l"(&sc->progress), "r"(own - posted) : "memory");
                    posted = own;
                }
                uint32_t v;
                asm volatile("ld.relaxed.gpu.global.u32 %0, [%1];" : "=r"(v) : "l"(&sc->progress) : "memory");
                const int diff = (int)v - (int)own * NCTA;
                pace[1] = diff > PACE_THR ? WINDOW + 1 : diff < -PACE_THR ? WINDOW - 1 : WINDOW;
                __nanosleep(200);
            }
        }
    } else {
        const int g = lane >> 2, t = lane & 3;
        const int bb = g & 1;
        const int eb = lane >> 4;
        const int ec = 64 * warp + 4 * (lane & 15);
        if (warp == 0) TSTAMP(0);
        Scratch* const sc = p.sc;
        const float c00 = __bfloat162float(p.c[tid]), c01 = __bfloat162float(p.c[tid + 256]);
        const float c10 = __bfloat162float(p.c[D_MODEL + tid]), c11 = __bfloat162float(p.c[D_MODEL + tid + 256]);
        const uint2 xe = __ldg((const uint2*)(p.x + eb * D_MODEL + ec));
        const float xpivot = __bfloat162float(p.x[eb * D_MODEL]);
        const uint32_t tag = *(volatile unsigned*)&sc->epoch + 1;
        const int ocol = cta * 4 + (lane & 3);
        const int wcol = (cta >= NCTA - NOWN ? cta - (NCTA - NOWN) : 0) * 16 + (lane & 15);
        const float xo = __bfloat162float(p.x[eb * D_MODEL + wcol]);

        float* red = (float*)(sgen + SM_RED);
        float* red2 = (float*)(sgen + SM_RED2);
        float2* stat = (float2*)(sgen + SM_STAT);
        uint32_t* hs = (uint32_t*)(sgen + SM_HS) + warp * 64;
        float xn[4];
        {
            float xv[4] = {bf_lo(xe.x), bf_hi(xe.x), bf_lo(xe.y), bf_hi(xe.y)};
            const float2 ps = half_warp_sums(xv, xpivot);
            if ((lane & 15) == 0) stat[warp * 2 + eb] = ps;
            const float s00 = silu_bf(c00), s01 = silu_bf(c01), s10 = silu_bf(c10), s11 = silu_bf(c11);
            __nv_bfloat16* scs = (__nv_bfloat16*)(sgen + SM_SC);
            scs[tid] = __float2bfloat16_rn(s00); scs[tid + 256] = __float2bfloat16_rn(s01);
            scs[512 + tid] = __float2bfloat16_rn(s10); scs[512 + tid + 256] = __float2bfloat16_rn(s11);
            asm volatile("bar.sync 2, 320;" ::: "memory");
            if (warp == 0) TSTAMP(23);
            float cp[4] = {0.f, 0.f, 0.f, 0.f};
            const uint32_t* sc32 = (const uint32_t*)(sgen + SM_SC) + bb * 256 + 32 * warp + t;
            mbar_wait(bar_p0w, 0);
#pragma unroll
            for (int s = 0; s < 4; s++) {
                uint32_t r0, r1;
                asm volatile("ldmatrix.sync.aligned.m8n8.x2.trans.shared.b16 {%0,%1}, [%2];"
                             : "=r"(r0), "=r"(r1) : "r"(sbase + SM_MRG + (64 * warp + 16 * s + (lane & 15)) * 16) : "memory");
                const uint32_t a[4] = {r0, r0, r1, r1};
                mma16816(cp, a, sc32[8 * s], sc32[8 * s + 4]);
            }
            if (t == 0) { red[warp * 16 + g] = cp[0]; red[warp * 16 + 8 + g] = cp[1]; }
            if (warp == 0) TSTAMP(14);
            cons_sync();
            if (warp == 0) {
                float s = 0.f;
#pragma unroll
                for (int w = 0; w < 8; w++) s += red[w * 16 + (lane & 15)];
                const float nx = __shfl_down_sync(0xffffffffu, s, 1);
                if (lane < 16 && !(lane & 1))
                    st_ll2(&sc->mod[lane >> 3][cta * 4 + ((lane & 7) >> 1)], pack_bf16(s, nx), tag);
                TSTAMP(1);
            }
            float mean_bf, rstd;
            ln_stats(stat, eb, xpivot, mean_bf, rstd);
#pragma unroll
            for (int i = 0; i < 4; i++) xn[i] = ln_norm(xv[i], mean_bf, rstd);
        }
        {
            uint4 sa, ca;
            for (int it = 0;; it++) {
                sa = ld_ll4((const uint4*)&sc->mod[eb][ec >> 1]);
                ca = ld_ll4((const uint4*)&sc->mod[eb][256 + (ec >> 1)]);
                const bool ok = sa.y == tag && sa.w == tag && ca.y == tag && ca.w == tag;
                if (__all_sync(0xffffffffu, ok) || it > SPIN_LIMIT) break;
            }
            *(uint2*)&hs[eb * 32 + 2 * (lane & 15)] =
                make_uint2(pack_bf16(ln_mod(xn[0], bf_lo(ca.x), bf_lo(sa.x)), ln_mod(xn[1], bf_hi(ca.x), bf_hi(sa.x))),
                           pack_bf16(ln_mod(xn[2], bf_lo(ca.z), bf_lo(sa.z)), ln_mod(xn[3], bf_hi(ca.z), bf_hi(sa.z))));
            __syncwarp();
            uint32_t hb[8];
#pragma unroll
            for (int i = 0; i < 8; i++) hb[i] = hs[bb * 32 + 8 * (i >> 1) + 4 * (i & 1) + t];
            if (warp == 0) TSTAMP(2);
            float cq[2][4] = {};
            const int ts = warp >> 2;
            mbar_wait(bar_full + 8 * ts, 0);
            const uint32_t tb = sbase + SM_RING + ts * TILE;
#pragma unroll
            for (int s = 0; s < 4; s++) {
                const int row = 64 * (warp & 3) + 16 * s + (lane & 7) + (lane >> 4) * 8;
#pragma unroll
                for (int mt = 0; mt < 2; mt++) {
                    const int ch = 2 * mt + ((lane >> 3) & 1);
                    uint32_t a[4];
                    ldsm4t(tb + row * 64 + ((ch ^ ((row >> 1) & 3)) << 4), a);
                    mma16816(cq[mt], a, hb[2 * s], hb[2 * s + 1]);
                }
            }
            if (t < 2) {
                const float v0 = t == 0 ? cq[0][0] : cq[1][0], v1 = t == 0 ? cq[0][1] : cq[1][1];
                const float v2 = t == 0 ? cq[0][2] : cq[1][2], v3 = t == 0 ? cq[0][3] : cq[1][3];
                *(float2*)&red2[warp * 64 + (16 * t + g) * 2] = make_float2(v0, v1);
                *(float2*)&red2[warp * 64 + (16 * t + g + 8) * 2] = make_float2(v2, v3);
            }
            cons_sync();
            if (warp < 4 && lane == 0) { mbar_arrive(bar_empty); mbar_arrive(bar_empty + 8); }
            if (warp == 0) {
                const int b = lane >> 4, cp = lane & 15;
                float q0 = 0.f, q1 = 0.f;
#pragma unroll
                for (int w = 0; w < 8; w++) {
                    const float4 v = *(const float4*)&red2[w * 64 + cp * 4];
                    q0 += b ? v.y : v.x; q1 += b ? v.w : v.z;
                }
                st_ll2(&sc->q[b][cta * 16 + cp], pack_bf16(q0, q1), tag);
                TSTAMP(3);
            }
        }
        const int pair = cta >> 3;
        uint32_t qf[16];
        {
            uint2* qs = (uint2*)(sgen + SM_QS);
            if (tid < 128) {
                const uint4* src = (const uint4*)&sc->q[pair >> 3][(pair & 7) * 256] + tid;
                uint4 v;
                for (int it = 0;; it++) {
                    v = ld_ll4(src);
                    if ((v.y == tag && v.w == tag) || it > SPIN_LIMIT) break;
                }
                qs[tid] = make_uint2(v.x, v.z);
            }
            cons_sync();
            const uint32_t* q32 = (const uint32_t*)(sgen + SM_QS);
#pragma unroll
            for (int s = 0; s < 8; s++) {
                qf[2 * s] = q32[(g & 3) * 64 + 8 * s + t];
                qf[2 * s + 1] = q32[(g & 3) * 64 + 8 * s + 4 + t];
            }
        }
        if (warp == 0) TSTAMP(4);

        float o[8][4];
#pragma unroll
        for (int i = 0; i < 8; i++) { o[i][0] = o[i][1] = o[i][2] = o[i][3] = 0.f; }
        uint32_t mrun = 0xff80ff80u;
        float ls[4] = {0.f, 0.f, 0.f, 0.f};
        uint4 m_sb, m_cb; uint2 m_ga, m_gb0, m_gb1;
        {
            const int grp = warp >> 2, wi = warp & 3;
            const int krow = 16 * wi + (lane & 7) + ((lane >> 3) & 1) * 8;
            const uint32_t koff = krow * 128 + ((((lane >> 4) & 1) ^ (lane & 7)) << 4);
            const int vrow = 16 * wi + (lane & 7) + (lane >> 4) * 8;
            const uint32_t voff = vrow * 128 + ((((lane >> 3) & 1) ^ (lane & 7)) << 4);
            const uint32_t ones[4] = {0x3f803f80u, 0x3f803f80u, 0x3f803f80u, 0x3f803f80u};
            for (int i = grp; i < KV_TILES; i += 2) {
                if (i == MOD_AT + grp) {
                    float cm[4] = {};
                    const uint32_t* sc32 = (const uint32_t*)(sgen + SM_SC) + bb * 256 + 32 * warp + t;
                    mbar_wait(bar_full + 8 * (IDX_MOD % NST), (IDX_MOD / NST) & 1);
                    const uint32_t tb = sbase + SM_RING + (IDX_MOD % NST) * TILE;
#pragma unroll
                    for (int s = 0; s < 4; s++) {
                        const int row = 64 * warp + 16 * s + (lane & 7) + (lane >> 4) * 8;
                        const int ch = (lane >> 3) & 1;
                        uint32_t a[4];
                        ldsm4t(tb + row * 32 + ((ch ^ ((row >> 2) & 1)) << 4), a);
                        mma16816(cm, a, sc32[8 * s], sc32[8 * s + 4]);
                    }
                    if (t == 0) {
                        *(float2*)&red[warp * 64 + g * 2] = make_float2(cm[0], cm[1]);
                        *(float2*)&red[warp * 64 + (g + 8) * 2] = make_float2(cm[2], cm[3]);
                    }
                    cons_sync();
                    if (warp < 4 && lane == 0) mbar_arrive(bar_empty + 8 * (IDX_MOD % NST));
                    if (warp == 1 && lane < 16) {
                        const int b = lane >> 3, cp = lane & 7;
                        float q0 = 0.f, q1 = 0.f;
#pragma unroll
                        for (int w = 0; w < 8; w++) {
                            const float4 v = *(const float4*)&red[w * 64 + cp * 4];
                            q0 += b ? v.y : v.x; q1 += b ? v.w : v.z;
                        }
                        st_ll2(&sc->mod[b][512 + cta * 8 + cp], pack_bf16(q0, q1), tag);
                    }
                }
                if (i == 56 + grp) {
                    m_sb = ld_ll4((const uint4*)&sc->mod[eb][768 + (ec >> 1)]);
                    m_cb = ld_ll4((const uint4*)&sc->mod[eb][1024 + (ec >> 1)]);
                    m_ga = ld_ll2(&sc->mod[eb][512 + (wcol >> 1)]);
                    m_gb0 = ld_ll2(&sc->mod[0][1280 + (ocol >> 1)]); m_gb1 = ld_ll2(&sc->mod[1][1280 + (ocol >> 1)]);
                }
                if (i == 60 + grp) {
                    for (int it = 0;; it++) {
                        const bool ok = m_sb.y == tag && m_sb.w == tag && m_cb.y == tag && m_cb.w == tag &&
                                        m_ga.y == tag && m_gb0.y == tag && m_gb1.y == tag;
                        if (__all_sync(0xffffffffu, ok) || it > SPIN_LIMIT) break;
                        m_sb = ld_ll4((const uint4*)&sc->mod[eb][768 + (ec >> 1)]);
                        m_cb = ld_ll4((const uint4*)&sc->mod[eb][1024 + (ec >> 1)]);
                        m_ga = ld_ll2(&sc->mod[eb][512 + (wcol >> 1)]);
                        m_gb0 = ld_ll2(&sc->mod[0][1280 + (ocol >> 1)]); m_gb1 = ld_ll2(&sc->mod[1][1280 + (ocol >> 1)]);
                    }
                    mbar_wait(bar_clear, 0);
                }
                const int ki = kv_idx(i), ks = ki % NST, vs = (ki + 1) % NST;
                const uint32_t kph = (ki / NST) & 1, vph = ((ki + 1) / NST) & 1;
                mbar_wait(bar_full + 8 * ks, kph);
                const uint32_t kb = sbase + SM_RING + ks * TILE + koff;
                float sa[4] = {0.f, 0.f, 0.f, 0.f}, sb[4] = {0.f, 0.f, 0.f, 0.f};
#pragma unroll
                for (int s = 0; s < 8; s += 2) {
                    uint32_t a0[4], a1[4];
                    ldsm4((kb ^ ((s & 3) << 5)) + (s >> 2) * 8192, a0);
                    ldsm4((kb ^ (((s + 1) & 3) << 5)) + (s >> 2) * 8192, a1);
                    mma16816(sa, a0, qf[2 * s], qf[2 * s + 1]);
                    mma16816(sb, a1, qf[2 * s + 2], qf[2 * s + 3]);
                }
                __syncwarp();
                if (lane == 0) mbar_arrive(bar_empty + 8 * ks);
                uint32_t r01 = pack_bf16(sa[0] + sb[0], sa[1] + sb[1]);
                uint32_t r23 = pack_bf16(sa[2] + sb[2], sa[3] + sb[3]);
                r01 = pack_bf16(bf_lo(r01) * QK_SCALE, bf_hi(r01) * QK_SCALE);
                r23 = pack_bf16(bf_lo(r23) * QK_SCALE, bf_hi(r23) * QK_SCALE);
                uint32_t mx = max_bf16x2(r01, r23);
                mx = max_bf16x2(mx, __shfl_xor_sync(0xffffffffu, mx, 4));
                mx = max_bf16x2(mx, __shfl_xor_sync(0xffffffffu, mx, 8));
                mx = max_bf16x2(mx, __shfl_xor_sync(0xffffffffu, mx, 16));
                const uint32_t mnew = max_bf16x2(mrun, mx);
                const float m0 = bf_lo(mnew), m1 = bf_hi(mnew);
                if (__any_sync(0xffffffffu, mnew != mrun)) {
                    const float al0 = ex2((bf_lo(mrun) - m0) * LOG2E), al1 = ex2((bf_hi(mrun) - m1) * LOG2E);
                    ls[0] *= al0; ls[1] *= al1;
#pragma unroll
                    for (int d = 0; d < 8; d++) { o[d][0] *= al0; o[d][1] *= al1; o[d][2] *= al0; o[d][3] *= al1; }
                    mrun = mnew;
                }
                const float p0 = ex2((bf_lo(r01) - m0) * LOG2E), p1 = ex2((bf_hi(r01) - m1) * LOG2E);
                const float p2 = ex2((bf_lo(r23) - m0) * LOG2E), p3 = ex2((bf_hi(r23) - m1) * LOG2E);
                const uint32_t pb0 = movmatrix_t(pack_bf16(p0, p1)), pb1 = movmatrix_t(pack_bf16(p2, p3));
                mma16816(ls, ones, pb0, pb1);
                mbar_wait(bar_full + 8 * vs, vph);
                const uint32_t vb = sbase + SM_RING + vs * TILE + voff;
#pragma unroll
                for (int d = 0; d < 8; d++) {
                    uint32_t a[4];
                    ldsm4t((vb ^ ((d & 3) << 5)) + (d >> 2) * 8192, a);
                    mma16816(o[d], a, pb0, pb1);
                }
                __syncwarp();
                if (lane == 0) mbar_arrive(bar_empty + 8 * vs);
            }
        }
        if (warp == 7) TSTAMP(5);
        {
            float* mrg = (float*)(sgen + SM_MRG);
            float2* ml = (float2*)(sgen + SM_ML);
            {
                const int hp = (t & 1) * 2, up = t >> 1;
                if (g == 0 && up == 0) { ml[warp * 4 + hp] = make_float2(bf_lo(mrun), ls[0]); ml[warp * 4 + hp + 1] = make_float2(bf_hi(mrun), ls[1]); }
                float* m0p = mrg + (warp * 4 + hp) * 136 + up * 72 + g;
#pragma unroll
                for (int d = 0; d < 4; d++) {
                    m0p[16 * d] = up ? o[d + 4][0] : o[d][0]; m0p[136 + 16 * d] = up ? o[d + 4][1] : o[d][1];
                    m0p[16 * d + 8] = up ? o[d + 4][2] : o[d][2]; m0p[136 + 16 * d + 8] = up ? o[d + 4][3] : o[d][3];
                }
            }
            cons_sync();
            const int hh = tid >> 6, dp = tid & 63;
            float2 mw[8];
            float M = -INFINITY;
#pragma unroll
            for (int w = 0; w < 8; w++) { mw[w] = ml[w * 4 + hh]; M = fmaxf(M, mw[w].x); }
            float L = 0.f, o0 = 0.f, o1 = 0.f;
#pragma unroll
            for (int w = 0; w < 8; w++) {
                const float wt = ex2((mw[w].x - M) * LOG2E);
                const float2 v = *(const float2*)&mrg[(w * 4 + hh) * 136 + 2 * dp + (dp >= 32 ? 8 : 0)];
                L += wt * mw[w].y; o0 += wt * v.x; o1 += wt * v.y;
            }
            st_ll2(&sc->part_o[cta][hh][dp], tagf(o0, F_PART), tagf(o1, F_PART));
            if (dp < 4) st_ll2(&sc->part_ml[cta][hh][dp], tagf(M, F_PART), tagf(L, F_PART));
        }
        if (warp == 0) TSTAMP(6);
        {
            const int hq = cta >> 2, kvh = hq >> 2, hh = hq & 3;
            const int b = tid >> 7, dc = (tid >> 3) & 15, j = tid & 7;
            const int pc = (b * 8 + kvh) * 8 + j;
            const uint4* po = (const uint4*)&sc->part_o[pc][hh][0] + dc * 2;
            const uint2* pm = &sc->part_ml[pc - j][hh][0];
            uint4 vo0, vo1; uint2 vm[8];
            bool oko = false, okm = false;
            for (int it = 0;; it++) {
                if (!oko) { vo0 = ld_ll4(po); vo1 = ld_ll4(po + 1); }
                if (!okm) {
#pragma unroll
                    for (int jj = 0; jj < 8; jj++) vm[jj] = ld_ll2(pm + jj * 16);
                }
                oko = (vo0.x & vo0.y & vo0.z & vo0.w & vo1.x & vo1.y & vo1.z & vo1.w & 3u) == F_PART;
                uint32_t all = vm[0].x & vm[0].y;
#pragma unroll
                for (int jj = 1; jj < 8; jj++) all &= vm[jj].x & vm[jj].y;
                okm = (all & 3u) == F_PART;
                if (__all_sync(0xffffffffu, oko && okm) || it > SPIN_LIMIT) break;
                spin_cycles(A_BACKOFF);
            }
            float M = untag(vm[0].x);
#pragma unroll
            for (int jj = 1; jj < 8; jj++) M = fmaxf(M, untag(vm[jj].x));
            float wt = 0.f, L = 0.f;
#pragma unroll
            for (int jj = 0; jj < 8; jj++) {
                const float w_ = ex2((untag(vm[jj].x) - M) * LOG2E);
                L += w_ * untag(vm[jj].y);
                wt = jj == j ? w_ : wt;
            }
            wt *= rcp_approx(L);
            float v[8] = {wt * untag(vo0.x), wt * untag(vo0.y), wt * untag(vo0.z), wt * untag(vo0.w),
                          wt * untag(vo1.x), wt * untag(vo1.y), wt * untag(vo1.z), wt * untag(vo1.w)};
#define XRED(N, O)                                                                       \
            {                                                                            \
                const bool up = lane & (O);                                              \
                _Pragma("unroll") for (int i = 0; i < (N); i++) {                        \
                    const float send = up ? v[i] : v[i + (N)], keep = up ? v[i + (N)] : v[i]; \
                    v[i] = keep + __shfl_xor_sync(0xffffffffu, send, (O));               \
                }                                                                        \
            }
            XRED(4, 1) XRED(2, 2) XRED(1, 4)
#undef XRED
            __nv_bfloat16* os = (__nv_bfloat16*)(sgen + SM_OS);
            os[b * 128 + dc * 8 + 4 * (j & 1) + 2 * ((j >> 1) & 1) + (j >> 2)] = __float2bfloat16_rn(v[0]);
            if (warp == 0) TSTAMP(15);
            uint32_t wf[8][4];
            const uint32_t aoff_o = (warp >> 2) * 8192 + ((lane & 7) + (lane >> 4) * 8) * 128 +
                                    (((((warp & 3) * 2 + ((lane >> 3) & 1)) ^ (lane & 7))) << 4);
#pragma unroll
            for (int s = 0; s < 2; s++) {
                const int idx = IDX_WO + s;
                mbar_wait(bar_full + 8 * (idx % NST), (idx / NST) & 1);
                const uint32_t tb = sbase + SM_RING + (idx % NST) * TILE + aoff_o;
#pragma unroll
                for (int k4 = 0; k4 < 4; k4++) ldsm4t(tb + k4 * 2048, wf[s * 4 + k4]);
            }
            cons_sync();
            if (warp == 0) TSTAMP(7);
            const uint32_t* os32 = (const uint32_t*)(sgen + SM_OS) + bb * 64 + t;
            float y0[4] = {}, y1[4] = {};
#pragma unroll
            for (int ks = 0; ks < 8; ks += 2) {
                mma16816(y0, wf[ks], os32[8 * ks], os32[8 * ks + 4]);
                mma16816(y1, wf[ks + 1], os32[8 * ks + 8], os32[8 * ks + 12]);
            }
            if (t == 0)
                st_v4(&sc->inbox_wo[(cta & 3) * 8 + warp][hq][g], tagf(y0[0] + y1[0], F_WO), tagf(y0[1] + y1[1], F_WO),
                      tagf(y0[2] + y1[2], F_WO), tagf(y0[3] + y1[3], F_WO));
        }
        const uint32_t t_wo = clock32();
        if (warp == 0) TSTAMP(8);
        if (cta >= NCTA - NOWN) {
            const uint4* pin = &sc->inbox_wo[cta - (NCTA - NOWN)][0][0] + tid;
            uint4 v;
            spin_cycles(DELAY_B1);
            bool ok = false;
            for (int it = 0;; it++) {
                if (!ok) {
                    v = ld_ll4(pin);
                    ok = (v.x & v.y & v.z & v.w & 3u) == F_WO;
                }
                if (__all_sync(0xffffffffu, ok) || it > SPIN_LIMIT) break;
            }
            const bool u1 = lane & 8, u2 = lane & 16;
            const float a0 = untag(v.x), a1 = untag(v.y), a2 = untag(v.z), a3 = untag(v.w);
            const float k0 = (u1 ? a2 : a0) + __shfl_xor_sync(0xffffffffu, u1 ? a0 : a2, 8);
            const float k1 = (u1 ? a3 : a1) + __shfl_xor_sync(0xffffffffu, u1 ? a1 : a3, 8);
            red2[warp * 32 + lane] = (u2 ? k1 : k0) + __shfl_xor_sync(0xffffffffu, u2 ? k0 : k1, 16);
            cons_sync();
            if (warp == 0) {
                float a = 0.f;
#pragma unroll
                for (int w = 0; w < 8; w++) a += red2[w * 32 + lane];
                const float ga = (wcol & 1) ? bf_hi(m_ga.x) : bf_lo(m_ga.x);
                const float xm = bf16r(xo + bf16r(ga * bf16r(a)));
                const float xm_b1 = __shfl_down_sync(0xffffffffu, xm, 16);
                if (lane < 16) st_ll2(&sc->x1[wcol], pack_bf16(xm, xm_b1), F_X1);
                TSTAMP(10);
            }
        }
        const uint32_t aoff = warp * 2048 + ((lane & 7) + (lane >> 4) * 8) * 128 + ((((lane >> 3) & 1) ^ (lane & 7)) << 4);
        if (cta < NFFN) {
            const uint4* px = (const uint4*)&sc->x1[ec];
            const uint4* pp = (const uint4*)&sc->x1[0];
            uint4 va, vb, pa, pb;
            const float c1v[4] = {bf16r(1.0f + bf_lo(m_cb.x)), bf16r(1.0f + bf_hi(m_cb.x)), bf16r(1.0f + bf_lo(m_cb.z)), bf16r(1.0f + bf_hi(m_cb.z))};
            float bg = 0.f, cgc = 0.f, bu = 0.f, cuc = 0.f;
            uint32_t gf[4][4], uf[4][4];
            const uint32_t bar_g = bar_gu + 8 * (2 * (warp >> 1));
            uint32_t* pre = (uint32_t*)(sgen + SM_MRG) + warp * 128;
            *(uint2*)&pre[eb * 32 + 2 * (lane & 15)] = make_uint2(pack_bf16(c1v[0], c1v[1]), pack_bf16(c1v[2], c1v[3]));
            *(uint2*)&pre[64 + eb * 32 + 2 * (lane & 15)] = make_uint2(m_sb.x, m_sb.z);
            __syncwarp();
            auto weights_and_bc = [&]() {
                mbar_wait(bar_g, 0);
                mbar_wait(bar_g + 8, 0);
                const uint32_t tg = sbase + SM_RING + (IDX_WG % NST) * TILE, tu = sbase + SM_RING + (IDX_WU % NST) * TILE;
#pragma unroll
                for (int s = 0; s < 4; s++) {
                    const int row = 64 * warp + 16 * s + (lane & 7) + (lane >> 4) * 8;
                    const uint32_t off = row * 32 + ((((lane >> 3) & 1) ^ ((row >> 2) & 1)) << 4);
                    ldsm4t(tg + off, gf[s]);
                    ldsm4t(tu + off, uf[s]);
                }
                float* bc = (float*)(sgen + SM_MRG + 4096);
                float yg[4] = {}, yu[4] = {};
                const uint32_t* pb = pre + ((g >> 1) & 1) * 64 + bb * 32 + t;
#pragma unroll
                for (int s = 0; s < 4; s++) {
                    const uint32_t b0 = pb[8 * s], b1 = pb[8 * s + 4];
                    mma16816(yg, gf[s], b0, b1);
                    mma16816(yu, uf[s], b0, b1);
                }
                const float y0 = t < 2 ? yg[0] : yu[0], y1 = t < 2 ? yg[1] : yu[1], y2 = t < 2 ? yg[2] : yu[2], y3 = t < 2 ? yg[3] : yu[3];
                float* dstp = bc + warp * 128 + (t >> 1) * 64 + (t & 1) * 32;
                *(float2*)&dstp[g * 2] = make_float2(y0, y1);
                *(float2*)&dstp[(g + 8) * 2] = make_float2(y2, y3);
                __syncwarp();
                if (lane == 0) mbar_arrive(bar_bc);
            };
            bool gu_early = false;
            do {
                gu_early = __all_sync(0xffffffffu, mbar_test(bar_g, 0) && mbar_test(bar_g + 8, 0));
            } while (!gu_early && clock32() - t_wo < DELAY_X1);
            if (gu_early) weights_and_bc();
            if (warp == 0) TSTAMP(11);
            float pivot2;
            {
                while (clock32() - t_wo < DELAY_X1) {}
                bool okx = false, okp = false;
                for (int it = 0;; it++) {
                    if (!okx) { va = ld_ll4(px); vb = ld_ll4(px + 1); }
                    if (!okp) { pa = ld_ll4(pp); pb = ld_ll4(pp + 1); }
                    okx = va.y == F_X1 && va.w == F_X1 && vb.y == F_X1 && vb.w == F_X1;
                    okp = pa.y == F_X1 && pa.w == F_X1 && pb.y == F_X1 && pb.w == F_X1;
                    if (__all_sync(0xffffffffu, okx && okp) || it > SPIN_LIMIT) break;
                }
                if (warp == 0) TSTAMP(9);
                const float xv[4] = {eb ? bf_hi(va.x) : bf_lo(va.x), eb ? bf_hi(va.z) : bf_lo(va.z),
                                     eb ? bf_hi(vb.x) : bf_lo(vb.x), eb ? bf_hi(vb.z) : bf_lo(vb.z)};
                const float p0 = 0.25f * ((bf_lo(pa.x) + bf_lo(pa.z)) + (bf_lo(pb.x) + bf_lo(pb.z)));
                const float p1 = 0.25f * ((bf_hi(pa.x) + bf_hi(pa.z)) + (bf_hi(pb.x) + bf_hi(pb.z)));
                const float pivot = eb ? p1 : p0;
                pivot2 = (lane & 1) ? p1 : p0;
                *(uint2*)&hs[eb * 32 + 2 * (lane & 15)] =
                    make_uint2(pack_bf16((xv[0] - pivot) * c1v[0], (xv[1] - pivot) * c1v[1]),
                               pack_bf16((xv[2] - pivot) * c1v[2], (xv[3] - pivot) * c1v[3]));
                __syncwarp();
                if (!gu_early) weights_and_bc();
                float cg[2][4] = {}, cu[2][4] = {};
#pragma unroll
                for (int s = 0; s < 4; s++) {
                    const uint32_t b0 = hs[bb * 32 + 8 * s + t], b1 = hs[bb * 32 + 8 * s + 4 + t];
                    mma16816(cg[s & 1], gf[s], b0, b1);
                    mma16816(cu[s & 1], uf[s], b0, b1);
                }
                const float2 ps = half_warp_sums(xv, pivot);
                if ((lane & 15) == 0) stat[warp * 2 + eb] = ps;
                {
                    const float* bc = (const float*)(sgen + SM_MRG + 4096);
                    mbar_wait(bar_bc, 0);
#pragma unroll
                    for (int w = 0; w < 8; w++) {
                        bg += bc[w * 128 + lane]; cgc += bc[w * 128 + 32 + lane];
                        bu += bc[w * 128 + 64 + lane]; cuc += bc[w * 128 + 96 + lane];
                    }
                }
                if (t < 2) {
                    float v[4];
#pragma unroll
                    for (int i = 0; i < 4; i++) v[i] = t ? cu[0][i] + cu[1][i] : cg[0][i] + cg[1][i];
                    *(float2*)&red[warp * 64 + t * 32 + g * 2] = make_float2(v[0], v[1]);
                    *(float2*)&red[warp * 64 + t * 32 + (g + 8) * 2] = make_float2(v[2], v[3]);
                }
            }
            uint32_t df[4][4];
            mbar_wait(bar_full + 8 * (IDX_WD % NST), (IDX_WD / NST) & 1);
#pragma unroll
            for (int mt = 0; mt < 4; mt++) ldsm4t((sbase + SM_RING + (IDX_WD % NST) * TILE + aoff) ^ (mt << 5), df[mt]);
            cons_sync();
            {
                float gs = 0.f, us = 0.f;
#pragma unroll
                for (int w = 0; w < 8; w++) { gs += red[w * 64 + lane]; us += red[w * 64 + 32 + lane]; }
                float mean_bf, rstd;
                ln_stats(stat, lane & 1, pivot2, mean_bf, rstd);
                const float dm = mean_bf - pivot2;
                gs = bf16r(rstd * (gs - dm * bg) + cgc);
                us = rstd * (us - dm * bu) + cuc;
                const float u2 = gs * (1.0f + 0.044715f * gs * gs) * (2.0f * 0.7978845608028654f * LOG2E);
                const float ge = bf16r(__fdividef(gs, 1.0f + ex2(-u2)));
                const float act = bf16r(ge * bf16r(us));
                const float a0 = __shfl_sync(0xffffffffu, act, 4 * t + bb), a1 = __shfl_sync(0xffffffffu, act, 4 * t + 2 + bb);
                const float a2 = __shfl_sync(0xffffffffu, act, 4 * t + 16 + bb), a3 = __shfl_sync(0xffffffffu, act, 4 * t + 18 + bb);
                const uint32_t b0 = pack_bf16(a0, a1), b1 = pack_bf16(a2, a3);
                float y[4][4] = {};
#pragma unroll
                for (int mt = 0; mt < 4; mt++) mma16816(y[mt], df[mt], b0, b1);
                float v[4];
#pragma unroll
                for (int i = 0; i < 4; i++) v[i] = t == 0 ? y[0][i] : t == 1 ? y[1][i] : t == 2 ? y[2][i] : y[3][i];
            {
                const bool odd = g & 1;
                const float sx = odd ? v[0] : v[2], sy = odd ? v[1] : v[3];
                const float rx = __shfl_xor_sync(0xffffffffu, sx, 4), ry = __shfl_xor_sync(0xffffffffu, sy, 4);
                const int c0 = 64 * warp + 16 * t + (odd ? g + 7 : g);
                const float e0 = odd ? rx : v[0], e1 = odd ? ry : v[1], e2 = odd ? v[2] : rx, e3 = odd ? v[3] : ry;
                st_v4(&sc->inbox_dn[c0 >> 2][cta][(c0 >> 1) & 1], tagf(e0, F_DOWN), tagf(e1, F_DOWN), tagf(e2, F_DOWN), tagf(e3, F_DOWN));
            }
            }
            if (warp == 0) TSTAMP(12);
        }
        {
            uint2 xw;
            float r0;
            {
                const uint4* pin = &sc->inbox_dn[cta][0][0] + tid;
                uint4 v = make_uint4(F_DOWN, F_DOWN, F_DOWN, F_DOWN);
                if (cta < NFFN) spin_cycles(DELAY_C);
                else while (clock32() - t_wo < DELAY_X1 + DELAY_NOFFN) {}
                xw = ld_ll2(&sc->x1[ocol]);
                bool ok = tid >= NFFN * 2;
                for (int it = 0;; it++) {
                    if (!ok) {
                        v = ld_ll4(pin);
                        ok = (v.x & v.y & v.z & v.w & 3u) == F_DOWN;
                    }
                    if (__all_sync(0xffffffffu, ok) || it > SPIN_LIMIT) break;
                }
                const bool u1 = lane & 2, u2 = lane & 4;
                const float a0 = untag(v.x), a1 = untag(v.y), a2 = untag(v.z), a3 = untag(v.w);
                const float k0 = (u1 ? a1 : a0) + __shfl_xor_sync(0xffffffffu, u1 ? a0 : a1, 2);
                const float k1 = (u1 ? a3 : a2) + __shfl_xor_sync(0xffffffffu, u1 ? a2 : a3, 2);
                r0 = (u2 ? k1 : k0) + __shfl_xor_sync(0xffffffffu, u2 ? k0 : k1, 4);
                r0 += __shfl_xor_sync(0xffffffffu, r0, 8);
                r0 += __shfl_xor_sync(0xffffffffu, r0, 16);
                if (lane < 8) red2[256 + warp * 8 + (2 * (lane & 1) + ((lane >> 2) & 1)) * 2 + ((lane >> 1) & 1)] = r0;
            }
            cons_sync();
            if (warp == 0) {
                float a0 = 0.f, a1 = 0.f;
#pragma unroll
                for (int w = 0; w < 8; w++) { const float2 v = *(const float2*)&red2[256 + w * 8 + (lane & 3) * 2]; a0 += v.x; a1 += v.y; }
                const bool hi = ocol & 1;
                const float gb0 = hi ? bf_hi(m_gb0.x) : bf_lo(m_gb0.x), gb1 = hi ? bf_hi(m_gb1.x) : bf_lo(m_gb1.x);
                for (int it = 0; !__all_sync(0xffffffffu, xw.y == F_X1) && it < SPIN_LIMIT; it++) xw = ld_ll2(&sc->x1[ocol]);
                if (lane < 4) {
                    p.out[ocol] = __float2bfloat16_rn(bf_lo(xw.x) + bf16r(gb0 * bf16r(a0)));
                    p.out[D_MODEL + ocol] = __float2bfloat16_rn(bf_hi(xw.x) + bf16r(gb1 * bf16r(a1)));
                }
                if (cta == 0 && lane == 0) *(volatile unsigned*)&sc->epoch = tag;
                TSTAMP(13);
            }
        }
    }
}

typedef CUresult (*EncodeFn)(CUtensorMap*, CUtensorMapDataType, cuuint32_t, void*, const cuuint64_t*, const cuuint64_t*,
                             const cuuint32_t*, const cuuint32_t*, CUtensorMapInterleave, CUtensorMapSwizzle,
                             CUtensorMapL2promotion, CUtensorMapFloatOOBfill);

struct Maps { CUtensorMap k, v, wq, wmod, wmod8, wo, wg, wu, wd; };

void encode(EncodeFn fn, CUtensorMap* m, const void* ptr, int rank, const cuuint64_t* dims, const cuuint64_t* strides,
            const cuuint32_t* box, CUtensorMapSwizzle sw) {
    const cuuint32_t es[3] = {1, 1, 1};
    fn(m, CU_TENSOR_MAP_DATA_TYPE_BFLOAT16, rank, const_cast<void*>(ptr), dims, strides, box, es,
       CU_TENSOR_MAP_INTERLEAVE_NONE, sw, CU_TENSOR_MAP_L2_PROMOTION_L2_256B, CU_TENSOR_MAP_FLOAT_OOB_FILL_NONE);
}

}

extern "C" void kernel_launch(void* const* d_in, const int* in_sizes, int n_in, void* d_out, int out_size) {
    (void)in_sizes; (void)n_in; (void)out_size;
    static EncodeFn enc = nullptr;
    static Scratch* scratch = nullptr;
    if (!enc) {
        cudaGetSymbolAddress((void**)&scratch, g_scratch);
        void* fn = nullptr;
        cudaDriverEntryPointQueryResult qr;
        cudaGetDriverEntryPoint("cuTensorMapEncodeTiled", &fn, cudaEnableDefault, &qr);
        enc = (EncodeFn)fn;
        cudaFuncSetAttribute(fused_block_kernel, cudaFuncAttributeMaxDynamicSharedMemorySize, SMEM_BYTES);
    }
    Maps m;
    {
        const cuuint64_t dims[3] = {64, (cuuint64_t)16 * SK, 2}, str[2] = {256, 128};
        const cuuint32_t box[3] = {64, 64, 2};
        encode(enc, &m.k, d_in[1], 3, dims, str, box, CU_TENSOR_MAP_SWIZZLE_128B);
        encode(enc, &m.v, d_in[2], 3, dims, str, box, CU_TENSOR_MAP_SWIZZLE_128B);
    }
    {
        const cuuint64_t dims[2] = {4096, 512}, str[1] = {8192};
        const cuuint32_t box[2] = {32, 256};
        encode(enc, &m.wq, d_in[3], 2, dims, str, box, CU_TENSOR_MAP_SWIZZLE_64B);
    }
    {
        const cuuint64_t dims[2] = {N_MOD, 512}, str[1] = {N_MOD * 2};
        const cuuint32_t box[2] = {16, 256};
        encode(enc, &m.wmod, d_in[10], 2, dims, str, box, CU_TENSOR_MAP_SWIZZLE_32B);
        const cuuint32_t box8[2] = {8, 256};
        encode(enc, &m.wmod8, d_in[10], 2, dims, str, box8, CU_TENSOR_MAP_SWIZZLE_NONE);
    }
    {
        const cuuint64_t dims_o[3] = {64, 4096, 8}, dims_d[3] = {64, D_FF, 8}, str[2] = {1024, 128};
        const cuuint32_t box[3] = {64, 16, 8}, box_o[3] = {64, 64, 2};
        encode(enc, &m.wo, d_in[4], 3, dims_o, str, box_o, CU_TENSOR_MAP_SWIZZLE_128B);
        encode(enc, &m.wd, d_in[8], 3, dims_d, str, box, CU_TENSOR_MAP_SWIZZLE_128B);
    }
    {
        const cuuint64_t dims[2] = {D_FF, 512}, str[1] = {D_FF * 2};
        const cuuint32_t box[2] = {16, 128};
        encode(enc, &m.wg, d_in[6], 2, dims, str, box, CU_TENSOR_MAP_SWIZZLE_32B);
        encode(enc, &m.wu, d_in[7], 2, dims, str, box, CU_TENSOR_MAP_SWIZZLE_32B);
    }
    Params p;
    p.x = (const __nv_bfloat16*)d_in[0];
    p.c = (const __nv_bfloat16*)d_in[9];
    p.out = (__nv_bfloat16*)d_out;
    p.sc = scratch;
    fused_block_kernel<<<NCTA, NTHREADS, SMEM_BYTES, cudaStreamPerThread>>>(p, m.k, m.v, m.wq, m.wmod, m.wmod8, m.wo, m.wg, m.wu, m.wd);
}
```

```cpp
#include <cuda_runtime.h>
#include <cuda.h>
#include <cuda_bf16.h>
#include <stdint.h>

namespace {

constexpr int D_MODEL = 512;
constexpr int N_HEADS = 32;
constexpr int SK = 32768;
constexpr int DH = 128;
constexpr int D_FF = 1792;
constexpr int N_MOD = 6 * D_MODEL;

constexpr int NCTA = 128;
constexpr int NFFN = D_FF / 16;
constexpr int NOWN = 32;
constexpr int NTHREADS = 320;
constexpr int NST = 12;
constexpr int TILE = 16384;
#define WINDOW 3
#define WINDOW_TAIL 1
#define GU_WIN 3
#define GU_EARLY 0
#define WD_WIN 2
#define PACE_THR 96
constexpr int KV_TILES = 64;
#define MOD_AT 8
static_assert(MOD_AT % 2 == 0 && MOD_AT >= 2 && MOD_AT < 56, "schedule");
__host__ __device__ constexpr int kv_idx(int i) { return 2 + 2 * i + (i >= MOD_AT ? 1 : 0); }
constexpr int IDX_MOD = 2 + 2 * MOD_AT;
constexpr int N_STREAM = kv_idx(KV_TILES - 1) + 2;
constexpr int IDX_WO = N_STREAM;
constexpr int IDX_WG = IDX_WO + 2;
constexpr int IDX_WU = IDX_WG + 1;
constexpr int IDX_WD = IDX_WU + 1;
constexpr int SPIN_LIMIT = 1 << 20;

constexpr float LOG2E = 1.4426950408889634f;
constexpr float QK_SCALE = 0.08838834764831845f;

constexpr int SM_RING = 0;
constexpr int SM_MRG = SM_RING + NST * TILE;
constexpr int SM_ML = SM_MRG + 8 * 4 * 136 * 4;
constexpr int SM_RED = SM_ML + 8 * 4 * 8;
constexpr int SM_RED2 = SM_RED + 8 * 64 * 4;
constexpr int SM_QS = SM_RED2 + 8 * 64 * 4;
constexpr int SM_OS = SM_QS + 512 * 2;
constexpr int SM_SC = SM_OS + 2 * 128 * 2;
constexpr int SM_HS = SM_SC + 2 * 512 * 2;
constexpr int SM_STAT = SM_HS + 8 * 2 * 32 * 4;
constexpr int SM_PACE = SM_STAT + 8 * 2 * 8;
constexpr int SM_BAR = SM_PACE + 8;
constexpr int SM_END = SM_BAR + (2 * NST + 1 + 8 + 2) * 8;
constexpr int SMEM_BYTES = SM_END + 1024;

struct Scratch {
    uint4 inbox_wo[NOWN][N_HEADS][8];
    uint4 inbox_dn[NCTA][NFFN][2];
    uint2 x1[D_MODEL];
    uint2 part_o[NCTA][4][64];
    uint2 part_ml[NCTA][4][4];
    uint2 mod[2][N_MOD / 2];
    uint2 q[2][N_HEADS * DH / 2];
    unsigned epoch;
    unsigned pad_[31];
    unsigned cleared;
    unsigned pad2_[31];
    unsigned progress;
};
__device__ Scratch g_scratch;
constexpr uint32_t F_PART = 1, F_WO = 1, F_DOWN = 1, F_X1 = 1;
__device__ __forceinline__ uint32_t tagf(float v, uint32_t f) { return (__float_as_uint(v) & ~3u) | f; }
__device__ __forceinline__ float untag(uint32_t v) { return __uint_as_float(v & ~3u); }

struct Params {
    const __nv_bfloat16* x;
    const __nv_bfloat16* c;
    __nv_bfloat16* out;
    Scratch* sc;
};

#define TSTAMP(i) do { } while (0)

__device__ __forceinline__ uint32_t smem_u32(const void* p) { return (uint32_t)__cvta_generic_to_shared(p); }

__device__ __forceinline__ void mbar_init(uint32_t bar, uint32_t cnt) {
    asm volatile("mbarrier.init.shared::cta.b64 [%0], %1;" ::"r"(bar), "r"(cnt) : "memory");
}
__device__ __forceinline__ void mbar_expect_tx(uint32_t bar, uint32_t bytes) {
    asm volatile("mbarrier.arrive.expect_tx.shared::cta.b64 _, [%0], %1;" ::"r"(bar), "r"(bytes) : "memory");
}
__device__ __forceinline__ void mbar_arrive(uint32_t bar) {
    asm volatile("mbarrier.arrive.shared::cta.b64 _, [%0];" ::"r"(bar) : "memory");
}
__device__ __forceinline__ bool mbar_try(uint32_t bar, uint32_t parity) {
    uint32_t ok;
    asm volatile(
        "{\n\t.reg .pred p;\n\t"
        "mbarrier.try_wait.parity.shared::cta.b64 p, [%1], %2;\n\t"
        "selp.u32 %0, 1, 0, p;\n\t}"
        : "=r"(ok) : "r"(bar), "r"(parity) : "memory");
    return ok != 0;
}
__device__ __forceinline__ void mbar_wait(uint32_t bar, uint32_t parity) {
    if (mbar_try(bar, parity)) return;
    const long long t0 = clock64();
    while (!mbar_try(bar, parity))
        if (clock64() - t0 > (1ll << 31)) return;
}
__device__ __forceinline__ void cons_sync() { asm volatile("bar.sync 1, 256;" ::: "memory"); }

__device__ __forceinline__ void tma_2d(uint32_t dst, const CUtensorMap* m, int c0, int c1, uint32_t bar) {
    asm volatile("cp.async.bulk.tensor.2d.shared::cluster.global.mbarrier::complete_tx::bytes [%0], [%1, {%3, %4}], [%2];"
                 ::"r"(dst), "l"(m), "r"(bar), "r"(c0), "r"(c1) : "memory");
}
__device__ __forceinline__ void tma_3d(uint32_t dst, const CUtensorMap* m, int c0, int c1, int c2, uint32_t bar) {
    asm volatile("cp.async.bulk.tensor.3d.shared::cluster.global.mbarrier::complete_tx::bytes [%0], [%1, {%3, %4, %5}], [%2];"
                 ::"r"(dst), "l"(m), "r"(bar), "r"(c0), "r"(c1), "r"(c2) : "memory");
}
__device__ __forceinline__ void tma_3d_hint(uint32_t dst, const CUtensorMap* m, int c0, int c1, int c2, uint32_t bar, uint64_t pol) {
    asm volatile("cp.async.bulk.tensor.3d.shared::cluster.global.mbarrier::complete_tx::bytes.L2::cache_hint [%0], [%1, {%3, %4, %5}], [%2], %6;"
                 ::"r"(dst), "l"(m), "r"(bar), "r"(c0), "r"(c1), "r"(c2), "l"(pol) : "memory");
}
__device__ __forceinline__ void prefetch_tmap(const CUtensorMap* m) {
    asm volatile("prefetch.tensormap [%0];" ::"l"(m) : "memory");
}

__device__ __forceinline__ void ldsm4(uint32_t addr, uint32_t (&r)[4]) {
    asm volatile("ldmatrix.sync.aligned.m8n8.x4.shared.b16 {%0,%1,%2,%3}, [%4];"
                 : "=r"(r[0]), "=r"(r[1]), "=r"(r[2]), "=r"(r[3]) : "r"(addr) : "memory");
}
__device__ __forceinline__ void ldsm4t(uint32_t addr, uint32_t (&r)[4]) {
    asm volatile("ldmatrix.sync.aligned.m8n8.x4.trans.shared.b16 {%0,%1,%2,%3}, [%4];"
                 : "=r"(r[0]), "=r"(r[1]), "=r"(r[2]), "=r"(r[3]) : "r"(addr) : "memory");
}
__device__ __forceinline__ void mma16816(float (&c)[4], const uint32_t (&a)[4], uint32_t b0, uint32_t b1) {
    asm volatile("mma.sync.aligned.m16n8k16.row.col.f32.bf16.bf16.f32 {%0,%1,%2,%3}, {%4,%5,%6,%7}, {%8,%9}, {%0,%1,%2,%3};"
                 : "+f"(c[0]), "+f"(c[1]), "+f"(c[2]), "+f"(c[3])
                 : "r"(a[0]), "r"(a[1]), "r"(a[2]), "r"(a[3]), "r"(b0), "r"(b1));
}
__device__ __forceinline__ uint32_t movmatrix_t(uint32_t a) {
    uint32_t d;
    asm volatile("movmatrix.sync.aligned.m8n8.trans.b16 %0, %1;" : "=r"(d) : "r"(a));
    return d;
}
__device__ __forceinline__ uint32_t pack_bf16(float a, float b) {
    uint32_t r;
    asm("cvt.rn.bf16x2.f32 %0, %1, %2;" : "=r"(r) : "f"(b), "f"(a));
    return r;
}
__device__ __forceinline__ float bf_lo(uint32_t v) { return __uint_as_float(v << 16); }
__device__ __forceinline__ float bf_hi(uint32_t v) { return __uint_as_float(v & 0xffff0000u); }
__device__ __forceinline__ float bf16r(float a) { return bf_lo(pack_bf16(a, 0.f)); }
__device__ __forceinline__ uint32_t max_bf16x2(uint32_t a, uint32_t b) {
    uint32_t r;
    asm("max.bf16x2 %0, %1, %2;" : "=r"(r) : "r"(a), "r"(b));
    return r;
}
__device__ __forceinline__ float ex2(float x) {
    float r;
    asm("ex2.approx.ftz.f32 %0, %1;" : "=f"(r) : "f"(x));
    return r;
}

__device__ __forceinline__ void st_ll2(uint2* p, uint32_t v, uint32_t tag) {
    asm volatile("st.relaxed.gpu.global.v2.u32 [%0], {%1, %2};" ::"l"(p), "r"(v), "r"(tag) : "memory");
}
__device__ __forceinline__ void st_ll4(uint4* p, uint32_t v0, uint32_t v1, uint32_t tag) {
    asm volatile("st.relaxed.gpu.global.v4.u32 [%0], {%1, %2, %3, %2};" ::"l"(p), "r"(v0), "r"(tag), "r"(v1) : "memory");
}
__device__ __forceinline__ void st_v4(uint4* p, uint32_t a, uint32_t b, uint32_t c, uint32_t d) {
    asm volatile("st.relaxed.gpu.global.v4.u32 [%0], {%1, %2, %3, %4};" ::"l"(p), "r"(a), "r"(b), "r"(c), "r"(d) : "memory");
}
__device__ __forceinline__ uint2 ld_ll2(const uint2* p) {
    uint2 v;
    asm volatile("ld.relaxed.gpu.global.v2.u32 {%0, %1}, [%2];" : "=r"(v.x), "=r"(v.y) : "l"(p) : "memory");
    return v;
}
__device__ __forceinline__ uint4 ld_ll4(const uint4* p) {
    uint4 v;
    asm volatile("ld.relaxed.gpu.global.v4.u32 {%0, %1, %2, %3}, [%4];"
                 : "=r"(v.x), "=r"(v.y), "=r"(v.z), "=r"(v.w) : "l"(p) : "memory");
    return v;
}

#define DELAY_B1 300
#define DELAY_X1 2000
#define DELAY_NOFFN 1500
#define A_BACKOFF 0
#define DELAY_C 600
__device__ __forceinline__ uint32_t clock32() {
    uint32_t c;
    asm volatile("mov.u32 %0, %clock;" : "=r"(c));
    return c;
}
__device__ __forceinline__ void spin_cycles(uint32_t n) {
    if (n > 0) { const uint32_t c0 = clock32(); while (clock32() - c0 < n) {} }
}
__device__ __forceinline__ float rcp_approx(float x) {
    float r;
    asm("rcp.approx.ftz.f32 %0, %1;" : "=f"(r) : "f"(x));
    return r;
}
__device__ __forceinline__ float sqrt_approx(float x) {
    float r;
    asm("sqrt.approx.f32 %0, %1;" : "=f"(r) : "f"(x));
    return r;
}

__device__ __forceinline__ float silu_bf(float v) { return bf16r(v / (1.0f + expf(-v))); }

__device__ __forceinline__ float2 half_warp_sums(const float (&v)[4], float pivot) {
    float s1 = 0.f, s2 = 0.f;
#pragma unroll
    for (int i = 0; i < 4; i++) { const float d = v[i] - pivot; s1 += d; s2 += d * d; }
#pragma unroll
    for (int o = 1; o < 16; o <<= 1) { s1 += __shfl_xor_sync(0xffffffffu, s1, o); s2 += __shfl_xor_sync(0xffffffffu, s2, o); }
    return make_float2(s1, s2);
}
__device__ __forceinline__ void ln_stats(const float2* stat, int b, float pivot, float& mean_bf, float& rstd) {
    float s1 = 0.f, s2 = 0.f;
#pragma unroll
    for (int w = 0; w < 8; w++) { const float2 v = stat[w * 2 + b]; s1 += v.x; s2 += v.y; }
    const float dm = s1 * (1.0f / D_MODEL);
    const float var = fmaxf(s2 * (1.0f / D_MODEL) - dm * dm, 0.f);
    mean_bf = bf16r(pivot + dm);
    rstd = rcp_approx(bf16r(sqrt_approx(bf16r(bf16r(var) + 1e-5f))));
}
__device__ __forceinline__ float ln_norm(float xv, float mean_bf, float rstd) { return bf16r(bf16r(xv - mean_bf) * rstd); }
__device__ __forceinline__ float ln_mod(float n, float cmul, float sadd) { return bf16r(n * bf16r(1.0f + cmul)) + sadd; }

__global__ void __launch_bounds__(NTHREADS, 1)
fused_block_kernel(const Params p, const __grid_constant__ CUtensorMap tm_k, const __grid_constant__ CUtensorMap tm_v,
                   const __grid_constant__ CUtensorMap tm_wq, const __grid_constant__ CUtensorMap tm_wmod,
                   const __grid_constant__ CUtensorMap tm_wmod8,
                   const __grid_constant__ CUtensorMap tm_wo, const __grid_constant__ CUtensorMap tm_wg,
                   const __grid_constant__ CUtensorMap tm_wu, const __grid_constant__ CUtensorMap tm_wd) {
    extern __shared__ unsigned char smem_raw[];
    const uint32_t sbase = (smem_u32(smem_raw) + 1023u) & ~1023u;
    unsigned char* sgen = smem_raw + (sbase - smem_u32(smem_raw));
    const int tid = threadIdx.x, warp = tid >> 5, lane = tid & 31;
    const int cta = blockIdx.x;
    const uint32_t bar_full = sbase + SM_BAR, bar_empty = bar_full + NST * 8;
    const uint32_t bar_clear = bar_empty + NST * 8;
    const uint32_t bar_gu = bar_clear + 8;
    const uint32_t bar_bc = bar_gu + 8 * 8;
    const uint32_t bar_p0w = bar_bc + 8;

    const int key0 = (cta >> 3) * SK + (cta & 7) * 64;
    uint64_t pol = 0;
    if (tid == 256) {
        asm volatile("createpolicy.fractional.L2::evict_first.b64 %0, 1.0;" : "=l"(pol));
        mbar_init(bar_p0w, 1);
#pragma unroll
        for (int i = 0; i < 4; i++) mbar_init(bar_full + 8 * i, 1);
        asm volatile("fence.mbarrier_init.release.cluster;" ::: "memory");
        mbar_expect_tx(bar_p0w, 8192);
        tma_2d(sbase + SM_MRG, &tm_wmod8, cta * 8, 0, bar_p0w);
        tma_2d(sbase + SM_MRG + 4096, &tm_wmod8, cta * 8, 256, bar_p0w);
#pragma unroll
        for (int i = 0; i < 4; i++) mbar_expect_tx(bar_full + 8 * i, TILE);
        tma_2d(sbase + SM_RING, &tm_wq, cta * 32, 0, bar_full);
        tma_2d(sbase + SM_RING + TILE, &tm_wq, cta * 32, 256, bar_full + 8);
        tma_3d_hint(sbase + SM_RING + 2 * TILE, &tm_k, 0, key0, 0, bar_full + 16, pol);
        tma_3d_hint(sbase + SM_RING + 3 * TILE, &tm_v, 0, key0, 0, bar_full + 24, pol);
    }

    if (warp == 8) {
        if (lane == 0) {
            for (int i = 0; i < NST; i++) { if (i >= 4) mbar_init(bar_full + 8 * i, 1); mbar_init(bar_empty + 8 * i, 4); }
            mbar_init(bar_clear, 1);
            for (int k = 0; k < 8; k++) mbar_init(bar_gu + 8 * k, 1);
            mbar_init(bar_bc, 8);
            ((volatile uint32_t*)(sgen + SM_PACE))[0] = 0;
            ((volatile uint32_t*)(sgen + SM_PACE))[1] = WINDOW;
            asm volatile("fence.mbarrier_init.release.cluster;" ::: "memory");
        }
        __syncwarp();
        asm volatile("bar.arrive 2, 320;" ::: "memory");
        asm volatile("bar.arrive 3, 64;" ::: "memory");
        if (lane == 0) {
            int slot = 4; uint32_t ph = 1;
            int landed = 0, wslot = 0; uint32_t wph = 0;
            int kv = 2;
            auto wait_window = [&](int idx, int window) {
                while (landed + window <= idx) {
                    mbar_wait(bar_full + 8 * wslot, wph);
                    if (++wslot == NST) { wslot = 0; wph ^= 1; }
                    landed++;
                }
            };
            volatile uint32_t* pace = (volatile uint32_t*)(sgen + SM_PACE);
            prefetch_tmap(&tm_wmod);
            pace[0] = 4;
            for (int idx = 4; idx < N_STREAM; idx++) {
                if (idx >= NST) mbar_wait(bar_empty + 8 * slot, ph);
                wait_window(idx, (int)pace[1]);
                if (idx == 12) { prefetch_tmap(&tm_wo); prefetch_tmap(&tm_wg); prefetch_tmap(&tm_wu); prefetch_tmap(&tm_wd); }
                const uint32_t fb = bar_full + 8 * slot, dst = sbase + SM_RING + slot * TILE;
                mbar_expect_tx(fb, TILE);
                if (idx == IDX_MOD) {
                    tma_2d(dst, &tm_wmod, 1024 + cta * 16, 0, fb);
                    tma_2d(dst + 8192, &tm_wmod, 1024 + cta * 16, 256, fb);
                } else {
                    tma_3d_hint(dst, (kv & 1) ? &tm_v : &tm_k, 0, key0 + (kv >> 1) * 512, 0, fb, pol);
                    kv++;
                }
                pace[0] = idx + 1;
                if (++slot == NST) { slot = 0; ph ^= 1; }
            }
            auto slot_free = [&](int idx) { mbar_wait(bar_empty + 8 * (idx % NST), ((idx / NST) & 1) ^ 1); };
#pragma unroll
            for (int s = 0; s < 2; s++) {
                const int idx = IDX_WO + s;
                slot_free(idx);
                wait_window(idx, WINDOW_TAIL);
                mbar_expect_tx(bar_full + 8 * (idx % NST), TILE);
                tma_3d(sbase + SM_RING + (idx % NST) * TILE, &tm_wo, 0, (cta >> 2) * 128 + s * 64, (cta & 3) * 2, bar_full + 8 * (idx % NST));
            }
            if (cta < NFFN) {
                slot_free(IDX_WG); slot_free(IDX_WU);
#pragma unroll
                for (int st = 0; st < 8; st++) {
                    if (st == GU_EARLY) {
                        mbar_wait(bar_full + 8 * (IDX_WO % NST), (IDX_WO / NST) & 1);
                        mbar_wait(bar_full + 8 * ((IDX_WO + 1) % NST), ((IDX_WO + 1) / NST) & 1);
                    }
                    if (st >= GU_WIN) mbar_wait(bar_gu + 8 * (st - GU_WIN), 0);
                    mbar_expect_tx(bar_gu + 8 * st, 4096);
                    tma_2d(sbase + SM_RING + (((st & 1) ? IDX_WU : IDX_WG) % NST) * TILE + (st >> 1) * 4096,
                           (st & 1) ? &tm_wu : &tm_wg, cta * 16, (st >> 1) * 128, bar_gu + 8 * st);
                }
                mbar_wait(bar_gu + 8 * (8 - WD_WIN), 0);
                slot_free(IDX_WD);
                mbar_expect_tx(bar_full + 8 * (IDX_WD % NST), TILE);
                tma_3d(sbase + SM_RING + (IDX_WD % NST) * TILE, &tm_wd, 0, cta * 16, 0, bar_full + 8 * (IDX_WD % NST));
            }
        }
    } else if (warp == 9) {
        Scratch* const sc = p.sc;
        const uint32_t tag = *(volatile unsigned*)&sc->epoch + 1;
        if (lane < 2) {
            st_ll4((uint4*)&sc->mod[lane][cta * 4], 0u, 0u, 0u);
            st_ll4((uint4*)&sc->mod[lane][cta * 4] + 1, 0u, 0u, 0u);
        }
        if (lane < 8) st_ll4((uint4*)&sc->mod[lane >> 2][512 + cta * 8] + (lane & 3), 0u, 0u, 0u);
        if (lane < 16) st_ll4((uint4*)&sc->q[lane >> 3][cta * 16] + (lane & 7), 0u, 0u, 0u);
        __syncwarp();
        asm volatile("bar.arrive 2, 320;" ::: "memory");
        asm volatile("bar.sync 3, 64;" ::: "memory");
#pragma unroll 4
        for (int i = 0; i < NFFN * 2 / 32; i++) st_v4(&sc->inbox_dn[cta][0][0] + i * 32 + lane, 0u, 0u, 0u, 0u);
        if (cta >= NCTA - NOWN) {
#pragma unroll 4
            for (int i = 0; i < 8; i++) st_v4(&sc->inbox_wo[cta - (NCTA - NOWN)][0][0] + i * 32 + lane, 0u, 0u, 0u, 0u);
            if (lane < 8) st_v4((uint4*)&sc->x1[(cta - (NCTA - NOWN)) * 16] + lane, 0u, 0u, 0u, 0u);
        }
#pragma unroll 4
        for (int i = 0; i < 4; i++) st_v4((uint4*)&sc->part_o[cta][0][0] + i * 32 + lane, 0u, 0u, 0u, 0u);
        if (lane < 8) st_v4((uint4*)&sc->part_ml[cta][0][0] + lane, 0u, 0u, 0u, 0u);
        if (cta == 0 && lane == 0) asm volatile("st.relaxed.gpu.global.u32 [%0], %1;" ::"l"(&sc->progress), "r"(0u) : "memory");
        asm volatile("fence.acq_rel.gpu;" ::: "memory");
        __syncwarp();
        if (lane == 0) {
            asm volatile("fence.acq_rel.gpu;" ::: "memory");
            asm volatile("red.relaxed.gpu.global.add.u32 [%0], %1;" ::"l"(&sc->cleared), "r"(1u) : "memory");
            const uint32_t target = tag * NCTA;
            for (int it = 0; it < SPIN_LIMIT; it++) {
                uint32_t v;
                asm volatile("ld.relaxed.gpu.global.u32 %0, [%1];" : "=r"(v) : "l"(&sc->cleared) : "memory");
                if ((int32_t)(v - target) >= 0) break;
                __nanosleep(500);
            }
            asm volatile("fence.acq_rel.gpu;" ::: "memory");
            mbar_arrive(bar_clear);
            volatile uint32_t* pace = (volatile uint32_t*)(sgen + SM_PACE);
            uint32_t posted = 0;
            for (int it = 0; it < SPIN_LIMIT; it++) {
                const uint32_t own = pace[0];
                if (own >= N_STREAM) break;
                if (own > posted) {
                    asm volatile("red.relaxed.gpu.global.add.u32 [%0], %1;" ::"l"(&sc->progress), "r"(own - posted) : "memory");
                    posted = own;
                }
                uint32_t v;
                asm volatile("ld.relaxed.gpu.global.u32 %0, [%1];" : "=r"(v) : "l"(&sc->progress) : "memory");
                const int diff = (int)v - (int)own * NCTA;
                pace[1] = diff > PACE_THR ? WINDOW + 1 : diff < -PACE_THR ? WINDOW - 1 : WINDOW;
                __nanosleep(200);
            }
            if (cta == 0) asm volatile("st.relaxed.gpu.global.u32 [%0], %1;" ::"l"(&sc->epoch), "r"(tag) : "memory");
        }
    } else {
        const int g = lane >> 2, t = lane & 3;
        const int bb = g & 1;
        const int eb = lane >> 4;
        const int ec = 64 * warp + 4 * (lane & 15);
        if (warp == 0) TSTAMP(0);
        Scratch* const sc = p.sc;
        const float c00 = __bfloat162float(p.c[tid]), c01 = __bfloat162float(p.c[tid + 256]);
        const float c10 = __bfloat162float(p.c[D_MODEL + tid]), c11 = __bfloat162float(p.c[D_MODEL + tid + 256]);
        const uint2 xe = __ldg((const uint2*)(p.x + eb * D_MODEL + ec));
        const float xpivot = __bfloat162float(p.x[eb * D_MODEL]);
        const uint32_t tag = *(volatile unsigned*)&sc->epoch + 1;
        const int ocol = cta * 4 + (lane & 3);
        const int wcol = (cta >= NCTA - NOWN ? cta - (NCTA - NOWN) : 0) * 16 + (lane & 15);
        const float xo = __bfloat162float(p.x[eb * D_MODEL + wcol]);

        float* red = (float*)(sgen + SM_RED);
        float* red2 = (float*)(sgen + SM_RED2);
        float2* stat = (float2*)(sgen + SM_STAT);
        uint32_t* hs = (uint32_t*)(sgen + SM_HS) + warp * 64;
        float xn[4];
        {
            float xv[4] = {bf_lo(xe.x), bf_hi(xe.x), bf_lo(xe.y), bf_hi(xe.y)};
            const float2 ps = half_warp_sums(xv, xpivot);
            if ((lane & 15) == 0) stat[warp * 2 + eb] = ps;
            const float s00 = silu_bf(c00), s01 = silu_bf(c01), s10 = silu_bf(c10), s11 = silu_bf(c11);
            __nv_bfloat16* scs = (__nv_bfloat16*)(sgen + SM_SC);
            scs[tid] = __float2bfloat16_rn(s00); scs[tid + 256] = __float2bfloat16_rn(s01);
            scs[512 + tid] = __float2bfloat16_rn(s10); scs[512 + tid + 256] = __float2bfloat16_rn(s11);
            asm volatile("bar.sync 2, 320;" ::: "memory");
            if (warp == 0) TSTAMP(23);
            float cp[4] = {0.f, 0.f, 0.f, 0.f};
            const uint32_t* sc32 = (const uint32_t*)(sgen + SM_SC) + bb * 256 + 32 * warp + t;
            mbar_wait(bar_p0w, 0);
#pragma unroll
            for (int s = 0; s < 4; s++) {
                uint32_t r0, r1;
                asm volatile("ldmatrix.sync.aligned.m8n8.x2.trans.shared.b16 {%0,%1}, [%2];"
                             : "=r"(r0), "=r"(r1) : "r"(sbase + SM_MRG + (64 * warp + 16 * s + (lane & 15)) * 16) : "memory");
                const uint32_t a[4] = {r0, r0, r1, r1};
                mma16816(cp, a, sc32[8 * s], sc32[8 * s + 4]);
            }
            if (t == 0) { red[warp * 16 + g] = cp[0]; red[warp * 16 + 8 + g] = cp[1]; }
            if (warp == 0) TSTAMP(14);
            cons_sync();
            if (warp == 0) {
                float s = 0.f;
#pragma unroll
                for (int w = 0; w < 8; w++) s += red[w * 16 + (lane & 15)];
                const float nx = __shfl_down_sync(0xffffffffu, s, 1);
                if (lane < 16 && !(lane & 1))
                    st_ll2(&sc->mod[lane >> 3][cta * 4 + ((lane & 7) >> 1)], pack_bf16(s, nx), tag);
                TSTAMP(1);
            }
            float mean_bf, rstd;
            ln_stats(stat, eb, xpivot, mean_bf, rstd);
#pragma unroll
            for (int i = 0; i < 4; i++) xn[i] = ln_norm(xv[i], mean_bf, rstd);
        }
        {
            uint4 sa, ca;
            for (int it = 0;; it++) {
                sa = ld_ll4((const uint4*)&sc->mod[eb][ec >> 1]);
                ca = ld_ll4((const uint4*)&sc->mod[eb][256 + (ec >> 1)]);
                const bool ok = sa.y == tag && sa.w == tag && ca.y == tag && ca.w == tag;
                if (__all_sync(0xffffffffu, ok) || it > SPIN_LIMIT) break;
            }
            *(uint2*)&hs[eb * 32 + 2 * (lane & 15)] =
                make_uint2(pack_bf16(ln_mod(xn[0], bf_lo(ca.x), bf_lo(sa.x)), ln_mod(xn[1], bf_hi(ca.x), bf_hi(sa.x))),
                           pack_bf16(ln_mod(xn[2], bf_lo(ca.z), bf_lo(sa.z)), ln_mod(xn[3], bf_hi(ca.z), bf_hi(sa.z))));
            __syncwarp();
            uint32_t hb[8];
#pragma unroll
            for (int i = 0; i < 8; i++) hb[i] = hs[bb * 32 + 8 * (i >> 1) + 4 * (i & 1) + t];
            if (warp == 0) TSTAMP(2);
            float cq[2][4] = {};
            const int ts = warp >> 2;
            mbar_wait(bar_full + 8 * ts, 0);
            const uint32_t tb = sbase + SM_RING + ts * TILE;
#pragma unroll
            for (int s = 0; s < 4; s++) {
                const int row = 64 * (warp & 3) + 16 * s + (lane & 7) + (lane >> 4) * 8;
#pragma unroll
                for (int mt = 0; mt < 2; mt++) {
                    const int ch = 2 * mt + ((lane >> 3) & 1);
                    uint32_t a[4];
                    ldsm4t(tb + row * 64 + ((ch ^ ((row >> 1) & 3)) << 4), a);
                    mma16816(cq[mt], a, hb[2 * s], hb[2 * s + 1]);
                }
            }
            if (t < 2) {
                const float v0 = t == 0 ? cq[0][0] : cq[1][0], v1 = t == 0 ? cq[0][1] : cq[1][1];
                const float v2 = t == 0 ? cq[0][2] : cq[1][2], v3 = t == 0 ? cq[0][3] : cq[1][3];
                *(float2*)&red2[warp * 64 + (16 * t + g) * 2] = make_float2(v0, v1);
                *(float2*)&red2[warp * 64 + (16 * t + g + 8) * 2] = make_float2(v2, v3);
            }
            cons_sync();
            if (warp < 4 && lane == 0) { mbar_arrive(bar_empty); mbar_arrive(bar_empty + 8); }
            if (warp == 0) {
                const int b = lane >> 4, cp = lane & 15;
                float q0 = 0.f, q1 = 0.f;
#pragma unroll
                for (int w = 0; w < 8; w++) {
                    const float4 v = *(const float4*)&red2[w * 64 + cp * 4];
                    q0 += b ? v.y : v.x; q1 += b ? v.w : v.z;
                }
                st_ll2(&sc->q[b][cta * 16 + cp], pack_bf16(q0, q1), tag);
                TSTAMP(3);
            }
        }
        const int pair = cta >> 3;
        uint32_t qf[16];
        {
            uint2* qs = (uint2*)(sgen + SM_QS);
            if (tid < 128) {
                const uint4* src = (const uint4*)&sc->q[pair >> 3][(pair & 7) * 256] + tid;
                uint4 v;
                for (int it = 0;; it++) {
                    v = ld_ll4(src);
                    if ((v.y == tag && v.w == tag) || it > SPIN_LIMIT) break;
                }
                qs[tid] = make_uint2(v.x, v.z);
            }
            cons_sync();
            const uint32_t* q32 = (const uint32_t*)(sgen + SM_QS);
#pragma unroll
            for (int s = 0; s < 8; s++) {
                qf[2 * s] = q32[(g & 3) * 64 + 8 * s + t];
                qf[2 * s + 1] = q32[(g & 3) * 64 + 8 * s + 4 + t];
            }
        }
        if (warp == 0) TSTAMP(4);

        float o[8][4];
#pragma unroll
        for (int i = 0; i < 8; i++) { o[i][0] = o[i][1] = o[i][2] = o[i][3] = 0.f; }
        uint32_t mrun = 0xff80ff80u;
        float ls[4] = {0.f, 0.f, 0.f, 0.f};
        uint4 m_sb, m_cb; uint2 m_ga, m_gb0, m_gb1;
        {
            const int grp = warp >> 2, wi = warp & 3;
            const int krow = 16 * wi + (lane & 7) + ((lane >> 3) & 1) * 8;
            const uint32_t koff = krow * 128 + ((((lane >> 4) & 1) ^ (lane & 7)) << 4);
            const int vrow = 16 * wi + (lane & 7) + (lane >> 4) * 8;
            const uint32_t voff = vrow * 128 + ((((lane >> 3) & 1) ^ (lane & 7)) << 4);
            const uint32_t ones[4] = {0x3f803f80u, 0x3f803f80u, 0x3f803f80u, 0x3f803f80u};
            for (int i = grp; i < KV_TILES; i += 2) {
                if (i == MOD_AT + grp) {
                    float cm[4] = {};
                    const uint32_t* sc32 = (const uint32_t*)(sgen + SM_SC) + bb * 256 + 32 * warp + t;
                    mbar_wait(bar_full + 8 * (IDX_MOD % NST), (IDX_MOD / NST) & 1);
                    const uint32_t tb = sbase + SM_RING + (IDX_MOD % NST) * TILE;
#pragma unroll
                    for (int s = 0; s < 4; s++) {
                        const int row = 64 * warp + 16 * s + (lane & 7) + (lane >> 4) * 8;
                        const int ch = (lane >> 3) & 1;
                        uint32_t a[4];
                        ldsm4t(tb + row * 32 + ((ch ^ ((row >> 2) & 1)) << 4), a);
                        mma16816(cm, a, sc32[8 * s], sc32[8 * s + 4]);
                    }
                    if (t == 0) {
                        *(float2*)&red[warp * 64 + g * 2] = make_float2(cm[0], cm[1]);
                        *(float2*)&red[warp * 64 + (g + 8) * 2] = make_float2(cm[2], cm[3]);
                    }
                    cons_sync();
                    if (warp < 4 && lane == 0) mbar_arrive(bar_empty + 8 * (IDX_MOD % NST));
                    if (warp == 1 && lane < 16) {
                        const int b = lane >> 3, cp = lane & 7;
                        float q0 = 0.f, q1 = 0.f;
#pragma unroll
                        for (int w = 0; w < 8; w++) {
                            const float4 v = *(const float4*)&red[w * 64 + cp * 4];
                            q0 += b ? v.y : v.x; q1 += b ? v.w : v.z;
                        }
                        st_ll2(&sc->mod[b][512 + cta * 8 + cp], pack_bf16(q0, q1), tag);
                    }
                }
                if (i == 56 + grp) {
                    m_sb = ld_ll4((const uint4*)&sc->mod[eb][768 + (ec >> 1)]);
                    m_cb = ld_ll4((const uint4*)&sc->mod[eb][1024 + (ec >> 1)]);
                    m_ga = ld_ll2(&sc->mod[eb][512 + (wcol >> 1)]);
                    m_gb0 = ld_ll2(&sc->mod[0][1280 + (ocol >> 1)]); m_gb1 = ld_ll2(&sc->mod[1][1280 + (ocol >> 1)]);
                }
                if (i == 60 + grp) {
                    for (int it = 0;; it++) {
                        const bool ok = m_sb.y == tag && m_sb.w == tag && m_cb.y == tag && m_cb.w == tag &&
                                        m_ga.y == tag && m_gb0.y == tag && m_gb1.y == tag;
                        if (__all_sync(0xffffffffu, ok) || it > SPIN_LIMIT) break;
                        m_sb = ld_ll4((const uint4*)&sc->mod[eb][768 + (ec >> 1)]);
                        m_cb = ld_ll4((const uint4*)&sc->mod[eb][1024 + (ec >> 1)]);
                        m_ga = ld_ll2(&sc->mod[eb][512 + (wcol >> 1)]);
                        m_gb0 = ld_ll2(&sc->mod[0][1280 + (ocol >> 1)]); m_gb1 = ld_ll2(&sc->mod[1][1280 + (ocol >> 1)]);
                    }
                    mbar_wait(bar_clear, 0);
                }
                const int ki = kv_idx(i), ks = ki % NST, vs = (ki + 1) % NST;
                const uint32_t kph = (ki / NST) & 1, vph = ((ki + 1) / NST) & 1;
                mbar_wait(bar_full + 8 * ks, kph);
                const uint32_t kb = sbase + SM_RING + ks * TILE + koff;
                float sa[4] = {0.f, 0.f, 0.f, 0.f}, sb[4] = {0.f, 0.f, 0.f, 0.f};
#pragma unroll
                for (int s = 0; s < 8; s += 2) {
                    uint32_t a0[4], a1[4];
                    ldsm4((kb ^ ((s & 3) << 5)) + (s >> 2) * 8192, a0);
                    ldsm4((kb ^ (((s + 1) & 3) << 5)) + (s >> 2) * 8192, a1);
                    mma16816(sa, a0, qf[2 * s], qf[2 * s + 1]);
                    mma16816(sb, a1, qf[2 * s + 2], qf[2 * s + 3]);
                }
                __syncwarp();
                if (lane == 0) mbar_arrive(bar_empty + 8 * ks);
                uint32_t r01 = pack_bf16(sa[0] + sb[0], sa[1] + sb[1]);
                uint32_t r23 = pack_bf16(sa[2] + sb[2], sa[3] + sb[3]);
                r01 = pack_bf16(bf_lo(r01) * QK_SCALE, bf_hi(r01) * QK_SCALE);
                r23 = pack_bf16(bf_lo(r23) * QK_SCALE, bf_hi(r23) * QK_SCALE);
                uint32_t mx = max_bf16x2(r01, r23);
                mx = max_bf16x2(mx, __shfl_xor_sync(0xffffffffu, mx, 4));
                mx = max_bf16x2(mx, __shfl_xor_sync(0xffffffffu, mx, 8));
                mx = max_bf16x2(mx, __shfl_xor_sync(0xffffffffu, mx, 16));
                const uint32_t mnew = max_bf16x2(mrun, mx);
                const float m0 = bf_lo(mnew), m1 = bf_hi(mnew);
                if (__any_sync(0xffffffffu, mnew != mrun)) {
                    const float al0 = ex2((bf_lo(mrun) - m0) * LOG2E), al1 = ex2((bf_hi(mrun) - m1) * LOG2E);
                    ls[0] *= al0; ls[1] *= al1;
#pragma unroll
                    for (int d = 0; d < 8; d++) { o[d][0] *= al0; o[d][1] *= al1; o[d][2] *= al0; o[d][3] *= al1; }
                    mrun = mnew;
                }
                const float p0 = ex2((bf_lo(r01) - m0) * LOG2E), p1 = ex2((bf_hi(r01) - m1) * LOG2E);
                const float p2 = ex2((bf_lo(r23) - m0) * LOG2E), p3 = ex2((bf_hi(r23) - m1) * LOG2E);
                const uint32_t pb0 = movmatrix_t(pack_bf16(p0, p1)), pb1 = movmatrix_t(pack_bf16(p2, p3));
                mma16816(ls, ones, pb0, pb1);
                mbar_wait(bar_full + 8 * vs, vph);
                const uint32_t vb = sbase + SM_RING + vs * TILE + voff;
#pragma unroll
                for (int d = 0; d < 8; d++) {
                    uint32_t a[4];
                    ldsm4t((vb ^ ((d & 3) << 5)) + (d >> 2) * 8192, a);
                    mma16816(o[d], a, pb0, pb1);
                }
                __syncwarp();
                if (lane == 0) mbar_arrive(bar_empty + 8 * vs);
            }
        }
        if (warp == 7) TSTAMP(5);
        {
            float* mrg = (float*)(sgen + SM_MRG);
            float2* ml = (float2*)(sgen + SM_ML);
            {
                const int hp = (t & 1) * 2, up = t >> 1;
                if (g == 0 && up == 0) { ml[warp * 4 + hp] = make_float2(bf_lo(mrun), ls[0]); ml[warp * 4 + hp + 1] = make_float2(bf_hi(mrun), ls[1]); }
                float* m0p = mrg + (warp * 4 + hp) * 136 + up * 72 + g;
#pragma unroll
                for (int d = 0; d < 4; d++) {
                    m0p[16 * d] = up ? o[d + 4][0] : o[d][0]; m0p[136 + 16 * d] = up ? o[d + 4][1] : o[d][1];
                    m0p[16 * d + 8] = up ? o[d + 4][2] : o[d][2]; m0p[136 + 16 * d + 8] = up ? o[d + 4][3] : o[d][3];
                }
            }
            cons_sync();
            const int hh = tid >> 6, dp = tid & 63;
            float2 mw[8];
            float M = -INFINITY;
#pragma unroll
            for (int w = 0; w < 8; w++) { mw[w] = ml[w * 4 + hh]; M = fmaxf(M, mw[w].x); }
            float L = 0.f, o0 = 0.f, o1 = 0.f;
#pragma unroll
            for (int w = 0; w < 8; w++) {
                const float wt = ex2((mw[w].x - M) * LOG2E);
                const float2 v = *(const float2*)&mrg[(w * 4 + hh) * 136 + 2 * dp + (dp >= 32 ? 8 : 0)];
                L += wt * mw[w].y; o0 += wt * v.x; o1 += wt * v.y;
            }
            st_ll2(&sc->part_o[cta][hh][dp], tagf(o0, F_PART), tagf(o1, F_PART));
            if (dp < 4) st_ll2(&sc->part_ml[cta][hh][dp], tagf(M, F_PART), tagf(L, F_PART));
        }
        if (warp == 0) TSTAMP(6);
        {
            const int hq = cta >> 2, kvh = hq >> 2, hh = hq & 3;
            const int b = tid >> 7, dc = (tid >> 3) & 15, j = tid & 7;
            const int pc = (b * 8 + kvh) * 8 + j;
            const uint4* po = (const uint4*)&sc->part_o[pc][hh][0] + dc * 2;
            const uint2* pm = &sc->part_ml[pc - j][hh][0];
            uint4 vo0, vo1; uint2 vm[8];
            bool oko = false, okm = false;
            for (int it = 0;; it++) {
                if (!oko) { vo0 = ld_ll4(po); vo1 = ld_ll4(po + 1); }
                if (!okm) {
#pragma unroll
                    for (int jj = 0; jj < 8; jj++) vm[jj] = ld_ll2(pm + jj * 16);
                }
                oko = (vo0.x & vo0.y & vo0.z & vo0.w & vo1.x & vo1.y & vo1.z & vo1.w & 3u) == F_PART;
                uint32_t all = vm[0].x & vm[0].y;
#pragma unroll
                for (int jj = 1; jj < 8; jj++) all &= vm[jj].x & vm[jj].y;
                okm = (all & 3u) == F_PART;
                if (__all_sync(0xffffffffu, oko && okm) || it > SPIN_LIMIT) break;
                spin_cycles(A_BACKOFF);
            }
            float M = untag(vm[0].x);
#pragma unroll
            for (int jj = 1; jj < 8; jj++) M = fmaxf(M, untag(vm[jj].x));
            float wt = 0.f, L = 0.f;
#pragma unroll
            for (int jj = 0; jj < 8; jj++) {
                const float w_ = ex2((untag(vm[jj].x) - M) * LOG2E);
                L += w_ * untag(vm[jj].y);
                wt = jj == j ? w_ : wt;
            }
            wt *= rcp_approx(L);
            float v[8] = {wt * untag(vo0.x), wt * untag(vo0.y), wt * untag(vo0.z), wt * untag(vo0.w),
                          wt * untag(vo1.x), wt * untag(vo1.y), wt * untag(vo1.z), wt * untag(vo1.w)};
#define XRED(N, O)                                                                       \
            {                                                                            \
                const bool up = lane & (O);                                              \
                _Pragma("unroll") for (int i = 0; i < (N); i++) {                        \
                    const float send = up ? v[i] : v[i + (N)], keep = up ? v[i + (N)] : v[i]; \
                    v[i] = keep + __shfl_xor_sync(0xffffffffu, send, (O));               \
                }                                                                        \
            }
            XRED(4, 1) XRED(2, 2) XRED(1, 4)
#undef XRED
            __nv_bfloat16* os = (__nv_bfloat16*)(sgen + SM_OS);
            os[b * 128 + dc * 8 + 4 * (j & 1) + 2 * ((j >> 1) & 1) + (j >> 2)] = __float2bfloat16_rn(v[0]);
            if (warp == 0) TSTAMP(15);
            uint32_t wf[8][4];
            const uint32_t aoff_o = (warp >> 2) * 8192 + ((lane & 7) + (lane >> 4) * 8) * 128 +
                                    (((((warp & 3) * 2 + ((lane >> 3) & 1)) ^ (lane & 7))) << 4);
#pragma unroll
            for (int s = 0; s < 2; s++) {
                const int idx = IDX_WO + s;
                mbar_wait(bar_full + 8 * (idx % NST), (idx / NST) & 1);
                const uint32_t tb = sbase + SM_RING + (idx % NST) * TILE + aoff_o;
#pragma unroll
                for (int k4 = 0; k4 < 4; k4++) ldsm4t(tb + k4 * 2048, wf[s * 4 + k4]);
            }
            cons_sync();
            if (warp == 0) TSTAMP(7);
            const uint32_t* os32 = (const uint32_t*)(sgen + SM_OS) + bb * 64 + t;
            float y0[4] = {}, y1[4] = {};
#pragma unroll
            for (int ks = 0; ks < 8; ks += 2) {
                mma16816(y0, wf[ks], os32[8 * ks], os32[8 * ks + 4]);
                mma16816(y1, wf[ks + 1], os32[8 * ks + 8], os32[8 * ks + 12]);
            }
            if (t == 0)
                st_v4(&sc->inbox_wo[(cta & 3) * 8 + warp][hq][g], tagf(y0[0] + y1[0], F_WO), tagf(y0[1] + y1[1], F_WO),
                      tagf(y0[2] + y1[2], F_WO), tagf(y0[3] + y1[3], F_WO));
        }
        const uint32_t t_wo = clock32();
        if (warp == 0) TSTAMP(8);
        if (cta >= NCTA - NOWN) {
            const uint4* pin = &sc->inbox_wo[cta - (NCTA - NOWN)][0][0] + tid;
            uint4 v;
            spin_cycles(DELAY_B1);
            bool ok = false;
            for (int it = 0;; it++) {
                if (!ok) {
                    v = ld_ll4(pin);
                    ok = (v.x & v.y & v.z & v.w & 3u) == F_WO;
                }
                if (__all_sync(0xffffffffu, ok) || it > SPIN_LIMIT) break;
            }
            const bool u1 = lane & 8, u2 = lane & 16;
            const float a0 = untag(v.x), a1 = untag(v.y), a2 = untag(v.z), a3 = untag(v.w);
            const float k0 = (u1 ? a2 : a0) + __shfl_xor_sync(0xffffffffu, u1 ? a0 : a2, 8);
            const float k1 = (u1 ? a3 : a1) + __shfl_xor_sync(0xffffffffu, u1 ? a1 : a3, 8);
            red2[warp * 32 + lane] = (u2 ? k1 : k0) + __shfl_xor_sync(0xffffffffu, u2 ? k0 : k1, 16);
            cons_sync();
            if (warp == 0) {
                float a = 0.f;
#pragma unroll
                for (int w = 0; w < 8; w++) a += red2[w * 32 + lane];
                const float ga = (wcol & 1) ? bf_hi(m_ga.x) : bf_lo(m_ga.x);
                const float xm = bf16r(xo + bf16r(ga * bf16r(a)));
                const float xm_b1 = __shfl_down_sync(0xffffffffu, xm, 16);
                if (lane < 16) st_ll2(&sc->x1[wcol], pack_bf16(xm, xm_b1), F_X1);
                TSTAMP(10);
            }
        }
        const uint32_t aoff = warp * 2048 + ((lane & 7) + (lane >> 4) * 8) * 128 + ((((lane >> 3) & 1) ^ (lane & 7)) << 4);
        if (cta < NFFN) {
            const uint4* px = (const uint4*)&sc->x1[ec];
            const uint4* pp = (const uint4*)&sc->x1[0];
            uint4 va, vb, pa, pb;
            uint32_t gf[4][4], uf[4][4];
            mbar_wait(bar_gu + 8 * (2 * (warp >> 1)), 0);
            mbar_wait(bar_gu + 8 * (2 * (warp >> 1) + 1), 0);
            {
                const uint32_t tg = sbase + SM_RING + (IDX_WG % NST) * TILE, tu = sbase + SM_RING + (IDX_WU % NST) * TILE;
#pragma unroll
                for (int s = 0; s < 4; s++) {
                    const int row = 64 * warp + 16 * s + (lane & 7) + (lane >> 4) * 8;
                    const uint32_t off = row * 32 + ((((lane >> 3) & 1) ^ ((row >> 2) & 1)) << 4);
                    ldsm4t(tg + off, gf[s]);
                    ldsm4t(tu + off, uf[s]);
                }
            }
            const float c1v[4] = {bf16r(1.0f + bf_lo(m_cb.x)), bf16r(1.0f + bf_hi(m_cb.x)), bf16r(1.0f + bf_lo(m_cb.z)), bf16r(1.0f + bf_hi(m_cb.z))};
            float bg = 0.f, cgc = 0.f, bu = 0.f, cuc = 0.f;
            {
                uint32_t* pre = (uint32_t*)(sgen + SM_MRG) + warp * 128;
                float* bc = (float*)(sgen + SM_MRG + 4096);
                *(uint2*)&pre[eb * 32 + 2 * (lane & 15)] = make_uint2(pack_bf16(c1v[0], c1v[1]), pack_bf16(c1v[2], c1v[3]));
                *(uint2*)&pre[64 + eb * 32 + 2 * (lane & 15)] = make_uint2(m_sb.x, m_sb.z);
                __syncwarp();
                float yg[4] = {}, yu[4] = {};
                const uint32_t* pb = pre + ((g >> 1) & 1) * 64 + bb * 32 + t;
#pragma unroll
                for (int s = 0; s < 4; s++) {
                    const uint32_t b0 = pb[8 * s], b1 = pb[8 * s + 4];
                    mma16816(yg, gf[s], b0, b1);
                    mma16816(yu, uf[s], b0, b1);
                }
                const float y0 = t < 2 ? yg[0] : yu[0], y1 = t < 2 ? yg[1] : yu[1], y2 = t < 2 ? yg[2] : yu[2], y3 = t < 2 ? yg[3] : yu[3];
                float* dstp = bc + warp * 128 + (t >> 1) * 64 + (t & 1) * 32;
                *(float2*)&dstp[g * 2] = make_float2(y0, y1);
                *(float2*)&dstp[(g + 8) * 2] = make_float2(y2, y3);
                __syncwarp();
                if (lane == 0) mbar_arrive(bar_bc);
            }
            if (warp == 0) TSTAMP(11);
            float pivot2;
            {
                while (clock32() - t_wo < DELAY_X1) {}
                bool okx = false, okp = false;
                for (int it = 0;; it++) {
                    if (!okx) { va = ld_ll4(px); vb = ld_ll4(px + 1); }
                    if (!okp) { pa = ld_ll4(pp); pb = ld_ll4(pp + 1); }
                    okx = va.y == F_X1 && va.w == F_X1 && vb.y == F_X1 && vb.w == F_X1;
                    okp = pa.y == F_X1 && pa.w == F_X1 && pb.y == F_X1 && pb.w == F_X1;
                    if (__all_sync(0xffffffffu, okx && okp) || it > SPIN_LIMIT) break;
                }
                if (warp == 0) TSTAMP(9);
                const float xv[4] = {eb ? bf_hi(va.x) : bf_lo(va.x), eb ? bf_hi(va.z) : bf_lo(va.z),
                                     eb ? bf_hi(vb.x) : bf_lo(vb.x), eb ? bf_hi(vb.z) : bf_lo(vb.z)};
                const float p0 = 0.25f * ((bf_lo(pa.x) + bf_lo(pa.z)) + (bf_lo(pb.x) + bf_lo(pb.z)));
                const float p1 = 0.25f * ((bf_hi(pa.x) + bf_hi(pa.z)) + (bf_hi(pb.x) + bf_hi(pb.z)));
                const float pivot = eb ? p1 : p0;
                pivot2 = (lane & 1) ? p1 : p0;
                *(uint2*)&hs[eb * 32 + 2 * (lane & 15)] =
                    make_uint2(pack_bf16((xv[0] - pivot) * c1v[0], (xv[1] - pivot) * c1v[1]),
                               pack_bf16((xv[2] - pivot) * c1v[2], (xv[3] - pivot) * c1v[3]));
                __syncwarp();
                float cg[2][4] = {}, cu[2][4] = {};
#pragma unroll
                for (int s = 0; s < 4; s++) {
                    const uint32_t b0 = hs[bb * 32 + 8 * s + t], b1 = hs[bb * 32 + 8 * s + 4 + t];
                    mma16816(cg[s & 1], gf[s], b0, b1);
                    mma16816(cu[s & 1], uf[s], b0, b1);
                }
                const float2 ps = half_warp_sums(xv, pivot);
                if ((lane & 15) == 0) stat[warp * 2 + eb] = ps;
                {
                    const float* bc = (const float*)(sgen + SM_MRG + 4096);
                    mbar_wait(bar_bc, 0);
#pragma unroll
                    for (int w = 0; w < 8; w++) {
                        bg += bc[w * 128 + lane]; cgc += bc[w * 128 + 32 + lane];
                        bu += bc[w * 128 + 64 + lane]; cuc += bc[w * 128 + 96 + lane];
                    }
                }
                if (t < 2) {
                    float v[4];
#pragma unroll
                    for (int i = 0; i < 4; i++) v[i] = t ? cu[0][i] + cu[1][i] : cg[0][i] + cg[1][i];
                    *(float2*)&red[warp * 64 + t * 32 + g * 2] = make_float2(v[0], v[1]);
                    *(float2*)&red[warp * 64 + t * 32 + (g + 8) * 2] = make_float2(v[2], v[3]);
                }
            }
            uint32_t df[4][4];
            mbar_wait(bar_full + 8 * (IDX_WD % NST), (IDX_WD / NST) & 1);
#pragma unroll
            for (int mt = 0; mt < 4; mt++) ldsm4t((sbase + SM_RING + (IDX_WD % NST) * TILE + aoff) ^ (mt << 5), df[mt]);
            cons_sync();
            {
                float gs = 0.f, us = 0.f;
#pragma unroll
                for (int w = 0; w < 8; w++) { gs += red[w * 64 + lane]; us += red[w * 64 + 32 + lane]; }
                float mean_bf, rstd;
                ln_stats(stat, lane & 1, pivot2, mean_bf, rstd);
                const float dm = mean_bf - pivot2;
                gs = bf16r(rstd * (gs - dm * bg) + cgc);
                us = rstd * (us - dm * bu) + cuc;
                const float u2 = gs * (1.0f + 0.044715f * gs * gs) * (2.0f * 0.7978845608028654f * LOG2E);
                const float ge = bf16r(__fdividef(gs, 1.0f + ex2(-u2)));
                const float act = bf16r(ge * bf16r(us));
                const float a0 = __shfl_sync(0xffffffffu, act, 4 * t + bb), a1 = __shfl_sync(0xffffffffu, act, 4 * t + 2 + bb);
                const float a2 = __shfl_sync(0xffffffffu, act, 4 * t + 16 + bb), a3 = __shfl_sync(0xffffffffu, act, 4 * t + 18 + bb);
                const uint32_t b0 = pack_bf16(a0, a1), b1 = pack_bf16(a2, a3);
                float y[4][4] = {};
#pragma unroll
                for (int mt = 0; mt < 4; mt++) mma16816(y[mt], df[mt], b0, b1);
                float v[4];
#pragma unroll
                for (int i = 0; i < 4; i++) v[i] = t == 0 ? y[0][i] : t == 1 ? y[1][i] : t == 2 ? y[2][i] : y[3][i];
            {
                const bool odd = g & 1;
                const float sx = odd ? v[0] : v[2], sy = odd ? v[1] : v[3];
                const float rx = __shfl_xor_sync(0xffffffffu, sx, 4), ry = __shfl_xor_sync(0xffffffffu, sy, 4);
                const int c0 = 64 * warp + 16 * t + (odd ? g + 7 : g);
                const float e0 = odd ? rx : v[0], e1 = odd ? ry : v[1], e2 = odd ? v[2] : rx, e3 = odd ? v[3] : ry;
                st_v4(&sc->inbox_dn[c0 >> 2][cta][(c0 >> 1) & 1], tagf(e0, F_DOWN), tagf(e1, F_DOWN), tagf(e2, F_DOWN), tagf(e3, F_DOWN));
            }
            }
            if (warp == 0) TSTAMP(12);
        }
        {
            uint2 xw;
            float r0;
            {
                const uint4* pin = &sc->inbox_dn[cta][0][0] + tid;
                uint4 v = make_uint4(F_DOWN, F_DOWN, F_DOWN, F_DOWN);
                if (cta < NFFN) spin_cycles(DELAY_C);
                else while (clock32() - t_wo < DELAY_X1 + DELAY_NOFFN) {}
                xw = ld_ll2(&sc->x1[ocol]);
                bool ok = tid >= NFFN * 2;
                for (int it = 0;; it++) {
                    if (!ok) {
                        v = ld_ll4(pin);
                        ok = (v.x & v.y & v.z & v.w & 3u) == F_DOWN;
                    }
                    if (__all_sync(0xffffffffu, ok) || it > SPIN_LIMIT) break;
                }
                const bool u1 = lane & 2, u2 = lane & 4;
                const float a0 = untag(v.x), a1 = untag(v.y), a2 = untag(v.z), a3 = untag(v.w);
                const float k0 = (u1 ? a1 : a0) + __shfl_xor_sync(0xffffffffu, u1 ? a0 : a1, 2);
                const float k1 = (u1 ? a3 : a2) + __shfl_xor_sync(0xffffffffu, u1 ? a2 : a3, 2);
                r0 = (u2 ? k1 : k0) + __shfl_xor_sync(0xffffffffu, u2 ? k0 : k1, 4);
                r0 += __shfl_xor_sync(0xffffffffu, r0, 8);
                r0 += __shfl_xor_sync(0xffffffffu, r0, 16);
                if (lane < 8) red2[256 + warp * 8 + (2 * (lane & 1) + ((lane >> 2) & 1)) * 2 + ((lane >> 1) & 1)] = r0;
            }
            cons_sync();
            if (warp == 0) {
                float a0 = 0.f, a1 = 0.f;
#pragma unroll
                for (int w = 0; w < 8; w++) { const float2 v = *(const float2*)&red2[256 + w * 8 + (lane & 3) * 2]; a0 += v.x; a1 += v.y; }
                const bool hi = ocol & 1;
                const float gb0 = hi ? bf_hi(m_gb0.x) : bf_lo(m_gb0.x), gb1 = hi ? bf_hi(m_gb1.x) : bf_lo(m_gb1.x);
                for (int it = 0; !__all_sync(0xffffffffu, xw.y == F_X1) && it < SPIN_LIMIT; it++) xw = ld_ll2(&sc->x1[ocol]);
                if (lane < 4) {
                    p.out[ocol] = __float2bfloat16_rn(bf_lo(xw.x) + bf16r(gb0 * bf16r(a0)));
                    p.out[D_MODEL + ocol] = __float2bfloat16_rn(bf_hi(xw.x) + bf16r(gb1 * bf16r(a1)));
                }
                TSTAMP(13);
            }
        }
    }
}

typedef CUresult (*EncodeFn)(CUtensorMap*, CUtensorMapDataType, cuuint32_t, void*, const cuuint64_t*, const cuuint64_t*,
                             const cuuint32_t*, const cuuint32_t*, CUtensorMapInterleave, CUtensorMapSwizzle,
                             CUtensorMapL2promotion, CUtensorMapFloatOOBfill);

struct Maps { CUtensorMap k, v, wq, wmod, wmod8, wo, wg, wu, wd; };

void encode(EncodeFn fn, CUtensorMap* m, const void* ptr, int rank, const cuuint64_t* dims, const cuuint64_t* strides,
            const cuuint32_t* box, CUtensorMapSwizzle sw) {
    const cuuint32_t es[3] = {1, 1, 1};
    fn(m, CU_TENSOR_MAP_DATA_TYPE_BFLOAT16, rank, const_cast<void*>(ptr), dims, strides, box, es,
       CU_TENSOR_MAP_INTERLEAVE_NONE, sw, CU_TENSOR_MAP_L2_PROMOTION_L2_256B, CU_TENSOR_MAP_FLOAT_OOB_FILL_NONE);
}

}

extern "C" void kernel_launch(void* const* d_in, const int* in_sizes, int n_in, void* d_out, int out_size) {
    (void)in_sizes; (void)n_in; (void)out_size;
    static EncodeFn enc = nullptr;
    static Scratch* scratch = nullptr;
    if (!enc) {
        cudaGetSymbolAddress((void**)&scratch, g_scratch);
        void* fn = nullptr;
        cudaDriverEntryPointQueryResult qr;
        cudaGetDriverEntryPoint("cuTensorMapEncodeTiled", &fn, cudaEnableDefault, &qr);
        enc = (EncodeFn)fn;
        cudaFuncSetAttribute(fused_block_kernel, cudaFuncAttributeMaxDynamicSharedMemorySize, SMEM_BYTES);
    }
    Maps m;
    {
        const cuuint64_t dims[3] = {64, (cuuint64_t)16 * SK, 2}, str[2] = {256, 128};
        const cuuint32_t box[3] = {64, 64, 2};
        encode(enc, &m.k, d_in[1], 3, dims, str, box, CU_TENSOR_MAP_SWIZZLE_128B);
        encode(enc, &m.v, d_in[2], 3, dims, str, box, CU_TENSOR_MAP_SWIZZLE_128B);
    }
    {
        const cuuint64_t dims[2] = {4096, 512}, str[1] = {8192};
        const cuuint32_t box[2] = {32, 256};
        encode(enc, &m.wq, d_in[3], 2, dims, str, box, CU_TENSOR_MAP_SWIZZLE_64B);
    }
    {
        const cuuint64_t dims[2] = {N_MOD, 512}, str[1] = {N_MOD * 2};
        const cuuint32_t box[2] = {16, 256};
        encode(enc, &m.wmod, d_in[10], 2, dims, str, box, CU_TENSOR_MAP_SWIZZLE_32B);
        const cuuint32_t box8[2] = {8, 256};
        encode(enc, &m.wmod8, d_in[10], 2, dims, str, box8, CU_TENSOR_MAP_SWIZZLE_NONE);
    }
    {
        const cuuint64_t dims_o[3] = {64, 4096, 8}, dims_d[3] = {64, D_FF, 8}, str[2] = {1024, 128};
        const cuuint32_t box[3] = {64, 16, 8}, box_o[3] = {64, 64, 2};
        encode(enc, &m.wo, d_in[4], 3, dims_o, str, box_o, CU_TENSOR_MAP_SWIZZLE_128B);
        encode(enc, &m.wd, d_in[8], 3, dims_d, str, box, CU_TENSOR_MAP_SWIZZLE_128B);
    }
    {
        const cuuint64_t dims[2] = {D_FF, 512}, str[1] = {D_FF * 2};
        const cuuint32_t box[2] = {16, 128};
        encode(enc, &m.wg, d_in[6], 2, dims, str, box, CU_TENSOR_MAP_SWIZZLE_32B);
        encode(enc, &m.wu, d_in[7], 2, dims, str, box, CU_TENSOR_MAP_SWIZZLE_32B);
    }
    Params p;
    p.x = (const __nv_bfloat16*)d_in[0];
    p.c = (const __nv_bfloat16*)d_in[9];
    p.out = (__nv_bfloat16*)d_out;
    p.sc = scratch;
    fused_block_kernel<<<NCTA, NTHREADS, SMEM_BYTES, cudaStreamPerThread>>>(p, m.k, m.v, m.wq, m.wmod, m.wmod8, m.wo, m.wg, m.wu, m.wd);
}
```

```cpp
#include <cuda_runtime.h>
#include <cuda.h>
#include <cuda_bf16.h>
#include <stdint.h>

namespace {

constexpr int D_MODEL = 512;
constexpr int N_HEADS = 32;
constexpr int SK = 32768;
constexpr int DH = 128;
constexpr int D_FF = 1792;
constexpr int N_MOD = 6 * D_MODEL;

constexpr int NCTA = 128;
constexpr int NFFN = D_FF / 16;
constexpr int NOWN = 32;
constexpr int NTHREADS = 320;
constexpr int NST = 12;
constexpr int TILE = 16384;
#define WINDOW 3
#define WINDOW_TAIL 1
#define GU_WIN 3
#define GU_EARLY 0
#define WD_WIN 2
#define FIRST 4
#define RAMP_END 4
#define RAMP_STEP 1250
#define PACE_THR 96
constexpr int KV_TILES = 64;
#define MOD_AT 8
static_assert(MOD_AT % 2 == 0 && MOD_AT >= 2 && MOD_AT < 56, "schedule");
__host__ __device__ constexpr int kv_idx(int i) { return 2 + 2 * i + (i >= MOD_AT ? 1 : 0); }
constexpr int IDX_MOD = 2 + 2 * MOD_AT;
constexpr int N_STREAM = kv_idx(KV_TILES - 1) + 2;
constexpr int IDX_WO = N_STREAM;
constexpr int IDX_WG = IDX_WO + 2;
constexpr int IDX_WU = IDX_WG + 1;
constexpr int IDX_WD = IDX_WU + 1;
constexpr int SPIN_LIMIT = 1 << 20;

constexpr float LOG2E = 1.4426950408889634f;
constexpr float QK_SCALE = 0.08838834764831845f;

constexpr int SM_RING = 0;
constexpr int SM_MRG = SM_RING + NST * TILE;
constexpr int SM_ML = SM_MRG + 8 * 4 * 136 * 4;
constexpr int SM_RED = SM_ML + 8 * 4 * 8;
constexpr int SM_RED2 = SM_RED + 8 * 64 * 4;
constexpr int SM_QS = SM_RED2 + 8 * 64 * 4;
constexpr int SM_OS = SM_QS + 512 * 2;
constexpr int SM_SC = SM_OS + 2 * 128 * 2;
constexpr int SM_HS = SM_SC + 2 * 512 * 2;
constexpr int SM_STAT = SM_HS + 8 * 2 * 32 * 4;
constexpr int SM_PACE = SM_STAT + 8 * 2 * 8;
constexpr int SM_BAR = SM_PACE + 8;
constexpr int SM_END = SM_BAR + (2 * NST + 1 + 8 + 2) * 8;
constexpr int SMEM_BYTES = SM_END + 1024;

struct Scratch {
    uint4 inbox_wo[NOWN][N_HEADS][8];
    uint4 inbox_dn[NCTA][NFFN][2];
    uint2 x1[D_MODEL];
    uint2 part_o[NCTA][4][64];
    uint2 part_ml[NCTA][4][4];
    uint2 mod[2][N_MOD / 2];
    uint2 q[2][N_HEADS * DH / 2];
    unsigned epoch;
    unsigned pad_[31];
    unsigned cleared;
    unsigned pad2_[31];
    unsigned progress;
};
__device__ Scratch g_scratch;
constexpr uint32_t F_PART = 1, F_WO = 1, F_DOWN = 1, F_X1 = 1;
__device__ __forceinline__ uint32_t tagf(float v, uint32_t f) { return (__float_as_uint(v) & ~3u) | f; }
__device__ __forceinline__ float untag(uint32_t v) { return __uint_as_float(v & ~3u); }

struct Params {
    const __nv_bfloat16* x;
    const __nv_bfloat16* c;
    __nv_bfloat16* out;
    Scratch* sc;
};

#define TSTAMP(i) do { } while (0)

__device__ __forceinline__ uint32_t smem_u32(const void* p) { return (uint32_t)__cvta_generic_to_shared(p); }

__device__ __forceinline__ void mbar_init(uint32_t bar, uint32_t cnt) {
    asm volatile("mbarrier.init.shared::cta.b64 [%0], %1;" ::"r"(bar), "r"(cnt) : "memory");
}
__device__ __forceinline__ void mbar_expect_tx(uint32_t bar, uint32_t bytes) {
    asm volatile("mbarrier.arrive.expect_tx.shared::cta.b64 _, [%0], %1;" ::"r"(bar), "r"(bytes) : "memory");
}
__device__ __forceinline__ void mbar_arrive(uint32_t bar) {
    asm volatile("mbarrier.arrive.shared::cta.b64 _, [%0];" ::"r"(bar) : "memory");
}
__device__ __forceinline__ bool mbar_try(uint32_t bar, uint32_t parity) {
    uint32_t ok;
    asm volatile(
        "{\n\t.reg .pred p;\n\t"
        "mbarrier.try_wait.parity.shared::cta.b64 p, [%1], %2;\n\t"
        "selp.u32 %0, 1, 0, p;\n\t}"
        : "=r"(ok) : "r"(bar), "r"(parity) : "memory");
    return ok != 0;
}
__device__ __forceinline__ void mbar_wait(uint32_t bar, uint32_t parity) {
    if (mbar_try(bar, parity)) return;
    const long long t0 = clock64();
    while (!mbar_try(bar, parity))
        if (clock64() - t0 > (1ll << 31)) return;
}
__device__ __forceinline__ void cons_sync() { asm volatile("bar.sync 1, 256;" ::: "memory"); }

__device__ __forceinline__ void tma_2d(uint32_t dst, const CUtensorMap* m, int c0, int c1, uint32_t bar) {
    asm volatile("cp.async.bulk.tensor.2d.shared::cluster.global.mbarrier::complete_tx::bytes [%0], [%1, {%3, %4}], [%2];"
                 ::"r"(dst), "l"(m), "r"(bar), "r"(c0), "r"(c1) : "memory");
}
__device__ __forceinline__ void tma_3d(uint32_t dst, const CUtensorMap* m, int c0, int c1, int c2, uint32_t bar) {
    asm volatile("cp.async.bulk.tensor.3d.shared::cluster.global.mbarrier::complete_tx::bytes [%0], [%1, {%3, %4, %5}], [%2];"
                 ::"r"(dst), "l"(m), "r"(bar), "r"(c0), "r"(c1), "r"(c2) : "memory");
}
__device__ __forceinline__ void tma_3d_hint(uint32_t dst, const CUtensorMap* m, int c0, int c1, int c2, uint32_t bar, uint64_t pol) {
    asm volatile("cp.async.bulk.tensor.3d.shared::cluster.global.mbarrier::complete_tx::bytes.L2::cache_hint [%0], [%1, {%3, %4, %5}], [%2], %6;"
                 ::"r"(dst), "l"(m), "r"(bar), "r"(c0), "r"(c1), "r"(c2), "l"(pol) : "memory");
}
__device__ __forceinline__ void prefetch_tmap(const CUtensorMap* m) {
    asm volatile("prefetch.tensormap [%0];" ::"l"(m) : "memory");
}

__device__ __forceinline__ void ldsm4(uint32_t addr, uint32_t (&r)[4]) {
    asm volatile("ldmatrix.sync.aligned.m8n8.x4.shared.b16 {%0,%1,%2,%3}, [%4];"
                 : "=r"(r[0]), "=r"(r[1]), "=r"(r[2]), "=r"(r[3]) : "r"(addr) : "memory");
}
__device__ __forceinline__ void ldsm4t(uint32_t addr, uint32_t (&r)[4]) {
    asm volatile("ldmatrix.sync.aligned.m8n8.x4.trans.shared.b16 {%0,%1,%2,%3}, [%4];"
                 : "=r"(r[0]), "=r"(r[1]), "=r"(r[2]), "=r"(r[3]) : "r"(addr) : "memory");
}
__device__ __forceinline__ void mma16816(float (&c)[4], const uint32_t (&a)[4], uint32_t b0, uint32_t b1) {
    asm volatile("mma.sync.aligned.m16n8k16.row.col.f32.bf16.bf16.f32 {%0,%1,%2,%3}, {%4,%5,%6,%7}, {%8,%9}, {%0,%1,%2,%3};"
                 : "+f"(c[0]), "+f"(c[1]), "+f"(c[2]), "+f"(c[3])
                 : "r"(a[0]), "r"(a[1]), "r"(a[2]), "r"(a[3]), "r"(b0), "r"(b1));
}
__device__ __forceinline__ uint32_t movmatrix_t(uint32_t a) {
    uint32_t d;
    asm volatile("movmatrix.sync.aligned.m8n8.trans.b16 %0, %1;" : "=r"(d) : "r"(a));
    return d;
}
__device__ __forceinline__ uint32_t pack_bf16(float a, float b) {
    uint32_t r;
    asm("cvt.rn.bf16x2.f32 %0, %1, %2;" : "=r"(r) : "f"(b), "f"(a));
    return r;
}
__device__ __forceinline__ float bf_lo(uint32_t v) { return __uint_as_float(v << 16); }
__device__ __forceinline__ float bf_hi(uint32_t v) { return __uint_as_float(v & 0xffff0000u); }
__device__ __forceinline__ float bf16r(float a) { return bf_lo(pack_bf16(a, 0.f)); }
__device__ __forceinline__ uint32_t max_bf16x2(uint32_t a, uint32_t b) {
    uint32_t r;
    asm("max.bf16x2 %0, %1, %2;" : "=r"(r) : "r"(a), "r"(b));
    return r;
}
__device__ __forceinline__ float ex2(float x) {
    float r;
    asm("ex2.approx.ftz.f32 %0, %1;" : "=f"(r) : "f"(x));
    return r;
}

__device__ __forceinline__ void st_ll2(uint2* p, uint32_t v, uint32_t tag) {
    asm volatile("st.relaxed.gpu.global.v2.u32 [%0], {%1, %2};" ::"l"(p), "r"(v), "r"(tag) : "memory");
}
__device__ __forceinline__ void st_ll4(uint4* p, uint32_t v0, uint32_t v1, uint32_t tag) {
    asm volatile("st.relaxed.gpu.global.v4.u32 [%0], {%1, %2, %3, %2};" ::"l"(p), "r"(v0), "r"(tag), "r"(v1) : "memory");
}
__device__ __forceinline__ void st_v4(uint4* p, uint32_t a, uint32_t b, uint32_t c, uint32_t d) {
    asm volatile("st.relaxed.gpu.global.v4.u32 [%0], {%1, %2, %3, %4};" ::"l"(p), "r"(a), "r"(b), "r"(c), "r"(d) : "memory");
}
__device__ __forceinline__ uint2 ld_ll2(const uint2* p) {
    uint2 v;
    asm volatile("ld.relaxed.gpu.global.v2.u32 {%0, %1}, [%2];" : "=r"(v.x), "=r"(v.y) : "l"(p) : "memory");
    return v;
}
__device__ __forceinline__ uint4 ld_ll4(const uint4* p) {
    uint4 v;
    asm volatile("ld.relaxed.gpu.global.v4.u32 {%0, %1, %2, %3}, [%4];"
                 : "=r"(v.x), "=r"(v.y), "=r"(v.z), "=r"(v.w) : "l"(p) : "memory");
    return v;
}

#define DELAY_B1 300
#define DELAY_X1 2000
#define DELAY_NOFFN 1500
#define A_BACKOFF 0
#define DELAY_C 600
__device__ __forceinline__ uint32_t clock32() {
    uint32_t c;
    asm volatile("mov.u32 %0, %clock;" : "=r"(c));
    return c;
}
__device__ __forceinline__ void spin_cycles(uint32_t n) {
    if (n > 0) { const uint32_t c0 = clock32(); while (clock32() - c0 < n) {} }
}
__device__ __forceinline__ float rcp_approx(float x) {
    float r;
    asm("rcp.approx.ftz.f32 %0, %1;" : "=f"(r) : "f"(x));
    return r;
}
__device__ __forceinline__ float sqrt_approx(float x) {
    float r;
    asm("sqrt.approx.f32 %0, %1;" : "=f"(r) : "f"(x));
    return r;
}

__device__ __forceinline__ float silu_bf(float v) { return bf16r(v / (1.0f + expf(-v))); }

__device__ __forceinline__ float2 half_warp_sums(const float (&v)[4], float pivot) {
    float s1 = 0.f, s2 = 0.f;
#pragma unroll
    for (int i = 0; i < 4; i++) { const float d = v[i] - pivot; s1 += d; s2 += d * d; }
#pragma unroll
    for (int o = 1; o < 16; o <<= 1) { s1 += __shfl_xor_sync(0xffffffffu, s1, o); s2 += __shfl_xor_sync(0xffffffffu, s2, o); }
    return make_float2(s1, s2);
}
__device__ __forceinline__ void ln_stats(const float2* stat, int b, float pivot, float& mean_bf, float& rstd) {
    float s1 = 0.f, s2 = 0.f;
#pragma unroll
    for (int w = 0; w < 8; w++) { const float2 v = stat[w * 2 + b]; s1 += v.x; s2 += v.y; }
    const float dm = s1 * (1.0f / D_MODEL);
    const float var = fmaxf(s2 * (1.0f / D_MODEL) - dm * dm, 0.f);
    mean_bf = bf16r(pivot + dm);
    rstd = rcp_approx(bf16r(sqrt_approx(bf16r(bf16r(var) + 1e-5f))));
}
__device__ __forceinline__ float ln_norm(float xv, float mean_bf, float rstd) { return bf16r(bf16r(xv - mean_bf) * rstd); }
__device__ __forceinline__ float ln_mod(float n, float cmul, float sadd) { return bf16r(n * bf16r(1.0f + cmul)) + sadd; }

__global__ void __launch_bounds__(NTHREADS, 1)
fused_block_kernel(const Params p, const __grid_constant__ CUtensorMap tm_k, const __grid_constant__ CUtensorMap tm_v,
                   const __grid_constant__ CUtensorMap tm_wq, const __grid_constant__ CUtensorMap tm_wmod,
                   const __grid_constant__ CUtensorMap tm_wmod8,
                   const __grid_constant__ CUtensorMap tm_wo, const __grid_constant__ CUtensorMap tm_wg,
                   const __grid_constant__ CUtensorMap tm_wu, const __grid_constant__ CUtensorMap tm_wd) {
    extern __shared__ unsigned char smem_raw[];
    const uint32_t sbase = (smem_u32(smem_raw) + 1023u) & ~1023u;
    unsigned char* sgen = smem_raw + (sbase - smem_u32(smem_raw));
    const int tid = threadIdx.x, warp = tid >> 5, lane = tid & 31;
    const int cta = blockIdx.x;
    const uint32_t bar_full = sbase + SM_BAR, bar_empty = bar_full + NST * 8;
    const uint32_t bar_clear = bar_empty + NST * 8;
    const uint32_t bar_gu = bar_clear + 8;
    const uint32_t bar_bc = bar_gu + 8 * 8;
    const uint32_t bar_p0w = bar_bc + 8;

    const int key0 = (cta >> 3) * SK + (cta & 7) * 64;
    uint64_t pol = 0;
    if (tid == 256) {
        asm volatile("createpolicy.fractional.L2::evict_first.b64 %0, 1.0;" : "=l"(pol));
        mbar_init(bar_p0w, 1);
#pragma unroll
        for (int i = 0; i < FIRST; i++) mbar_init(bar_full + 8 * i, 1);
        asm volatile("fence.mbarrier_init.release.cluster;" ::: "memory");
        mbar_expect_tx(bar_p0w, 8192);
        tma_2d(sbase + SM_MRG, &tm_wmod8, cta * 8, 0, bar_p0w);
        tma_2d(sbase + SM_MRG + 4096, &tm_wmod8, cta * 8, 256, bar_p0w);
#pragma unroll
        for (int i = 0; i < FIRST; i++) mbar_expect_tx(bar_full + 8 * i, TILE);
        tma_2d(sbase + SM_RING, &tm_wq, cta * 32, 0, bar_full);
        tma_2d(sbase + SM_RING + TILE, &tm_wq, cta * 32, 256, bar_full + 8);
        if (FIRST > 2) tma_3d_hint(sbase + SM_RING + 2 * TILE, &tm_k, 0, key0, 0, bar_full + 16, pol);
        if (FIRST > 3) tma_3d_hint(sbase + SM_RING + 3 * TILE, &tm_v, 0, key0, 0, bar_full + 24, pol);
    }
    const uint32_t c_start = clock32();

    if (warp == 8) {
        if (lane == 0) {
            for (int i = 0; i < NST; i++) { if (i >= FIRST) mbar_init(bar_full + 8 * i, 1); mbar_init(bar_empty + 8 * i, 4); }
            mbar_init(bar_clear, 1);
            for (int k = 0; k < 8; k++) mbar_init(bar_gu + 8 * k, 1);
            mbar_init(bar_bc, 8);
            ((volatile uint32_t*)(sgen + SM_PACE))[0] = 0;
            ((volatile uint32_t*)(sgen + SM_PACE))[1] = WINDOW;
            asm volatile("fence.mbarrier_init.release.cluster;" ::: "memory");
        }
        __syncwarp();
        asm volatile("bar.arrive 2, 320;" ::: "memory");
        asm volatile("bar.arrive 3, 64;" ::: "memory");
        if (lane == 0) {
            int slot = FIRST; uint32_t ph = 1;
            int landed = 0, wslot = 0; uint32_t wph = 0;
            int kv = FIRST - 2;
            auto wait_window = [&](int idx, int window) {
                while (landed + window <= idx) {
                    mbar_wait(bar_full + 8 * wslot, wph);
                    if (++wslot == NST) { wslot = 0; wph ^= 1; }
                    landed++;
                }
            };
            volatile uint32_t* pace = (volatile uint32_t*)(sgen + SM_PACE);
            prefetch_tmap(&tm_wmod);
            pace[0] = FIRST;
            for (int idx = FIRST; idx < N_STREAM; idx++) {
                if (idx >= NST) mbar_wait(bar_empty + 8 * slot, ph);
                if (idx < RAMP_END) {
                    while (clock32() - c_start < (uint32_t)(idx - FIRST + 1) * RAMP_STEP) {}
                } else {
                    wait_window(idx, (int)pace[1]);
                }
                if (idx == 12) { prefetch_tmap(&tm_wo); prefetch_tmap(&tm_wg); prefetch_tmap(&tm_wu); prefetch_tmap(&tm_wd); }
                const uint32_t fb = bar_full + 8 * slot, dst = sbase + SM_RING + slot * TILE;
                mbar_expect_tx(fb, TILE);
                if (idx == IDX_MOD) {
                    tma_2d(dst, &tm_wmod, 1024 + cta * 16, 0, fb);
                    tma_2d(dst + 8192, &tm_wmod, 1024 + cta * 16, 256, fb);
                } else {
                    tma_3d_hint(dst, (kv & 1) ? &tm_v : &tm_k, 0, key0 + (kv >> 1) * 512, 0, fb, pol);
                    kv++;
                }
                pace[0] = idx + 1;
                if (++slot == NST) { slot = 0; ph ^= 1; }
            }
            auto slot_free = [&](int idx) { mbar_wait(bar_empty + 8 * (idx % NST), ((idx / NST) & 1) ^ 1); };
#pragma unroll
            for (int s = 0; s < 2; s++) {
                const int idx = IDX_WO + s;
                slot_free(idx);
                wait_window(idx, WINDOW_TAIL);
                mbar_expect_tx(bar_full + 8 * (idx % NST), TILE);
                tma_3d(sbase + SM_RING + (idx % NST) * TILE, &tm_wo, 0, (cta >> 2) * 128 + s * 64, (cta & 3) * 2, bar_full + 8 * (idx % NST));
            }
            if (cta < NFFN) {
                slot_free(IDX_WG); slot_free(IDX_WU);
#pragma unroll
                for (int st = 0; st < 8; st++) {
                    if (st == GU_EARLY) {
                        mbar_wait(bar_full + 8 * (IDX_WO % NST), (IDX_WO / NST) & 1);
                        mbar_wait(bar_full + 8 * ((IDX_WO + 1) % NST), ((IDX_WO + 1) / NST) & 1);
                    }
                    if (st >= GU_WIN) mbar_wait(bar_gu + 8 * (st - GU_WIN), 0);
                    mbar_expect_tx(bar_gu + 8 * st, 4096);
                    tma_2d(sbase + SM_RING + (((st & 1) ? IDX_WU : IDX_WG) % NST) * TILE + (st >> 1) * 4096,
                           (st & 1) ? &tm_wu : &tm_wg, cta * 16, (st >> 1) * 128, bar_gu + 8 * st);
                }
                mbar_wait(bar_gu + 8 * (8 - WD_WIN), 0);
                slot_free(IDX_WD);
                mbar_expect_tx(bar_full + 8 * (IDX_WD % NST), TILE);
                tma_3d(sbase + SM_RING + (IDX_WD % NST) * TILE, &tm_wd, 0, cta * 16, 0, bar_full + 8 * (IDX_WD % NST));
            }
        }
    } else if (warp == 9) {
        Scratch* const sc = p.sc;
        const uint32_t tag = *(volatile unsigned*)&sc->epoch + 1;
        if (lane < 2) {
            st_ll4((uint4*)&sc->mod[lane][cta * 4], 0u, 0u, 0u);
            st_ll4((uint4*)&sc->mod[lane][cta * 4] + 1, 0u, 0u, 0u);
        }
        if (lane < 8) st_ll4((uint4*)&sc->mod[lane >> 2][512 + cta * 8] + (lane & 3), 0u, 0u, 0u);
        if (lane < 16) st_ll4((uint4*)&sc->q[lane >> 3][cta * 16] + (lane & 7), 0u, 0u, 0u);
        __syncwarp();
        asm volatile("bar.arrive 2, 320;" ::: "memory");
        asm volatile("bar.sync 3, 64;" ::: "memory");
#pragma unroll 4
        for (int i = 0; i < NFFN * 2 / 32; i++) st_v4(&sc->inbox_dn[cta][0][0] + i * 32 + lane, 0u, 0u, 0u, 0u);
        if (cta >= NCTA - NOWN) {
#pragma unroll 4
            for (int i = 0; i < 8; i++) st_v4(&sc->inbox_wo[cta - (NCTA - NOWN)][0][0] + i * 32 + lane, 0u, 0u, 0u, 0u);
            if (lane < 8) st_v4((uint4*)&sc->x1[(cta - (NCTA - NOWN)) * 16] + lane, 0u, 0u, 0u, 0u);
        }
#pragma unroll 4
        for (int i = 0; i < 4; i++) st_v4((uint4*)&sc->part_o[cta][0][0] + i * 32 + lane, 0u, 0u, 0u, 0u);
        if (lane < 8) st_v4((uint4*)&sc->part_ml[cta][0][0] + lane, 0u, 0u, 0u, 0u);
        if (cta == 0 && lane == 0) asm volatile("st.relaxed.gpu.global.u32 [%0], %1;" ::"l"(&sc->progress), "r"(0u) : "memory");
        asm volatile("fence.acq_rel.gpu;" ::: "memory");
        __syncwarp();
        if (lane == 0) {
            asm volatile("fence.acq_rel.gpu;" ::: "memory");
            asm volatile("red.relaxed.gpu.global.add.u32 [%0], %1;" ::"l"(&sc->cleared), "r"(1u) : "memory");
            const uint32_t target = tag * NCTA;
            for (int it = 0; it < SPIN_LIMIT; it++) {
                uint32_t v;
                asm volatile("ld.relaxed.gpu.global.u32 %0, [%1];" : "=r"(v) : "l"(&sc->cleared) : "memory");
                if ((int32_t)(v - target) >= 0) break;
                __nanosleep(500);
            }
            asm volatile("fence.acq_rel.gpu;" ::: "memory");
            mbar_arrive(bar_clear);
            volatile uint32_t* pace = (volatile uint32_t*)(sgen + SM_PACE);
            uint32_t posted = 0;
            for (int it = 0; it < SPIN_LIMIT; it++) {
                const uint32_t own = pace[0];
                if (own >= N_STREAM) break;
                if (own > posted) {
                    asm volatile("red.relaxed.gpu.global.add.u32 [%0], %1;" ::"l"(&sc->progress), "r"(own - posted) : "memory");
                    posted = own;
                }
                uint32_t v;
                asm volatile("ld.relaxed.gpu.global.u32 %0, [%1];" : "=r"(v) : "l"(&sc->progress) : "memory");
                const int diff = (int)v - (int)own * NCTA;
                pace[1] = diff > PACE_THR ? WINDOW + 1 : diff < -PACE_THR ? WINDOW - 1 : WINDOW;
                __nanosleep(200);
            }
            if (cta == 0) asm volatile("st.relaxed.gpu.global.u32 [%0], %1;" ::"l"(&sc->epoch), "r"(tag) : "memory");
        }
    } else {
        const int g = lane >> 2, t = lane & 3;
        const int bb = g & 1;
        const int eb = lane >> 4;
        const int ec = 64 * warp + 4 * (lane & 15);
        if (warp == 0) TSTAMP(0);
        Scratch* const sc = p.sc;
        const float c00 = __bfloat162float(p.c[tid]), c01 = __bfloat162float(p.c[tid + 256]);
        const float c10 = __bfloat162float(p.c[D_MODEL + tid]), c11 = __bfloat162float(p.c[D_MODEL + tid + 256]);
        const uint2 xe = __ldg((const uint2*)(p.x + eb * D_MODEL + ec));
        const float xpivot = __bfloat162float(p.x[eb * D_MODEL]);
        const uint32_t tag = *(volatile unsigned*)&sc->epoch + 1;
        const int ocol = cta * 4 + (lane & 3);
        const int wcol = (cta >= NCTA - NOWN ? cta - (NCTA - NOWN) : 0) * 16 + (lane & 15);
        const float xo = __bfloat162float(p.x[eb * D_MODEL + wcol]);

        float* red = (float*)(sgen + SM_RED);
        float* red2 = (float*)(sgen + SM_RED2);
        float2* stat = (float2*)(sgen + SM_STAT);
        uint32_t* hs = (uint32_t*)(sgen + SM_HS) + warp * 64;
        float xn[4];
        {
            float xv[4] = {bf_lo(xe.x), bf_hi(xe.x), bf_lo(xe.y), bf_hi(xe.y)};
            const float2 ps = half_warp_sums(xv, xpivot);
            if ((lane & 15) == 0) stat[warp * 2 + eb] = ps;
            const float s00 = silu_bf(c00), s01 = silu_bf(c01), s10 = silu_bf(c10), s11 = silu_bf(c11);
            __nv_bfloat16* scs = (__nv_bfloat16*)(sgen + SM_SC);
            scs[tid] = __float2bfloat16_rn(s00); scs[tid + 256] = __float2bfloat16_rn(s01);
            scs[512 + tid] = __float2bfloat16_rn(s10); scs[512 + tid + 256] = __float2bfloat16_rn(s11);
            asm volatile("bar.sync 2, 320;" ::: "memory");
            if (warp == 0) TSTAMP(23);
            float cp[4] = {0.f, 0.f, 0.f, 0.f};
            const uint32_t* sc32 = (const uint32_t*)(sgen + SM_SC) + bb * 256 + 32 * warp + t;
            mbar_wait(bar_p0w, 0);
#pragma unroll
            for (int s = 0; s < 4; s++) {
                uint32_t r0, r1;
                asm volatile("ldmatrix.sync.aligned.m8n8.x2.trans.shared.b16 {%0,%1}, [%2];"
                             : "=r"(r0), "=r"(r1) : "r"(sbase + SM_MRG + (64 * warp + 16 * s + (lane & 15)) * 16) : "memory");
                const uint32_t a[4] = {r0, r0, r1, r1};
                mma16816(cp, a, sc32[8 * s], sc32[8 * s + 4]);
            }
            if (t == 0) { red[warp * 16 + g] = cp[0]; red[warp * 16 + 8 + g] = cp[1]; }
            if (warp == 0) TSTAMP(14);
            cons_sync();
            if (warp == 0) {
                float s = 0.f;
#pragma unroll
                for (int w = 0; w < 8; w++) s += red[w * 16 + (lane & 15)];
                const float nx = __shfl_down_sync(0xffffffffu, s, 1);
                if (lane < 16 && !(lane & 1))
                    st_ll2(&sc->mod[lane >> 3][cta * 4 + ((lane & 7) >> 1)], pack_bf16(s, nx), tag);
                TSTAMP(1);
            }
            float mean_bf, rstd;
            ln_stats(stat, eb, xpivot, mean_bf, rstd);
#pragma unroll
            for (int i = 0; i < 4; i++) xn[i] = ln_norm(xv[i], mean_bf, rstd);
        }
        {
            uint4 sa, ca;
            for (int it = 0;; it++) {
                sa = ld_ll4((const uint4*)&sc->mod[eb][ec >> 1]);
                ca = ld_ll4((const uint4*)&sc->mod[eb][256 + (ec >> 1)]);
                const bool ok = sa.y == tag && sa.w == tag && ca.y == tag && ca.w == tag;
                if (__all_sync(0xffffffffu, ok) || it > SPIN_LIMIT) break;
            }
            *(uint2*)&hs[eb * 32 + 2 * (lane & 15)] =
                make_uint2(pack_bf16(ln_mod(xn[0], bf_lo(ca.x), bf_lo(sa.x)), ln_mod(xn[1], bf_hi(ca.x), bf_hi(sa.x))),
                           pack_bf16(ln_mod(xn[2], bf_lo(ca.z), bf_lo(sa.z)), ln_mod(xn[3], bf_hi(ca.z), bf_hi(sa.z))));
            __syncwarp();
            uint32_t hb[8];
#pragma unroll
            for (int i = 0; i < 8; i++) hb[i] = hs[bb * 32 + 8 * (i >> 1) + 4 * (i & 1) + t];
            if (warp == 0) TSTAMP(2);
            float cq[2][4] = {};
            const int ts = warp >> 2;
            mbar_wait(bar_full + 8 * ts, 0);
            const uint32_t tb = sbase + SM_RING + ts * TILE;
#pragma unroll
            for (int s = 0; s < 4; s++) {
                const int row = 64 * (warp & 3) + 16 * s + (lane & 7) + (lane >> 4) * 8;
#pragma unroll
                for (int mt = 0; mt < 2; mt++) {
                    const int ch = 2 * mt + ((lane >> 3) & 1);
                    uint32_t a[4];
                    ldsm4t(tb + row * 64 + ((ch ^ ((row >> 1) & 3)) << 4), a);
                    mma16816(cq[mt], a, hb[2 * s], hb[2 * s + 1]);
                }
            }
            if (t < 2) {
                const float v0 = t == 0 ? cq[0][0] : cq[1][0], v1 = t == 0 ? cq[0][1] : cq[1][1];
                const float v2 = t == 0 ? cq[0][2] : cq[1][2], v3 = t == 0 ? cq[0][3] : cq[1][3];
                *(float2*)&red2[warp * 64 + (16 * t + g) * 2] = make_float2(v0, v1);
                *(float2*)&red2[warp * 64 + (16 * t + g + 8) * 2] = make_float2(v2, v3);
            }
            cons_sync();
            if (warp < 4 && lane == 0) { mbar_arrive(bar_empty); mbar_arrive(bar_empty + 8); }
            if (warp == 0) {
                const int b = lane >> 4, cp = lane & 15;
                float q0 = 0.f, q1 = 0.f;
#pragma unroll
                for (int w = 0; w < 8; w++) {
                    const float4 v = *(const float4*)&red2[w * 64 + cp * 4];
                    q0 += b ? v.y : v.x; q1 += b ? v.w : v.z;
                }
                st_ll2(&sc->q[b][cta * 16 + cp], pack_bf16(q0, q1), tag);
                TSTAMP(3);
            }
        }
        const int pair = cta >> 3;
        uint32_t qf[16];
        {
            uint2* qs = (uint2*)(sgen + SM_QS);
            if (tid < 128) {
                const uint4* src = (const uint4*)&sc->q[pair >> 3][(pair & 7) * 256] + tid;
                uint4 v;
                for (int it = 0;; it++) {
                    v = ld_ll4(src);
                    if ((v.y == tag && v.w == tag) || it > SPIN_LIMIT) break;
                }
                qs[tid] = make_uint2(v.x, v.z);
            }
            cons_sync();
            const uint32_t* q32 = (const uint32_t*)(sgen + SM_QS);
#pragma unroll
            for (int s = 0; s < 8; s++) {
                qf[2 * s] = q32[(g & 3) * 64 + 8 * s + t];
                qf[2 * s + 1] = q32[(g & 3) * 64 + 8 * s + 4 + t];
            }
        }
        if (warp == 0) TSTAMP(4);

        float o[8][4];
#pragma unroll
        for (int i = 0; i < 8; i++) { o[i][0] = o[i][1] = o[i][2] = o[i][3] = 0.f; }
        uint32_t mrun = 0xff80ff80u;
        float ls[4] = {0.f, 0.f, 0.f, 0.f};
        uint4 m_sb, m_cb; uint2 m_ga, m_gb0, m_gb1;
        {
            const int grp = warp >> 2, wi = warp & 3;
            const int krow = 16 * wi + (lane & 7) + ((lane >> 3) & 1) * 8;
            const uint32_t koff = krow * 128 + ((((lane >> 4) & 1) ^ (lane & 7)) << 4);
            const int vrow = 16 * wi + (lane & 7) + (lane >> 4) * 8;
            const uint32_t voff = vrow * 128 + ((((lane >> 3) & 1) ^ (lane & 7)) << 4);
            const uint32_t ones[4] = {0x3f803f80u, 0x3f803f80u, 0x3f803f80u, 0x3f803f80u};
            for (int i = grp; i < KV_TILES; i += 2) {
                if (i == MOD_AT + grp) {
                    float cm[4] = {};
                    const uint32_t* sc32 = (const uint32_t*)(sgen + SM_SC) + bb * 256 + 32 * warp + t;
                    mbar_wait(bar_full + 8 * (IDX_MOD % NST), (IDX_MOD / NST) & 1);
                    const uint32_t tb = sbase + SM_RING + (IDX_MOD % NST) * TILE;
#pragma unroll
                    for (int s = 0; s < 4; s++) {
                        const int row = 64 * warp + 16 * s + (lane & 7) + (lane >> 4) * 8;
                        const int ch = (lane >> 3) & 1;
                        uint32_t a[4];
                        ldsm4t(tb + row * 32 + ((ch ^ ((row >> 2) & 1)) << 4), a);
                        mma16816(cm, a, sc32[8 * s], sc32[8 * s + 4]);
                    }
                    if (t == 0) {
                        *(float2*)&red[warp * 64 + g * 2] = make_float2(cm[0], cm[1]);
                        *(float2*)&red[warp * 64 + (g + 8) * 2] = make_float2(cm[2], cm[3]);
                    }
                    cons_sync();
                    if (warp < 4 && lane == 0) mbar_arrive(bar_empty + 8 * (IDX_MOD % NST));
                    if (warp == 1 && lane < 16) {
                        const int b = lane >> 3, cp = lane & 7;
                        float q0 = 0.f, q1 = 0.f;
#pragma unroll
                        for (int w = 0; w < 8; w++) {
                            const float4 v = *(const float4*)&red[w * 64 + cp * 4];
                            q0 += b ? v.y : v.x; q1 += b ? v.w : v.z;
                        }
                        st_ll2(&sc->mod[b][512 + cta * 8 + cp], pack_bf16(q0, q1), tag);
                    }
                }
                if (i == 56 + grp) {
                    m_sb = ld_ll4((const uint4*)&sc->mod[eb][768 + (ec >> 1)]);
                    m_cb = ld_ll4((const uint4*)&sc->mod[eb][1024 + (ec >> 1)]);
                    m_ga = ld_ll2(&sc->mod[eb][512 + (wcol >> 1)]);
                    m_gb0 = ld_ll2(&sc->mod[0][1280 + (ocol >> 1)]); m_gb1 = ld_ll2(&sc->mod[1][1280 + (ocol >> 1)]);
                }
                if (i == 60 + grp) {
                    for (int it = 0;; it++) {
                        const bool ok = m_sb.y == tag && m_sb.w == tag && m_cb.y == tag && m_cb.w == tag &&
                                        m_ga.y == tag && m_gb0.y == tag && m_gb1.y == tag;
                        if (__all_sync(0xffffffffu, ok) || it > SPIN_LIMIT) break;
                        m_sb = ld_ll4((const uint4*)&sc->mod[eb][768 + (ec >> 1)]);
                        m_cb = ld_ll4((const uint4*)&sc->mod[eb][1024 + (ec >> 1)]);
                        m_ga = ld_ll2(&sc->mod[eb][512 + (wcol >> 1)]);
                        m_gb0 = ld_ll2(&sc->mod[0][1280 + (ocol >> 1)]); m_gb1 = ld_ll2(&sc->mod[1][1280 + (ocol >> 1)]);
                    }
                    mbar_wait(bar_clear, 0);
                }
                const int ki = kv_idx(i), ks = ki % NST, vs = (ki + 1) % NST;
                const uint32_t kph = (ki / NST) & 1, vph = ((ki + 1) / NST) & 1;
                mbar_wait(bar_full + 8 * ks, kph);
                const uint32_t kb = sbase + SM_RING + ks * TILE + koff;
                float sa[4] = {0.f, 0.f, 0.f, 0.f}, sb[4] = {0.f, 0.f, 0.f, 0.f};
#pragma unroll
                for (int s = 0; s < 8; s += 2) {
                    uint32_t a0[4], a1[4];
                    ldsm4((kb ^ ((s & 3) << 5)) + (s >> 2) * 8192, a0);
                    ldsm4((kb ^ (((s + 1) & 3) << 5)) + (s >> 2) * 8192, a1);
                    mma16816(sa, a0, qf[2 * s], qf[2 * s + 1]);
                    mma16816(sb, a1, qf[2 * s + 2], qf[2 * s + 3]);
                }
                __syncwarp();
                if (lane == 0) mbar_arrive(bar_empty + 8 * ks);
                uint32_t r01 = pack_bf16(sa[0] + sb[0], sa[1] + sb[1]);
                uint32_t r23 = pack_bf16(sa[2] + sb[2], sa[3] + sb[3]);
                r01 = pack_bf16(bf_lo(r01) * QK_SCALE, bf_hi(r01) * QK_SCALE);
                r23 = pack_bf16(bf_lo(r23) * QK_SCALE, bf_hi(r23) * QK_SCALE);
                uint32_t mx = max_bf16x2(r01, r23);
                mx = max_bf16x2(mx, __shfl_xor_sync(0xffffffffu, mx, 4));
                mx = max_bf16x2(mx, __shfl_xor_sync(0xffffffffu, mx, 8));
                mx = max_bf16x2(mx, __shfl_xor_sync(0xffffffffu, mx, 16));
                const uint32_t mnew = max_bf16x2(mrun, mx);
                const float m0 = bf_lo(mnew), m1 = bf_hi(mnew);
                if (__any_sync(0xffffffffu, mnew != mrun)) {
                    const float al0 = ex2((bf_lo(mrun) - m0) * LOG2E), al1 = ex2((bf_hi(mrun) - m1) * LOG2E);
                    ls[0] *= al0; ls[1] *= al1;
#pragma unroll
                    for (int d = 0; d < 8; d++) { o[d][0] *= al0; o[d][1] *= al1; o[d][2] *= al0; o[d][3] *= al1; }
                    mrun = mnew;
                }
                const float p0 = ex2((bf_lo(r01) - m0) * LOG2E), p1 = ex2((bf_hi(r01) - m1) * LOG2E);
                const float p2 = ex2((bf_lo(r23) - m0) * LOG2E), p3 = ex2((bf_hi(r23) - m1) * LOG2E);
                const uint32_t pb0 = movmatrix_t(pack_bf16(p0, p1)), pb1 = movmatrix_t(pack_bf16(p2, p3));
                mma16816(ls, ones, pb0, pb1);
                mbar_wait(bar_full + 8 * vs, vph);
                const uint32_t vb = sbase + SM_RING + vs * TILE + voff;
#pragma unroll
                for (int d = 0; d < 8; d++) {
                    uint32_t a[4];
                    ldsm4t((vb ^ ((d & 3) << 5)) + (d >> 2) * 8192, a);
                    mma16816(o[d], a, pb0, pb1);
                }
                __syncwarp();
                if (lane == 0) mbar_arrive(bar_empty + 8 * vs);
            }
        }
        if (warp == 7) TSTAMP(5);
        {
            float* mrg = (float*)(sgen + SM_MRG);
            float2* ml = (float2*)(sgen + SM_ML);
            {
                const int hp = (t & 1) * 2, up = t >> 1;
                if (g == 0 && up == 0) { ml[warp * 4 + hp] = make_float2(bf_lo(mrun), ls[0]); ml[warp * 4 + hp + 1] = make_float2(bf_hi(mrun), ls[1]); }
                float* m0p = mrg + (warp * 4 + hp) * 136 + up * 72 + g;
#pragma unroll
                for (int d = 0; d < 4; d++) {
                    m0p[16 * d] = up ? o[d + 4][0] : o[d][0]; m0p[136 + 16 * d] = up ? o[d + 4][1] : o[d][1];
                    m0p[16 * d + 8] = up ? o[d + 4][2] : o[d][2]; m0p[136 + 16 * d + 8] = up ? o[d + 4][3] : o[d][3];
                }
            }
            cons_sync();
            const int hh = tid >> 6, dp = tid & 63;
            float2 mw[8];
            float M = -INFINITY;
#pragma unroll
            for (int w = 0; w < 8; w++) { mw[w] = ml[w * 4 + hh]; M = fmaxf(M, mw[w].x); }
            float L = 0.f, o0 = 0.f, o1 = 0.f;
#pragma unroll
            for (int w = 0; w < 8; w++) {
                const float wt = ex2((mw[w].x - M) * LOG2E);
                const float2 v = *(const float2*)&mrg[(w * 4 + hh) * 136 + 2 * dp + (dp >= 32 ? 8 : 0)];
                L += wt * mw[w].y; o0 += wt * v.x; o1 += wt * v.y;
            }
            st_ll2(&sc->part_o[cta][hh][dp], tagf(o0, F_PART), tagf(o1, F_PART));
            if (dp < 4) st_ll2(&sc->part_ml[cta][hh][dp], tagf(M, F_PART), tagf(L, F_PART));
        }
        if (warp == 0) TSTAMP(6);
        {
            const int hq = cta >> 2, kvh = hq >> 2, hh = hq & 3;
            const int b = tid >> 7, dc = (tid >> 3) & 15, j = tid & 7;
            const int pc = (b * 8 + kvh) * 8 + j;
            const uint4* po = (const uint4*)&sc->part_o[pc][hh][0] + dc * 2;
            const uint2* pm = &sc->part_ml[pc - j][hh][0];
            uint4 vo0, vo1; uint2 vm[8];
            bool oko = false, okm = false;
            for (int it = 0;; it++) {
                if (!oko) { vo0 = ld_ll4(po); vo1 = ld_ll4(po + 1); }
                if (!okm) {
#pragma unroll
                    for (int jj = 0; jj < 8; jj++) vm[jj] = ld_ll2(pm + jj * 16);
                }
                oko = (vo0.x & vo0.y & vo0.z & vo0.w & vo1.x & vo1.y & vo1.z & vo1.w & 3u) == F_PART;
                uint32_t all = vm[0].x & vm[0].y;
#pragma unroll
                for (int jj = 1; jj < 8; jj++) all &= vm[jj].x & vm[jj].y;
                okm = (all & 3u) == F_PART;
                if (__all_sync(0xffffffffu, oko && okm) || it > SPIN_LIMIT) break;
                spin_cycles(A_BACKOFF);
            }
            float M = untag(vm[0].x);
#pragma unroll
            for (int jj = 1; jj < 8; jj++) M = fmaxf(M, untag(vm[jj].x));
            float wt = 0.f, L = 0.f;
#pragma unroll
            for (int jj = 0; jj < 8; jj++) {
                const float w_ = ex2((untag(vm[jj].x) - M) * LOG2E);
                L += w_ * untag(vm[jj].y);
                wt = jj == j ? w_ : wt;
            }
            wt *= rcp_approx(L);
            float v[8] = {wt * untag(vo0.x), wt * untag(vo0.y), wt * untag(vo0.z), wt * untag(vo0.w),
                          wt * untag(vo1.x), wt * untag(vo1.y), wt * untag(vo1.z), wt * untag(vo1.w)};
#define XRED(N, O)                                                                       \
            {                                                                            \
                const bool up = lane & (O);                                              \
                _Pragma("unroll") for (int i = 0; i < (N); i++) {                        \
                    const float send = up ? v[i] : v[i + (N)], keep = up ? v[i + (N)] : v[i]; \
                    v[i] = keep + __shfl_xor_sync(0xffffffffu, send, (O));               \
                }                                                                        \
            }
            XRED(4, 1) XRED(2, 2) XRED(1, 4)
#undef XRED
            __nv_bfloat16* os = (__nv_bfloat16*)(sgen + SM_OS);
            os[b * 128 + dc * 8 + 4 * (j & 1) + 2 * ((j >> 1) & 1) + (j >> 2)] = __float2bfloat16_rn(v[0]);
            if (warp == 0) TSTAMP(15);
            uint32_t wf[8][4];
            const uint32_t aoff_o = (warp >> 2) * 8192 + ((lane & 7) + (lane >> 4) * 8) * 128 +
                                    (((((warp & 3) * 2 + ((lane >> 3) & 1)) ^ (lane & 7))) << 4);
#pragma unroll
            for (int s = 0; s < 2; s++) {
                const int idx = IDX_WO + s;
                mbar_wait(bar_full + 8 * (idx % NST), (idx / NST) & 1);
                const uint32_t tb = sbase + SM_RING + (idx % NST) * TILE + aoff_o;
#pragma unroll
                for (int k4 = 0; k4 < 4; k4++) ldsm4t(tb + k4 * 2048, wf[s * 4 + k4]);
            }
            cons_sync();
            if (warp == 0) TSTAMP(7);
            const uint32_t* os32 = (const uint32_t*)(sgen + SM_OS) + bb * 64 + t;
            float y0[4] = {}, y1[4] = {};
#pragma unroll
            for (int ks = 0; ks < 8; ks += 2) {
                mma16816(y0, wf[ks], os32[8 * ks], os32[8 * ks + 4]);
                mma16816(y1, wf[ks + 1], os32[8 * ks + 8], os32[8 * ks + 12]);
            }
            if (t == 0)
                st_v4(&sc->inbox_wo[(cta & 3) * 8 + warp][hq][g], tagf(y0[0] + y1[0], F_WO), tagf(y0[1] + y1[1], F_WO),
                      tagf(y0[2] + y1[2], F_WO), tagf(y0[3] + y1[3], F_WO));
        }
        const uint32_t t_wo = clock32();
        if (warp == 0) TSTAMP(8);
        if (cta >= NCTA - NOWN) {
            const uint4* pin = &sc->inbox_wo[cta - (NCTA - NOWN)][0][0] + tid;
            uint4 v;
            spin_cycles(DELAY_B1);
            bool ok = false;
            for (int it = 0;; it++) {
                if (!ok) {
                    v = ld_ll4(pin);
                    ok = (v.x & v.y & v.z & v.w & 3u) == F_WO;
                }
                if (__all_sync(0xffffffffu, ok) || it > SPIN_LIMIT) break;
            }
            const bool u1 = lane & 8, u2 = lane & 16;
            const float a0 = untag(v.x), a1 = untag(v.y), a2 = untag(v.z), a3 = untag(v.w);
            const float k0 = (u1 ? a2 : a0) + __shfl_xor_sync(0xffffffffu, u1 ? a0 : a2, 8);
            const float k1 = (u1 ? a3 : a1) + __shfl_xor_sync(0xffffffffu, u1 ? a1 : a3, 8);
            red2[warp * 32 + lane] = (u2 ? k1 : k0) + __shfl_xor_sync(0xffffffffu, u2 ? k0 : k1, 16);
            cons_sync();
            if (warp == 0) {
                float a = 0.f;
#pragma unroll
                for (int w = 0; w < 8; w++) a += red2[w * 32 + lane];
                const float ga = (wcol & 1) ? bf_hi(m_ga.x) : bf_lo(m_ga.x);
                const float xm = bf16r(xo + bf16r(ga * bf16r(a)));
                const float xm_b1 = __shfl_down_sync(0xffffffffu, xm, 16);
                if (lane < 16) st_ll2(&sc->x1[wcol], pack_bf16(xm, xm_b1), F_X1);
                TSTAMP(10);
            }
        }
        const uint32_t aoff = warp * 2048 + ((lane & 7) + (lane >> 4) * 8) * 128 + ((((lane >> 3) & 1) ^ (lane & 7)) << 4);
        if (cta < NFFN) {
            const uint4* px = (const uint4*)&sc->x1[ec];
            const uint4* pp = (const uint4*)&sc->x1[0];
            uint4 va, vb, pa, pb;
            uint32_t gf[4][4], uf[4][4];
            mbar_wait(bar_gu + 8 * (2 * (warp >> 1)), 0);
            mbar_wait(bar_gu + 8 * (2 * (warp >> 1) + 1), 0);
            {
                const uint32_t tg = sbase + SM_RING + (IDX_WG % NST) * TILE, tu = sbase + SM_RING + (IDX_WU % NST) * TILE;
#pragma unroll
                for (int s = 0; s < 4; s++) {
                    const int row = 64 * warp + 16 * s + (lane & 7) + (lane >> 4) * 8;
                    const uint32_t off = row * 32 + ((((lane >> 3) & 1) ^ ((row >> 2) & 1)) << 4);
                    ldsm4t(tg + off, gf[s]);
                    ldsm4t(tu + off, uf[s]);
                }
            }
            const float c1v[4] = {bf16r(1.0f + bf_lo(m_cb.x)), bf16r(1.0f + bf_hi(m_cb.x)), bf16r(1.0f + bf_lo(m_cb.z)), bf16r(1.0f + bf_hi(m_cb.z))};
            float bg = 0.f, cgc = 0.f, bu = 0.f, cuc = 0.f;
            {
                uint32_t* pre = (uint32_t*)(sgen + SM_MRG) + warp * 128;
                float* bc = (float*)(sgen + SM_MRG + 4096);
                *(uint2*)&pre[eb * 32 + 2 * (lane & 15)] = make_uint2(pack_bf16(c1v[0], c1v[1]), pack_bf16(c1v[2], c1v[3]));
                *(uint2*)&pre[64 + eb * 32 + 2 * (lane & 15)] = make_uint2(m_sb.x, m_sb.z);
                __syncwarp();
                float yg[4] = {}, yu[4] = {};
                const uint32_t* pb = pre + ((g >> 1) & 1) * 64 + bb * 32 + t;
#pragma unroll
                for (int s = 0; s < 4; s++) {
                    const uint32_t b0 = pb[8 * s], b1 = pb[8 * s + 4];
                    mma16816(yg, gf[s], b0, b1);
                    mma16816(yu, uf[s], b0, b1);
                }
                const float y0 = t < 2 ? yg[0] : yu[0], y1 = t < 2 ? yg[1] : yu[1], y2 = t < 2 ? yg[2] : yu[2], y3 = t < 2 ? yg[3] : yu[3];
                float* dstp = bc + warp * 128 + (t >> 1) * 64 + (t & 1) * 32;
                *(float2*)&dstp[g * 2] = make_float2(y0, y1);
                *(float2*)&dstp[(g + 8) * 2] = make_float2(y2, y3);
                __syncwarp();
                if (lane == 0) mbar_arrive(bar_bc);
            }
            if (warp == 0) TSTAMP(11);
            float pivot2;
            {
                while (clock32() - t_wo < DELAY_X1) {}
                bool okx = false, okp = false;
                for (int it = 0;; it++) {
                    if (!okx) { va = ld_ll4(px); vb = ld_ll4(px + 1); }
                    if (!okp) { pa = ld_ll4(pp); pb = ld_ll4(pp + 1); }
                    okx = va.y == F_X1 && va.w == F_X1 && vb.y == F_X1 && vb.w == F_X1;
                    okp = pa.y == F_X1 && pa.w == F_X1 && pb.y == F_X1 && pb.w == F_X1;
                    if (__all_sync(0xffffffffu, okx && okp) || it > SPIN_LIMIT) break;
                }
                if (warp == 0) TSTAMP(9);
                const float xv[4] = {eb ? bf_hi(va.x) : bf_lo(va.x), eb ? bf_hi(va.z) : bf_lo(va.z),
                                     eb ? bf_hi(vb.x) : bf_lo(vb.x), eb ? bf_hi(vb.z) : bf_lo(vb.z)};
                const float p0 = 0.25f * ((bf_lo(pa.x) + bf_lo(pa.z)) + (bf_lo(pb.x) + bf_lo(pb.z)));
                const float p1 = 0.25f * ((bf_hi(pa.x) + bf_hi(pa.z)) + (bf_hi(pb.x) + bf_hi(pb.z)));
                const float pivot = eb ? p1 : p0;
                pivot2 = (lane & 1) ? p1 : p0;
                *(uint2*)&hs[eb * 32 + 2 * (lane & 15)] =
                    make_uint2(pack_bf16((xv[0] - pivot) * c1v[0], (xv[1] - pivot) * c1v[1]),
                               pack_bf16((xv[2] - pivot) * c1v[2], (xv[3] - pivot) * c1v[3]));
                __syncwarp();
                float cg[2][4] = {}, cu[2][4] = {};
#pragma unroll
                for (int s = 0; s < 4; s++) {
                    const uint32_t b0 = hs[bb * 32 + 8 * s + t], b1 = hs[bb * 32 + 8 * s + 4 + t];
                    mma16816(cg[s & 1], gf[s], b0, b1);
                    mma16816(cu[s & 1], uf[s], b0, b1);
                }
                const float2 ps = half_warp_sums(xv, pivot);
                if ((lane & 15) == 0) stat[warp * 2 + eb] = ps;
                {
                    const float* bc = (const float*)(sgen + SM_MRG + 4096);
                    mbar_wait(bar_bc, 0);
#pragma unroll
                    for (int w = 0; w < 8; w++) {
                        bg += bc[w * 128 + lane]; cgc += bc[w * 128 + 32 + lane];
                        bu += bc[w * 128 + 64 + lane]; cuc += bc[w * 128 + 96 + lane];
                    }
                }
                if (t < 2) {
                    float v[4];
#pragma unroll
                    for (int i = 0; i < 4; i++) v[i] = t ? cu[0][i] + cu[1][i] : cg[0][i] + cg[1][i];
                    *(float2*)&red[warp * 64 + t * 32 + g * 2] = make_float2(v[0], v[1]);
                    *(float2*)&red[warp * 64 + t * 32 + (g + 8) * 2] = make_float2(v[2], v[3]);
                }
            }
            uint32_t df[4][4];
            mbar_wait(bar_full + 8 * (IDX_WD % NST), (IDX_WD / NST) & 1);
#pragma unroll
            for (int mt = 0; mt < 4; mt++) ldsm4t((sbase + SM_RING + (IDX_WD % NST) * TILE + aoff) ^ (mt << 5), df[mt]);
            cons_sync();
            {
                float gs = 0.f, us = 0.f;
#pragma unroll
                for (int w = 0; w < 8; w++) { gs += red[w * 64 + lane]; us += red[w * 64 + 32 + lane]; }
                float mean_bf, rstd;
                ln_stats(stat, lane & 1, pivot2, mean_bf, rstd);
                const float dm = mean_bf - pivot2;
                gs = bf16r(rstd * (gs - dm * bg) + cgc);
                us = rstd * (us - dm * bu) + cuc;
                const float u2 = gs * (1.0f + 0.044715f * gs * gs) * (2.0f * 0.7978845608028654f * LOG2E);
                const float ge = bf16r(__fdividef(gs, 1.0f + ex2(-u2)));
                const float act = bf16r(ge * bf16r(us));
                const float a0 = __shfl_sync(0xffffffffu, act, 4 * t + bb), a1 = __shfl_sync(0xffffffffu, act, 4 * t + 2 + bb);
                const float a2 = __shfl_sync(0xffffffffu, act, 4 * t + 16 + bb), a3 = __shfl_sync(0xffffffffu, act, 4 * t + 18 + bb);
                const uint32_t b0 = pack_bf16(a0, a1), b1 = pack_bf16(a2, a3);
                float y[4][4] = {};
#pragma unroll
                for (int mt = 0; mt < 4; mt++) mma16816(y[mt], df[mt], b0, b1);
                float v[4];
#pragma unroll
                for (int i = 0; i < 4; i++) v[i] = t == 0 ? y[0][i] : t == 1 ? y[1][i] : t == 2 ? y[2][i] : y[3][i];
            {
                const bool odd = g & 1;
                const float sx = odd ? v[0] : v[2], sy = odd ? v[1] : v[3];
                const float rx = __shfl_xor_sync(0xffffffffu, sx, 4), ry = __shfl_xor_sync(0xffffffffu, sy, 4);
                const int c0 = 64 * warp + 16 * t + (odd ? g + 7 : g);
                const float e0 = odd ? rx : v[0], e1 = odd ? ry : v[1], e2 = odd ? v[2] : rx, e3 = odd ? v[3] : ry;
                st_v4(&sc->inbox_dn[c0 >> 2][cta][(c0 >> 1) & 1], tagf(e0, F_DOWN), tagf(e1, F_DOWN), tagf(e2, F_DOWN), tagf(e3, F_DOWN));
            }
            }
            if (warp == 0) TSTAMP(12);
        }
        {
            uint2 xw;
            float r0;
            {
                const uint4* pin = &sc->inbox_dn[cta][0][0] + tid;
                uint4 v = make_uint4(F_DOWN, F_DOWN, F_DOWN, F_DOWN);
                if (cta < NFFN) spin_cycles(DELAY_C);
                else while (clock32() - t_wo < DELAY_X1 + DELAY_NOFFN) {}
                xw = ld_ll2(&sc->x1[ocol]);
                bool ok = tid >= NFFN * 2;
                for (int it = 0;; it++) {
                    if (!ok) {
                        v = ld_ll4(pin);
                        ok = (v.x & v.y & v.z & v.w & 3u) == F_DOWN;
                    }
                    if (__all_sync(0xffffffffu, ok) || it > SPIN_LIMIT) break;
                }
                const bool u1 = lane & 2, u2 = lane & 4;
                const float a0 = untag(v.x), a1 = untag(v.y), a2 = untag(v.z), a3 = untag(v.w);
                const float k0 = (u1 ? a1 : a0) + __shfl_xor_sync(0xffffffffu, u1 ? a0 : a1, 2);
                const float k1 = (u1 ? a3 : a2) + __shfl_xor_sync(0xffffffffu, u1 ? a2 : a3, 2);
                r0 = (u2 ? k1 : k0) + __shfl_xor_sync(0xffffffffu, u2 ? k0 : k1, 4);
                r0 += __shfl_xor_sync(0xffffffffu, r0, 8);
                r0 += __shfl_xor_sync(0xffffffffu, r0, 16);
                if (lane < 8) red2[256 + warp * 8 + (2 * (lane & 1) + ((lane >> 2) & 1)) * 2 + ((lane >> 1) & 1)] = r0;
            }
            cons_sync();
            if (warp == 0) {
                float a0 = 0.f, a1 = 0.f;
#pragma unroll
                for (int w = 0; w < 8; w++) { const float2 v = *(const float2*)&red2[256 + w * 8 + (lane & 3) * 2]; a0 += v.x; a1 += v.y; }
                const bool hi = ocol & 1;
                const float gb0 = hi ? bf_hi(m_gb0.x) : bf_lo(m_gb0.x), gb1 = hi ? bf_hi(m_gb1.x) : bf_lo(m_gb1.x);
                for (int it = 0; !__all_sync(0xffffffffu, xw.y == F_X1) && it < SPIN_LIMIT; it++) xw = ld_ll2(&sc->x1[ocol]);
                if (lane < 4) {
                    p.out[ocol] = __float2bfloat16_rn(bf_lo(xw.x) + bf16r(gb0 * bf16r(a0)));
                    p.out[D_MODEL + ocol] = __float2bfloat16_rn(bf_hi(xw.x) + bf16r(gb1 * bf16r(a1)));
                }
                TSTAMP(13);
            }
        }
    }
}

typedef CUresult (*EncodeFn)(CUtensorMap*, CUtensorMapDataType, cuuint32_t, void*, const cuuint64_t*, const cuuint64_t*,
                             const cuuint32_t*, const cuuint32_t*, CUtensorMapInterleave, CUtensorMapSwizzle,
                             CUtensorMapL2promotion, CUtensorMapFloatOOBfill);

struct Maps { CUtensorMap k, v, wq, wmod, wmod8, wo, wg, wu, wd; };

void encode(EncodeFn fn, CUtensorMap* m, const void* ptr, int rank, const cuuint64_t* dims, const cuuint64_t* strides,
            const cuuint32_t* box, CUtensorMapSwizzle sw) {
    const cuuint32_t es[3] = {1, 1, 1};
    fn(m, CU_TENSOR_MAP_DATA_TYPE_BFLOAT16, rank, const_cast<void*>(ptr), dims, strides, box, es,
       CU_TENSOR_MAP_INTERLEAVE_NONE, sw, CU_TENSOR_MAP_L2_PROMOTION_L2_256B, CU_TENSOR_MAP_FLOAT_OOB_FILL_NONE);
}

}

extern "C" void kernel_launch(void* const* d_in, const int* in_sizes, int n_in, void* d_out, int out_size) {
    (void)in_sizes; (void)n_in; (void)out_size;
    static EncodeFn enc = nullptr;
    static Scratch* scratch = nullptr;
    if (!enc) {
        cudaGetSymbolAddress((void**)&scratch, g_scratch);
        void* fn = nullptr;
        cudaDriverEntryPointQueryResult qr;
        cudaGetDriverEntryPoint("cuTensorMapEncodeTiled", &fn, cudaEnableDefault, &qr);
        enc = (EncodeFn)fn;
        cudaFuncSetAttribute(fused_block_kernel, cudaFuncAttributeMaxDynamicSharedMemorySize, SMEM_BYTES);
    }
    Maps m;
    {
        const cuuint64_t dims[3] = {64, (cuuint64_t)16 * SK, 2}, str[2] = {256, 128};
        const cuuint32_t box[3] = {64, 64, 2};
        encode(enc, &m.k, d_in[1], 3, dims, str, box, CU_TENSOR_MAP_SWIZZLE_128B);
        encode(enc, &m.v, d_in[2], 3, dims, str, box, CU_TENSOR_MAP_SWIZZLE_128B);
    }
    {
        const cuuint64_t dims[2] = {4096, 512}, str[1] = {8192};
        const cuuint32_t box[2] = {32, 256};
        encode(enc, &m.wq, d_in[3], 2, dims, str, box, CU_TENSOR_MAP_SWIZZLE_64B);
    }
    {
        const cuuint64_t dims[2] = {N_MOD, 512}, str[1] = {N_MOD * 2};
        const cuuint32_t box[2] = {16, 256};
        encode(enc, &m.wmod, d_in[10], 2, dims, str, box, CU_TENSOR_MAP_SWIZZLE_32B);
        const cuuint32_t box8[2] = {8, 256};
        encode(enc, &m.wmod8, d_in[10], 2, dims, str, box8, CU_TENSOR_MAP_SWIZZLE_NONE);
    }
    {
        const cuuint64_t dims_o[3] = {64, 4096, 8}, dims_d[3] = {64, D_FF, 8}, str[2] = {1024, 128};
        const cuuint32_t box[3] = {64, 16, 8}, box_o[3] = {64, 64, 2};
        encode(enc, &m.wo, d_in[4], 3, dims_o, str, box_o, CU_TENSOR_MAP_SWIZZLE_128B);
        encode(enc, &m.wd, d_in[8], 3, dims_d, str, box, CU_TENSOR_MAP_SWIZZLE_128B);
    }
    {
        const cuuint64_t dims[2] = {D_FF, 512}, str[1] = {D_FF * 2};
        const cuuint32_t box[2] = {16, 128};
        encode(enc, &m.wg, d_in[6], 2, dims, str, box, CU_TENSOR_MAP_SWIZZLE_32B);
        encode(enc, &m.wu, d_in[7], 2, dims, str, box, CU_TENSOR_MAP_SWIZZLE_32B);
    }
    Params p;
    p.x = (const __nv_bfloat16*)d_in[0];
    p.c = (const __nv_bfloat16*)d_in[9];
    p.out = (__nv_bfloat16*)d_out;
    p.sc = scratch;
    fused_block_kernel<<<NCTA, NTHREADS, SMEM_BYTES, cudaStreamPerThread>>>(p, m.k, m.v, m.wq, m.wmod, m.wmod8, m.wo, m.wg, m.wu, m.wd);
}
```

```cpp
#include <cuda_runtime.h>
#include <cuda.h>
#include <cuda_bf16.h>
#include <stdint.h>

namespace {

constexpr int D_MODEL = 512;
constexpr int N_HEADS = 32;
constexpr int SK = 32768;
constexpr int DH = 128;
constexpr int D_FF = 1792;
constexpr int N_MOD = 6 * D_MODEL;

constexpr int NCTA = 128;
constexpr int NFFN = D_FF / 16;
constexpr int NOWN = 32;
constexpr int NTHREADS = 320;
constexpr int NST = 12;
constexpr int TILE = 16384;
#define WINDOW 3
#define WINDOW_TAIL 1
#define WINDOW_TAIL2 1
#define GU_WIN 3
#define PACE_THR 96
constexpr int KV_TILES = 64;
#define MOD_AT 8
static_assert(MOD_AT % 2 == 0 && MOD_AT >= 2 && MOD_AT < 56, "schedule");
__host__ __device__ constexpr int kv_idx(int i) { return 2 + 2 * i + (i >= MOD_AT ? 1 : 0); }
constexpr int IDX_MOD = 2 + 2 * MOD_AT;
constexpr int N_STREAM = kv_idx(KV_TILES - 1) + 2;
constexpr int IDX_WO = N_STREAM;
constexpr int IDX_WG = IDX_WO + 2;
constexpr int IDX_WU = IDX_WG + 1;
constexpr int IDX_WD = IDX_WU + 1;
constexpr int SPIN_LIMIT = 1 << 20;

constexpr float LOG2E = 1.4426950408889634f;
constexpr float QK_SCALE = 0.08838834764831845f;

constexpr int SM_RING = 0;
constexpr int SM_MRG = SM_RING + NST * TILE;
constexpr int SM_ML = SM_MRG + 8 * 4 * 136 * 4;
constexpr int SM_RED = SM_ML + 8 * 4 * 8;
constexpr int SM_RED2 = SM_RED + 8 * 64 * 4;
constexpr int SM_QS = SM_RED2 + 8 * 64 * 4;
constexpr int SM_OS = SM_QS + 512 * 2;
constexpr int SM_SC = SM_OS + 2 * 128 * 2;
constexpr int SM_HS = SM_SC + 2 * 512 * 2;
constexpr int SM_STAT = SM_HS + 8 * 2 * 32 * 4;
constexpr int SM_PACE = SM_STAT + 8 * 2 * 8;
constexpr int SM_BAR = SM_PACE + 8;
constexpr int SM_END = SM_BAR + (2 * NST + 1 + 8 + 2) * 8;
constexpr int SMEM_BYTES = SM_END + 1024;

struct Scratch {
    uint4 inbox_wo[NOWN][N_HEADS][8];
    uint4 inbox_dn[NCTA][NFFN][2];
    uint2 x1[D_MODEL];
    uint2 part_o[NCTA][4][64];
    uint2 part_ml[NCTA][4][4];
    uint2 mod[2][N_MOD / 2];
    uint2 q[2][N_HEADS * DH / 2];
    unsigned epoch;
    unsigned pad_[31];
    unsigned cleared;
    unsigned pad2_[31];
    unsigned progress;
};
__device__ Scratch g_scratch;
constexpr uint32_t F_PART = 1, F_WO = 1, F_DOWN = 1, F_X1 = 1;
__device__ __forceinline__ uint32_t tagf(float v, uint32_t f) { return (__float_as_uint(v) & ~3u) | f; }
__device__ __forceinline__ float untag(uint32_t v) { return __uint_as_float(v & ~3u); }

struct Params {
    const __nv_bfloat16* x;
    const __nv_bfloat16* c;
    __nv_bfloat16* out;
    Scratch* sc;
};

#define TSTAMP(i) do { } while (0)

__device__ __forceinline__ uint32_t smem_u32(const void* p) { return (uint32_t)__cvta_generic_to_shared(p); }

__device__ __forceinline__ void mbar_init(uint32_t bar, uint32_t cnt) {
    asm volatile("mbarrier.init.shared::cta.b64 [%0], %1;" ::"r"(bar), "r"(cnt) : "memory");
}
__device__ __forceinline__ void mbar_expect_tx(uint32_t bar, uint32_t bytes) {
    asm volatile("mbarrier.arrive.expect_tx.shared::cta.b64 _, [%0], %1;" ::"r"(bar), "r"(bytes) : "memory");
}
__device__ __forceinline__ void mbar_arrive(uint32_t bar) {
    asm volatile("mbarrier.arrive.shared::cta.b64 _, [%0];" ::"r"(bar) : "memory");
}
__device__ __forceinline__ bool mbar_try(uint32_t bar, uint32_t parity) {
    uint32_t ok;
    asm volatile(
        "{\n\t.reg .pred p;\n\t"
        "mbarrier.try_wait.parity.shared::cta.b64 p, [%1], %2;\n\t"
        "selp.u32 %0, 1, 0, p;\n\t}"
        : "=r"(ok) : "r"(bar), "r"(parity) : "memory");
    return ok != 0;
}
__device__ __forceinline__ void mbar_wait(uint32_t bar, uint32_t parity) {
    if (mbar_try(bar, parity)) return;
    const long long t0 = clock64();
    while (!mbar_try(bar, parity))
        if (clock64() - t0 > (1ll << 31)) return;
}
__device__ __forceinline__ void cons_sync() { asm volatile("bar.sync 1, 256;" ::: "memory"); }

__device__ __forceinline__ void tma_2d(uint32_t dst, const CUtensorMap* m, int c0, int c1, uint32_t bar) {
    asm volatile("cp.async.bulk.tensor.2d.shared::cluster.global.mbarrier::complete_tx::bytes [%0], [%1, {%3, %4}], [%2];"
                 ::"r"(dst), "l"(m), "r"(bar), "r"(c0), "r"(c1) : "memory");
}
__device__ __forceinline__ void tma_3d(uint32_t dst, const CUtensorMap* m, int c0, int c1, int c2, uint32_t bar) {
    asm volatile("cp.async.bulk.tensor.3d.shared::cluster.global.mbarrier::complete_tx::bytes [%0], [%1, {%3, %4, %5}], [%2];"
                 ::"r"(dst), "l"(m), "r"(bar), "r"(c0), "r"(c1), "r"(c2) : "memory");
}
__device__ __forceinline__ void tma_3d_hint(uint32_t dst, const CUtensorMap* m, int c0, int c1, int c2, uint32_t bar, uint64_t pol) {
    asm volatile("cp.async.bulk.tensor.3d.shared::cluster.global.mbarrier::complete_tx::bytes.L2::cache_hint [%0], [%1, {%3, %4, %5}], [%2], %6;"
                 ::"r"(dst), "l"(m), "r"(bar), "r"(c0), "r"(c1), "r"(c2), "l"(pol) : "memory");
}
__device__ __forceinline__ void prefetch_tmap(const CUtensorMap* m) {
    asm volatile("prefetch.tensormap [%0];" ::"l"(m) : "memory");
}

__device__ __forceinline__ void ldsm4(uint32_t addr, uint32_t (&r)[4]) {
    asm volatile("ldmatrix.sync.aligned.m8n8.x4.shared.b16 {%0,%1,%2,%3}, [%4];"
                 : "=r"(r[0]), "=r"(r[1]), "=r"(r[2]), "=r"(r[3]) : "r"(addr) : "memory");
}
__device__ __forceinline__ void ldsm4t(uint32_t addr, uint32_t (&r)[4]) {
    asm volatile("ldmatrix.sync.aligned.m8n8.x4.trans.shared.b16 {%0,%1,%2,%3}, [%4];"
                 : "=r"(r[0]), "=r"(r[1]), "=r"(r[2]), "=r"(r[3]) : "r"(addr) : "memory");
}
__device__ __forceinline__ void mma16816(float (&c)[4], const uint32_t (&a)[4], uint32_t b0, uint32_t b1) {
    asm volatile("mma.sync.aligned.m16n8k16.row.col.f32.bf16.bf16.f32 {%0,%1,%2,%3}, {%4,%5,%6,%7}, {%8,%9}, {%0,%1,%2,%3};"
                 : "+f"(c[0]), "+f"(c[1]), "+f"(c[2]), "+f"(c[3])
                 : "r"(a[0]), "r"(a[1]), "r"(a[2]), "r"(a[3]), "r"(b0), "r"(b1));
}
__device__ __forceinline__ uint32_t movmatrix_t(uint32_t a) {
    uint32_t d;
    asm volatile("movmatrix.sync.aligned.m8n8.trans.b16 %0, %1;" : "=r"(d) : "r"(a));
    return d;
}
__device__ __forceinline__ uint32_t pack_bf16(float a, float b) {
    uint32_t r;
    asm("cvt.rn.bf16x2.f32 %0, %1, %2;" : "=r"(r) : "f"(b), "f"(a));
    return r;
}
__device__ __forceinline__ float bf_lo(uint32_t v) { return __uint_as_float(v << 16); }
__device__ __forceinline__ float bf_hi(uint32_t v) { return __uint_as_float(v & 0xffff0000u); }
__device__ __forceinline__ float bf16r(float a) { return bf_lo(pack_bf16(a, 0.f)); }
__device__ __forceinline__ uint32_t max_bf16x2(uint32_t a, uint32_t b) {
    uint32_t r;
    asm("max.bf16x2 %0, %1, %2;" : "=r"(r) : "r"(a), "r"(b));
    return r;
}
__device__ __forceinline__ float ex2(float x) {
    float r;
    asm("ex2.approx.ftz.f32 %0, %1;" : "=f"(r) : "f"(x));
    return r;
}

__device__ __forceinline__ void st_ll2(uint2* p, uint32_t v, uint32_t tag) {
    asm volatile("st.relaxed.gpu.global.v2.u32 [%0], {%1, %2};" ::"l"(p), "r"(v), "r"(tag) : "memory");
}
__device__ __forceinline__ void st_ll4(uint4* p, uint32_t v0, uint32_t v1, uint32_t tag) {
    asm volatile("st.relaxed.gpu.global.v4.u32 [%0], {%1, %2, %3, %2};" ::"l"(p), "r"(v0), "r"(tag), "r"(v1) : "memory");
}
__device__ __forceinline__ void st_v4(uint4* p, uint32_t a, uint32_t b, uint32_t c, uint32_t d) {
    asm volatile("st.relaxed.gpu.global.v4.u32 [%0], {%1, %2, %3, %4};" ::"l"(p), "r"(a), "r"(b), "r"(c), "r"(d) : "memory");
}
__device__ __forceinline__ uint2 ld_ll2(const uint2* p) {
    uint2 v;
    asm volatile("ld.relaxed.gpu.global.v2.u32 {%0, %1}, [%2];" : "=r"(v.x), "=r"(v.y) : "l"(p) : "memory");
    return v;
}
__device__ __forceinline__ uint4 ld_ll4(const uint4* p) {
    uint4 v;
    asm volatile("ld.relaxed.gpu.global.v4.u32 {%0, %1, %2, %3}, [%4];"
                 : "=r"(v.x), "=r"(v.y), "=r"(v.z), "=r"(v.w) : "l"(p) : "memory");
    return v;
}

#define DELAY_B1 300
#define DELAY_X1 2000
#define DELAY_NOFFN 1500
#define DELAY_C 600
__device__ __forceinline__ uint32_t clock32() {
    uint32_t c;
    asm volatile("mov.u32 %0, %clock;" : "=r"(c));
    return c;
}
__device__ __forceinline__ void spin_cycles(uint32_t n) {
    if (n > 0) { const uint32_t c0 = clock32(); while (clock32() - c0 < n) {} }
}
__device__ __forceinline__ float rcp_approx(float x) {
    float r;
    asm("rcp.approx.ftz.f32 %0, %1;" : "=f"(r) : "f"(x));
    return r;
}
__device__ __forceinline__ float sqrt_approx(float x) {
    float r;
    asm("sqrt.approx.f32 %0, %1;" : "=f"(r) : "f"(x));
    return r;
}

__device__ __forceinline__ float silu_bf(float v) { return bf16r(v / (1.0f + expf(-v))); }

__device__ __forceinline__ float2 half_warp_sums(const float (&v)[4], float pivot) {
    float s1 = 0.f, s2 = 0.f;
#pragma unroll
    for (int i = 0; i < 4; i++) { const float d = v[i] - pivot; s1 += d; s2 += d * d; }
#pragma unroll
    for (int o = 1; o < 16; o <<= 1) { s1 += __shfl_xor_sync(0xffffffffu, s1, o); s2 += __shfl_xor_sync(0xffffffffu, s2, o); }
    return make_float2(s1, s2);
}
__device__ __forceinline__ void ln_stats(const float2* stat, int b, float pivot, float& mean_bf, float& rstd) {
    float s1 = 0.f, s2 = 0.f;
#pragma unroll
    for (int w = 0; w < 8; w++) { const float2 v = stat[w * 2 + b]; s1 += v.x; s2 += v.y; }
    const float dm = s1 * (1.0f / D_MODEL);
    const float var = fmaxf(s2 * (1.0f / D_MODEL) - dm * dm, 0.f);
    mean_bf = bf16r(pivot + dm);
    rstd = rcp_approx(bf16r(sqrt_approx(bf16r(bf16r(var) + 1e-5f))));
}
__device__ __forceinline__ float ln_norm(float xv, float mean_bf, float rstd) { return bf16r(bf16r(xv - mean_bf) * rstd); }
__device__ __forceinline__ float ln_mod(float n, float cmul, float sadd) { return bf16r(n * bf16r(1.0f + cmul)) + sadd; }

__global__ void __launch_bounds__(NTHREADS, 1)
fused_block_kernel(const Params p, const __grid_constant__ CUtensorMap tm_k, const __grid_constant__ CUtensorMap tm_v,
                   const __grid_constant__ CUtensorMap tm_wq, const __grid_constant__ CUtensorMap tm_wmod,
                   const __grid_constant__ CUtensorMap tm_wmod8,
                   const __grid_constant__ CUtensorMap tm_wo, const __grid_constant__ CUtensorMap tm_wg,
                   const __grid_constant__ CUtensorMap tm_wu, const __grid_constant__ CUtensorMap tm_wd) {
    extern __shared__ unsigned char smem_raw[];
    const uint32_t sbase = (smem_u32(smem_raw) + 1023u) & ~1023u;
    unsigned char* sgen = smem_raw + (sbase - smem_u32(smem_raw));
    const int tid = threadIdx.x, warp = tid >> 5, lane = tid & 31;
    const int cta = blockIdx.x;
    const uint32_t bar_full = sbase + SM_BAR, bar_empty = bar_full + NST * 8;
    const uint32_t bar_clear = bar_empty + NST * 8;
    const uint32_t bar_gu = bar_clear + 8;
    const uint32_t bar_bc = bar_gu + 8 * 8;
    const uint32_t bar_p0w = bar_bc + 8;

    const int key0 = (cta >> 3) * SK + (cta & 7) * 64;
    uint64_t pol = 0;
    if (tid == 256) {
        asm volatile("createpolicy.fractional.L2::evict_first.b64 %0, 1.0;" : "=l"(pol));
        mbar_init(bar_p0w, 1);
#pragma unroll
        for (int i = 0; i < 4; i++) mbar_init(bar_full + 8 * i, 1);
        asm volatile("fence.mbarrier_init.release.cluster;" ::: "memory");
        mbar_expect_tx(bar_p0w, 8192);
        tma_2d(sbase + SM_MRG, &tm_wmod8, cta * 8, 0, bar_p0w);
        tma_2d(sbase + SM_MRG + 4096, &tm_wmod8, cta * 8, 256, bar_p0w);
#pragma unroll
        for (int i = 0; i < 4; i++) mbar_expect_tx(bar_full + 8 * i, TILE);
        tma_2d(sbase + SM_RING, &tm_wq, cta * 32, 0, bar_full);
        tma_2d(sbase + SM_RING + TILE, &tm_wq, cta * 32, 256, bar_full + 8);
        tma_3d_hint(sbase + SM_RING + 2 * TILE, &tm_k, 0, key0, 0, bar_full + 16, pol);
        tma_3d_hint(sbase + SM_RING + 3 * TILE, &tm_v, 0, key0, 0, bar_full + 24, pol);
    }

    if (warp == 8) {
        if (lane == 0) {
            for (int i = 0; i < NST; i++) { if (i >= 4) mbar_init(bar_full + 8 * i, 1); mbar_init(bar_empty + 8 * i, 4); }
            mbar_init(bar_clear, 1);
            for (int k = 0; k < 8; k++) mbar_init(bar_gu + 8 * k, 1);
            mbar_init(bar_bc, 8);
            ((volatile uint32_t*)(sgen + SM_PACE))[0] = 0;
            ((volatile uint32_t*)(sgen + SM_PACE))[1] = WINDOW;
            asm volatile("fence.mbarrier_init.release.cluster;" ::: "memory");
        }
        __syncwarp();
        asm volatile("bar.arrive 2, 320;" ::: "memory");
        asm volatile("bar.arrive 3, 64;" ::: "memory");
        if (lane == 0) {
            int slot = 4; uint32_t ph = 1;
            int landed = 0, wslot = 0; uint32_t wph = 0;
            int kv = 2;
            auto wait_window = [&](int idx, int window) {
                while (landed + window <= idx) {
                    mbar_wait(bar_full + 8 * wslot, wph);
                    if (++wslot == NST) { wslot = 0; wph ^= 1; }
                    landed++;
                }
            };
            volatile uint32_t* pace = (volatile uint32_t*)(sgen + SM_PACE);
            prefetch_tmap(&tm_wmod);
            pace[0] = 4;
            for (int idx = 4; idx < N_STREAM; idx++) {
                if (idx >= NST) mbar_wait(bar_empty + 8 * slot, ph);
                wait_window(idx, (int)pace[1]);
                if (idx == 12) { prefetch_tmap(&tm_wo); prefetch_tmap(&tm_wg); prefetch_tmap(&tm_wu); prefetch_tmap(&tm_wd); }
                const uint32_t fb = bar_full + 8 * slot, dst = sbase + SM_RING + slot * TILE;
                mbar_expect_tx(fb, TILE);
                if (idx == IDX_MOD) {
                    tma_2d(dst, &tm_wmod, 1024 + cta * 16, 0, fb);
                    tma_2d(dst + 8192, &tm_wmod, 1024 + cta * 16, 256, fb);
                } else {
                    tma_3d_hint(dst, (kv & 1) ? &tm_v : &tm_k, 0, key0 + (kv >> 1) * 512, 0, fb, pol);
                    kv++;
                }
                pace[0] = idx + 1;
                if (++slot == NST) { slot = 0; ph ^= 1; }
            }
            auto slot_free = [&](int idx) { mbar_wait(bar_empty + 8 * (idx % NST), ((idx / NST) & 1) ^ 1); };
#pragma unroll
            for (int s = 0; s < 2; s++) {
                const int idx = IDX_WO + s;
                slot_free(idx);
                wait_window(idx, s == 0 ? WINDOW_TAIL : WINDOW_TAIL2);
                mbar_expect_tx(bar_full + 8 * (idx % NST), TILE);
                tma_3d(sbase + SM_RING + (idx % NST) * TILE, &tm_wo, 0, (cta >> 2) * 128 + s * 64, (cta & 3) * 2, bar_full + 8 * (idx % NST));
            }
            if (cta < NFFN) {
                slot_free(IDX_WG); slot_free(IDX_WU);
                mbar_wait(bar_full + 8 * (IDX_WO % NST), (IDX_WO / NST) & 1);
                mbar_wait(bar_full + 8 * ((IDX_WO + 1) % NST), ((IDX_WO + 1) / NST) & 1);
#pragma unroll
                for (int st = 0; st < 8; st++) {
                    if (st >= GU_WIN) mbar_wait(bar_gu + 8 * (st - GU_WIN), 0);
                    mbar_expect_tx(bar_gu + 8 * st, 4096);
                    tma_2d(sbase + SM_RING + (((st & 1) ? IDX_WU : IDX_WG) % NST) * TILE + (st >> 1) * 4096,
                           (st & 1) ? &tm_wu : &tm_wg, cta * 16, (st >> 1) * 128, bar_gu + 8 * st);
                }
                mbar_wait(bar_gu + 8 * 6, 0);
                slot_free(IDX_WD);
                mbar_expect_tx(bar_full + 8 * (IDX_WD % NST), TILE);
                tma_3d(sbase + SM_RING + (IDX_WD % NST) * TILE, &tm_wd, 0, cta * 16, 0, bar_full + 8 * (IDX_WD % NST));
            }
        }
    } else if (warp == 9) {
        Scratch* const sc = p.sc;
        const uint32_t tag = *(volatile unsigned*)&sc->epoch + 1;
        if (lane < 2) {
            st_ll4((uint4*)&sc->mod[lane][cta * 4], 0u, 0u, 0u);
            st_ll4((uint4*)&sc->mod[lane][cta * 4] + 1, 0u, 0u, 0u);
        }
        if (lane < 8) st_ll4((uint4*)&sc->mod[lane >> 2][512 + cta * 8] + (lane & 3), 0u, 0u, 0u);
        if (lane < 16) st_ll4((uint4*)&sc->q[lane >> 3][cta * 16] + (lane & 7), 0u, 0u, 0u);
        __syncwarp();
        asm volatile("bar.arrive 2, 320;" ::: "memory");
        asm volatile("bar.sync 3, 64;" ::: "memory");
#pragma unroll 4
        for (int i = 0; i < NFFN * 2 / 32; i++) st_v4(&sc->inbox_dn[cta][0][0] + i * 32 + lane, 0u, 0u, 0u, 0u);
        if (cta >= NCTA - NOWN) {
#pragma unroll 4
            for (int i = 0; i < 8; i++) st_v4(&sc->inbox_wo[cta - (NCTA - NOWN)][0][0] + i * 32 + lane, 0u, 0u, 0u, 0u);
            if (lane < 8) st_v4((uint4*)&sc->x1[(cta - (NCTA - NOWN)) * 16] + lane, 0u, 0u, 0u, 0u);
        }
#pragma unroll 4
        for (int i = 0; i < 4; i++) st_v4((uint4*)&sc->part_o[cta][0][0] + i * 32 + lane, 0u, 0u, 0u, 0u);
        if (lane < 8) st_v4((uint4*)&sc->part_ml[cta][0][0] + lane, 0u, 0u, 0u, 0u);
        if (cta == 0 && lane == 0) asm volatile("st.relaxed.gpu.global.u32 [%0], %1;" ::"l"(&sc->progress), "r"(0u) : "memory");
        asm volatile("fence.acq_rel.gpu;" ::: "memory");
        __syncwarp();
        if (lane == 0) {
            asm volatile("fence.acq_rel.gpu;" ::: "memory");
            asm volatile("red.relaxed.gpu.global.add.u32 [%0], %1;" ::"l"(&sc->cleared), "r"(1u) : "memory");
            const uint32_t target = tag * NCTA;
            for (int it = 0; it < SPIN_LIMIT; it++) {
                uint32_t v;
                asm volatile("ld.relaxed.gpu.global.u32 %0, [%1];" : "=r"(v) : "l"(&sc->cleared) : "memory");
                if ((int32_t)(v - target) >= 0) break;
                __nanosleep(500);
            }
            asm volatile("fence.acq_rel.gpu;" ::: "memory");
            mbar_arrive(bar_clear);
            volatile uint32_t* pace = (volatile uint32_t*)(sgen + SM_PACE);
            uint32_t posted = 0;
            for (int it = 0; it < SPIN_LIMIT; it++) {
                const uint32_t own = pace[0];
                if (own >= N_STREAM) break;
                if (own > posted) {
                    asm volatile("red.relaxed.gpu.global.add.u32 [%0], %1;" ::"l"(&sc->progress), "r"(own - posted) : "memory");
                    posted = own;
                }
                uint32_t v;
                asm volatile("ld.relaxed.gpu.global.u32 %0, [%1];" : "=r"(v) : "l"(&sc->progress) : "memory");
                const int diff = (int)v - (int)own * NCTA;
                pace[1] = diff > PACE_THR ? WINDOW + 1 : diff < -PACE_THR ? WINDOW - 1 : WINDOW;
                __nanosleep(200);
            }
            if (cta == 0) asm volatile("st.relaxed.gpu.global.u32 [%0], %1;" ::"l"(&sc->epoch), "r"(tag) : "memory");
        }
    } else {
        const int g = lane >> 2, t = lane & 3;
        const int bb = g & 1;
        const int eb = lane >> 4;
        const int ec = 64 * warp + 4 * (lane & 15);
        if (warp == 0) TSTAMP(0);
        Scratch* const sc = p.sc;
        const float c00 = __bfloat162float(p.c[tid]), c01 = __bfloat162float(p.c[tid + 256]);
        const float c10 = __bfloat162float(p.c[D_MODEL + tid]), c11 = __bfloat162float(p.c[D_MODEL + tid + 256]);
        const uint2 xe = __ldg((const uint2*)(p.x + eb * D_MODEL + ec));
        const float xpivot = __bfloat162float(p.x[eb * D_MODEL]);
        const uint32_t tag = *(volatile unsigned*)&sc->epoch + 1;
        const int ocol = cta * 4 + (lane & 3);
        const int wcol = (cta >= NCTA - NOWN ? cta - (NCTA - NOWN) : 0) * 16 + (lane & 15);
        const float xo = __bfloat162float(p.x[eb * D_MODEL + wcol]);

        float* red = (float*)(sgen + SM_RED);
        float* red2 = (float*)(sgen + SM_RED2);
        float2* stat = (float2*)(sgen + SM_STAT);
        uint32_t* hs = (uint32_t*)(sgen + SM_HS) + warp * 64;
        float xn[4];
        {
            float xv[4] = {bf_lo(xe.x), bf_hi(xe.x), bf_lo(xe.y), bf_hi(xe.y)};
            const float2 ps = half_warp_sums(xv, xpivot);
            if ((lane & 15) == 0) stat[warp * 2 + eb] = ps;
            const float s00 = silu_bf(c00), s01 = silu_bf(c01), s10 = silu_bf(c10), s11 = silu_bf(c11);
            __nv_bfloat16* scs = (__nv_bfloat16*)(sgen + SM_SC);
            scs[tid] = __float2bfloat16_rn(s00); scs[tid + 256] = __float2bfloat16_rn(s01);
            scs[512 + tid] = __float2bfloat16_rn(s10); scs[512 + tid + 256] = __float2bfloat16_rn(s11);
            asm volatile("bar.sync 2, 320;" ::: "memory");
            if (warp == 0) TSTAMP(23);
            float cp[4] = {0.f, 0.f, 0.f, 0.f};
            const uint32_t* sc32 = (const uint32_t*)(sgen + SM_SC) + bb * 256 + 32 * warp + t;
            mbar_wait(bar_p0w, 0);
#pragma unroll
            for (int s = 0; s < 4; s++) {
                uint32_t r0, r1;
                asm volatile("ldmatrix.sync.aligned.m8n8.x2.trans.shared.b16 {%0,%1}, [%2];"
                             : "=r"(r0), "=r"(r1) : "r"(sbase + SM_MRG + (64 * warp + 16 * s + (lane & 15)) * 16) : "memory");
                const uint32_t a[4] = {r0, r0, r1, r1};
                mma16816(cp, a, sc32[8 * s], sc32[8 * s + 4]);
            }
            if (t == 0) { red[warp * 16 + g] = cp[0]; red[warp * 16 + 8 + g] = cp[1]; }
            if (warp == 0) TSTAMP(14);
            cons_sync();
            if (warp == 0) {
                float s = 0.f;
#pragma unroll
                for (int w = 0; w < 8; w++) s += red[w * 16 + (lane & 15)];
                const float nx = __shfl_down_sync(0xffffffffu, s, 1);
                if (lane < 16 && !(lane & 1))
                    st_ll2(&sc->mod[lane >> 3][cta * 4 + ((lane & 7) >> 1)], pack_bf16(s, nx), tag);
                TSTAMP(1);
            }
            float mean_bf, rstd;
            ln_stats(stat, eb, xpivot, mean_bf, rstd);
#pragma unroll
            for (int i = 0; i < 4; i++) xn[i] = ln_norm(xv[i], mean_bf, rstd);
        }
        {
            uint4 sa, ca;
            for (int it = 0;; it++) {
                sa = ld_ll4((const uint4*)&sc->mod[eb][ec >> 1]);
                ca = ld_ll4((const uint4*)&sc->mod[eb][256 + (ec >> 1)]);
                const bool ok = sa.y == tag && sa.w == tag && ca.y == tag && ca.w == tag;
                if (__all_sync(0xffffffffu, ok) || it > SPIN_LIMIT) break;
            }
            *(uint2*)&hs[eb * 32 + 2 * (lane & 15)] =
                make_uint2(pack_bf16(ln_mod(xn[0], bf_lo(ca.x), bf_lo(sa.x)), ln_mod(xn[1], bf_hi(ca.x), bf_hi(sa.x))),
                           pack_bf16(ln_mod(xn[2], bf_lo(ca.z), bf_lo(sa.z)), ln_mod(xn[3], bf_hi(ca.z), bf_hi(sa.z))));
            __syncwarp();
            uint32_t hb[8];
#pragma unroll
            for (int i = 0; i < 8; i++) hb[i] = hs[bb * 32 + 8 * (i >> 1) + 4 * (i & 1) + t];
            if (warp == 0) TSTAMP(2);
            float cq[2][4] = {};
            const int ts = warp >> 2;
            mbar_wait(bar_full + 8 * ts, 0);
            const uint32_t tb = sbase + SM_RING + ts * TILE;
#pragma unroll
            for (int s = 0; s < 4; s++) {
                const int row = 64 * (warp & 3) + 16 * s + (lane & 7) + (lane >> 4) * 8;
#pragma unroll
                for (int mt = 0; mt < 2; mt++) {
                    const int ch = 2 * mt + ((lane >> 3) & 1);
                    uint32_t a[4];
                    ldsm4t(tb + row * 64 + ((ch ^ ((row >> 1) & 3)) << 4), a);
                    mma16816(cq[mt], a, hb[2 * s], hb[2 * s + 1]);
                }
            }
            if (t < 2) {
                const float v0 = t == 0 ? cq[0][0] : cq[1][0], v1 = t == 0 ? cq[0][1] : cq[1][1];
                const float v2 = t == 0 ? cq[0][2] : cq[1][2], v3 = t == 0 ? cq[0][3] : cq[1][3];
                *(float2*)&red2[warp * 64 + (16 * t + g) * 2] = make_float2(v0, v1);
                *(float2*)&red2[warp * 64 + (16 * t + g + 8) * 2] = make_float2(v2, v3);
            }
            cons_sync();
            if (warp < 4 && lane == 0) { mbar_arrive(bar_empty); mbar_arrive(bar_empty + 8); }
            if (warp == 0) {
                const int b = lane >> 4, cp = lane & 15;
                float q0 = 0.f, q1 = 0.f;
#pragma unroll
                for (int w = 0; w < 8; w++) {
                    const float4 v = *(const float4*)&red2[w * 64 + cp * 4];
                    q0 += b ? v.y : v.x; q1 += b ? v.w : v.z;
                }
                st_ll2(&sc->q[b][cta * 16 + cp], pack_bf16(q0, q1), tag);
                TSTAMP(3);
            }
        }
        const int pair = cta >> 3;
        uint32_t qf[16];
        {
            uint2* qs = (uint2*)(sgen + SM_QS);
            if (tid < 128) {
                const uint4* src = (const uint4*)&sc->q[pair >> 3][(pair & 7) * 256] + tid;
                uint4 v;
                for (int it = 0;; it++) {
                    v = ld_ll4(src);
                    if ((v.y == tag && v.w == tag) || it > SPIN_LIMIT) break;
                }
                qs[tid] = make_uint2(v.x, v.z);
            }
            cons_sync();
            const uint32_t* q32 = (const uint32_t*)(sgen + SM_QS);
#pragma unroll
            for (int s = 0; s < 8; s++) {
                qf[2 * s] = q32[(g & 3) * 64 + 8 * s + t];
                qf[2 * s + 1] = q32[(g & 3) * 64 + 8 * s + 4 + t];
            }
        }
        if (warp == 0) TSTAMP(4);

        float o[8][4];
#pragma unroll
        for (int i = 0; i < 8; i++) { o[i][0] = o[i][1] = o[i][2] = o[i][3] = 0.f; }
        uint32_t mrun = 0xff80ff80u;
        float ls[4] = {0.f, 0.f, 0.f, 0.f};
        uint4 m_sb, m_cb; uint2 m_ga, m_gb0, m_gb1;
        {
            const int grp = warp >> 2, wi = warp & 3;
            const int krow = 16 * wi + (lane & 7) + ((lane >> 3) & 1) * 8;
            const uint32_t koff = krow * 128 + ((((lane >> 4) & 1) ^ (lane & 7)) << 4);
            const int vrow = 16 * wi + (lane & 7) + (lane >> 4) * 8;
            const uint32_t voff = vrow * 128 + ((((lane >> 3) & 1) ^ (lane & 7)) << 4);
            const uint32_t ones[4] = {0x3f803f80u, 0x3f803f80u, 0x3f803f80u, 0x3f803f80u};
            for (int i = grp; i < KV_TILES; i += 2) {
                if (i == MOD_AT + grp) {
                    float cm[4] = {};
                    const uint32_t* sc32 = (const uint32_t*)(sgen + SM_SC) + bb * 256 + 32 * warp + t;
                    mbar_wait(bar_full + 8 * (IDX_MOD % NST), (IDX_MOD / NST) & 1);
                    const uint32_t tb = sbase + SM_RING + (IDX_MOD % NST) * TILE;
#pragma unroll
                    for (int s = 0; s < 4; s++) {
                        const int row = 64 * warp + 16 * s + (lane & 7) + (lane >> 4) * 8;
                        const int ch = (lane >> 3) & 1;
                        uint32_t a[4];
                        ldsm4t(tb + row * 32 + ((ch ^ ((row >> 2) & 1)) << 4), a);
                        mma16816(cm, a, sc32[8 * s], sc32[8 * s + 4]);
                    }
                    if (t == 0) {
                        *(float2*)&red[warp * 64 + g * 2] = make_float2(cm[0], cm[1]);
                        *(float2*)&red[warp * 64 + (g + 8) * 2] = make_float2(cm[2], cm[3]);
                    }
                    cons_sync();
                    if (warp < 4 && lane == 0) mbar_arrive(bar_empty + 8 * (IDX_MOD % NST));
                    if (warp == 1 && lane < 16) {
                        const int b = lane >> 3, cp = lane & 7;
                        float q0 = 0.f, q1 = 0.f;
#pragma unroll
                        for (int w = 0; w < 8; w++) {
                            const float4 v = *(const float4*)&red[w * 64 + cp * 4];
                            q0 += b ? v.y : v.x; q1 += b ? v.w : v.z;
                        }
                        st_ll2(&sc->mod[b][512 + cta * 8 + cp], pack_bf16(q0, q1), tag);
                    }
                }
                if (i == 56 + grp) {
                    m_sb = ld_ll4((const uint4*)&sc->mod[eb][768 + (ec >> 1)]);
                    m_cb = ld_ll4((const uint4*)&sc->mod[eb][1024 + (ec >> 1)]);
                    m_ga = ld_ll2(&sc->mod[eb][512 + (wcol >> 1)]);
                    m_gb0 = ld_ll2(&sc->mod[0][1280 + (ocol >> 1)]); m_gb1 = ld_ll2(&sc->mod[1][1280 + (ocol >> 1)]);
                }
                if (i == 60 + grp) {
                    for (int it = 0;; it++) {
                        const bool ok = m_sb.y == tag && m_sb.w == tag && m_cb.y == tag && m_cb.w == tag &&
                                        m_ga.y == tag && m_gb0.y == tag && m_gb1.y == tag;
                        if (__all_sync(0xffffffffu, ok) || it > SPIN_LIMIT) break;
                        m_sb = ld_ll4((const uint4*)&sc->mod[eb][768 + (ec >> 1)]);
                        m_cb = ld_ll4((const uint4*)&sc->mod[eb][1024 + (ec >> 1)]);
                        m_ga = ld_ll2(&sc->mod[eb][512 + (wcol >> 1)]);
                        m_gb0 = ld_ll2(&sc->mod[0][1280 + (ocol >> 1)]); m_gb1 = ld_ll2(&sc->mod[1][1280 + (ocol >> 1)]);
                    }
                    mbar_wait(bar_clear, 0);
                }
                const int ki = kv_idx(i), ks = ki % NST, vs = (ki + 1) % NST;
                const uint32_t kph = (ki / NST) & 1, vph = ((ki + 1) / NST) & 1;
                mbar_wait(bar_full + 8 * ks, kph);
                const uint32_t kb = sbase + SM_RING + ks * TILE + koff;
                float sa[4] = {0.f, 0.f, 0.f, 0.f}, sb[4] = {0.f, 0.f, 0.f, 0.f};
#pragma unroll
                for (int s = 0; s < 8; s += 2) {
                    uint32_t a0[4], a1[4];
                    ldsm4((kb ^ ((s & 3) << 5)) + (s >> 2) * 8192, a0);
                    ldsm4((kb ^ (((s + 1) & 3) << 5)) + (s >> 2) * 8192, a1);
                    mma16816(sa, a0, qf[2 * s], qf[2 * s + 1]);
                    mma16816(sb, a1, qf[2 * s + 2], qf[2 * s + 3]);
                }
                __syncwarp();
                if (lane == 0) mbar_arrive(bar_empty + 8 * ks);
                uint32_t r01 = pack_bf16(sa[0] + sb[0], sa[1] + sb[1]);
                uint32_t r23 = pack_bf16(sa[2] + sb[2], sa[3] + sb[3]);
                r01 = pack_bf16(bf_lo(r01) * QK_SCALE, bf_hi(r01) * QK_SCALE);
                r23 = pack_bf16(bf_lo(r23) * QK_SCALE, bf_hi(r23) * QK_SCALE);
                uint32_t mx = max_bf16x2(r01, r23);
                mx = max_bf16x2(mx, __shfl_xor_sync(0xffffffffu, mx, 4));
                mx = max_bf16x2(mx, __shfl_xor_sync(0xffffffffu, mx, 8));
                mx = max_bf16x2(mx, __shfl_xor_sync(0xffffffffu, mx, 16));
                const uint32_t mnew = max_bf16x2(mrun, mx);
                const float m0 = bf_lo(mnew), m1 = bf_hi(mnew);
                if (__any_sync(0xffffffffu, mnew != mrun)) {
                    const float al0 = ex2((bf_lo(mrun) - m0) * LOG2E), al1 = ex2((bf_hi(mrun) - m1) * LOG2E);
                    ls[0] *= al0; ls[1] *= al1;
#pragma unroll
                    for (int d = 0; d < 8; d++) { o[d][0] *= al0; o[d][1] *= al1; o[d][2] *= al0; o[d][3] *= al1; }
                    mrun = mnew;
                }
                const float p0 = ex2((bf_lo(r01) - m0) * LOG2E), p1 = ex2((bf_hi(r01) - m1) * LOG2E);
                const float p2 = ex2((bf_lo(r23) - m0) * LOG2E), p3 = ex2((bf_hi(r23) - m1) * LOG2E);
                const uint32_t pb0 = movmatrix_t(pack_bf16(p0, p1)), pb1 = movmatrix_t(pack_bf16(p2, p3));
                mma16816(ls, ones, pb0, pb1);
                mbar_wait(bar_full + 8 * vs, vph);
                const uint32_t vb = sbase + SM_RING + vs * TILE + voff;
#pragma unroll
                for (int d = 0; d < 8; d++) {
                    uint32_t a[4];
                    ldsm4t((vb ^ ((d & 3) << 5)) + (d >> 2) * 8192, a);
                    mma16816(o[d], a, pb0, pb1);
                }
                __syncwarp();
                if (lane == 0) mbar_arrive(bar_empty + 8 * vs);
            }
        }
        if (warp == 7) TSTAMP(5);
        {
            float* mrg = (float*)(sgen + SM_MRG);
            float2* ml = (float2*)(sgen + SM_ML);
            {
                const int hp = (t & 1) * 2, up = t >> 1;
                if (g == 0 && up == 0) { ml[warp * 4 + hp] = make_float2(bf_lo(mrun), ls[0]); ml[warp * 4 + hp + 1] = make_float2(bf_hi(mrun), ls[1]); }
                float* m0p = mrg + (warp * 4 + hp) * 136 + up * 72 + g;
#pragma unroll
                for (int d = 0; d < 4; d++) {
                    m0p[16 * d] = up ? o[d + 4][0] : o[d][0]; m0p[136 + 16 * d] = up ? o[d + 4][1] : o[d][1];
                    m0p[16 * d + 8] = up ? o[d + 4][2] : o[d][2]; m0p[136 + 16 * d + 8] = up ? o[d + 4][3] : o[d][3];
                }
            }
            cons_sync();
            const int hh = tid >> 6, dp = tid & 63;
            float2 mw[8];
            float M = -INFINITY;
#pragma unroll
            for (int w = 0; w < 8; w++) { mw[w] = ml[w * 4 + hh]; M = fmaxf(M, mw[w].x); }
            float L = 0.f, o0 = 0.f, o1 = 0.f;
#pragma unroll
            for (int w = 0; w < 8; w++) {
                const float wt = ex2((mw[w].x - M) * LOG2E);
                const float2 v = *(const float2*)&mrg[(w * 4 + hh) * 136 + 2 * dp + (dp >= 32 ? 8 : 0)];
                L += wt * mw[w].y; o0 += wt * v.x; o1 += wt * v.y;
            }
            st_ll2(&sc->part_o[cta][hh][dp], tagf(o0, F_PART), tagf(o1, F_PART));
            if (dp < 4) st_ll2(&sc->part_ml[cta][hh][dp], tagf(M, F_PART), tagf(L, F_PART));
        }
        if (warp == 0) TSTAMP(6);
        {
            const int hq = cta >> 2, kvh = hq >> 2, hh = hq & 3;
            const int b = tid >> 7, dc = (tid >> 3) & 15, j = tid & 7;
            const int pc = (b * 8 + kvh) * 8 + j;
            const uint4* po = (const uint4*)&sc->part_o[pc][hh][0] + dc * 2;
            const uint2* pm = &sc->part_ml[pc - j][hh][0];
            uint4 vo0, vo1; uint2 vm[8];
            bool oko = false, okm = false;
            for (int it = 0;; it++) {
                if (!oko) { vo0 = ld_ll4(po); vo1 = ld_ll4(po + 1); }
                if (!okm) {
#pragma unroll
                    for (int jj = 0; jj < 8; jj++) vm[jj] = ld_ll2(pm + jj * 16);
                }
                oko = (vo0.x & vo0.y & vo0.z & vo0.w & vo1.x & vo1.y & vo1.z & vo1.w & 3u) == F_PART;
                uint32_t all = vm[0].x & vm[0].y;
#pragma unroll
                for (int jj = 1; jj < 8; jj++) all &= vm[jj].x & vm[jj].y;
                okm = (all & 3u) == F_PART;
                if (__all_sync(0xffffffffu, oko && okm) || it > SPIN_LIMIT) break;
            }
            float M = untag(vm[0].x);
#pragma unroll
            for (int jj = 1; jj < 8; jj++) M = fmaxf(M, untag(vm[jj].x));
            float wt = 0.f, L = 0.f;
#pragma unroll
            for (int jj = 0; jj < 8; jj++) {
                const float w_ = ex2((untag(vm[jj].x) - M) * LOG2E);
                L += w_ * untag(vm[jj].y);
                wt = jj == j ? w_ : wt;
            }
            wt *= rcp_approx(L);
            float v[8] = {wt * untag(vo0.x), wt * untag(vo0.y), wt * untag(vo0.z), wt * untag(vo0.w),
                          wt * untag(vo1.x), wt * untag(vo1.y), wt * untag(vo1.z), wt * untag(vo1.w)};
#define XRED(N, O)                                                                       \
            {                                                                            \
                const bool up = lane & (O);                                              \
                _Pragma("unroll") for (int i = 0; i < (N); i++) {                        \
                    const float send = up ? v[i] : v[i + (N)], keep = up ? v[i + (N)] : v[i]; \
                    v[i] = keep + __shfl_xor_sync(0xffffffffu, send, (O));               \
                }                                                                        \
            }
            XRED(4, 1) XRED(2, 2) XRED(1, 4)
#undef XRED
            __nv_bfloat16* os = (__nv_bfloat16*)(sgen + SM_OS);
            os[b * 128 + dc * 8 + 4 * (j & 1) + 2 * ((j >> 1) & 1) + (j >> 2)] = __float2bfloat16_rn(v[0]);
            if (warp == 0) TSTAMP(15);
            uint32_t wf[8][4];
            const uint32_t aoff_o = (warp >> 2) * 8192 + ((lane & 7) + (lane >> 4) * 8) * 128 +
                                    (((((warp & 3) * 2 + ((lane >> 3) & 1)) ^ (lane & 7))) << 4);
#pragma unroll
            for (int s = 0; s < 2; s++) {
                const int idx = IDX_WO + s;
                mbar_wait(bar_full + 8 * (idx % NST), (idx / NST) & 1);
                const uint32_t tb = sbase + SM_RING + (idx % NST) * TILE + aoff_o;
#pragma unroll
                for (int k4 = 0; k4 < 4; k4++) ldsm4t(tb + k4 * 2048, wf[s * 4 + k4]);
            }
            cons_sync();
            if (warp == 0) TSTAMP(7);
            const uint32_t* os32 = (const uint32_t*)(sgen + SM_OS) + bb * 64 + t;
            float y0[4] = {}, y1[4] = {};
#pragma unroll
            for (int ks = 0; ks < 8; ks += 2) {
                mma16816(y0, wf[ks], os32[8 * ks], os32[8 * ks + 4]);
                mma16816(y1, wf[ks + 1], os32[8 * ks + 8], os32[8 * ks + 12]);
            }
            if (t == 0)
                st_v4(&sc->inbox_wo[(cta & 3) * 8 + warp][hq][g], tagf(y0[0] + y1[0], F_WO), tagf(y0[1] + y1[1], F_WO),
                      tagf(y0[2] + y1[2], F_WO), tagf(y0[3] + y1[3], F_WO));
        }
        const uint32_t t_wo = clock32();
        if (warp == 0) TSTAMP(8);
        if (cta >= NCTA - NOWN) {
            const uint4* pin = &sc->inbox_wo[cta - (NCTA - NOWN)][0][0] + tid;
            uint4 v;
            spin_cycles(DELAY_B1);
            bool ok = false;
            for (int it = 0;; it++) {
                if (!ok) {
                    v = ld_ll4(pin);
                    ok = (v.x & v.y & v.z & v.w & 3u) == F_WO;
                }
                if (__all_sync(0xffffffffu, ok) || it > SPIN_LIMIT) break;
            }
            const bool u1 = lane & 8, u2 = lane & 16;
            const float a0 = untag(v.x), a1 = untag(v.y), a2 = untag(v.z), a3 = untag(v.w);
            const float k0 = (u1 ? a2 : a0) + __shfl_xor_sync(0xffffffffu, u1 ? a0 : a2, 8);
            const float k1 = (u1 ? a3 : a1) + __shfl_xor_sync(0xffffffffu, u1 ? a1 : a3, 8);
            red2[warp * 32 + lane] = (u2 ? k1 : k0) + __shfl_xor_sync(0xffffffffu, u2 ? k0 : k1, 16);
            cons_sync();
            if (warp == 0) {
                float a = 0.f;
#pragma unroll
                for (int w = 0; w < 8; w++) a += red2[w * 32 + lane];
                const float ga = (wcol & 1) ? bf_hi(m_ga.x) : bf_lo(m_ga.x);
                const float xm = bf16r(xo + bf16r(ga * bf16r(a)));
                const float xm_b1 = __shfl_down_sync(0xffffffffu, xm, 16);
                if (lane < 16) st_ll2(&sc->x1[wcol], pack_bf16(xm, xm_b1), F_X1);
                TSTAMP(10);
            }
        }
        const uint32_t aoff = warp * 2048 + ((lane & 7) + (lane >> 4) * 8) * 128 + ((((lane >> 3) & 1) ^ (lane & 7)) << 4);
        if (cta < NFFN) {
            const uint4* px = (const uint4*)&sc->x1[ec];
            const uint4* pp = (const uint4*)&sc->x1[0];
            uint4 va, vb, pa, pb;
            uint32_t gf[4][4], uf[4][4];
            mbar_wait(bar_gu + 8 * (2 * (warp >> 1)), 0);
            mbar_wait(bar_gu + 8 * (2 * (warp >> 1) + 1), 0);
            {
                const uint32_t tg = sbase + SM_RING + (IDX_WG % NST) * TILE, tu = sbase + SM_RING + (IDX_WU % NST) * TILE;
#pragma unroll
                for (int s = 0; s < 4; s++) {
                    const int row = 64 * warp + 16 * s + (lane & 7) + (lane >> 4) * 8;
                    const uint32_t off = row * 32 + ((((lane >> 3) & 1) ^ ((row >> 2) & 1)) << 4);
                    ldsm4t(tg + off, gf[s]);
                    ldsm4t(tu + off, uf[s]);
                }
            }
            const float c1v[4] = {bf16r(1.0f + bf_lo(m_cb.x)), bf16r(1.0f + bf_hi(m_cb.x)), bf16r(1.0f + bf_lo(m_cb.z)), bf16r(1.0f + bf_hi(m_cb.z))};
            float bg = 0.f, cgc = 0.f, bu = 0.f, cuc = 0.f;
            {
                uint32_t* pre = (uint32_t*)(sgen + SM_MRG) + warp * 128;
                float* bc = (float*)(sgen + SM_MRG + 4096);
                *(uint2*)&pre[eb * 32 + 2 * (lane & 15)] = make_uint2(pack_bf16(c1v[0], c1v[1]), pack_bf16(c1v[2], c1v[3]));
                *(uint2*)&pre[64 + eb * 32 + 2 * (lane & 15)] = make_uint2(m_sb.x, m_sb.z);
                __syncwarp();
                float yg[4] = {}, yu[4] = {};
                const uint32_t* pb = pre + ((g >> 1) & 1) * 64 + bb * 32 + t;
#pragma unroll
                for (int s = 0; s < 4; s++) {
                    const uint32_t b0 = pb[8 * s], b1 = pb[8 * s + 4];
                    mma16816(yg, gf[s], b0, b1);
                    mma16816(yu, uf[s], b0, b1);
                }
                const float y0 = t < 2 ? yg[0] : yu[0], y1 = t < 2 ? yg[1] : yu[1], y2 = t < 2 ? yg[2] : yu[2], y3 = t < 2 ? yg[3] : yu[3];
                float* dstp = bc + warp * 128 + (t >> 1) * 64 + (t & 1) * 32;
                *(float2*)&dstp[g * 2] = make_float2(y0, y1);
                *(float2*)&dstp[(g + 8) * 2] = make_float2(y2, y3);
                __syncwarp();
                if (lane == 0) mbar_arrive(bar_bc);
            }
            if (warp == 0) TSTAMP(11);
            float pivot2;
            {
                while (clock32() - t_wo < DELAY_X1) {}
                bool okx = false, okp = false;
                for (int it = 0;; it++) {
                    if (!okx) { va = ld_ll4(px); vb = ld_ll4(px + 1); }
                    if (!okp) { pa = ld_ll4(pp); pb = ld_ll4(pp + 1); }
                    okx = va.y == F_X1 && va.w == F_X1 && vb.y == F_X1 && vb.w == F_X1;
                    okp = pa.y == F_X1 && pa.w == F_X1 && pb.y == F_X1 && pb.w == F_X1;
                    if (__all_sync(0xffffffffu, okx && okp) || it > SPIN_LIMIT) break;
                }
                if (warp == 0) TSTAMP(9);
                const float xv[4] = {eb ? bf_hi(va.x) : bf_lo(va.x), eb ? bf_hi(va.z) : bf_lo(va.z),
                                     eb ? bf_hi(vb.x) : bf_lo(vb.x), eb ? bf_hi(vb.z) : bf_lo(vb.z)};
                const float p0 = 0.25f * ((bf_lo(pa.x) + bf_lo(pa.z)) + (bf_lo(pb.x) + bf_lo(pb.z)));
                const float p1 = 0.25f * ((bf_hi(pa.x) + bf_hi(pa.z)) + (bf_hi(pb.x) + bf_hi(pb.z)));
                const float pivot = eb ? p1 : p0;
                pivot2 = (lane & 1) ? p1 : p0;
                *(uint2*)&hs[eb * 32 + 2 * (lane & 15)] =
                    make_uint2(pack_bf16((xv[0] - pivot) * c1v[0], (xv[1] - pivot) * c1v[1]),
                               pack_bf16((xv[2] - pivot) * c1v[2], (xv[3] - pivot) * c1v[3]));
                __syncwarp();
                float cg[2][4] = {}, cu[2][4] = {};
#pragma unroll
                for (int s = 0; s < 4; s++) {
                    const uint32_t b0 = hs[bb * 32 + 8 * s + t], b1 = hs[bb * 32 + 8 * s + 4 + t];
                    mma16816(cg[s & 1], gf[s], b0, b1);
                    mma16816(cu[s & 1], uf[s], b0, b1);
                }
                const float2 ps = half_warp_sums(xv, pivot);
                if ((lane & 15) == 0) stat[warp * 2 + eb] = ps;
                {
                    const float* bc = (const float*)(sgen + SM_MRG + 4096);
                    mbar_wait(bar_bc, 0);
#pragma unroll
                    for (int w = 0; w < 8; w++) {
                        bg += bc[w * 128 + lane]; cgc += bc[w * 128 + 32 + lane];
                        bu += bc[w * 128 + 64 + lane]; cuc += bc[w * 128 + 96 + lane];
                    }
                }
                if (t < 2) {
                    float v[4];
#pragma unroll
                    for (int i = 0; i < 4; i++) v[i] = t ? cu[0][i] + cu[1][i] : cg[0][i] + cg[1][i];
                    *(float2*)&red[warp * 64 + t * 32 + g * 2] = make_float2(v[0], v[1]);
                    *(float2*)&red[warp * 64 + t * 32 + (g + 8) * 2] = make_float2(v[2], v[3]);
                }
            }
            uint32_t df[4][4];
            mbar_wait(bar_full + 8 * (IDX_WD % NST), (IDX_WD / NST) & 1);
#pragma unroll
            for (int mt = 0; mt < 4; mt++) ldsm4t((sbase + SM_RING + (IDX_WD % NST) * TILE + aoff) ^ (mt << 5), df[mt]);
            cons_sync();
            {
                float gs = 0.f, us = 0.f;
#pragma unroll
                for (int w = 0; w < 8; w++) { gs += red[w * 64 + lane]; us += red[w * 64 + 32 + lane]; }
                float mean_bf, rstd;
                ln_stats(stat, lane & 1, pivot2, mean_bf, rstd);
                const float dm = mean_bf - pivot2;
                gs = bf16r(rstd * (gs - dm * bg) + cgc);
                us = rstd * (us - dm * bu) + cuc;
                const float u2 = gs * (1.0f + 0.044715f * gs * gs) * (2.0f * 0.7978845608028654f * LOG2E);
                const float ge = bf16r(__fdividef(gs, 1.0f + ex2(-u2)));
                const float act = bf16r(ge * bf16r(us));
                const float a0 = __shfl_sync(0xffffffffu, act, 4 * t + bb), a1 = __shfl_sync(0xffffffffu, act, 4 * t + 2 + bb);
                const float a2 = __shfl_sync(0xffffffffu, act, 4 * t + 16 + bb), a3 = __shfl_sync(0xffffffffu, act, 4 * t + 18 + bb);
                const uint32_t b0 = pack_bf16(a0, a1), b1 = pack_bf16(a2, a3);
                float y[4][4] = {};
#pragma unroll
                for (int mt = 0; mt < 4; mt++) mma16816(y[mt], df[mt], b0, b1);
                float v[4];
#pragma unroll
                for (int i = 0; i < 4; i++) v[i] = t == 0 ? y[0][i] : t == 1 ? y[1][i] : t == 2 ? y[2][i] : y[3][i];
            {
                const bool odd = g & 1;
                const float sx = odd ? v[0] : v[2], sy = odd ? v[1] : v[3];
                const float rx = __shfl_xor_sync(0xffffffffu, sx, 4), ry = __shfl_xor_sync(0xffffffffu, sy, 4);
                const int c0 = 64 * warp + 16 * t + (odd ? g + 7 : g);
                const float e0 = odd ? rx : v[0], e1 = odd ? ry : v[1], e2 = odd ? v[2] : rx, e3 = odd ? v[3] : ry;
                st_v4(&sc->inbox_dn[c0 >> 2][cta][(c0 >> 1) & 1], tagf(e0, F_DOWN), tagf(e1, F_DOWN), tagf(e2, F_DOWN), tagf(e3, F_DOWN));
            }
            }
            if (warp == 0) TSTAMP(12);
        }
        {
            uint2 xw;
            float r0;
            {
                const uint4* pin = &sc->inbox_dn[cta][0][0] + tid;
                uint4 v = make_uint4(F_DOWN, F_DOWN, F_DOWN, F_DOWN);
                if (cta < NFFN) spin_cycles(DELAY_C);
                else while (clock32() - t_wo < DELAY_X1 + DELAY_NOFFN) {}
                xw = ld_ll2(&sc->x1[ocol]);
                bool ok = tid >= NFFN * 2;
                for (int it = 0;; it++) {
                    if (!ok) {
                        v = ld_ll4(pin);
                        ok = (v.x & v.y & v.z & v.w & 3u) == F_DOWN;
                    }
                    if (__all_sync(0xffffffffu, ok) || it > SPIN_LIMIT) break;
                }
                const bool u1 = lane & 2, u2 = lane & 4;
                const float a0 = untag(v.x), a1 = untag(v.y), a2 = untag(v.z), a3 = untag(v.w);
                const float k0 = (u1 ? a1 : a0) + __shfl_xor_sync(0xffffffffu, u1 ? a0 : a1, 2);
                const float k1 = (u1 ? a3 : a2) + __shfl_xor_sync(0xffffffffu, u1 ? a2 : a3, 2);
                r0 = (u2 ? k1 : k0) + __shfl_xor_sync(0xffffffffu, u2 ? k0 : k1, 4);
                r0 += __shfl_xor_sync(0xffffffffu, r0, 8);
                r0 += __shfl_xor_sync(0xffffffffu, r0, 16);
                if (lane < 8) red2[256 + warp * 8 + (2 * (lane & 1) + ((lane >> 2) & 1)) * 2 + ((lane >> 1) & 1)] = r0;
            }
            cons_sync();
            if (warp == 0) {
                float a0 = 0.f, a1 = 0.f;
#pragma unroll
                for (int w = 0; w < 8; w++) { const float2 v = *(const float2*)&red2[256 + w * 8 + (lane & 3) * 2]; a0 += v.x; a1 += v.y; }
                const bool hi = ocol & 1;
                const float gb0 = hi ? bf_hi(m_gb0.x) : bf_lo(m_gb0.x), gb1 = hi ? bf_hi(m_gb1.x) : bf_lo(m_gb1.x);
                for (int it = 0; !__all_sync(0xffffffffu, xw.y == F_X1) && it < SPIN_LIMIT; it++) xw = ld_ll2(&sc->x1[ocol]);
                if (lane < 4) {
                    p.out[ocol] = __float2bfloat16_rn(bf_lo(xw.x) + bf16r(gb0 * bf16r(a0)));
                    p.out[D_MODEL + ocol] = __float2bfloat16_rn(bf_hi(xw.x) + bf16r(gb1 * bf16r(a1)));
                }
                TSTAMP(13);
            }
        }
    }
}

typedef CUresult (*EncodeFn)(CUtensorMap*, CUtensorMapDataType, cuuint32_t, void*, const cuuint64_t*, const cuuint64_t*,
                             const cuuint32_t*, const cuuint32_t*, CUtensorMapInterleave, CUtensorMapSwizzle,
                             CUtensorMapL2promotion, CUtensorMapFloatOOBfill);

struct Maps { CUtensorMap k, v, wq, wmod, wmod8, wo, wg, wu, wd; };

void encode(EncodeFn fn, CUtensorMap* m, const void* ptr, int rank, const cuuint64_t* dims, const cuuint64_t* strides,
            const cuuint32_t* box, CUtensorMapSwizzle sw) {
    const cuuint32_t es[3] = {1, 1, 1};
    fn(m, CU_TENSOR_MAP_DATA_TYPE_BFLOAT16, rank, const_cast<void*>(ptr), dims, strides, box, es,
       CU_TENSOR_MAP_INTERLEAVE_NONE, sw, CU_TENSOR_MAP_L2_PROMOTION_L2_256B, CU_TENSOR_MAP_FLOAT_OOB_FILL_NONE);
}

}

extern "C" void kernel_launch(void* const* d_in, const int* in_sizes, int n_in, void* d_out, int out_size) {
    (void)in_sizes; (void)n_in; (void)out_size;
    static EncodeFn enc = nullptr;
    static Scratch* scratch = nullptr;
    if (!enc) {
        cudaGetSymbolAddress((void**)&scratch, g_scratch);
        void* fn = nullptr;
        cudaDriverEntryPointQueryResult qr;
        cudaGetDriverEntryPoint("cuTensorMapEncodeTiled", &fn, cudaEnableDefault, &qr);
        enc = (EncodeFn)fn;
        cudaFuncSetAttribute(fused_block_kernel, cudaFuncAttributeMaxDynamicSharedMemorySize, SMEM_BYTES);
    }
    Maps m;
    {
        const cuuint64_t dims[3] = {64, (cuuint64_t)16 * SK, 2}, str[2] = {256, 128};
        const cuuint32_t box[3] = {64, 64, 2};
        encode(enc, &m.k, d_in[1], 3, dims, str, box, CU_TENSOR_MAP_SWIZZLE_128B);
        encode(enc, &m.v, d_in[2], 3, dims, str, box, CU_TENSOR_MAP_SWIZZLE_128B);
    }
    {
        const cuuint64_t dims[2] = {4096, 512}, str[1] = {8192};
        const cuuint32_t box[2] = {32, 256};
        encode(enc, &m.wq, d_in[3], 2, dims, str, box, CU_TENSOR_MAP_SWIZZLE_64B);
    }
    {
        const cuuint64_t dims[2] = {N_MOD, 512}, str[1] = {N_MOD * 2};
        const cuuint32_t box[2] = {16, 256};
        encode(enc, &m.wmod, d_in[10], 2, dims, str, box, CU_TENSOR_MAP_SWIZZLE_32B);
        const cuuint32_t box8[2] = {8, 256};
        encode(enc, &m.wmod8, d_in[10], 2, dims, str, box8, CU_TENSOR_MAP_SWIZZLE_NONE);
    }
    {
        const cuuint64_t dims_o[3] = {64, 4096, 8}, dims_d[3] = {64, D_FF, 8}, str[2] = {1024, 128};
        const cuuint32_t box[3] = {64, 16, 8}, box_o[3] = {64, 64, 2};
        encode(enc, &m.wo, d_in[4], 3, dims_o, str, box_o, CU_TENSOR_MAP_SWIZZLE_128B);
        encode(enc, &m.wd, d_in[8], 3, dims_d, str, box, CU_TENSOR_MAP_SWIZZLE_128B);
    }
    {
        const cuuint64_t dims[2] = {D_FF, 512}, str[1] = {D_FF * 2};
        const cuuint32_t box[2] = {16, 128};
        encode(enc, &m.wg, d_in[6], 2, dims, str, box, CU_TENSOR_MAP_SWIZZLE_32B);
        encode(enc, &m.wu, d_in[7], 2, dims, str, box, CU_TENSOR_MAP_SWIZZLE_32B);
    }
    Params p;
    p.x = (const __nv_bfloat16*)d_in[0];
    p.c = (const __nv_bfloat16*)d_in[9];
    p.out = (__nv_bfloat16*)d_out;
    p.sc = scratch;
    fused_block_kernel<<<NCTA, NTHREADS, SMEM_BYTES, cudaStreamPerThread>>>(p, m.k, m.v, m.wq, m.wmod, m.wmod8, m.wo, m.wg, m.wu, m.wd);
}
```

```cpp
#include <cuda_runtime.h>
#include <cuda.h>
#include <cuda_bf16.h>
#include <stdint.h>

namespace {

constexpr int D_MODEL = 512;
constexpr int N_HEADS = 32;
constexpr int SK = 32768;
constexpr int DH = 128;
constexpr int D_FF = 1792;
constexpr int N_MOD = 6 * D_MODEL;

constexpr int NCTA = 128;
constexpr int NFFN = D_FF / 16;
constexpr int NOWN = 32;
constexpr int OWN0 = NFFN;
constexpr int NTHREADS = 320;
constexpr int NST = 12;
constexpr int TILE = 16384;
#define WINDOW 3
#define WINDOW_TAIL 1
#define GU_WIN 3
#define PACE_THR 96
constexpr int KV_TILES = 64;
#define MOD_AT 8
static_assert(MOD_AT % 2 == 0 && MOD_AT >= 2 && MOD_AT < 56, "schedule");
__host__ __device__ constexpr int kv_idx(int i) { return 2 + 2 * i + (i >= MOD_AT ? 1 : 0); }
constexpr int IDX_MOD = 2 + 2 * MOD_AT;
constexpr int N_STREAM = kv_idx(KV_TILES - 1) + 2;
constexpr int IDX_WO = N_STREAM;
constexpr int IDX_WG = IDX_WO + 2;
constexpr int IDX_WU = IDX_WG + 1;
constexpr int IDX_WD = IDX_WU + 1;
constexpr int SPIN_LIMIT = 1 << 20;

constexpr float LOG2E = 1.4426950408889634f;
constexpr float QK_SCALE = 0.08838834764831845f;

constexpr int SM_RING = 0;
constexpr int SM_MRG = SM_RING + NST * TILE;
constexpr int SM_ML = SM_MRG + 8 * 4 * 136 * 4;
constexpr int SM_RED = SM_ML + 8 * 4 * 8;
constexpr int SM_RED2 = SM_RED + 8 * 64 * 4;
constexpr int SM_QS = SM_RED2 + 8 * 64 * 4;
constexpr int SM_OS = SM_QS + 512 * 2;
constexpr int SM_SC = SM_OS + 2 * 128 * 2;
constexpr int SM_HS = SM_SC + 2 * 512 * 2;
constexpr int SM_STAT = SM_HS + 8 * 2 * 32 * 4;
constexpr int SM_PACE = SM_STAT + 8 * 2 * 8;
constexpr int SM_BAR = SM_PACE + 8;
constexpr int SM_END = SM_BAR + (2 * NST + 1 + 8 + 2) * 8;
constexpr int SMEM_BYTES = SM_END + 1024;

struct Scratch {
    uint4 inbox_wo[NOWN][N_HEADS][8];
    uint4 inbox_dn[NCTA][NFFN][2];
    uint2 x1[D_MODEL];
    uint2 part_o[NCTA][4][64];
    uint2 part_ml[NCTA][4][4];
    uint2 mod[2][N_MOD / 2];
    uint2 q[2][N_HEADS * DH / 2];
    unsigned epoch;
    unsigned pad_[31];
    unsigned cleared;
    unsigned pad2_[31];
    unsigned progress;
};
__device__ Scratch g_scratch;
constexpr uint32_t F_PART = 1, F_WO = 1, F_DOWN = 1, F_X1 = 1;
__device__ __forceinline__ uint32_t tagf(float v, uint32_t f) { return (__float_as_uint(v) & ~3u) | f; }
__device__ __forceinline__ float untag(uint32_t v) { return __uint_as_float(v & ~3u); }

struct Params {
    const __nv_bfloat16* x;
    const __nv_bfloat16* c;
    __nv_bfloat16* out;
    Scratch* sc;
};

#define TSTAMP(i) do { } while (0)

__device__ __forceinline__ uint32_t smem_u32(const void* p) { return (uint32_t)__cvta_generic_to_shared(p); }

__device__ __forceinline__ void mbar_init(uint32_t bar, uint32_t cnt) {
    asm volatile("mbarrier.init.shared::cta.b64 [%0], %1;" ::"r"(bar), "r"(cnt) : "memory");
}
__device__ __forceinline__ void mbar_expect_tx(uint32_t bar, uint32_t bytes) {
    asm volatile("mbarrier.arrive.expect_tx.shared::cta.b64 _, [%0], %1;" ::"r"(bar), "r"(bytes) : "memory");
}
__device__ __forceinline__ void mbar_arrive(uint32_t bar) {
    asm volatile("mbarrier.arrive.shared::cta.b64 _, [%0];" ::"r"(bar) : "memory");
}
__device__ __forceinline__ bool mbar_try(uint32_t bar, uint32_t parity) {
    uint32_t ok;
    asm volatile(
        "{\n\t.reg .pred p;\n\t"
        "mbarrier.try_wait.parity.shared::cta.b64 p, [%1], %2;\n\t"
        "selp.u32 %0, 1, 0, p;\n\t}"
        : "=r"(ok) : "r"(bar), "r"(parity) : "memory");
    return ok != 0;
}
__device__ __forceinline__ void mbar_wait(uint32_t bar, uint32_t parity) {
    if (mbar_try(bar, parity)) return;
    const long long t0 = clock64();
    while (!mbar_try(bar, parity))
        if (clock64() - t0 > (1ll << 31)) return;
}
__device__ __forceinline__ void cons_sync() { asm volatile("bar.sync 1, 256;" ::: "memory"); }

__device__ __forceinline__ void tma_2d(uint32_t dst, const CUtensorMap* m, int c0, int c1, uint32_t bar) {
    asm volatile("cp.async.bulk.tensor.2d.shared::cluster.global.mbarrier::complete_tx::bytes [%0], [%1, {%3, %4}], [%2];"
                 ::"r"(dst), "l"(m), "r"(bar), "r"(c0), "r"(c1) : "memory");
}
__device__ __forceinline__ void tma_3d(uint32_t dst, const CUtensorMap* m, int c0, int c1, int c2, uint32_t bar) {
    asm volatile("cp.async.bulk.tensor.3d.shared::cluster.global.mbarrier::complete_tx::bytes [%0], [%1, {%3, %4, %5}], [%2];"
                 ::"r"(dst), "l"(m), "r"(bar), "r"(c0), "r"(c1), "r"(c2) : "memory");
}
__device__ __forceinline__ void tma_3d_hint(uint32_t dst, const CUtensorMap* m, int c0, int c1, int c2, uint32_t bar, uint64_t pol) {
    asm volatile("cp.async.bulk.tensor.3d.shared::cluster.global.mbarrier::complete_tx::bytes.L2::cache_hint [%0], [%1, {%3, %4, %5}], [%2], %6;"
                 ::"r"(dst), "l"(m), "r"(bar), "r"(c0), "r"(c1), "r"(c2), "l"(pol) : "memory");
}
__device__ __forceinline__ void prefetch_tmap(const CUtensorMap* m) {
    asm volatile("prefetch.tensormap [%0];" ::"l"(m) : "memory");
}

__device__ __forceinline__ void ldsm4(uint32_t addr, uint32_t (&r)[4]) {
    asm volatile("ldmatrix.sync.aligned.m8n8.x4.shared.b16 {%0,%1,%2,%3}, [%4];"
                 : "=r"(r[0]), "=r"(r[1]), "=r"(r[2]), "=r"(r[3]) : "r"(addr) : "memory");
}
__device__ __forceinline__ void ldsm4t(uint32_t addr, uint32_t (&r)[4]) {
    asm volatile("ldmatrix.sync.aligned.m8n8.x4.trans.shared.b16 {%0,%1,%2,%3}, [%4];"
                 : "=r"(r[0]), "=r"(r[1]), "=r"(r[2]), "=r"(r[3]) : "r"(addr) : "memory");
}
__device__ __forceinline__ void mma16816(float (&c)[4], const uint32_t (&a)[4], uint32_t b0, uint32_t b1) {
    asm volatile("mma.sync.aligned.m16n8k16.row.col.f32.bf16.bf16.f32 {%0,%1,%2,%3}, {%4,%5,%6,%7}, {%8,%9}, {%0,%1,%2,%3};"
                 : "+f"(c[0]), "+f"(c[1]), "+f"(c[2]), "+f"(c[3])
                 : "r"(a[0]), "r"(a[1]), "r"(a[2]), "r"(a[3]), "r"(b0), "r"(b1));
}
__device__ __forceinline__ uint32_t movmatrix_t(uint32_t a) {
    uint32_t d;
    asm volatile("movmatrix.sync.aligned.m8n8.trans.b16 %0, %1;" : "=r"(d) : "r"(a));
    return d;
}
__device__ __forceinline__ uint32_t pack_bf16(float a, float b) {
    uint32_t r;
    asm("cvt.rn.bf16x2.f32 %0, %1, %2;" : "=r"(r) : "f"(b), "f"(a));
    return r;
}
__device__ __forceinline__ float bf_lo(uint32_t v) { return __uint_as_float(v << 16); }
__device__ __forceinline__ float bf_hi(uint32_t v) { return __uint_as_float(v & 0xffff0000u); }
__device__ __forceinline__ float bf16r(float a) { return bf_lo(pack_bf16(a, 0.f)); }
__device__ __forceinline__ uint32_t max_bf16x2(uint32_t a, uint32_t b) {
    uint32_t r;
    asm("max.bf16x2 %0, %1, %2;" : "=r"(r) : "r"(a), "r"(b));
    return r;
}
__device__ __forceinline__ float ex2(float x) {
    float r;
    asm("ex2.approx.ftz.f32 %0, %1;" : "=f"(r) : "f"(x));
    return r;
}

__device__ __forceinline__ void st_ll2(uint2* p, uint32_t v, uint32_t tag) {
    asm volatile("st.relaxed.gpu.global.v2.u32 [%0], {%1, %2};" ::"l"(p), "r"(v), "r"(tag) : "memory");
}
__device__ __forceinline__ void st_ll4(uint4* p, uint32_t v0, uint32_t v1, uint32_t tag) {
    asm volatile("st.relaxed.gpu.global.v4.u32 [%0], {%1, %2, %3, %2};" ::"l"(p), "r"(v0), "r"(tag), "r"(v1) : "memory");
}
__device__ __forceinline__ void st_v4(uint4* p, uint32_t a, uint32_t b, uint32_t c, uint32_t d) {
    asm volatile("st.relaxed.gpu.global.v4.u32 [%0], {%1, %2, %3, %4};" ::"l"(p), "r"(a), "r"(b), "r"(c), "r"(d) : "memory");
}
__device__ __forceinline__ uint2 ld_ll2(const uint2* p) {
    uint2 v;
    asm volatile("ld.relaxed.gpu.global.v2.u32 {%0, %1}, [%2];" : "=r"(v.x), "=r"(v.y) : "l"(p) : "memory");
    return v;
}
__device__ __forceinline__ uint4 ld_ll4(const uint4* p) {
    uint4 v;
    asm volatile("ld.relaxed.gpu.global.v4.u32 {%0, %1, %2, %3}, [%4];"
                 : "=r"(v.x), "=r"(v.y), "=r"(v.z), "=r"(v.w) : "l"(p) : "memory");
    return v;
}

#define DELAY_B1 300
#define DELAY_X1 2000
#define DELAY_NOFFN 1500
#define DELAY_C 600
__device__ __forceinline__ uint32_t clock32() {
    uint32_t c;
    asm volatile("mov.u32 %0, %clock;" : "=r"(c));
    return c;
}
__device__ __forceinline__ void spin_cycles(uint32_t n) {
    if (n > 0) { const uint32_t c0 = clock32(); while (clock32() - c0 < n) {} }
}
__device__ __forceinline__ float rcp_approx(float x) {
    float r;
    asm("rcp.approx.ftz.f32 %0, %1;" : "=f"(r) : "f"(x));
    return r;
}
__device__ __forceinline__ float sqrt_approx(float x) {
    float r;
    asm("sqrt.approx.f32 %0, %1;" : "=f"(r) : "f"(x));
    return r;
}

__device__ __forceinline__ float silu_bf(float v) { return bf16r(v / (1.0f + expf(-v))); }

__device__ __forceinline__ float2 half_warp_sums(const float (&v)[4], float pivot) {
    float s1 = 0.f, s2 = 0.f;
#pragma unroll
    for (int i = 0; i < 4; i++) { const float d = v[i] - pivot; s1 += d; s2 += d * d; }
#pragma unroll
    for (int o = 1; o < 16; o <<= 1) { s1 += __shfl_xor_sync(0xffffffffu, s1, o); s2 += __shfl_xor_sync(0xffffffffu, s2, o); }
    return make_float2(s1, s2);
}
__device__ __forceinline__ void ln_stats(const float2* stat, int b, float pivot, float& mean_bf, float& rstd) {
    float s1 = 0.f, s2 = 0.f;
#pragma unroll
    for (int w = 0; w < 8; w++) { const float2 v = stat[w * 2 + b]; s1 += v.x; s2 += v.y; }
    const float dm = s1 * (1.0f / D_MODEL);
    const float var = fmaxf(s2 * (1.0f / D_MODEL) - dm * dm, 0.f);
    mean_bf = bf16r(pivot + dm);
    rstd = rcp_approx(bf16r(sqrt_approx(bf16r(bf16r(var) + 1e-5f))));
}
__device__ __forceinline__ float ln_norm(float xv, float mean_bf, float rstd) { return bf16r(bf16r(xv - mean_bf) * rstd); }
__device__ __forceinline__ float ln_mod(float n, float cmul, float sadd) { return bf16r(n * bf16r(1.0f + cmul)) + sadd; }

__global__ void __launch_bounds__(NTHREADS, 1)
fused_block_kernel(const Params p, const __grid_constant__ CUtensorMap tm_k, const __grid_constant__ CUtensorMap tm_v,
                   const __grid_constant__ CUtensorMap tm_wq, const __grid_constant__ CUtensorMap tm_wmod,
                   const __grid_constant__ CUtensorMap tm_wmod8,
                   const __grid_constant__ CUtensorMap tm_wo, const __grid_constant__ CUtensorMap tm_wg,
                   const __grid_constant__ CUtensorMap tm_wu, const __grid_constant__ CUtensorMap tm_wd) {
    extern __shared__ unsigned char smem_raw[];
    const uint32_t sbase = (smem_u32(smem_raw) + 1023u) & ~1023u;
    unsigned char* sgen = smem_raw + (sbase - smem_u32(smem_raw));
    const int tid = threadIdx.x, warp = tid >> 5, lane = tid & 31;
    const int cta = blockIdx.x;
    const uint32_t bar_full = sbase + SM_BAR, bar_empty = bar_full + NST * 8;
    const uint32_t bar_clear = bar_empty + NST * 8;
    const uint32_t bar_gu = bar_clear + 8;
    const uint32_t bar_bc = bar_gu + 8 * 8;
    const uint32_t bar_p0w = bar_bc + 8;

    const int key0 = (cta >> 3) * SK + (cta & 7) * 64;
    uint64_t pol = 0;
    if (tid == 256) {
        asm volatile("createpolicy.fractional.L2::evict_first.b64 %0, 1.0;" : "=l"(pol));
        mbar_init(bar_p0w, 1);
#pragma unroll
        for (int i = 0; i < 4; i++) mbar_init(bar_full + 8 * i, 1);
        asm volatile("fence.mbarrier_init.release.cluster;" ::: "memory");
        mbar_expect_tx(bar_p0w, 8192);
        tma_2d(sbase + SM_MRG, &tm_wmod8, cta * 8, 0, bar_p0w);
        tma_2d(sbase + SM_MRG + 4096, &tm_wmod8, cta * 8, 256, bar_p0w);
#pragma unroll
        for (int i = 0; i < 4; i++) mbar_expect_tx(bar_full + 8 * i, TILE);
        tma_2d(sbase + SM_RING, &tm_wq, cta * 32, 0, bar_full);
        tma_2d(sbase + SM_RING + TILE, &tm_wq, cta * 32, 256, bar_full + 8);
        tma_3d_hint(sbase + SM_RING + 2 * TILE, &tm_k, 0, key0, 0, bar_full + 16, pol);
        tma_3d_hint(sbase + SM_RING + 3 * TILE, &tm_v, 0, key0, 0, bar_full + 24, pol);
    }

    if (warp == 8) {
        if (lane == 0) {
            for (int i = 0; i < NST; i++) { if (i >= 4) mbar_init(bar_full + 8 * i, 1); mbar_init(bar_empty + 8 * i, 4); }
            mbar_init(bar_clear, 1);
            for (int k = 0; k < 8; k++) mbar_init(bar_gu + 8 * k, 1);
            mbar_init(bar_bc, 8);
            ((volatile uint32_t*)(sgen + SM_PACE))[0] = 0;
            ((volatile uint32_t*)(sgen + SM_PACE))[1] = WINDOW;
            asm volatile("fence.mbarrier_init.release.cluster;" ::: "memory");
        }
        __syncwarp();
        asm volatile("bar.arrive 2, 320;" ::: "memory");
        asm volatile("bar.arrive 3, 64;" ::: "memory");
        if (lane == 0) {
            int slot = 4; uint32_t ph = 1;
            int landed = 0, wslot = 0; uint32_t wph = 0;
            int kv = 2;
            auto wait_window = [&](int idx, int window) {
                while (landed + window <= idx) {
                    mbar_wait(bar_full + 8 * wslot, wph);
                    if (++wslot == NST) { wslot = 0; wph ^= 1; }
                    landed++;
                }
            };
            volatile uint32_t* pace = (volatile uint32_t*)(sgen + SM_PACE);
            prefetch_tmap(&tm_wmod);
            pace[0] = 4;
            for (int idx = 4; idx < N_STREAM; idx++) {
                if (idx >= NST) mbar_wait(bar_empty + 8 * slot, ph);
                wait_window(idx, (int)pace[1]);
                if (idx == 12) { prefetch_tmap(&tm_wo); prefetch_tmap(&tm_wg); prefetch_tmap(&tm_wu); prefetch_tmap(&tm_wd); }
                const uint32_t fb = bar_full + 8 * slot, dst = sbase + SM_RING + slot * TILE;
                mbar_expect_tx(fb, TILE);
                if (idx == IDX_MOD) {
                    tma_2d(dst, &tm_wmod, 1024 + cta * 16, 0, fb);
                    tma_2d(dst + 8192, &tm_wmod, 1024 + cta * 16, 256, fb);
                } else {
                    tma_3d_hint(dst, (kv & 1) ? &tm_v : &tm_k, 0, key0 + (kv >> 1) * 512, 0, fb, pol);
                    kv++;
                }
                pace[0] = idx + 1;
                if (++slot == NST) { slot = 0; ph ^= 1; }
            }
            auto slot_free = [&](int idx) { mbar_wait(bar_empty + 8 * (idx % NST), ((idx / NST) & 1) ^ 1); };
#pragma unroll
            for (int s = 0; s < 2; s++) {
                const int idx = IDX_WO + s;
                slot_free(idx);
                wait_window(idx, WINDOW_TAIL);
                mbar_expect_tx(bar_full + 8 * (idx % NST), TILE);
                tma_3d(sbase + SM_RING + (idx % NST) * TILE, &tm_wo, 0, (cta >> 2) * 128 + s * 64, (cta & 3) * 2, bar_full + 8 * (idx % NST));
            }
            if (cta < NFFN) {
                slot_free(IDX_WG); slot_free(IDX_WU);
                mbar_wait(bar_full + 8 * (IDX_WO % NST), (IDX_WO / NST) & 1);
                mbar_wait(bar_full + 8 * ((IDX_WO + 1) % NST), ((IDX_WO + 1) / NST) & 1);
#pragma unroll
                for (int st = 0; st < 8; st++) {
                    if (st >= GU_WIN) mbar_wait(bar_gu + 8 * (st - GU_WIN), 0);
                    mbar_expect_tx(bar_gu + 8 * st, 4096);
                    tma_2d(sbase + SM_RING + (((st & 1) ? IDX_WU : IDX_WG) % NST) * TILE + (st >> 1) * 4096,
                           (st & 1) ? &tm_wu : &tm_wg, cta * 16, (st >> 1) * 128, bar_gu + 8 * st);
                }
                mbar_wait(bar_gu + 8 * 6, 0);
                slot_free(IDX_WD);
                mbar_expect_tx(bar_full + 8 * (IDX_WD % NST), TILE);
                tma_3d(sbase + SM_RING + (IDX_WD % NST) * TILE, &tm_wd, 0, cta * 16, 0, bar_full + 8 * (IDX_WD % NST));
            }
        }
    } else if (warp == 9) {
        Scratch* const sc = p.sc;
        const uint32_t tag = *(volatile unsigned*)&sc->epoch + 1;
        if (lane < 2) {
            st_ll4((uint4*)&sc->mod[lane][cta * 4], 0u, 0u, 0u);
            st_ll4((uint4*)&sc->mod[lane][cta * 4] + 1, 0u, 0u, 0u);
        }
        if (lane < 8) st_ll4((uint4*)&sc->mod[lane >> 2][512 + cta * 8] + (lane & 3), 0u, 0u, 0u);
        if (lane < 16) st_ll4((uint4*)&sc->q[lane >> 3][cta * 16] + (lane & 7), 0u, 0u, 0u);
        __syncwarp();
        asm volatile("bar.arrive 2, 320;" ::: "memory");
        asm volatile("bar.sync 3, 64;" ::: "memory");
#pragma unroll 4
        for (int i = 0; i < NFFN * 2 / 32; i++) st_v4(&sc->inbox_dn[cta][0][0] + i * 32 + lane, 0u, 0u, 0u, 0u);
        if (cta >= OWN0) {
#pragma unroll 4
            for (int i = 0; i < 16; i++) st_v4(&sc->inbox_wo[2 * (cta - OWN0)][0][0] + i * 32 + lane, 0u, 0u, 0u, 0u);
            if (lane < 16) st_v4((uint4*)&sc->x1[(cta - OWN0) * 32] + lane, 0u, 0u, 0u, 0u);
        }
#pragma unroll 4
        for (int i = 0; i < 4; i++) st_v4((uint4*)&sc->part_o[cta][0][0] + i * 32 + lane, 0u, 0u, 0u, 0u);
        if (lane < 8) st_v4((uint4*)&sc->part_ml[cta][0][0] + lane, 0u, 0u, 0u, 0u);
        if (cta == 0 && lane == 0) asm volatile("st.relaxed.gpu.global.u32 [%0], %1;" ::"l"(&sc->progress), "r"(0u) : "memory");
        asm volatile("fence.acq_rel.gpu;" ::: "memory");
        __syncwarp();
        if (lane == 0) {
            asm volatile("fence.acq_rel.gpu;" ::: "memory");
            asm volatile("red.relaxed.gpu.global.add.u32 [%0], %1;" ::"l"(&sc->cleared), "r"(1u) : "memory");
            const uint32_t target = tag * NCTA;
            for (int it = 0; it < SPIN_LIMIT; it++) {
                uint32_t v;
                asm volatile("ld.relaxed.gpu.global.u32 %0, [%1];" : "=r"(v) : "l"(&sc->cleared) : "memory");
                if ((int32_t)(v - target) >= 0) break;
                __nanosleep(500);
            }
            asm volatile("fence.acq_rel.gpu;" ::: "memory");
            mbar_arrive(bar_clear);
            volatile uint32_t* pace = (volatile uint32_t*)(sgen + SM_PACE);
            uint32_t posted = 0;
            for (int it = 0; it < SPIN_LIMIT; it++) {
                const uint32_t own = pace[0];
                if (own >= N_STREAM) break;
                if (own > posted) {
                    asm volatile("red.relaxed.gpu.global.add.u32 [%0], %1;" ::"l"(&sc->progress), "r"(own - posted) : "memory");
                    posted = own;
                }
                uint32_t v;
                asm volatile("ld.relaxed.gpu.global.u32 %0, [%1];" : "=r"(v) : "l"(&sc->progress) : "memory");
                const int diff = (int)v - (int)own * NCTA;
                pace[1] = diff > PACE_THR ? WINDOW + 1 : diff < -PACE_THR ? WINDOW - 1 : WINDOW;
                __nanosleep(200);
            }
            if (cta == 0) asm volatile("st.relaxed.gpu.global.u32 [%0], %1;" ::"l"(&sc->epoch), "r"(tag) : "memory");
        }
    } else {
        const int g = lane >> 2, t = lane & 3;
        const int bb = g & 1;
        const int eb = lane >> 4;
        const int ec = 64 * warp + 4 * (lane & 15);
        if (warp == 0) TSTAMP(0);
        Scratch* const sc = p.sc;
        const float c00 = __bfloat162float(p.c[tid]), c01 = __bfloat162float(p.c[tid + 256]);
        const float c10 = __bfloat162float(p.c[D_MODEL + tid]), c11 = __bfloat162float(p.c[D_MODEL + tid + 256]);
        const uint2 xe = __ldg((const uint2*)(p.x + eb * D_MODEL + ec));
        const float xpivot = __bfloat162float(p.x[eb * D_MODEL]);
        const uint32_t tag = *(volatile unsigned*)&sc->epoch + 1;
        const int ocol = cta * 4 + (lane & 3);
        const int wcol = (cta >= OWN0 ? 2 * (cta - OWN0) + (warp & 1) : 0) * 16 + (lane & 15);
        const float xo = __bfloat162float(p.x[eb * D_MODEL + wcol]);

        float* red = (float*)(sgen + SM_RED);
        float* red2 = (float*)(sgen + SM_RED2);
        float2* stat = (float2*)(sgen + SM_STAT);
        uint32_t* hs = (uint32_t*)(sgen + SM_HS) + warp * 64;
        float xn[4];
        {
            float xv[4] = {bf_lo(xe.x), bf_hi(xe.x), bf_lo(xe.y), bf_hi(xe.y)};
            const float2 ps = half_warp_sums(xv, xpivot);
            if ((lane & 15) == 0) stat[warp * 2 + eb] = ps;
            const float s00 = silu_bf(c00), s01 = silu_bf(c01), s10 = silu_bf(c10), s11 = silu_bf(c11);
            __nv_bfloat16* scs = (__nv_bfloat16*)(sgen + SM_SC);
            scs[tid] = __float2bfloat16_rn(s00); scs[tid + 256] = __float2bfloat16_rn(s01);
            scs[512 + tid] = __float2bfloat16_rn(s10); scs[512 + tid + 256] = __float2bfloat16_rn(s11);
            asm volatile("bar.sync 2, 320;" ::: "memory");
            if (warp == 0) TSTAMP(23);
            float cp[4] = {0.f, 0.f, 0.f, 0.f};
            const uint32_t* sc32 = (const uint32_t*)(sgen + SM_SC) + bb * 256 + 32 * warp + t;
            mbar_wait(bar_p0w, 0);
#pragma unroll
            for (int s = 0; s < 4; s++) {
                uint32_t r0, r1;
                asm volatile("ldmatrix.sync.aligned.m8n8.x2.trans.shared.b16 {%0,%1}, [%2];"
                             : "=r"(r0), "=r"(r1) : "r"(sbase + SM_MRG + (64 * warp + 16 * s + (lane & 15)) * 16) : "memory");
                const uint32_t a[4] = {r0, r0, r1, r1};
                mma16816(cp, a, sc32[8 * s], sc32[8 * s + 4]);
            }
            if (t == 0) { red[warp * 16 + g] = cp[0]; red[warp * 16 + 8 + g] = cp[1]; }
            if (warp == 0) TSTAMP(14);
            cons_sync();
            if (warp == 0) {
                float s = 0.f;
#pragma unroll
                for (int w = 0; w < 8; w++) s += red[w * 16 + (lane & 15)];
                const float nx = __shfl_down_sync(0xffffffffu, s, 1);
                if (lane < 16 && !(lane & 1))
                    st_ll2(&sc->mod[lane >> 3][cta * 4 + ((lane & 7) >> 1)], pack_bf16(s, nx), tag);
                TSTAMP(1);
            }
            float mean_bf, rstd;
            ln_stats(stat, eb, xpivot, mean_bf, rstd);
#pragma unroll
            for (int i = 0; i < 4; i++) xn[i] = ln_norm(xv[i], mean_bf, rstd);
        }
        {
            uint4 sa, ca;
            for (int it = 0;; it++) {
                sa = ld_ll4((const uint4*)&sc->mod[eb][ec >> 1]);
                ca = ld_ll4((const uint4*)&sc->mod[eb][256 + (ec >> 1)]);
                const bool ok = sa.y == tag && sa.w == tag && ca.y == tag && ca.w == tag;
                if (__all_sync(0xffffffffu, ok) || it > SPIN_LIMIT) break;
            }
            *(uint2*)&hs[eb * 32 + 2 * (lane & 15)] =
                make_uint2(pack_bf16(ln_mod(xn[0], bf_lo(ca.x), bf_lo(sa.x)), ln_mod(xn[1], bf_hi(ca.x), bf_hi(sa.x))),
                           pack_bf16(ln_mod(xn[2], bf_lo(ca.z), bf_lo(sa.z)), ln_mod(xn[3], bf_hi(ca.z), bf_hi(sa.z))));
            __syncwarp();
            uint32_t hb[8];
#pragma unroll
            for (int i = 0; i < 8; i++) hb[i] = hs[bb * 32 + 8 * (i >> 1) + 4 * (i & 1) + t];
            if (warp == 0) TSTAMP(2);
            float cq[2][4] = {};
            const int ts = warp >> 2;
            mbar_wait(bar_full + 8 * ts, 0);
            const uint32_t tb = sbase + SM_RING + ts * TILE;
#pragma unroll
            for (int s = 0; s < 4; s++) {
                const int row = 64 * (warp & 3) + 16 * s + (lane & 7) + (lane >> 4) * 8;
#pragma unroll
                for (int mt = 0; mt < 2; mt++) {
                    const int ch = 2 * mt + ((lane >> 3) & 1);
                    uint32_t a[4];
                    ldsm4t(tb + row * 64 + ((ch ^ ((row >> 1) & 3)) << 4), a);
                    mma16816(cq[mt], a, hb[2 * s], hb[2 * s + 1]);
                }
            }
            if (t < 2) {
                const float v0 = t == 0 ? cq[0][0] : cq[1][0], v1 = t == 0 ? cq[0][1] : cq[1][1];
                const float v2 = t == 0 ? cq[0][2] : cq[1][2], v3 = t == 0 ? cq[0][3] : cq[1][3];
                *(float2*)&red2[warp * 64 + (16 * t + g) * 2] = make_float2(v0, v1);
                *(float2*)&red2[warp * 64 + (16 * t + g + 8) * 2] = make_float2(v2, v3);
            }
            cons_sync();
            if (warp < 4 && lane == 0) { mbar_arrive(bar_empty); mbar_arrive(bar_empty + 8); }
            if (warp == 0) {
                const int b = lane >> 4, cp = lane & 15;
                float q0 = 0.f, q1 = 0.f;
#pragma unroll
                for (int w = 0; w < 8; w++) {
                    const float4 v = *(const float4*)&red2[w * 64 + cp * 4];
                    q0 += b ? v.y : v.x; q1 += b ? v.w : v.z;
                }
                st_ll2(&sc->q[b][cta * 16 + cp], pack_bf16(q0, q1), tag);
                TSTAMP(3);
            }
        }
        const int pair = cta >> 3;
        uint32_t qf[16];
        {
            uint2* qs = (uint2*)(sgen + SM_QS);
            if (tid < 128) {
                const uint4* src = (const uint4*)&sc->q[pair >> 3][(pair & 7) * 256] + tid;
                uint4 v;
                for (int it = 0;; it++) {
                    v = ld_ll4(src);
                    if ((v.y == tag && v.w == tag) || it > SPIN_LIMIT) break;
                }
                qs[tid] = make_uint2(v.x, v.z);
            }
            cons_sync();
            const uint32_t* q32 = (const uint32_t*)(sgen + SM_QS);
#pragma unroll
            for (int s = 0; s < 8; s++) {
                qf[2 * s] = q32[(g & 3) * 64 + 8 * s + t];
                qf[2 * s + 1] = q32[(g & 3) * 64 + 8 * s + 4 + t];
            }
        }
        if (warp == 0) TSTAMP(4);

        float o[8][4];
#pragma unroll
        for (int i = 0; i < 8; i++) { o[i][0] = o[i][1] = o[i][2] = o[i][3] = 0.f; }
        uint32_t mrun = 0xff80ff80u;
        float ls[4] = {0.f, 0.f, 0.f, 0.f};
        uint4 m_sb, m_cb; uint2 m_ga, m_gb0, m_gb1;
        {
            const int grp = warp >> 2, wi = warp & 3;
            const int krow = 16 * wi + (lane & 7) + ((lane >> 3) & 1) * 8;
            const uint32_t koff = krow * 128 + ((((lane >> 4) & 1) ^ (lane & 7)) << 4);
            const int vrow = 16 * wi + (lane & 7) + (lane >> 4) * 8;
            const uint32_t voff = vrow * 128 + ((((lane >> 3) & 1) ^ (lane & 7)) << 4);
            const uint32_t ones[4] = {0x3f803f80u, 0x3f803f80u, 0x3f803f80u, 0x3f803f80u};
            for (int i = grp; i < KV_TILES; i += 2) {
                if (i == MOD_AT + grp) {
                    float cm[4] = {};
                    const uint32_t* sc32 = (const uint32_t*)(sgen + SM_SC) + bb * 256 + 32 * warp + t;
                    mbar_wait(bar_full + 8 * (IDX_MOD % NST), (IDX_MOD / NST) & 1);
                    const uint32_t tb = sbase + SM_RING + (IDX_MOD % NST) * TILE;
#pragma unroll
                    for (int s = 0; s < 4; s++) {
                        const int row = 64 * warp + 16 * s + (lane & 7) + (lane >> 4) * 8;
                        const int ch = (lane >> 3) & 1;
                        uint32_t a[4];
                        ldsm4t(tb + row * 32 + ((ch ^ ((row >> 2) & 1)) << 4), a);
                        mma16816(cm, a, sc32[8 * s], sc32[8 * s + 4]);
                    }
                    if (t == 0) {
                        *(float2*)&red[warp * 64 + g * 2] = make_float2(cm[0], cm[1]);
                        *(float2*)&red[warp * 64 + (g + 8) * 2] = make_float2(cm[2], cm[3]);
                    }
                    cons_sync();
                    if (warp < 4 && lane == 0) mbar_arrive(bar_empty + 8 * (IDX_MOD % NST));
                    if (warp == 1 && lane < 16) {
                        const int b = lane >> 3, cp = lane & 7;
                        float q0 = 0.f, q1 = 0.f;
#pragma unroll
                        for (int w = 0; w < 8; w++) {
                            const float4 v = *(const float4*)&red[w * 64 + cp * 4];
                            q0 += b ? v.y : v.x; q1 += b ? v.w : v.z;
                        }
                        st_ll2(&sc->mod[b][512 + cta * 8 + cp], pack_bf16(q0, q1), tag);
                    }
                }
                if (i == 56 + grp) {
                    m_sb = ld_ll4((const uint4*)&sc->mod[eb][768 + (ec >> 1)]);
                    m_cb = ld_ll4((const uint4*)&sc->mod[eb][1024 + (ec >> 1)]);
                    m_ga = ld_ll2(&sc->mod[eb][512 + (wcol >> 1)]);
                    m_gb0 = ld_ll2(&sc->mod[0][1280 + (ocol >> 1)]); m_gb1 = ld_ll2(&sc->mod[1][1280 + (ocol >> 1)]);
                }
                if (i == 60 + grp) {
                    for (int it = 0;; it++) {
                        const bool ok = m_sb.y == tag && m_sb.w == tag && m_cb.y == tag && m_cb.w == tag &&
                                        m_ga.y == tag && m_gb0.y == tag && m_gb1.y == tag;
                        if (__all_sync(0xffffffffu, ok) || it > SPIN_LIMIT) break;
                        m_sb = ld_ll4((const uint4*)&sc->mod[eb][768 + (ec >> 1)]);
                        m_cb = ld_ll4((const uint4*)&sc->mod[eb][1024 + (ec >> 1)]);
                        m_ga = ld_ll2(&sc->mod[eb][512 + (wcol >> 1)]);
                        m_gb0 = ld_ll2(&sc->mod[0][1280 + (ocol >> 1)]); m_gb1 = ld_ll2(&sc->mod[1][1280 + (ocol >> 1)]);
                    }
                    mbar_wait(bar_clear, 0);
                }
                const int ki = kv_idx(i), ks = ki % NST, vs = (ki + 1) % NST;
                const uint32_t kph = (ki / NST) & 1, vph = ((ki + 1) / NST) & 1;
                mbar_wait(bar_full + 8 * ks, kph);
                const uint32_t kb = sbase + SM_RING + ks * TILE + koff;
                float sa[4] = {0.f, 0.f, 0.f, 0.f}, sb[4] = {0.f, 0.f, 0.f, 0.f};
#pragma unroll
                for (int s = 0; s < 8; s += 2) {
                    uint32_t a0[4], a1[4];
                    ldsm4((kb ^ ((s & 3) << 5)) + (s >> 2) * 8192, a0);
                    ldsm4((kb ^ (((s + 1) & 3) << 5)) + (s >> 2) * 8192, a1);
                    mma16816(sa, a0, qf[2 * s], qf[2 * s + 1]);
                    mma16816(sb, a1, qf[2 * s + 2], qf[2 * s + 3]);
                }
                __syncwarp();
                if (lane == 0) mbar_arrive(bar_empty + 8 * ks);
                uint32_t r01 = pack_bf16(sa[0] + sb[0], sa[1] + sb[1]);
                uint32_t r23 = pack_bf16(sa[2] + sb[2], sa[3] + sb[3]);
                r01 = pack_bf16(bf_lo(r01) * QK_SCALE, bf_hi(r01) * QK_SCALE);
                r23 = pack_bf16(bf_lo(r23) * QK_SCALE, bf_hi(r23) * QK_SCALE);
                uint32_t mx = max_bf16x2(r01, r23);
                mx = max_bf16x2(mx, __shfl_xor_sync(0xffffffffu, mx, 4));
                mx = max_bf16x2(mx, __shfl_xor_sync(0xffffffffu, mx, 8));
                mx = max_bf16x2(mx, __shfl_xor_sync(0xffffffffu, mx, 16));
                const uint32_t mnew = max_bf16x2(mrun, mx);
                const float m0 = bf_lo(mnew), m1 = bf_hi(mnew);
                if (__any_sync(0xffffffffu, mnew != mrun)) {
                    const float al0 = ex2((bf_lo(mrun) - m0) * LOG2E), al1 = ex2((bf_hi(mrun) - m1) * LOG2E);
                    ls[0] *= al0; ls[1] *= al1;
#pragma unroll
                    for (int d = 0; d < 8; d++) { o[d][0] *= al0; o[d][1] *= al1; o[d][2] *= al0; o[d][3] *= al1; }
                    mrun = mnew;
                }
                const float p0 = ex2((bf_lo(r01) - m0) * LOG2E), p1 = ex2((bf_hi(r01) - m1) * LOG2E);
                const float p2 = ex2((bf_lo(r23) - m0) * LOG2E), p3 = ex2((bf_hi(r23) - m1) * LOG2E);
                const uint32_t pb0 = movmatrix_t(pack_bf16(p0, p1)), pb1 = movmatrix_t(pack_bf16(p2, p3));
                mma16816(ls, ones, pb0, pb1);
                mbar_wait(bar_full + 8 * vs, vph);
                const uint32_t vb = sbase + SM_RING + vs * TILE + voff;
#pragma unroll
                for (int d = 0; d < 8; d++) {
                    uint32_t a[4];
                    ldsm4t((vb ^ ((d & 3) << 5)) + (d >> 2) * 8192, a);
                    mma16816(o[d], a, pb0, pb1);
                }
                __syncwarp();
                if (lane == 0) mbar_arrive(bar_empty + 8 * vs);
            }
        }
        if (warp == 7) TSTAMP(5);
        {
            float* mrg = (float*)(sgen + SM_MRG);
            float2* ml = (float2*)(sgen + SM_ML);
            {
                const int hp = (t & 1) * 2, up = t >> 1;
                if (g == 0 && up == 0) { ml[warp * 4 + hp] = make_float2(bf_lo(mrun), ls[0]); ml[warp * 4 + hp + 1] = make_float2(bf_hi(mrun), ls[1]); }
                float* m0p = mrg + (warp * 4 + hp) * 136 + up * 72 + g;
#pragma unroll
                for (int d = 0; d < 4; d++) {
                    m0p[16 * d] = up ? o[d + 4][0] : o[d][0]; m0p[136 + 16 * d] = up ? o[d + 4][1] : o[d][1];
                    m0p[16 * d + 8] = up ? o[d + 4][2] : o[d][2]; m0p[136 + 16 * d + 8] = up ? o[d + 4][3] : o[d][3];
                }
            }
            cons_sync();
            const int hh = tid >> 6, dp = tid & 63;
            float2 mw[8];
            float M = -INFINITY;
#pragma unroll
            for (int w = 0; w < 8; w++) { mw[w] = ml[w * 4 + hh]; M = fmaxf(M, mw[w].x); }
            float L = 0.f, o0 = 0.f, o1 = 0.f;
#pragma unroll
            for (int w = 0; w < 8; w++) {
                const float wt = ex2((mw[w].x - M) * LOG2E);
                const float2 v = *(const float2*)&mrg[(w * 4 + hh) * 136 + 2 * dp + (dp >= 32 ? 8 : 0)];
                L += wt * mw[w].y; o0 += wt * v.x; o1 += wt * v.y;
            }
            st_ll2(&sc->part_o[cta][hh][dp], tagf(o0, F_PART), tagf(o1, F_PART));
            if (dp < 4) st_ll2(&sc->part_ml[cta][hh][dp], tagf(M, F_PART), tagf(L, F_PART));
        }
        if (warp == 0) TSTAMP(6);
        {
            const int hq = cta >> 2, kvh = hq >> 2, hh = hq & 3;
            const int b = tid >> 7, dc = (tid >> 3) & 15, j = tid & 7;
            const int pc = (b * 8 + kvh) * 8 + j;
            const uint4* po = (const uint4*)&sc->part_o[pc][hh][0] + dc * 2;
            const uint2* pm = &sc->part_ml[pc - j][hh][0];
            uint4 vo0, vo1; uint2 vm[8];
            bool oko = false, okm = false;
            for (int it = 0;; it++) {
                if (!oko) { vo0 = ld_ll4(po); vo1 = ld_ll4(po + 1); }
                if (!okm) {
#pragma unroll
                    for (int jj = 0; jj < 8; jj++) vm[jj] = ld_ll2(pm + jj * 16);
                }
                oko = (vo0.x & vo0.y & vo0.z & vo0.w & vo1.x & vo1.y & vo1.z & vo1.w & 3u) == F_PART;
                uint32_t all = vm[0].x & vm[0].y;
#pragma unroll
                for (int jj = 1; jj < 8; jj++) all &= vm[jj].x & vm[jj].y;
                okm = (all & 3u) == F_PART;
                if (__all_sync(0xffffffffu, oko && okm) || it > SPIN_LIMIT) break;
            }
            float M = untag(vm[0].x);
#pragma unroll
            for (int jj = 1; jj < 8; jj++) M = fmaxf(M, untag(vm[jj].x));
            float wt = 0.f, L = 0.f;
#pragma unroll
            for (int jj = 0; jj < 8; jj++) {
                const float w_ = ex2((untag(vm[jj].x) - M) * LOG2E);
                L += w_ * untag(vm[jj].y);
                wt = jj == j ? w_ : wt;
            }
            wt *= rcp_approx(L);
            float v[8] = {wt * untag(vo0.x), wt * untag(vo0.y), wt * untag(vo0.z), wt * untag(vo0.w),
                          wt * untag(vo1.x), wt * untag(vo1.y), wt * untag(vo1.z), wt * untag(vo1.w)};
#define XRED(N, O)                                                                       \
            {                                                                            \
                const bool up = lane & (O);                                              \
                _Pragma("unroll") for (int i = 0; i < (N); i++) {                        \
                    const float send = up ? v[i] : v[i + (N)], keep = up ? v[i + (N)] : v[i]; \
                    v[i] = keep + __shfl_xor_sync(0xffffffffu, send, (O));               \
                }                                                                        \
            }
            XRED(4, 1) XRED(2, 2) XRED(1, 4)
#undef XRED
            __nv_bfloat16* os = (__nv_bfloat16*)(sgen + SM_OS);
            os[b * 128 + dc * 8 + 4 * (j & 1) + 2 * ((j >> 1) & 1) + (j >> 2)] = __float2bfloat16_rn(v[0]);
            if (warp == 0) TSTAMP(15);
            uint32_t wf[8][4];
            const uint32_t aoff_o = (warp >> 2) * 8192 + ((lane & 7) + (lane >> 4) * 8) * 128 +
                                    (((((warp & 3) * 2 + ((lane >> 3) & 1)) ^ (lane & 7))) << 4);
#pragma unroll
            for (int s = 0; s < 2; s++) {
                const int idx = IDX_WO + s;
                mbar_wait(bar_full + 8 * (idx % NST), (idx / NST) & 1);
                const uint32_t tb = sbase + SM_RING + (idx % NST) * TILE + aoff_o;
#pragma unroll
                for (int k4 = 0; k4 < 4; k4++) ldsm4t(tb + k4 * 2048, wf[s * 4 + k4]);
            }
            cons_sync();
            if (warp == 0) TSTAMP(7);
            const uint32_t* os32 = (const uint32_t*)(sgen + SM_OS) + bb * 64 + t;
            float y0[4] = {}, y1[4] = {};
#pragma unroll
            for (int ks = 0; ks < 8; ks += 2) {
                mma16816(y0, wf[ks], os32[8 * ks], os32[8 * ks + 4]);
                mma16816(y1, wf[ks + 1], os32[8 * ks + 8], os32[8 * ks + 12]);
            }
            if (t == 0)
                st_v4(&sc->inbox_wo[(cta & 3) * 8 + warp][hq][g], tagf(y0[0] + y1[0], F_WO), tagf(y0[1] + y1[1], F_WO),
                      tagf(y0[2] + y1[2], F_WO), tagf(y0[3] + y1[3], F_WO));
        }
        const uint32_t t_wo = clock32();
        if (warp == 0) TSTAMP(8);
        if (cta >= OWN0) {
            const uint4* pin = &sc->inbox_wo[2 * (cta - OWN0)][0][0] + tid;
            uint4 v[2];
            spin_cycles(DELAY_B1);
            bool ok0 = false, ok1 = false;
            for (int it = 0;; it++) {
                if (!ok0) v[0] = ld_ll4(pin);
                if (!ok1) v[1] = ld_ll4(pin + 256);
                ok0 = (v[0].x & v[0].y & v[0].z & v[0].w & 3u) == F_WO;
                ok1 = (v[1].x & v[1].y & v[1].z & v[1].w & 3u) == F_WO;
                if (__all_sync(0xffffffffu, ok0 && ok1) || it > SPIN_LIMIT) break;
            }
            const bool u1 = lane & 8, u2 = lane & 16;
#pragma unroll
            for (int q = 0; q < 2; q++) {
                const float a0 = untag(v[q].x), a1 = untag(v[q].y), a2 = untag(v[q].z), a3 = untag(v[q].w);
                const float k0 = (u1 ? a2 : a0) + __shfl_xor_sync(0xffffffffu, u1 ? a0 : a2, 8);
                const float k1 = (u1 ? a3 : a1) + __shfl_xor_sync(0xffffffffu, u1 ? a1 : a3, 8);
                (q ? red : red2)[warp * 32 + lane] = (u2 ? k1 : k0) + __shfl_xor_sync(0xffffffffu, u2 ? k0 : k1, 16);
            }
            cons_sync();
            if (warp < 2) {
                const float* rr = warp ? red : red2;
                float a = 0.f;
#pragma unroll
                for (int w = 0; w < 8; w++) a += rr[w * 32 + lane];
                const float ga = (wcol & 1) ? bf_hi(m_ga.x) : bf_lo(m_ga.x);
                const float xm = bf16r(xo + bf16r(ga * bf16r(a)));
                const float xm_b1 = __shfl_down_sync(0xffffffffu, xm, 16);
                if (lane < 16) st_ll2(&sc->x1[wcol], pack_bf16(xm, xm_b1), F_X1);
                if (warp == 0) TSTAMP(10);
            }
        }
        const uint32_t aoff = warp * 2048 + ((lane & 7) + (lane >> 4) * 8) * 128 + ((((lane >> 3) & 1) ^ (lane & 7)) << 4);
        if (cta < NFFN) {
            const uint4* px = (const uint4*)&sc->x1[ec];
            const uint4* pp = (const uint4*)&sc->x1[0];
            uint4 va, vb, pa, pb;
            uint32_t gf[4][4], uf[4][4];
            mbar_wait(bar_gu + 8 * (2 * (warp >> 1)), 0);
            mbar_wait(bar_gu + 8 * (2 * (warp >> 1) + 1), 0);
            {
                const uint32_t tg = sbase + SM_RING + (IDX_WG % NST) * TILE, tu = sbase + SM_RING + (IDX_WU % NST) * TILE;
#pragma unroll
                for (int s = 0; s < 4; s++) {
                    const int row = 64 * warp + 16 * s + (lane & 7) + (lane >> 4) * 8;
                    const uint32_t off = row * 32 + ((((lane >> 3) & 1) ^ ((row >> 2) & 1)) << 4);
                    ldsm4t(tg + off, gf[s]);
                    ldsm4t(tu + off, uf[s]);
                }
            }
            const float c1v[4] = {bf16r(1.0f + bf_lo(m_cb.x)), bf16r(1.0f + bf_hi(m_cb.x)), bf16r(1.0f + bf_lo(m_cb.z)), bf16r(1.0f + bf_hi(m_cb.z))};
            float bg = 0.f, cgc = 0.f, bu = 0.f, cuc = 0.f;
            {
                uint32_t* pre = (uint32_t*)(sgen + SM_MRG) + warp * 128;
                float* bc = (float*)(sgen + SM_MRG + 4096);
                *(uint2*)&pre[eb * 32 + 2 * (lane & 15)] = make_uint2(pack_bf16(c1v[0], c1v[1]), pack_bf16(c1v[2], c1v[3]));
                *(uint2*)&pre[64 + eb * 32 + 2 * (lane & 15)] = make_uint2(m_sb.x, m_sb.z);
                __syncwarp();
                float yg[4] = {}, yu[4] = {};
                const uint32_t* pb = pre + ((g >> 1) & 1) * 64 + bb * 32 + t;
#pragma unroll
                for (int s = 0; s < 4; s++) {
                    const uint32_t b0 = pb[8 * s], b1 = pb[8 * s + 4];
                    mma16816(yg, gf[s], b0, b1);
                    mma16816(yu, uf[s], b0, b1);
                }
                const float y0 = t < 2 ? yg[0] : yu[0], y1 = t < 2 ? yg[1] : yu[1], y2 = t < 2 ? yg[2] : yu[2], y3 = t < 2 ? yg[3] : yu[3];
                float* dstp = bc + warp * 128 + (t >> 1) * 64 + (t & 1) * 32;
                *(float2*)&dstp[g * 2] = make_float2(y0, y1);
                *(float2*)&dstp[(g + 8) * 2] = make_float2(y2, y3);
                __syncwarp();
                if (lane == 0) mbar_arrive(bar_bc);
            }
            if (warp == 0) TSTAMP(11);
            float pivot2;
            {
                while (clock32() - t_wo < DELAY_X1) {}
                bool okx = false, okp = false;
                for (int it = 0;; it++) {
                    if (!okx) { va = ld_ll4(px); vb = ld_ll4(px + 1); }
                    if (!okp) { pa = ld_ll4(pp); pb = ld_ll4(pp + 1); }
                    okx = va.y == F_X1 && va.w == F_X1 && vb.y == F_X1 && vb.w == F_X1;
                    okp = pa.y == F_X1 && pa.w == F_X1 && pb.y == F_X1 && pb.w == F_X1;
                    if (__all_sync(0xffffffffu, okx && okp) || it > SPIN_LIMIT) break;
                }
                if (warp == 0) TSTAMP(9);
                const float xv[4] = {eb ? bf_hi(va.x) : bf_lo(va.x), eb ? bf_hi(va.z) : bf_lo(va.z),
                                     eb ? bf_hi(vb.x) : bf_lo(vb.x), eb ? bf_hi(vb.z) : bf_lo(vb.z)};
                const float p0 = 0.25f * ((bf_lo(pa.x) + bf_lo(pa.z)) + (bf_lo(pb.x) + bf_lo(pb.z)));
                const float p1 = 0.25f * ((bf_hi(pa.x) + bf_hi(pa.z)) + (bf_hi(pb.x) + bf_hi(pb.z)));
                const float pivot = eb ? p1 : p0;
                pivot2 = (lane & 1) ? p1 : p0;
                *(uint2*)&hs[eb * 32 + 2 * (lane & 15)] =
                    make_uint2(pack_bf16((xv[0] - pivot) * c1v[0], (xv[1] - pivot) * c1v[1]),
                               pack_bf16((xv[2] - pivot) * c1v[2], (xv[3] - pivot) * c1v[3]));
                __syncwarp();
                float cg[2][4] = {}, cu[2][4] = {};
#pragma unroll
                for (int s = 0; s < 4; s++) {
                    const uint32_t b0 = hs[bb * 32 + 8 * s + t], b1 = hs[bb * 32 + 8 * s + 4 + t];
                    mma16816(cg[s & 1], gf[s], b0, b1);
                    mma16816(cu[s & 1], uf[s], b0, b1);
                }
                const float2 ps = half_warp_sums(xv, pivot);
                if ((lane & 15) == 0) stat[warp * 2 + eb] = ps;
                {
                    const float* bc = (const float*)(sgen + SM_MRG + 4096);
                    mbar_wait(bar_bc, 0);
#pragma unroll
                    for (int w = 0; w < 8; w++) {
                        bg += bc[w * 128 + lane]; cgc += bc[w * 128 + 32 + lane];
                        bu += bc[w * 128 + 64 + lane]; cuc += bc[w * 128 + 96 + lane];
                    }
                }
                if (t < 2) {
                    float v[4];
#pragma unroll
                    for (int i = 0; i < 4; i++) v[i] = t ? cu[0][i] + cu[1][i] : cg[0][i] + cg[1][i];
                    *(float2*)&red[warp * 64 + t * 32 + g * 2] = make_float2(v[0], v[1]);
                    *(float2*)&red[warp * 64 + t * 32 + (g + 8) * 2] = make_float2(v[2], v[3]);
                }
            }
            uint32_t df[4][4];
            mbar_wait(bar_full + 8 * (IDX_WD % NST), (IDX_WD / NST) & 1);
#pragma unroll
            for (int mt = 0; mt < 4; mt++) ldsm4t((sbase + SM_RING + (IDX_WD % NST) * TILE + aoff) ^ (mt << 5), df[mt]);
            cons_sync();
            {
                float gs = 0.f, us = 0.f;
#pragma unroll
                for (int w = 0; w < 8; w++) { gs += red[w * 64 + lane]; us += red[w * 64 + 32 + lane]; }
                float mean_bf, rstd;
                ln_stats(stat, lane & 1, pivot2, mean_bf, rstd);
                const float dm = mean_bf - pivot2;
                gs = bf16r(rstd * (gs - dm * bg) + cgc);
                us = rstd * (us - dm * bu) + cuc;
                const float u2 = gs * (1.0f + 0.044715f * gs * gs) * (2.0f * 0.7978845608028654f * LOG2E);
                const float ge = bf16r(__fdividef(gs, 1.0f + ex2(-u2)));
                const float act = bf16r(ge * bf16r(us));
                const float a0 = __shfl_sync(0xffffffffu, act, 4 * t + bb), a1 = __shfl_sync(0xffffffffu, act, 4 * t + 2 + bb);
                const float a2 = __shfl_sync(0xffffffffu, act, 4 * t + 16 + bb), a3 = __shfl_sync(0xffffffffu, act, 4 * t + 18 + bb);
                const uint32_t b0 = pack_bf16(a0, a1), b1 = pack_bf16(a2, a3);
                float y[4][4] = {};
#pragma unroll
                for (int mt = 0; mt < 4; mt++) mma16816(y[mt], df[mt], b0, b1);
                float v[4];
#pragma unroll
                for (int i = 0; i < 4; i++) v[i] = t == 0 ? y[0][i] : t == 1 ? y[1][i] : t == 2 ? y[2][i] : y[3][i];
            {
                const bool odd = g & 1;
                const float sx = odd ? v[0] : v[2], sy = odd ? v[1] : v[3];
                const float rx = __shfl_xor_sync(0xffffffffu, sx, 4), ry = __shfl_xor_sync(0xffffffffu, sy, 4);
                const int c0 = 64 * warp + 16 * t + (odd ? g + 7 : g);
                const float e0 = odd ? rx : v[0], e1 = odd ? ry : v[1], e2 = odd ? v[2] : rx, e3 = odd ? v[3] : ry;
                st_v4(&sc->inbox_dn[c0 >> 2][cta][(c0 >> 1) & 1], tagf(e0, F_DOWN), tagf(e1, F_DOWN), tagf(e2, F_DOWN), tagf(e3, F_DOWN));
            }
            }
            if (warp == 0) TSTAMP(12);
        }
        {
            uint2 xw;
            float r0;
            {
                const uint4* pin = &sc->inbox_dn[cta][0][0] + tid;
                uint4 v = make_uint4(F_DOWN, F_DOWN, F_DOWN, F_DOWN);
                if (cta < NFFN) spin_cycles(DELAY_C);
                else while (clock32() - t_wo < DELAY_X1 + DELAY_NOFFN) {}
                xw = ld_ll2(&sc->x1[ocol]);
                bool ok = tid >= NFFN * 2;
                for (int it = 0;; it++) {
                    if (!ok) {
                        v = ld_ll4(pin);
                        ok = (v.x & v.y & v.z & v.w & 3u) == F_DOWN;
                    }
                    if (__all_sync(0xffffffffu, ok) || it > SPIN_LIMIT) break;
                }
                const bool u1 = lane & 2, u2 = lane & 4;
                const float a0 = untag(v.x), a1 = untag(v.y), a2 = untag(v.z), a3 = untag(v.w);
                const float k0 = (u1 ? a1 : a0) + __shfl_xor_sync(0xffffffffu, u1 ? a0 : a1, 2);
                const float k1 = (u1 ? a3 : a2) + __shfl_xor_sync(0xffffffffu, u1 ? a2 : a3, 2);
                r0 = (u2 ? k1 : k0) + __shfl_xor_sync(0xffffffffu, u2 ? k0 : k1, 4);
                r0 += __shfl_xor_sync(0xffffffffu, r0, 8);
                r0 += __shfl_xor_sync(0xffffffffu, r0, 16);
                if (lane < 8) red2[256 + warp * 8 + (2 * (lane & 1) + ((lane >> 2) & 1)) * 2 + ((lane >> 1) & 1)] = r0;
            }
            cons_sync();
            if (warp == 0) {
                float a0 = 0.f, a1 = 0.f;
#pragma unroll
                for (int w = 0; w < 8; w++) { const float2 v = *(const float2*)&red2[256 + w * 8 + (lane & 3) * 2]; a0 += v.x; a1 += v.y; }
                const bool hi = ocol & 1;
                const float gb0 = hi ? bf_hi(m_gb0.x) : bf_lo(m_gb0.x), gb1 = hi ? bf_hi(m_gb1.x) : bf_lo(m_gb1.x);
                for (int it = 0; !__all_sync(0xffffffffu, xw.y == F_X1) && it < SPIN_LIMIT; it++) xw = ld_ll2(&sc->x1[ocol]);
                if (lane < 4) {
                    p.out[ocol] = __float2bfloat16_rn(bf_lo(xw.x) + bf16r(gb0 * bf16r(a0)));
                    p.out[D_MODEL + ocol] = __float2bfloat16_rn(bf_hi(xw.x) + bf16r(gb1 * bf16r(a1)));
                }
                TSTAMP(13);
            }
        }
    }
}

typedef CUresult (*EncodeFn)(CUtensorMap*, CUtensorMapDataType, cuuint32_t, void*, const cuuint64_t*, const cuuint64_t*,
                             const cuuint32_t*, const cuuint32_t*, CUtensorMapInterleave, CUtensorMapSwizzle,
                             CUtensorMapL2promotion, CUtensorMapFloatOOBfill);

struct Maps { CUtensorMap k, v, wq, wmod, wmod8, wo, wg, wu, wd; };

void encode(EncodeFn fn, CUtensorMap* m, const void* ptr, int rank, const cuuint64_t* dims, const cuuint64_t* strides,
            const cuuint32_t* box, CUtensorMapSwizzle sw) {
    const cuuint32_t es[3] = {1, 1, 1};
    fn(m, CU_TENSOR_MAP_DATA_TYPE_BFLOAT16, rank, const_cast<void*>(ptr), dims, strides, box, es,
       CU_TENSOR_MAP_INTERLEAVE_NONE, sw, CU_TENSOR_MAP_L2_PROMOTION_L2_256B, CU_TENSOR_MAP_FLOAT_OOB_FILL_NONE);
}

}

extern "C" void kernel_launch(void* const* d_in, const int* in_sizes, int n_in, void* d_out, int out_size) {
    (void)in_sizes; (void)n_in; (void)out_size;
    static EncodeFn enc = nullptr;
    static Scratch* scratch = nullptr;
    if (!enc) {
        cudaGetSymbolAddress((void**)&scratch, g_scratch);
        void* fn = nullptr;
        cudaDriverEntryPointQueryResult qr;
        cudaGetDriverEntryPoint("cuTensorMapEncodeTiled", &fn, cudaEnableDefault, &qr);
        enc = (EncodeFn)fn;
        cudaFuncSetAttribute(fused_block_kernel, cudaFuncAttributeMaxDynamicSharedMemorySize, SMEM_BYTES);
    }
    Maps m;
    {
        const cuuint64_t dims[3] = {64, (cuuint64_t)16 * SK, 2}, str[2] = {256, 128};
        const cuuint32_t box[3] = {64, 64, 2};
        encode(enc, &m.k, d_in[1], 3, dims, str, box, CU_TENSOR_MAP_SWIZZLE_128B);
        encode(enc, &m.v, d_in[2], 3, dims, str, box, CU_TENSOR_MAP_SWIZZLE_128B);
    }
    {
        const cuuint64_t dims[2] = {4096, 512}, str[1] = {8192};
        const cuuint32_t box[2] = {32, 256};
        encode(enc, &m.wq, d_in[3], 2, dims, str, box, CU_TENSOR_MAP_SWIZZLE_64B);
    }
    {
        const cuuint64_t dims[2] = {N_MOD, 512}, str[1] = {N_MOD * 2};
        const cuuint32_t box[2] = {16, 256};
        encode(enc, &m.wmod, d_in[10], 2, dims, str, box, CU_TENSOR_MAP_SWIZZLE_32B);
        const cuuint32_t box8[2] = {8, 256};
        encode(enc, &m.wmod8, d_in[10], 2, dims, str, box8, CU_TENSOR_MAP_SWIZZLE_NONE);
    }
    {
        const cuuint64_t dims_o[3] = {64, 4096, 8}, dims_d[3] = {64, D_FF, 8}, str[2] = {1024, 128};
        const cuuint32_t box[3] = {64, 16, 8}, box_o[3] = {64, 64, 2};
        encode(enc, &m.wo, d_in[4], 3, dims_o, str, box_o, CU_TENSOR_MAP_SWIZZLE_128B);
        encode(enc, &m.wd, d_in[8], 3, dims_d, str, box, CU_TENSOR_MAP_SWIZZLE_128B);
    }
    {
        const cuuint64_t dims[2] = {D_FF, 512}, str[1] = {D_FF * 2};
        const cuuint32_t box[2] = {16, 128};
        encode(enc, &m.wg, d_in[6], 2, dims, str, box, CU_TENSOR_MAP_SWIZZLE_32B);
        encode(enc, &m.wu, d_in[7], 2, dims, str, box, CU_TENSOR_MAP_SWIZZLE_32B);
    }
    Params p;
    p.x = (const __nv_bfloat16*)d_in[0];
    p.c = (const __nv_bfloat16*)d_in[9];
    p.out = (__nv_bfloat16*)d_out;
    p.sc = scratch;
    fused_block_kernel<<<NCTA, NTHREADS, SMEM_BYTES, cudaStreamPerThread>>>(p, m.k, m.v, m.wq, m.wmod, m.wmod8, m.wo, m.wg, m.wu, m.wd);
}
```

```cpp
#include <cuda_runtime.h>
#include <cuda.h>
#include <cuda_bf16.h>
#include <stdint.h>

namespace {

constexpr int D_MODEL = 512;
constexpr int N_HEADS = 32;
constexpr int SK = 32768;
constexpr int DH = 128;
constexpr int D_FF = 1792;
constexpr int N_MOD = 6 * D_MODEL;

constexpr int NCTA = 128;
constexpr int NFFN = D_FF / 16;
constexpr int NOWN = 32;
constexpr int NTHREADS = 320;
constexpr int NST = 12;
constexpr int TILE = 16384;
#define WINDOW 3
#define WINDOW_TAIL 1
#define GU_WIN 3
#define PACE_THR 96
constexpr int KV_TILES = 64;
#define MOD_AT 8
static_assert(MOD_AT % 2 == 0 && MOD_AT >= 2 && MOD_AT < 56, "schedule");
__host__ __device__ constexpr int kv_idx(int i) { return 2 + 2 * i + (i >= MOD_AT ? 1 : 0); }
constexpr int IDX_MOD = 2 + 2 * MOD_AT;
constexpr int N_STREAM = kv_idx(KV_TILES - 1) + 2;
constexpr int IDX_WO = N_STREAM;
constexpr int IDX_WG = IDX_WO + 2;
constexpr int IDX_WU = IDX_WG + 1;
constexpr int IDX_WD = IDX_WU + 1;
constexpr int SPIN_LIMIT = 1 << 20;

constexpr float LOG2E = 1.4426950408889634f;
constexpr float QK_SCALE = 0.08838834764831845f;

constexpr int SM_RING = 0;
constexpr int SM_MRG = SM_RING + NST * TILE;
constexpr int SM_ML = SM_MRG + 8 * 4 * 136 * 4;
constexpr int SM_RED = SM_ML + 8 * 4 * 8;
constexpr int SM_RED2 = SM_RED + 8 * 64 * 4;
constexpr int SM_QS = SM_RED2 + 8 * 64 * 4;
constexpr int SM_OS = SM_QS + 512 * 2;
constexpr int SM_SC = SM_OS + 2 * 128 * 2;
constexpr int SM_HS = SM_SC + 2 * 512 * 2;
constexpr int SM_STAT = SM_HS + 8 * 2 * 32 * 4;
constexpr int SM_PACE = SM_STAT + 8 * 2 * 8;
constexpr int SM_BAR = SM_PACE + 8;
constexpr int SM_END = SM_BAR + (2 * NST + 1 + 8 + 2) * 8;
constexpr int SMEM_BYTES = SM_END + 1024;

struct Scratch {
    uint4 inbox_wo[NOWN][N_HEADS][8];
    uint4 inbox_dn[NCTA][NFFN][2];
    uint2 x1[D_MODEL];
    uint2 part_o[NCTA][4][64];
    uint2 part_ml[NCTA][4][4];
    uint2 mod[2][N_MOD / 2];
    uint2 q[2][N_HEADS * DH / 2];
    unsigned epoch;
    unsigned pad_[31];
    unsigned cleared;
    unsigned pad2_[31];
    unsigned progress;
};
__device__ Scratch g_scratch;
constexpr uint32_t F_PART = 1, F_WO = 1, F_DOWN = 1, F_X1 = 1;
__device__ __forceinline__ uint32_t tagf(float v, uint32_t f) { return (__float_as_uint(v) & ~3u) | f; }
__device__ __forceinline__ float untag(uint32_t v) { return __uint_as_float(v & ~3u); }

struct Params {
    const __nv_bfloat16* x;
    const __nv_bfloat16* c;
    __nv_bfloat16* out;
    Scratch* sc;
};

#define TSTAMP(i) do { } while (0)

__device__ __forceinline__ uint32_t smem_u32(const void* p) { return (uint32_t)__cvta_generic_to_shared(p); }

__device__ __forceinline__ void mbar_init(uint32_t bar, uint32_t cnt) {
    asm volatile("mbarrier.init.shared::cta.b64 [%0], %1;" ::"r"(bar), "r"(cnt) : "memory");
}
__device__ __forceinline__ void mbar_expect_tx(uint32_t bar, uint32_t bytes) {
    asm volatile("mbarrier.arrive.expect_tx.shared::cta.b64 _, [%0], %1;" ::"r"(bar), "r"(bytes) : "memory");
}
__device__ __forceinline__ void mbar_arrive(uint32_t bar) {
    asm volatile("mbarrier.arrive.shared::cta.b64 _, [%0];" ::"r"(bar) : "memory");
}
__device__ __forceinline__ bool mbar_try(uint32_t bar, uint32_t parity) {
    uint32_t ok;
    asm volatile(
        "{\n\t.reg .pred p;\n\t"
        "mbarrier.try_wait.parity.shared::cta.b64 p, [%1], %2;\n\t"
        "selp.u32 %0, 1, 0, p;\n\t}"
        : "=r"(ok) : "r"(bar), "r"(parity) : "memory");
    return ok != 0;
}
__device__ __forceinline__ void mbar_wait(uint32_t bar, uint32_t parity) {
    if (mbar_try(bar, parity)) return;
    const long long t0 = clock64();
    while (!mbar_try(bar, parity))
        if (clock64() - t0 > (1ll << 31)) return;
}
__device__ __forceinline__ void cons_sync() { asm volatile("bar.sync 1, 256;" ::: "memory"); }

__device__ __forceinline__ void tma_2d(uint32_t dst, const CUtensorMap* m, int c0, int c1, uint32_t bar) {
    asm volatile("cp.async.bulk.tensor.2d.shared::cluster.global.mbarrier::complete_tx::bytes [%0], [%1, {%3, %4}], [%2];"
                 ::"r"(dst), "l"(m), "r"(bar), "r"(c0), "r"(c1) : "memory");
}
__device__ __forceinline__ void tma_3d(uint32_t dst, const CUtensorMap* m, int c0, int c1, int c2, uint32_t bar) {
    asm volatile("cp.async.bulk.tensor.3d.shared::cluster.global.mbarrier::complete_tx::bytes [%0], [%1, {%3, %4, %5}], [%2];"
                 ::"r"(dst), "l"(m), "r"(bar), "r"(c0), "r"(c1), "r"(c2) : "memory");
}
__device__ __forceinline__ void tma_3d_hint(uint32_t dst, const CUtensorMap* m, int c0, int c1, int c2, uint32_t bar, uint64_t pol) {
    asm volatile("cp.async.bulk.tensor.3d.shared::cluster.global.mbarrier::complete_tx::bytes.L2::cache_hint [%0], [%1, {%3, %4, %5}], [%2], %6;"
                 ::"r"(dst), "l"(m), "r"(bar), "r"(c0), "r"(c1), "r"(c2), "l"(pol) : "memory");
}
__device__ __forceinline__ void prefetch_tmap(const CUtensorMap* m) {
    asm volatile("prefetch.tensormap [%0];" ::"l"(m) : "memory");
}

__device__ __forceinline__ void ldsm4(uint32_t addr, uint32_t (&r)[4]) {
    asm volatile("ldmatrix.sync.aligned.m8n8.x4.shared.b16 {%0,%1,%2,%3}, [%4];"
                 : "=r"(r[0]), "=r"(r[1]), "=r"(r[2]), "=r"(r[3]) : "r"(addr) : "memory");
}
__device__ __forceinline__ void ldsm4t(uint32_t addr, uint32_t (&r)[4]) {
    asm volatile("ldmatrix.sync.aligned.m8n8.x4.trans.shared.b16 {%0,%1,%2,%3}, [%4];"
                 : "=r"(r[0]), "=r"(r[1]), "=r"(r[2]), "=r"(r[3]) : "r"(addr) : "memory");
}
__device__ __forceinline__ void mma16816(float (&c)[4], const uint32_t (&a)[4], uint32_t b0, uint32_t b1) {
    asm volatile("mma.sync.aligned.m16n8k16.row.col.f32.bf16.bf16.f32 {%0,%1,%2,%3}, {%4,%5,%6,%7}, {%8,%9}, {%0,%1,%2,%3};"
                 : "+f"(c[0]), "+f"(c[1]), "+f"(c[2]), "+f"(c[3])
                 : "r"(a[0]), "r"(a[1]), "r"(a[2]), "r"(a[3]), "r"(b0), "r"(b1));
}
__device__ __forceinline__ uint32_t movmatrix_t(uint32_t a) {
    uint32_t d;
    asm volatile("movmatrix.sync.aligned.m8n8.trans.b16 %0, %1;" : "=r"(d) : "r"(a));
    return d;
}
__device__ __forceinline__ uint32_t pack_bf16(float a, float b) {
    uint32_t r;
    asm("cvt.rn.bf16x2.f32 %0, %1, %2;" : "=r"(r) : "f"(b), "f"(a));
    return r;
}
__device__ __forceinline__ float bf_lo(uint32_t v) { return __uint_as_float(v << 16); }
__device__ __forceinline__ float bf_hi(uint32_t v) { return __uint_as_float(v & 0xffff0000u); }
__device__ __forceinline__ float bf16r(float a) { return bf_lo(pack_bf16(a, 0.f)); }
__device__ __forceinline__ uint32_t max_bf16x2(uint32_t a, uint32_t b) {
    uint32_t r;
    asm("max.bf16x2 %0, %1, %2;" : "=r"(r) : "r"(a), "r"(b));
    return r;
}
__device__ __forceinline__ float ex2(float x) {
    float r;
    asm("ex2.approx.ftz.f32 %0, %1;" : "=f"(r) : "f"(x));
    return r;
}

__device__ __forceinline__ void st_ll2(uint2* p, uint32_t v, uint32_t tag) {
    asm volatile("st.relaxed.gpu.global.v2.u32 [%0], {%1, %2};" ::"l"(p), "r"(v), "r"(tag) : "memory");
}
__device__ __forceinline__ void st_ll4(uint4* p, uint32_t v0, uint32_t v1, uint32_t tag) {
    asm volatile("st.relaxed.gpu.global.v4.u32 [%0], {%1, %2, %3, %2};" ::"l"(p), "r"(v0), "r"(tag), "r"(v1) : "memory");
}
__device__ __forceinline__ void st_v4(uint4* p, uint32_t a, uint32_t b, uint32_t c, uint32_t d) {
    asm volatile("st.relaxed.gpu.global.v4.u32 [%0], {%1, %2, %3, %4};" ::"l"(p), "r"(a), "r"(b), "r"(c), "r"(d) : "memory");
}
__device__ __forceinline__ uint2 ld_ll2(const uint2* p) {
    uint2 v;
    asm volatile("ld.relaxed.gpu.global.v2.u32 {%0, %1}, [%2];" : "=r"(v.x), "=r"(v.y) : "l"(p) : "memory");
    return v;
}
__device__ __forceinline__ uint4 ld_ll4(const uint4* p) {
    uint4 v;
    asm volatile("ld.relaxed.gpu.global.v4.u32 {%0, %1, %2, %3}, [%4];"
                 : "=r"(v.x), "=r"(v.y), "=r"(v.z), "=r"(v.w) : "l"(p) : "memory");
    return v;
}

#define DELAY_P1 0
#define DELAY_Q 0
#define DELAY_B1 300
#define DELAY_X1 2000
#define DELAY_NOFFN 1500
#define DELAY_C 600
__device__ __forceinline__ uint32_t clock32() {
    uint32_t c;
    asm volatile("mov.u32 %0, %clock;" : "=r"(c));
    return c;
}
__device__ __forceinline__ void spin_cycles(uint32_t n) {
    if (n > 0) { const uint32_t c0 = clock32(); while (clock32() - c0 < n) {} }
}
__device__ __forceinline__ float rcp_approx(float x) {
    float r;
    asm("rcp.approx.ftz.f32 %0, %1;" : "=f"(r) : "f"(x));
    return r;
}
__device__ __forceinline__ float sqrt_approx(float x) {
    float r;
    asm("sqrt.approx.f32 %0, %1;" : "=f"(r) : "f"(x));
    return r;
}

__device__ __forceinline__ float silu_bf(float v) { return bf16r(v / (1.0f + expf(-v))); }

__device__ __forceinline__ float2 half_warp_sums(const float (&v)[4], float pivot) {
    float s1 = 0.f, s2 = 0.f;
#pragma unroll
    for (int i = 0; i < 4; i++) { const float d = v[i] - pivot; s1 += d; s2 += d * d; }
#pragma unroll
    for (int o = 1; o < 16; o <<= 1) { s1 += __shfl_xor_sync(0xffffffffu, s1, o); s2 += __shfl_xor_sync(0xffffffffu, s2, o); }
    return make_float2(s1, s2);
}
__device__ __forceinline__ void ln_stats(const float2* stat, int b, float pivot, float& mean_bf, float& rstd) {
    float s1 = 0.f, s2 = 0.f;
#pragma unroll
    for (int w = 0; w < 8; w++) { const float2 v = stat[w * 2 + b]; s1 += v.x; s2 += v.y; }
    const float dm = s1 * (1.0f / D_MODEL);
    const float var = fmaxf(s2 * (1.0f / D_MODEL) - dm * dm, 0.f);
    mean_bf = bf16r(pivot + dm);
    rstd = rcp_approx(bf16r(sqrt_approx(bf16r(bf16r(var) + 1e-5f))));
}
__device__ __forceinline__ float ln_norm(float xv, float mean_bf, float rstd) { return bf16r(bf16r(xv - mean_bf) * rstd); }
__device__ __forceinline__ float ln_mod(float n, float cmul, float sadd) { return bf16r(n * bf16r(1.0f + cmul)) + sadd; }

__global__ void __launch_bounds__(NTHREADS, 1)
fused_block_kernel(const Params p, const __grid_constant__ CUtensorMap tm_k, const __grid_constant__ CUtensorMap tm_v,
                   const __grid_constant__ CUtensorMap tm_wq, const __grid_constant__ CUtensorMap tm_wmod,
                   const __grid_constant__ CUtensorMap tm_wmod8,
                   const __grid_constant__ CUtensorMap tm_wo, const __grid_constant__ CUtensorMap tm_wg,
                   const __grid_constant__ CUtensorMap tm_wu, const __grid_constant__ CUtensorMap tm_wd) {
    extern __shared__ unsigned char smem_raw[];
    const uint32_t sbase = (smem_u32(smem_raw) + 1023u) & ~1023u;
    unsigned char* sgen = smem_raw + (sbase - smem_u32(smem_raw));
    const int tid = threadIdx.x, warp = tid >> 5, lane = tid & 31;
    const int cta = blockIdx.x;
    const uint32_t bar_full = sbase + SM_BAR, bar_empty = bar_full + NST * 8;
    const uint32_t bar_clear = bar_empty + NST * 8;
    const uint32_t bar_gu = bar_clear + 8;
    const uint32_t bar_bc = bar_gu + 8 * 8;
    const uint32_t bar_p0w = bar_bc + 8;

    const int key0 = (cta >> 3) * SK + (cta & 7) * 64;
    uint64_t pol = 0;
    if (tid == 256) {
        asm volatile("createpolicy.fractional.L2::evict_first.b64 %0, 1.0;" : "=l"(pol));
        mbar_init(bar_p0w, 1);
#pragma unroll
        for (int i = 0; i < 4; i++) mbar_init(bar_full + 8 * i, 1);
        asm volatile("fence.mbarrier_init.release.cluster;" ::: "memory");
        mbar_expect_tx(bar_p0w, 8192);
        tma_2d(sbase + SM_MRG, &tm_wmod8, cta * 8, 0, bar_p0w);
        tma_2d(sbase + SM_MRG + 4096, &tm_wmod8, cta * 8, 256, bar_p0w);
#pragma unroll
        for (int i = 0; i < 4; i++) mbar_expect_tx(bar_full + 8 * i, TILE);
        tma_2d(sbase + SM_RING, &tm_wq, cta * 32, 0, bar_full);
        tma_2d(sbase + SM_RING + TILE, &tm_wq, cta * 32, 256, bar_full + 8);
        tma_3d_hint(sbase + SM_RING + 2 * TILE, &tm_k, 0, key0, 0, bar_full + 16, pol);
        tma_3d_hint(sbase + SM_RING + 3 * TILE, &tm_v, 0, key0, 0, bar_full + 24, pol);
    }

    if (warp == 8) {
        if (lane == 0) {
            for (int i = 0; i < NST; i++) { if (i >= 4) mbar_init(bar_full + 8 * i, 1); mbar_init(bar_empty + 8 * i, 4); }
            mbar_init(bar_clear, 1);
            for (int k = 0; k < 8; k++) mbar_init(bar_gu + 8 * k, 1);
            mbar_init(bar_bc, 8);
            ((volatile uint32_t*)(sgen + SM_PACE))[0] = 0;
            ((volatile uint32_t*)(sgen + SM_PACE))[1] = WINDOW;
            asm volatile("fence.mbarrier_init.release.cluster;" ::: "memory");
        }
        __syncwarp();
        asm volatile("bar.arrive 2, 320;" ::: "memory");
        asm volatile("bar.arrive 3, 64;" ::: "memory");
        if (lane == 0) {
            int slot = 4; uint32_t ph = 1;
            int landed = 0, wslot = 0; uint32_t wph = 0;
            int kv = 2;
            auto wait_window = [&](int idx, int window) {
                while (landed + window <= idx) {
                    mbar_wait(bar_full + 8 * wslot, wph);
                    if (++wslot == NST) { wslot = 0; wph ^= 1; }
                    landed++;
                }
            };
            volatile uint32_t* pace = (volatile uint32_t*)(sgen + SM_PACE);
            prefetch_tmap(&tm_wmod);
            pace[0] = 4;
            for (int idx = 4; idx < N_STREAM; idx++) {
                if (idx >= NST) mbar_wait(bar_empty + 8 * slot, ph);
                wait_window(idx, (int)pace[1]);
                if (idx == 12) { prefetch_tmap(&tm_wo); prefetch_tmap(&tm_wg); prefetch_tmap(&tm_wu); prefetch_tmap(&tm_wd); }
                const uint32_t fb = bar_full + 8 * slot, dst = sbase + SM_RING + slot * TILE;
                mbar_expect_tx(fb, TILE);
                if (idx == IDX_MOD) {
                    tma_2d(dst, &tm_wmod, 1024 + cta * 16, 0, fb);
                    tma_2d(dst + 8192, &tm_wmod, 1024 + cta * 16, 256, fb);
                } else {
                    tma_3d_hint(dst, (kv & 1) ? &tm_v : &tm_k, 0, key0 + (kv >> 1) * 512, 0, fb, pol);
                    kv++;
                }
                pace[0] = idx + 1;
                if (++slot == NST) { slot = 0; ph ^= 1; }
            }
            auto slot_free = [&](int idx) { mbar_wait(bar_empty + 8 * (idx % NST), ((idx / NST) & 1) ^ 1); };
#pragma unroll
            for (int s = 0; s < 2; s++) {
                const int idx = IDX_WO + s;
                slot_free(idx);
                wait_window(idx, WINDOW_TAIL);
                mbar_expect_tx(bar_full + 8 * (idx % NST), TILE);
                tma_3d(sbase + SM_RING + (idx % NST) * TILE, &tm_wo, 0, (cta >> 2) * 128 + s * 64, (cta & 3) * 2, bar_full + 8 * (idx % NST));
            }
            if (cta < NFFN) {
                slot_free(IDX_WG); slot_free(IDX_WU);
                mbar_wait(bar_full + 8 * (IDX_WO % NST), (IDX_WO / NST) & 1);
                mbar_wait(bar_full + 8 * ((IDX_WO + 1) % NST), ((IDX_WO + 1) / NST) & 1);
#pragma unroll
                for (int st = 0; st < 8; st++) {
                    if (st >= GU_WIN) mbar_wait(bar_gu + 8 * (st - GU_WIN), 0);
                    mbar_expect_tx(bar_gu + 8 * st, 4096);
                    tma_2d(sbase + SM_RING + (((st & 1) ? IDX_WU : IDX_WG) % NST) * TILE + (st >> 1) * 4096,
                           (st & 1) ? &tm_wu : &tm_wg, cta * 16, (st >> 1) * 128, bar_gu + 8 * st);
                }
                mbar_wait(bar_gu + 8 * 6, 0);
                slot_free(IDX_WD);
                mbar_expect_tx(bar_full + 8 * (IDX_WD % NST), TILE);
                tma_3d(sbase + SM_RING + (IDX_WD % NST) * TILE, &tm_wd, 0, cta * 16, 0, bar_full + 8 * (IDX_WD % NST));
            }
        }
    } else if (warp == 9) {
        Scratch* const sc = p.sc;
        const uint32_t tag = *(volatile unsigned*)&sc->epoch + 1;
        asm volatile("bar.arrive 2, 320;" ::: "memory");
        asm volatile("bar.sync 3, 64;" ::: "memory");
#pragma unroll 4
        for (int i = 0; i < NFFN * 2 / 32; i++) st_v4(&sc->inbox_dn[cta][0][0] + i * 32 + lane, 0u, 0u, 0u, 0u);
        if (cta >= NCTA - NOWN) {
#pragma unroll 4
            for (int i = 0; i < 8; i++) st_v4(&sc->inbox_wo[cta - (NCTA - NOWN)][0][0] + i * 32 + lane, 0u, 0u, 0u, 0u);
            if (lane < 8) st_v4((uint4*)&sc->x1[(cta - (NCTA - NOWN)) * 16] + lane, 0u, 0u, 0u, 0u);
        }
#pragma unroll 4
        for (int i = 0; i < 4; i++) st_v4((uint4*)&sc->part_o[cta][0][0] + i * 32 + lane, 0u, 0u, 0u, 0u);
        if (lane < 8) st_v4((uint4*)&sc->part_ml[cta][0][0] + lane, 0u, 0u, 0u, 0u);
        if (cta == 0 && lane == 0) asm volatile("st.relaxed.gpu.global.u32 [%0], %1;" ::"l"(&sc->progress), "r"(0u) : "memory");
        asm volatile("fence.acq_rel.gpu;" ::: "memory");
        __syncwarp();
        if (lane == 0) {
            asm volatile("fence.acq_rel.gpu;" ::: "memory");
            asm volatile("red.relaxed.gpu.global.add.u32 [%0], %1;" ::"l"(&sc->cleared), "r"(1u) : "memory");
            const uint32_t target = tag * NCTA;
            for (int it = 0; it < SPIN_LIMIT; it++) {
                uint32_t v;
                asm volatile("ld.relaxed.gpu.global.u32 %0, [%1];" : "=r"(v) : "l"(&sc->cleared) : "memory");
                if ((int32_t)(v - target) >= 0) break;
                __nanosleep(500);
            }
            asm volatile("fence.acq_rel.gpu;" ::: "memory");
            mbar_arrive(bar_clear);
            volatile uint32_t* pace = (volatile uint32_t*)(sgen + SM_PACE);
            uint32_t posted = 0;
            for (int it = 0; it < SPIN_LIMIT; it++) {
                const uint32_t own = pace[0];
                if (own >= N_STREAM) break;
                if (own > posted) {
                    asm volatile("red.relaxed.gpu.global.add.u32 [%0], %1;" ::"l"(&sc->progress), "r"(own - posted) : "memory");
                    posted = own;
                }
                uint32_t v;
                asm volatile("ld.relaxed.gpu.global.u32 %0, [%1];" : "=r"(v) : "l"(&sc->progress) : "memory");
                const int diff = (int)v - (int)own * NCTA;
                pace[1] = diff > PACE_THR ? WINDOW + 1 : diff < -PACE_THR ? WINDOW - 1 : WINDOW;
                __nanosleep(200);
            }
            if (cta == 0) asm volatile("st.relaxed.gpu.global.u32 [%0], %1;" ::"l"(&sc->epoch), "r"(tag) : "memory");
        }
    } else {
        const int g = lane >> 2, t = lane & 3;
        const int bb = g & 1;
        const int eb = lane >> 4;
        const int ec = 64 * warp + 4 * (lane & 15);
        if (warp == 0) TSTAMP(0);
        Scratch* const sc = p.sc;
        const float c00 = __bfloat162float(p.c[tid]), c01 = __bfloat162float(p.c[tid + 256]);
        const float c10 = __bfloat162float(p.c[D_MODEL + tid]), c11 = __bfloat162float(p.c[D_MODEL + tid + 256]);
        const uint2 xe = __ldg((const uint2*)(p.x + eb * D_MODEL + ec));
        const float xpivot = __bfloat162float(p.x[eb * D_MODEL]);
        const uint32_t tag = *(volatile unsigned*)&sc->epoch + 1;
        const int ocol = cta * 4 + (lane & 3);
        const int wcol = (cta >= NCTA - NOWN ? cta - (NCTA - NOWN) : 0) * 16 + (lane & 15);
        const float xo = __bfloat162float(p.x[eb * D_MODEL + wcol]);

        float* red = (float*)(sgen + SM_RED);
        float* red2 = (float*)(sgen + SM_RED2);
        float2* stat = (float2*)(sgen + SM_STAT);
        uint32_t* hs = (uint32_t*)(sgen + SM_HS) + warp * 64;
        float xn[4];
        {
            float xv[4] = {bf_lo(xe.x), bf_hi(xe.x), bf_lo(xe.y), bf_hi(xe.y)};
            const float2 ps = half_warp_sums(xv, xpivot);
            if ((lane & 15) == 0) stat[warp * 2 + eb] = ps;
            const float s00 = silu_bf(c00), s01 = silu_bf(c01), s10 = silu_bf(c10), s11 = silu_bf(c11);
            __nv_bfloat16* scs = (__nv_bfloat16*)(sgen + SM_SC);
            scs[tid] = __float2bfloat16_rn(s00); scs[tid + 256] = __float2bfloat16_rn(s01);
            scs[512 + tid] = __float2bfloat16_rn(s10); scs[512 + tid + 256] = __float2bfloat16_rn(s11);
            asm volatile("bar.sync 2, 320;" ::: "memory");
            if (warp == 0) TSTAMP(23);
            float cp[4] = {0.f, 0.f, 0.f, 0.f};
            const uint32_t* sc32 = (const uint32_t*)(sgen + SM_SC) + bb * 256 + 32 * warp + t;
            mbar_wait(bar_p0w, 0);
#pragma unroll
            for (int s = 0; s < 4; s++) {
                uint32_t r0, r1;
                asm volatile("ldmatrix.sync.aligned.m8n8.x2.trans.shared.b16 {%0,%1}, [%2];"
                             : "=r"(r0), "=r"(r1) : "r"(sbase + SM_MRG + (64 * warp + 16 * s + (lane & 15)) * 16) : "memory");
                const uint32_t a[4] = {r0, r0, r1, r1};
                mma16816(cp, a, sc32[8 * s], sc32[8 * s + 4]);
            }
            if (t == 0) { red[warp * 16 + g] = cp[0]; red[warp * 16 + 8 + g] = cp[1]; }
            if (warp == 0) TSTAMP(14);
            cons_sync();
            if (warp == 0) {
                float s = 0.f;
#pragma unroll
                for (int w = 0; w < 8; w++) s += red[w * 16 + (lane & 15)];
                const float nx = __shfl_down_sync(0xffffffffu, s, 1);
                if (lane < 16 && !(lane & 1))
                    st_ll2(&sc->mod[lane >> 3][cta * 4 + ((lane & 7) >> 1)], pack_bf16(s, nx), tag);
                TSTAMP(1);
            }
            float mean_bf, rstd;
            ln_stats(stat, eb, xpivot, mean_bf, rstd);
#pragma unroll
            for (int i = 0; i < 4; i++) xn[i] = ln_norm(xv[i], mean_bf, rstd);
        }
        {
            uint4 sa, ca;
            spin_cycles(DELAY_P1);
            for (int it = 0;; it++) {
                sa = ld_ll4((const uint4*)&sc->mod[eb][ec >> 1]);
                ca = ld_ll4((const uint4*)&sc->mod[eb][256 + (ec >> 1)]);
                const bool ok = sa.y == tag && sa.w == tag && ca.y == tag && ca.w == tag;
                if (__all_sync(0xffffffffu, ok) || it > SPIN_LIMIT) break;
            }
            *(uint2*)&hs[eb * 32 + 2 * (lane & 15)] =
                make_uint2(pack_bf16(ln_mod(xn[0], bf_lo(ca.x), bf_lo(sa.x)), ln_mod(xn[1], bf_hi(ca.x), bf_hi(sa.x))),
                           pack_bf16(ln_mod(xn[2], bf_lo(ca.z), bf_lo(sa.z)), ln_mod(xn[3], bf_hi(ca.z), bf_hi(sa.z))));
            __syncwarp();
            uint32_t hb[8];
#pragma unroll
            for (int i = 0; i < 8; i++) hb[i] = hs[bb * 32 + 8 * (i >> 1) + 4 * (i & 1) + t];
            if (warp == 0) TSTAMP(2);
            float cq[2][4] = {};
            const int ts = warp >> 2;
            mbar_wait(bar_full + 8 * ts, 0);
            const uint32_t tb = sbase + SM_RING + ts * TILE;
#pragma unroll
            for (int s = 0; s < 4; s++) {
                const int row = 64 * (warp & 3) + 16 * s + (lane & 7) + (lane >> 4) * 8;
#pragma unroll
                for (int mt = 0; mt < 2; mt++) {
                    const int ch = 2 * mt + ((lane >> 3) & 1);
                    uint32_t a[4];
                    ldsm4t(tb + row * 64 + ((ch ^ ((row >> 1) & 3)) << 4), a);
                    mma16816(cq[mt], a, hb[2 * s], hb[2 * s + 1]);
                }
            }
            if (t < 2) {
                const float v0 = t == 0 ? cq[0][0] : cq[1][0], v1 = t == 0 ? cq[0][1] : cq[1][1];
                const float v2 = t == 0 ? cq[0][2] : cq[1][2], v3 = t == 0 ? cq[0][3] : cq[1][3];
                *(float2*)&red2[warp * 64 + (16 * t + g) * 2] = make_float2(v0, v1);
                *(float2*)&red2[warp * 64 + (16 * t + g + 8) * 2] = make_float2(v2, v3);
            }
            cons_sync();
            if (warp < 4 && lane == 0) { mbar_arrive(bar_empty); mbar_arrive(bar_empty + 8); }
            if (warp == 0) {
                const int b = lane >> 4, cp = lane & 15;
                float q0 = 0.f, q1 = 0.f;
#pragma unroll
                for (int w = 0; w < 8; w++) {
                    const float4 v = *(const float4*)&red2[w * 64 + cp * 4];
                    q0 += b ? v.y : v.x; q1 += b ? v.w : v.z;
                }
                st_ll2(&sc->q[b][cta * 16 + cp], pack_bf16(q0, q1), tag);
                TSTAMP(3);
            }
        }
        const int pair = cta >> 3;
        uint32_t qf[16];
        {
            uint2* qs = (uint2*)(sgen + SM_QS);
            if (tid < 128) {
                const uint4* src = (const uint4*)&sc->q[pair >> 3][(pair & 7) * 256] + tid;
                uint4 v;
                spin_cycles(DELAY_Q);
                for (int it = 0;; it++) {
                    v = ld_ll4(src);
                    if ((v.y == tag && v.w == tag) || it > SPIN_LIMIT) break;
                }
                qs[tid] = make_uint2(v.x, v.z);
            }
            cons_sync();
            const uint32_t* q32 = (const uint32_t*)(sgen + SM_QS);
#pragma unroll
            for (int s = 0; s < 8; s++) {
                qf[2 * s] = q32[(g & 3) * 64 + 8 * s + t];
                qf[2 * s + 1] = q32[(g & 3) * 64 + 8 * s + 4 + t];
            }
        }
        if (warp == 0) TSTAMP(4);

        float o[8][4];
#pragma unroll
        for (int i = 0; i < 8; i++) { o[i][0] = o[i][1] = o[i][2] = o[i][3] = 0.f; }
        uint32_t mrun = 0xff80ff80u;
        float ls[4] = {0.f, 0.f, 0.f, 0.f};
        uint4 m_sb, m_cb; uint2 m_ga, m_gb0, m_gb1;
        {
            const int grp = warp >> 2, wi = warp & 3;
            const int krow = 16 * wi + (lane & 7) + ((lane >> 3) & 1) * 8;
            const uint32_t koff = krow * 128 + ((((lane >> 4) & 1) ^ (lane & 7)) << 4);
            const int vrow = 16 * wi + (lane & 7) + (lane >> 4) * 8;
            const uint32_t voff = vrow * 128 + ((((lane >> 3) & 1) ^ (lane & 7)) << 4);
            const uint32_t ones[4] = {0x3f803f80u, 0x3f803f80u, 0x3f803f80u, 0x3f803f80u};
            for (int i = grp; i < KV_TILES; i += 2) {
                if (i == MOD_AT + grp) {
                    float cm[4] = {};
                    const uint32_t* sc32 = (const uint32_t*)(sgen + SM_SC) + bb * 256 + 32 * warp + t;
                    mbar_wait(bar_full + 8 * (IDX_MOD % NST), (IDX_MOD / NST) & 1);
                    const uint32_t tb = sbase + SM_RING + (IDX_MOD % NST) * TILE;
#pragma unroll
                    for (int s = 0; s < 4; s++) {
                        const int row = 64 * warp + 16 * s + (lane & 7) + (lane >> 4) * 8;
                        const int ch = (lane >> 3) & 1;
                        uint32_t a[4];
                        ldsm4t(tb + row * 32 + ((ch ^ ((row >> 2) & 1)) << 4), a);
                        mma16816(cm, a, sc32[8 * s], sc32[8 * s + 4]);
                    }
                    if (t == 0) {
                        *(float2*)&red[warp * 64 + g * 2] = make_float2(cm[0], cm[1]);
                        *(float2*)&red[warp * 64 + (g + 8) * 2] = make_float2(cm[2], cm[3]);
                    }
                    cons_sync();
                    if (warp < 4 && lane == 0) mbar_arrive(bar_empty + 8 * (IDX_MOD % NST));
                    if (warp == 1 && lane < 16) {
                        const int b = lane >> 3, cp = lane & 7;
                        float q0 = 0.f, q1 = 0.f;
#pragma unroll
                        for (int w = 0; w < 8; w++) {
                            const float4 v = *(const float4*)&red[w * 64 + cp * 4];
                            q0 += b ? v.y : v.x; q1 += b ? v.w : v.z;
                        }
                        st_ll2(&sc->mod[b][512 + cta * 8 + cp], pack_bf16(q0, q1), tag);
                    }
                }
                if (i == 56 + grp) {
                    m_sb = ld_ll4((const uint4*)&sc->mod[eb][768 + (ec >> 1)]);
                    m_cb = ld_ll4((const uint4*)&sc->mod[eb][1024 + (ec >> 1)]);
                    m_ga = ld_ll2(&sc->mod[eb][512 + (wcol >> 1)]);
                    m_gb0 = ld_ll2(&sc->mod[0][1280 + (ocol >> 1)]); m_gb1 = ld_ll2(&sc->mod[1][1280 + (ocol >> 1)]);
                }
                if (i == 60 + grp) {
                    for (int it = 0;; it++) {
                        const bool ok = m_sb.y == tag && m_sb.w == tag && m_cb.y == tag && m_cb.w == tag &&
                                        m_ga.y == tag && m_gb0.y == tag && m_gb1.y == tag;
                        if (__all_sync(0xffffffffu, ok) || it > SPIN_LIMIT) break;
                        m_sb = ld_ll4((const uint4*)&sc->mod[eb][768 + (ec >> 1)]);
                        m_cb = ld_ll4((const uint4*)&sc->mod[eb][1024 + (ec >> 1)]);
                        m_ga = ld_ll2(&sc->mod[eb][512 + (wcol >> 1)]);
                        m_gb0 = ld_ll2(&sc->mod[0][1280 + (ocol >> 1)]); m_gb1 = ld_ll2(&sc->mod[1][1280 + (ocol >> 1)]);
                    }
                    mbar_wait(bar_clear, 0);
                }
                const int ki = kv_idx(i), ks = ki % NST, vs = (ki + 1) % NST;
                const uint32_t kph = (ki / NST) & 1, vph = ((ki + 1) / NST) & 1;
                mbar_wait(bar_full + 8 * ks, kph);
                const uint32_t kb = sbase + SM_RING + ks * TILE + koff;
                float sa[4] = {0.f, 0.f, 0.f, 0.f}, sb[4] = {0.f, 0.f, 0.f, 0.f};
#pragma unroll
                for (int s = 0; s < 8; s += 2) {
                    uint32_t a0[4], a1[4];
                    ldsm4((kb ^ ((s & 3) << 5)) + (s >> 2) * 8192, a0);
                    ldsm4((kb ^ (((s + 1) & 3) << 5)) + (s >> 2) * 8192, a1);
                    mma16816(sa, a0, qf[2 * s], qf[2 * s + 1]);
                    mma16816(sb, a1, qf[2 * s + 2], qf[2 * s + 3]);
                }
                __syncwarp();
                if (lane == 0) mbar_arrive(bar_empty + 8 * ks);
                uint32_t r01 = pack_bf16(sa[0] + sb[0], sa[1] + sb[1]);
                uint32_t r23 = pack_bf16(sa[2] + sb[2], sa[3] + sb[3]);
                r01 = pack_bf16(bf_lo(r01) * QK_SCALE, bf_hi(r01) * QK_SCALE);
                r23 = pack_bf16(bf_lo(r23) * QK_SCALE, bf_hi(r23) * QK_SCALE);
                uint32_t mx = max_bf16x2(r01, r23);
                mx = max_bf16x2(mx, __shfl_xor_sync(0xffffffffu, mx, 4));
                mx = max_bf16x2(mx, __shfl_xor_sync(0xffffffffu, mx, 8));
                mx = max_bf16x2(mx, __shfl_xor_sync(0xffffffffu, mx, 16));
                const uint32_t mnew = max_bf16x2(mrun, mx);
                const float m0 = bf_lo(mnew), m1 = bf_hi(mnew);
                if (__any_sync(0xffffffffu, mnew != mrun)) {
                    const float al0 = ex2((bf_lo(mrun) - m0) * LOG2E), al1 = ex2((bf_hi(mrun) - m1) * LOG2E);
                    ls[0] *= al0; ls[1] *= al1;
#pragma unroll
                    for (int d = 0; d < 8; d++) { o[d][0] *= al0; o[d][1] *= al1; o[d][2] *= al0; o[d][3] *= al1; }
                    mrun = mnew;
                }
                const float p0 = ex2((bf_lo(r01) - m0) * LOG2E), p1 = ex2((bf_hi(r01) - m1) * LOG2E);
                const float p2 = ex2((bf_lo(r23) - m0) * LOG2E), p3 = ex2((bf_hi(r23) - m1) * LOG2E);
                const uint32_t pb0 = movmatrix_t(pack_bf16(p0, p1)), pb1 = movmatrix_t(pack_bf16(p2, p3));
                mma16816(ls, ones, pb0, pb1);
                mbar_wait(bar_full + 8 * vs, vph);
                const uint32_t vb = sbase + SM_RING + vs * TILE + voff;
#pragma unroll
                for (int d = 0; d < 8; d++) {
                    uint32_t a[4];
                    ldsm4t((vb ^ ((d & 3) << 5)) + (d >> 2) * 8192, a);
                    mma16816(o[d], a, pb0, pb1);
                }
                __syncwarp();
                if (lane == 0) mbar_arrive(bar_empty + 8 * vs);
            }
        }
        if (warp == 7) TSTAMP(5);
        {
            float* mrg = (float*)(sgen + SM_MRG);
            float2* ml = (float2*)(sgen + SM_ML);
            {
                const int hp = (t & 1) * 2, up = t >> 1;
                if (g == 0 && up == 0) { ml[warp * 4 + hp] = make_float2(bf_lo(mrun), ls[0]); ml[warp * 4 + hp + 1] = make_float2(bf_hi(mrun), ls[1]); }
                float* m0p = mrg + (warp * 4 + hp) * 136 + up * 72 + g;
#pragma unroll
                for (int d = 0; d < 4; d++) {
                    m0p[16 * d] = up ? o[d + 4][0] : o[d][0]; m0p[136 + 16 * d] = up ? o[d + 4][1] : o[d][1];
                    m0p[16 * d + 8] = up ? o[d + 4][2] : o[d][2]; m0p[136 + 16 * d + 8] = up ? o[d + 4][3] : o[d][3];
                }
            }
            cons_sync();
            const int hh = tid >> 6, dp = tid & 63;
            float2 mw[8];
            float M = -INFINITY;
#pragma unroll
            for (int w = 0; w < 8; w++) { mw[w] = ml[w * 4 + hh]; M = fmaxf(M, mw[w].x); }
            float L = 0.f, o0 = 0.f, o1 = 0.f;
#pragma unroll
            for (int w = 0; w < 8; w++) {
                const float wt = ex2((mw[w].x - M) * LOG2E);
                const float2 v = *(const float2*)&mrg[(w * 4 + hh) * 136 + 2 * dp + (dp >= 32 ? 8 : 0)];
                L += wt * mw[w].y; o0 += wt * v.x; o1 += wt * v.y;
            }
            st_ll2(&sc->part_o[cta][hh][dp], tagf(o0, F_PART), tagf(o1, F_PART));
            if (dp < 4) st_ll2(&sc->part_ml[cta][hh][dp], tagf(M, F_PART), tagf(L, F_PART));
        }
        if (warp == 0) TSTAMP(6);
        {
            const int hq = cta >> 2, kvh = hq >> 2, hh = hq & 3;
            const int b = tid >> 7, dc = (tid >> 3) & 15, j = tid & 7;
            const int pc = (b * 8 + kvh) * 8 + j;
            const uint4* po = (const uint4*)&sc->part_o[pc][hh][0] + dc * 2;
            const uint2* pm = &sc->part_ml[pc - j][hh][0];
            uint4 vo0, vo1; uint2 vm[8];
            bool oko = false, okm = false;
            for (int it = 0;; it++) {
                if (!oko) { vo0 = ld_ll4(po); vo1 = ld_ll4(po + 1); }
                if (!okm) {
#pragma unroll
                    for (int jj = 0; jj < 8; jj++) vm[jj] = ld_ll2(pm + jj * 16);
                }
                oko = (vo0.x & vo0.y & vo0.z & vo0.w & vo1.x & vo1.y & vo1.z & vo1.w & 3u) == F_PART;
                uint32_t all = vm[0].x & vm[0].y;
#pragma unroll
                for (int jj = 1; jj < 8; jj++) all &= vm[jj].x & vm[jj].y;
                okm = (all & 3u) == F_PART;
                if (__all_sync(0xffffffffu, oko && okm) || it > SPIN_LIMIT) break;
            }
            float M = untag(vm[0].x);
#pragma unroll
            for (int jj = 1; jj < 8; jj++) M = fmaxf(M, untag(vm[jj].x));
            float wt = 0.f, L = 0.f;
#pragma unroll
            for (int jj = 0; jj < 8; jj++) {
                const float w_ = ex2((untag(vm[jj].x) - M) * LOG2E);
                L += w_ * untag(vm[jj].y);
                wt = jj == j ? w_ : wt;
            }
            wt *= rcp_approx(L);
            float v[8] = {wt * untag(vo0.x), wt * untag(vo0.y), wt * untag(vo0.z), wt * untag(vo0.w),
                          wt * untag(vo1.x), wt * untag(vo1.y), wt * untag(vo1.z), wt * untag(vo1.w)};
#define XRED(N, O)                                                                       \
            {                                                                            \
                const bool up = lane & (O);                                              \
                _Pragma("unroll") for (int i = 0; i < (N); i++) {                        \
                    const float send = up ? v[i] : v[i + (N)], keep = up ? v[i + (N)] : v[i]; \
                    v[i] = keep + __shfl_xor_sync(0xffffffffu, send, (O));               \
                }                                                                        \
            }
            XRED(4, 1) XRED(2, 2) XRED(1, 4)
#undef XRED
            __nv_bfloat16* os = (__nv_bfloat16*)(sgen + SM_OS);
            os[b * 128 + dc * 8 + 4 * (j & 1) + 2 * ((j >> 1) & 1) + (j >> 2)] = __float2bfloat16_rn(v[0]);
            if (warp == 0) TSTAMP(15);
            uint32_t wf[8][4];
            const uint32_t aoff_o = (warp >> 2) * 8192 + ((lane & 7) + (lane >> 4) * 8) * 128 +
                                    (((((warp & 3) * 2 + ((lane >> 3) & 1)) ^ (lane & 7))) << 4);
#pragma unroll
            for (int s = 0; s < 2; s++) {
                const int idx = IDX_WO + s;
                mbar_wait(bar_full + 8 * (idx % NST), (idx / NST) & 1);
                const uint32_t tb = sbase + SM_RING + (idx % NST) * TILE + aoff_o;
#pragma unroll
                for (int k4 = 0; k4 < 4; k4++) ldsm4t(tb + k4 * 2048, wf[s * 4 + k4]);
            }
            cons_sync();
            if (warp == 0) TSTAMP(7);
            const uint32_t* os32 = (const uint32_t*)(sgen + SM_OS) + bb * 64 + t;
            float y0[4] = {}, y1[4] = {};
#pragma unroll
            for (int ks = 0; ks < 8; ks += 2) {
                mma16816(y0, wf[ks], os32[8 * ks], os32[8 * ks + 4]);
                mma16816(y1, wf[ks + 1], os32[8 * ks + 8], os32[8 * ks + 12]);
            }
            if (t == 0)
                st_v4(&sc->inbox_wo[(cta & 3) * 8 + warp][hq][g], tagf(y0[0] + y1[0], F_WO), tagf(y0[1] + y1[1], F_WO),
                      tagf(y0[2] + y1[2], F_WO), tagf(y0[3] + y1[3], F_WO));
        }
        const uint32_t t_wo = clock32();
        if (warp == 0) TSTAMP(8);
        if (cta >= NCTA - NOWN) {
            const uint4* pin = &sc->inbox_wo[cta - (NCTA - NOWN)][0][0] + tid;
            uint4 v;
            spin_cycles(DELAY_B1);
            bool ok = false;
            for (int it = 0;; it++) {
                if (!ok) {
                    v = ld_ll4(pin);
                    ok = (v.x & v.y & v.z & v.w & 3u) == F_WO;
                }
                if (__all_sync(0xffffffffu, ok) || it > SPIN_LIMIT) break;
            }
            const bool u1 = lane & 8, u2 = lane & 16;
            const float a0 = untag(v.x), a1 = untag(v.y), a2 = untag(v.z), a3 = untag(v.w);
            const float k0 = (u1 ? a2 : a0) + __shfl_xor_sync(0xffffffffu, u1 ? a0 : a2, 8);
            const float k1 = (u1 ? a3 : a1) + __shfl_xor_sync(0xffffffffu, u1 ? a1 : a3, 8);
            red2[warp * 32 + lane] = (u2 ? k1 : k0) + __shfl_xor_sync(0xffffffffu, u2 ? k0 : k1, 16);
            cons_sync();
            if (warp == 0) {
                float a = 0.f;
#pragma unroll
                for (int w = 0; w < 8; w++) a += red2[w * 32 + lane];
                const float ga = (wcol & 1) ? bf_hi(m_ga.x) : bf_lo(m_ga.x);
                const float xm = bf16r(xo + bf16r(ga * bf16r(a)));
                const float xm_b1 = __shfl_down_sync(0xffffffffu, xm, 16);
                if (lane < 16) st_ll2(&sc->x1[wcol], pack_bf16(xm, xm_b1), F_X1);
                TSTAMP(10);
            }
        }
        const uint32_t aoff = warp * 2048 + ((lane & 7) + (lane >> 4) * 8) * 128 + ((((lane >> 3) & 1) ^ (lane & 7)) << 4);
        if (cta < NFFN) {
            const uint4* px = (const uint4*)&sc->x1[ec];
            const uint4* pp = (const uint4*)&sc->x1[0];
            uint4 va, vb, pa, pb;
            uint32_t gf[4][4], uf[4][4];
            mbar_wait(bar_gu + 8 * (2 * (warp >> 1)), 0);
            mbar_wait(bar_gu + 8 * (2 * (warp >> 1) + 1), 0);
            {
                const uint32_t tg = sbase + SM_RING + (IDX_WG % NST) * TILE, tu = sbase + SM_RING + (IDX_WU % NST) * TILE;
#pragma unroll
                for (int s = 0; s < 4; s++) {
                    const int row = 64 * warp + 16 * s + (lane & 7) + (lane >> 4) * 8;
                    const uint32_t off = row * 32 + ((((lane >> 3) & 1) ^ ((row >> 2) & 1)) << 4);
                    ldsm4t(tg + off, gf[s]);
                    ldsm4t(tu + off, uf[s]);
                }
            }
            const float c1v[4] = {bf16r(1.0f + bf_lo(m_cb.x)), bf16r(1.0f + bf_hi(m_cb.x)), bf16r(1.0f + bf_lo(m_cb.z)), bf16r(1.0f + bf_hi(m_cb.z))};
            float bg = 0.f, cgc = 0.f, bu = 0.f, cuc = 0.f;
            {
                uint32_t* pre = (uint32_t*)(sgen + SM_MRG) + warp * 128;
                float* bc = (float*)(sgen + SM_MRG + 4096);
                *(uint2*)&pre[eb * 32 + 2 * (lane & 15)] = make_uint2(pack_bf16(c1v[0], c1v[1]), pack_bf16(c1v[2], c1v[3]));
                *(uint2*)&pre[64 + eb * 32 + 2 * (lane & 15)] = make_uint2(m_sb.x, m_sb.z);
                __syncwarp();
                float yg[4] = {}, yu[4] = {};
                const uint32_t* pb = pre + ((g >> 1) & 1) * 64 + bb * 32 + t;
#pragma unroll
                for (int s = 0; s < 4; s++) {
                    const uint32_t b0 = pb[8 * s], b1 = pb[8 * s + 4];
                    mma16816(yg, gf[s], b0, b1);
                    mma16816(yu, uf[s], b0, b1);
                }
                const float y0 = t < 2 ? yg[0] : yu[0], y1 = t < 2 ? yg[1] : yu[1], y2 = t < 2 ? yg[2] : yu[2], y3 = t < 2 ? yg[3] : yu[3];
                float* dstp = bc + warp * 128 + (t >> 1) * 64 + (t & 1) * 32;
                *(float2*)&dstp[g * 2] = make_float2(y0, y1);
                *(float2*)&dstp[(g + 8) * 2] = make_float2(y2, y3);
                __syncwarp();
                if (lane == 0) mbar_arrive(bar_bc);
            }
            if (warp == 0) TSTAMP(11);
            float pivot2;
            {
                while (clock32() - t_wo < DELAY_X1) {}
                bool okx = false, okp = false;
                for (int it = 0;; it++) {
                    if (!okx) { va = ld_ll4(px); vb = ld_ll4(px + 1); }
                    if (!okp) { pa = ld_ll4(pp); pb = ld_ll4(pp + 1); }
                    okx = va.y == F_X1 && va.w == F_X1 && vb.y == F_X1 && vb.w == F_X1;
                    okp = pa.y == F_X1 && pa.w == F_X1 && pb.y == F_X1 && pb.w == F_X1;
                    if (__all_sync(0xffffffffu, okx && okp) || it > SPIN_LIMIT) break;
                }
                if (warp == 0) TSTAMP(9);
                const float xv[4] = {eb ? bf_hi(va.x) : bf_lo(va.x), eb ? bf_hi(va.z) : bf_lo(va.z),
                                     eb ? bf_hi(vb.x) : bf_lo(vb.x), eb ? bf_hi(vb.z) : bf_lo(vb.z)};
                const float p0 = 0.25f * ((bf_lo(pa.x) + bf_lo(pa.z)) + (bf_lo(pb.x) + bf_lo(pb.z)));
                const float p1 = 0.25f * ((bf_hi(pa.x) + bf_hi(pa.z)) + (bf_hi(pb.x) + bf_hi(pb.z)));
                const float pivot = eb ? p1 : p0;
                pivot2 = (lane & 1) ? p1 : p0;
                *(uint2*)&hs[eb * 32 + 2 * (lane & 15)] =
                    make_uint2(pack_bf16((xv[0] - pivot) * c1v[0], (xv[1] - pivot) * c1v[1]),
                               pack_bf16((xv[2] - pivot) * c1v[2], (xv[3] - pivot) * c1v[3]));
                __syncwarp();
                float cg[2][4] = {}, cu[2][4] = {};
#pragma unroll
                for (int s = 0; s < 4; s++) {
                    const uint32_t b0 = hs[bb * 32 + 8 * s + t], b1 = hs[bb * 32 + 8 * s + 4 + t];
                    mma16816(cg[s & 1], gf[s], b0, b1);
                    mma16816(cu[s & 1], uf[s], b0, b1);
                }
                const float2 ps = half_warp_sums(xv, pivot);
                if ((lane & 15) == 0) stat[warp * 2 + eb] = ps;
                {
                    const float* bc = (const float*)(sgen + SM_MRG + 4096);
                    mbar_wait(bar_bc, 0);
#pragma unroll
                    for (int w = 0; w < 8; w++) {
                        bg += bc[w * 128 + lane]; cgc += bc[w * 128 + 32 + lane];
                        bu += bc[w * 128 + 64 + lane]; cuc += bc[w * 128 + 96 + lane];
                    }
                }
                if (t < 2) {
                    float v[4];
#pragma unroll
                    for (int i = 0; i < 4; i++) v[i] = t ? cu[0][i] + cu[1][i] : cg[0][i] + cg[1][i];
                    *(float2*)&red[warp * 64 + t * 32 + g * 2] = make_float2(v[0], v[1]);
                    *(float2*)&red[warp * 64 + t * 32 + (g + 8) * 2] = make_float2(v[2], v[3]);
                }
            }
            uint32_t df[4][4];
            mbar_wait(bar_full + 8 * (IDX_WD % NST), (IDX_WD / NST) & 1);
#pragma unroll
            for (int mt = 0; mt < 4; mt++) ldsm4t((sbase + SM_RING + (IDX_WD % NST) * TILE + aoff) ^ (mt << 5), df[mt]);
            cons_sync();
            {
                float gs = 0.f, us = 0.f;
#pragma unroll
                for (int w = 0; w < 8; w++) { gs += red[w * 64 + lane]; us += red[w * 64 + 32 + lane]; }
                float mean_bf, rstd;
                ln_stats(stat, lane & 1, pivot2, mean_bf, rstd);
                const float dm = mean_bf - pivot2;
                gs = bf16r(rstd * (gs - dm * bg) + cgc);
                us = rstd * (us - dm * bu) + cuc;
                const float u2 = gs * (1.0f + 0.044715f * gs * gs) * (2.0f * 0.7978845608028654f * LOG2E);
                const float ge = bf16r(__fdividef(gs, 1.0f + ex2(-u2)));
                const float act = bf16r(ge * bf16r(us));
                const float a0 = __shfl_sync(0xffffffffu, act, 4 * t + bb), a1 = __shfl_sync(0xffffffffu, act, 4 * t + 2 + bb);
                const float a2 = __shfl_sync(0xffffffffu, act, 4 * t + 16 + bb), a3 = __shfl_sync(0xffffffffu, act, 4 * t + 18 + bb);
                const uint32_t b0 = pack_bf16(a0, a1), b1 = pack_bf16(a2, a3);
                float y[4][4] = {};
#pragma unroll
                for (int mt = 0; mt < 4; mt++) mma16816(y[mt], df[mt], b0, b1);
                float v[4];
#pragma unroll
                for (int i = 0; i < 4; i++) v[i] = t == 0 ? y[0][i] : t == 1 ? y[1][i] : t == 2 ? y[2][i] : y[3][i];
            {
                const bool odd = g & 1;
                const float sx = odd ? v[0] : v[2], sy = odd ? v[1] : v[3];
                const float rx = __shfl_xor_sync(0xffffffffu, sx, 4), ry = __shfl_xor_sync(0xffffffffu, sy, 4);
                const int c0 = 64 * warp + 16 * t + (odd ? g + 7 : g);
                const float e0 = odd ? rx : v[0], e1 = odd ? ry : v[1], e2 = odd ? v[2] : rx, e3 = odd ? v[3] : ry;
                st_v4(&sc->inbox_dn[c0 >> 2][cta][(c0 >> 1) & 1], tagf(e0, F_DOWN), tagf(e1, F_DOWN), tagf(e2, F_DOWN), tagf(e3, F_DOWN));
            }
            }
            if (warp == 0) TSTAMP(12);
        }
        {
            uint2 xw;
            float r0;
            {
                const uint4* pin = &sc->inbox_dn[cta][0][0] + tid;
                uint4 v = make_uint4(F_DOWN, F_DOWN, F_DOWN, F_DOWN);
                if (cta < NFFN) spin_cycles(DELAY_C);
                else while (clock32() - t_wo < DELAY_X1 + DELAY_NOFFN) {}
                xw = ld_ll2(&sc->x1[ocol]);
                bool ok = tid >= NFFN * 2;
                for (int it = 0;; it++) {
                    if (!ok) {
                        v = ld_ll4(pin);
                        ok = (v.x & v.y & v.z & v.w & 3u) == F_DOWN;
                    }
                    if (__all_sync(0xffffffffu, ok) || it > SPIN_LIMIT) break;
                }
                const bool u1 = lane & 2, u2 = lane & 4;
                const float a0 = untag(v.x), a1 = untag(v.y), a2 = untag(v.z), a3 = untag(v.w);
                const float k0 = (u1 ? a1 : a0) + __shfl_xor_sync(0xffffffffu, u1 ? a0 : a1, 2);
                const float k1 = (u1 ? a3 : a2) + __shfl_xor_sync(0xffffffffu, u1 ? a2 : a3, 2);
                r0 = (u2 ? k1 : k0) + __shfl_xor_sync(0xffffffffu, u2 ? k0 : k1, 4);
                r0 += __shfl_xor_sync(0xffffffffu, r0, 8);
                r0 += __shfl_xor_sync(0xffffffffu, r0, 16);
                if (lane < 8) red2[256 + warp * 8 + (2 * (lane & 1) + ((lane >> 2) & 1)) * 2 + ((lane >> 1) & 1)] = r0;
            }
            cons_sync();
            if (warp == 0) {
                float a0 = 0.f, a1 = 0.f;
#pragma unroll
                for (int w = 0; w < 8; w++) { const float2 v = *(const float2*)&red2[256 + w * 8 + (lane & 3) * 2]; a0 += v.x; a1 += v.y; }
                const bool hi = ocol & 1;
                const float gb0 = hi ? bf_hi(m_gb0.x) : bf_lo(m_gb0.x), gb1 = hi ? bf_hi(m_gb1.x) : bf_lo(m_gb1.x);
                for (int it = 0; !__all_sync(0xffffffffu, xw.y == F_X1) && it < SPIN_LIMIT; it++) xw = ld_ll2(&sc->x1[ocol]);
                if (lane < 4) {
                    p.out[ocol] = __float2bfloat16_rn(bf_lo(xw.x) + bf16r(gb0 * bf16r(a0)));
                    p.out[D_MODEL + ocol] = __float2bfloat16_rn(bf_hi(xw.x) + bf16r(gb1 * bf16r(a1)));
                }
                TSTAMP(13);
            }
        }
    }
}

typedef CUresult (*EncodeFn)(CUtensorMap*, CUtensorMapDataType, cuuint32_t, void*, const cuuint64_t*, const cuuint64_t*,
                             const cuuint32_t*, const cuuint32_t*, CUtensorMapInterleave, CUtensorMapSwizzle,
                             CUtensorMapL2promotion, CUtensorMapFloatOOBfill);

struct Maps { CUtensorMap k, v, wq, wmod, wmod8, wo, wg, wu, wd; };

void encode(EncodeFn fn, CUtensorMap* m, const void* ptr, int rank, const cuuint64_t* dims, const cuuint64_t* strides,
            const cuuint32_t* box, CUtensorMapSwizzle sw) {
    const cuuint32_t es[3] = {1, 1, 1};
    fn(m, CU_TENSOR_MAP_DATA_TYPE_BFLOAT16, rank, const_cast<void*>(ptr), dims, strides, box, es,
       CU_TENSOR_MAP_INTERLEAVE_NONE, sw, CU_TENSOR_MAP_L2_PROMOTION_L2_256B, CU_TENSOR_MAP_FLOAT_OOB_FILL_NONE);
}

}

extern "C" void kernel_launch(void* const* d_in, const int* in_sizes, int n_in, void* d_out, int out_size) {
    (void)in_sizes; (void)n_in; (void)out_size;
    static EncodeFn enc = nullptr;
    static Scratch* scratch = nullptr;
    if (!enc) {
        cudaGetSymbolAddress((void**)&scratch, g_scratch);
        void* fn = nullptr;
        cudaDriverEntryPointQueryResult qr;
        cudaGetDriverEntryPoint("cuTensorMapEncodeTiled", &fn, cudaEnableDefault, &qr);
        enc = (EncodeFn)fn;
        cudaFuncSetAttribute(fused_block_kernel, cudaFuncAttributeMaxDynamicSharedMemorySize, SMEM_BYTES);
    }
    Maps m;
    {
        const cuuint64_t dims[3] = {64, (cuuint64_t)16 * SK, 2}, str[2] = {256, 128};
        const cuuint32_t box[3] = {64, 64, 2};
        encode(enc, &m.k, d_in[1], 3, dims, str, box, CU_TENSOR_MAP_SWIZZLE_128B);
        encode(enc, &m.v, d_in[2], 3, dims, str, box, CU_TENSOR_MAP_SWIZZLE_128B);
    }
    {
        const cuuint64_t dims[2] = {4096, 512}, str[1] = {8192};
        const cuuint32_t box[2] = {32, 256};
        encode(enc, &m.wq, d_in[3], 2, dims, str, box, CU_TENSOR_MAP_SWIZZLE_64B);
    }
    {
        const cuuint64_t dims[2] = {N_MOD, 512}, str[1] = {N_MOD * 2};
        const cuuint32_t box[2] = {16, 256};
        encode(enc, &m.wmod, d_in[10], 2, dims, str, box, CU_TENSOR_MAP_SWIZZLE_32B);
        const cuuint32_t box8[2] = {8, 256};
        encode(enc, &m.wmod8, d_in[10], 2, dims, str, box8, CU_TENSOR_MAP_SWIZZLE_NONE);
    }
    {
        const cuuint64_t dims_o[3] = {64, 4096, 8}, dims_d[3] = {64, D_FF, 8}, str[2] = {1024, 128};
        const cuuint32_t box[3] = {64, 16, 8}, box_o[3] = {64, 64, 2};
        encode(enc, &m.wo, d_in[4], 3, dims_o, str, box_o, CU_TENSOR_MAP_SWIZZLE_128B);
        encode(enc, &m.wd, d_in[8], 3, dims_d, str, box, CU_TENSOR_MAP_SWIZZLE_128B);
    }
    {
        const cuuint64_t dims[2] = {D_FF, 512}, str[1] = {D_FF * 2};
        const cuuint32_t box[2] = {16, 128};
        encode(enc, &m.wg, d_in[6], 2, dims, str, box, CU_TENSOR_MAP_SWIZZLE_32B);
        encode(enc, &m.wu, d_in[7], 2, dims, str, box, CU_TENSOR_MAP_SWIZZLE_32B);
    }
    Params p;
    p.x = (const __nv_bfloat16*)d_in[0];
    p.c = (const __nv_bfloat16*)d_in[9];
    p.out = (__nv_bfloat16*)d_out;
    p.sc = scratch;
    fused_block_kernel<<<NCTA, NTHREADS, SMEM_BYTES, cudaStreamPerThread>>>(p, m.k, m.v, m.wq, m.wmod, m.wmod8, m.wo, m.wg, m.wu, m.wd);
}
```

```cpp
#include <cuda_runtime.h>
#include <cuda.h>
#include <cuda_bf16.h>
#include <stdint.h>

namespace {

constexpr int D_MODEL = 512;
constexpr int N_HEADS = 32;
constexpr int SK = 32768;
constexpr int DH = 128;
constexpr int D_FF = 1792;
constexpr int N_MOD = 6 * D_MODEL;

constexpr int NCTA = 128;
constexpr int NFFN = D_FF / 16;
constexpr int NOWN = 32;
constexpr int NTHREADS = 320;
constexpr int NST = 12;
constexpr int TILE = 16384;
#define WINDOW 3
#define WINDOW_TAIL 1
#define GU_WIN 3
#define PACE_THR 96
constexpr int KV_TILES = 64;
#define MOD_AT 8
static_assert(MOD_AT % 2 == 0 && MOD_AT >= 2 && MOD_AT < 56, "schedule");
__host__ __device__ constexpr int kv_idx(int i) { return 2 + 2 * i + (i >= MOD_AT ? 1 : 0); }
constexpr int IDX_MOD = 2 + 2 * MOD_AT;
constexpr int N_STREAM = kv_idx(KV_TILES - 1) + 2;
constexpr int IDX_WO = N_STREAM;
constexpr int IDX_WG = IDX_WO + 2;
constexpr int IDX_WU = IDX_WG + 1;
constexpr int IDX_WD = IDX_WU + 1;
constexpr int SPIN_LIMIT = 1 << 20;

constexpr float LOG2E = 1.4426950408889634f;
constexpr float QK_SCALE = 0.08838834764831845f;

constexpr int SM_RING = 0;
constexpr int SM_MRG = SM_RING + NST * TILE;
constexpr int SM_ML = SM_MRG + 8 * 4 * 136 * 4;
constexpr int SM_RED = SM_ML + 8 * 4 * 8;
constexpr int SM_RED2 = SM_RED + 8 * 64 * 4;
constexpr int SM_QS = SM_RED2 + 8 * 64 * 4;
constexpr int SM_OS = SM_QS + 512 * 2;
constexpr int SM_SC = SM_OS + 2 * 128 * 2;
constexpr int SM_HS = SM_SC + 2 * 512 * 2;
constexpr int SM_STAT = SM_HS + 8 * 2 * 32 * 4;
constexpr int SM_PACE = SM_STAT + 8 * 2 * 8;
constexpr int SM_BAR = SM_PACE + 8;
constexpr int SM_END = SM_BAR + (2 * NST + 1 + 8 + 2) * 8;
constexpr int SMEM_BYTES = SM_END + 1024;

struct Scratch {
    uint4 inbox_wo[NOWN][N_HEADS][8];
    uint4 inbox_dn[NCTA][NFFN][2];
    uint2 x1[D_MODEL];
    uint2 part_o[NCTA][4][64];
    uint2 part_ml[NCTA][4][4];
    uint2 mod[2][N_MOD / 2];
    uint2 q[2][N_HEADS * DH / 2];
    unsigned epoch;
    unsigned pad_[31];
    unsigned cleared;
    unsigned pad2_[31];
    unsigned progress;
};
__device__ Scratch g_scratch;
constexpr uint32_t F_PART = 1, F_WO = 1, F_DOWN = 1, F_X1 = 1;
__device__ __forceinline__ uint32_t tagf(float v, uint32_t f) { return (__float_as_uint(v) & ~3u) | f; }
__device__ __forceinline__ float untag(uint32_t v) { return __uint_as_float(v & ~3u); }

struct Params {
    const __nv_bfloat16* x;
    const __nv_bfloat16* c;
    __nv_bfloat16* out;
    Scratch* sc;
};

#define TSTAMP(i) do { } while (0)

__device__ __forceinline__ uint32_t smem_u32(const void* p) { return (uint32_t)__cvta_generic_to_shared(p); }

__device__ __forceinline__ void mbar_init(uint32_t bar, uint32_t cnt) {
    asm volatile("mbarrier.init.shared::cta.b64 [%0], %1;" ::"r"(bar), "r"(cnt) : "memory");
}
__device__ __forceinline__ void mbar_expect_tx(uint32_t bar, uint32_t bytes) {
    asm volatile("mbarrier.arrive.expect_tx.shared::cta.b64 _, [%0], %1;" ::"r"(bar), "r"(bytes) : "memory");
}
__device__ __forceinline__ void mbar_arrive(uint32_t bar) {
    asm volatile("mbarrier.arrive.shared::cta.b64 _, [%0];" ::"r"(bar) : "memory");
}
__device__ __forceinline__ bool mbar_try(uint32_t bar, uint32_t parity) {
    uint32_t ok;
    asm volatile(
        "{\n\t.reg .pred p;\n\t"
        "mbarrier.try_wait.parity.shared::cta.b64 p, [%1], %2;\n\t"
        "selp.u32 %0, 1, 0, p;\n\t}"
        : "=r"(ok) : "r"(bar), "r"(parity) : "memory");
    return ok != 0;
}
__device__ __forceinline__ void mbar_wait(uint32_t bar, uint32_t parity) {
    if (mbar_try(bar, parity)) return;
    const long long t0 = clock64();
    while (!mbar_try(bar, parity))
        if (clock64() - t0 > (1ll << 31)) return;
}
__device__ __forceinline__ void cons_sync() { asm volatile("bar.sync 1, 256;" ::: "memory"); }

__device__ __forceinline__ void tma_2d(uint32_t dst, const CUtensorMap* m, int c0, int c1, uint32_t bar) {
    asm volatile("cp.async.bulk.tensor.2d.shared::cluster.global.mbarrier::complete_tx::bytes [%0], [%1, {%3, %4}], [%2];"
                 ::"r"(dst), "l"(m), "r"(bar), "r"(c0), "r"(c1) : "memory");
}
__device__ __forceinline__ void tma_3d(uint32_t dst, const CUtensorMap* m, int c0, int c1, int c2, uint32_t bar) {
    asm volatile("cp.async.bulk.tensor.3d.shared::cluster.global.mbarrier::complete_tx::bytes [%0], [%1, {%3, %4, %5}], [%2];"
                 ::"r"(dst), "l"(m), "r"(bar), "r"(c0), "r"(c1), "r"(c2) : "memory");
}
__device__ __forceinline__ void tma_3d_hint(uint32_t dst, const CUtensorMap* m, int c0, int c1, int c2, uint32_t bar, uint64_t pol) {
    asm volatile("cp.async.bulk.tensor.3d.shared::cluster.global.mbarrier::complete_tx::bytes.L2::cache_hint [%0], [%1, {%3, %4, %5}], [%2], %6;"
                 ::"r"(dst), "l"(m), "r"(bar), "r"(c0), "r"(c1), "r"(c2), "l"(pol) : "memory");
}
__device__ __forceinline__ void prefetch_tmap(const CUtensorMap* m) {
    asm volatile("prefetch.tensormap [%0];" ::"l"(m) : "memory");
}

__device__ __forceinline__ void ldsm4(uint32_t addr, uint32_t (&r)[4]) {
    asm volatile("ldmatrix.sync.aligned.m8n8.x4.shared.b16 {%0,%1,%2,%3}, [%4];"
                 : "=r"(r[0]), "=r"(r[1]), "=r"(r[2]), "=r"(r[3]) : "r"(addr) : "memory");
}
__device__ __forceinline__ void ldsm4t(uint32_t addr, uint32_t (&r)[4]) {
    asm volatile("ldmatrix.sync.aligned.m8n8.x4.trans.shared.b16 {%0,%1,%2,%3}, [%4];"
                 : "=r"(r[0]), "=r"(r[1]), "=r"(r[2]), "=r"(r[3]) : "r"(addr) : "memory");
}
__device__ __forceinline__ void mma16816(float (&c)[4], const uint32_t (&a)[4], uint32_t b0, uint32_t b1) {
    asm volatile("mma.sync.aligned.m16n8k16.row.col.f32.bf16.bf16.f32 {%0,%1,%2,%3}, {%4,%5,%6,%7}, {%8,%9}, {%0,%1,%2,%3};"
                 : "+f"(c[0]), "+f"(c[1]), "+f"(c[2]), "+f"(c[3])
                 : "r"(a[0]), "r"(a[1]), "r"(a[2]), "r"(a[3]), "r"(b0), "r"(b1));
}
__device__ __forceinline__ uint32_t movmatrix_t(uint32_t a) {
    uint32_t d;
    asm volatile("movmatrix.sync.aligned.m8n8.trans.b16 %0, %1;" : "=r"(d) : "r"(a));
    return d;
}
__device__ __forceinline__ uint32_t pack_bf16(float a, float b) {
    uint32_t r;
    asm("cvt.rn.bf16x2.f32 %0, %1, %2;" : "=r"(r) : "f"(b), "f"(a));
    return r;
}
__device__ __forceinline__ float bf_lo(uint32_t v) { return __uint_as_float(v << 16); }
__device__ __forceinline__ float bf_hi(uint32_t v) { return __uint_as_float(v & 0xffff0000u); }
__device__ __forceinline__ float bf16r(float a) { return bf_lo(pack_bf16(a, 0.f)); }
__device__ __forceinline__ uint32_t max_bf16x2(uint32_t a, uint32_t b) {
    uint32_t r;
    asm("max.bf16x2 %0, %1, %2;" : "=r"(r) : "r"(a), "r"(b));
    return r;
}
__device__ __forceinline__ float ex2(float x) {
    float r;
    asm("ex2.approx.ftz.f32 %0, %1;" : "=f"(r) : "f"(x));
    return r;
}

__device__ __forceinline__ void st_ll2(uint2* p, uint32_t v, uint32_t tag) {
    asm volatile("st.relaxed.gpu.global.v2.u32 [%0], {%1, %2};" ::"l"(p), "r"(v), "r"(tag) : "memory");
}
__device__ __forceinline__ void st_v4(uint4* p, uint32_t a, uint32_t b, uint32_t c, uint32_t d) {
    asm volatile("st.relaxed.gpu.global.v4.u32 [%0], {%1, %2, %3, %4};" ::"l"(p), "r"(a), "r"(b), "r"(c), "r"(d) : "memory");
}
__device__ __forceinline__ uint2 ld_ll2(const uint2* p) {
    uint2 v;
    asm volatile("ld.relaxed.gpu.global.v2.u32 {%0, %1}, [%2];" : "=r"(v.x), "=r"(v.y) : "l"(p) : "memory");
    return v;
}
__device__ __forceinline__ uint4 ld_ll4(const uint4* p) {
    uint4 v;
    asm volatile("ld.relaxed.gpu.global.v4.u32 {%0, %1, %2, %3}, [%4];"
                 : "=r"(v.x), "=r"(v.y), "=r"(v.z), "=r"(v.w) : "l"(p) : "memory");
    return v;
}

#define DELAY_P1 1800
#define DELAY_Q 1800
#define DELAY_B1 300
#define DELAY_X1 2000
#define DELAY_NOFFN 1500
#define DELAY_C 600
__device__ __forceinline__ uint32_t clock32() {
    uint32_t c;
    asm volatile("mov.u32 %0, %clock;" : "=r"(c));
    return c;
}
__device__ __forceinline__ void spin_cycles(uint32_t n) {
    if (n > 0) { const uint32_t c0 = clock32(); while (clock32() - c0 < n) {} }
}
__device__ __forceinline__ float rcp_approx(float x) {
    float r;
    asm("rcp.approx.ftz.f32 %0, %1;" : "=f"(r) : "f"(x));
    return r;
}
__device__ __forceinline__ float sqrt_approx(float x) {
    float r;
    asm("sqrt.approx.f32 %0, %1;" : "=f"(r) : "f"(x));
    return r;
}

__device__ __forceinline__ float silu_bf(float v) { return bf16r(v / (1.0f + expf(-v))); }

__device__ __forceinline__ float2 half_warp_sums(const float (&v)[4], float pivot) {
    float s1 = 0.f, s2 = 0.f;
#pragma unroll
    for (int i = 0; i < 4; i++) { const float d = v[i] - pivot; s1 += d; s2 += d * d; }
#pragma unroll
    for (int o = 1; o < 16; o <<= 1) { s1 += __shfl_xor_sync(0xffffffffu, s1, o); s2 += __shfl_xor_sync(0xffffffffu, s2, o); }
    return make_float2(s1, s2);
}
__device__ __forceinline__ void ln_stats(const float2* stat, int b, float pivot, float& mean_bf, float& rstd) {
    float s1 = 0.f, s2 = 0.f;
#pragma unroll
    for (int w = 0; w < 8; w++) { const float2 v = stat[w * 2 + b]; s1 += v.x; s2 += v.y; }
    const float dm = s1 * (1.0f / D_MODEL);
    const float var = fmaxf(s2 * (1.0f / D_MODEL) - dm * dm, 0.f);
    mean_bf = bf16r(pivot + dm);
    rstd = rcp_approx(bf16r(sqrt_approx(bf16r(bf16r(var) + 1e-5f))));
}
__device__ __forceinline__ float ln_norm(float xv, float mean_bf, float rstd) { return bf16r(bf16r(xv - mean_bf) * rstd); }
__device__ __forceinline__ float ln_mod(float n, float cmul, float sadd) { return bf16r(n * bf16r(1.0f + cmul)) + sadd; }

__global__ void __launch_bounds__(NTHREADS, 1)
fused_block_kernel(const Params p, const __grid_constant__ CUtensorMap tm_k, const __grid_constant__ CUtensorMap tm_v,
                   const __grid_constant__ CUtensorMap tm_wq, const __grid_constant__ CUtensorMap tm_wmod,
                   const __grid_constant__ CUtensorMap tm_wmod8,
                   const __grid_constant__ CUtensorMap tm_wo, const __grid_constant__ CUtensorMap tm_wg,
                   const __grid_constant__ CUtensorMap tm_wu, const __grid_constant__ CUtensorMap tm_wd) {
    extern __shared__ unsigned char smem_raw[];
    const uint32_t sbase = (smem_u32(smem_raw) + 1023u) & ~1023u;
    unsigned char* sgen = smem_raw + (sbase - smem_u32(smem_raw));
    const int tid = threadIdx.x, warp = tid >> 5, lane = tid & 31;
    const int cta = blockIdx.x;
    const uint32_t bar_full = sbase + SM_BAR, bar_empty = bar_full + NST * 8;
    const uint32_t bar_clear = bar_empty + NST * 8;
    const uint32_t bar_gu = bar_clear + 8;
    const uint32_t bar_bc = bar_gu + 8 * 8;
    const uint32_t bar_p0w = bar_bc + 8;

    const int key0 = (cta >> 3) * SK + (cta & 7) * 64;
    uint64_t pol = 0;
    if (tid == 256) {
        asm volatile("createpolicy.fractional.L2::evict_first.b64 %0, 1.0;" : "=l"(pol));
        mbar_init(bar_p0w, 1);
#pragma unroll
        for (int i = 0; i < 4; i++) mbar_init(bar_full + 8 * i, 1);
        asm volatile("fence.mbarrier_init.release.cluster;" ::: "memory");
        mbar_expect_tx(bar_p0w, 8192);
        tma_2d(sbase + SM_MRG, &tm_wmod8, cta * 8, 0, bar_p0w);
        tma_2d(sbase + SM_MRG + 4096, &tm_wmod8, cta * 8, 256, bar_p0w);
#pragma unroll
        for (int i = 0; i < 4; i++) mbar_expect_tx(bar_full + 8 * i, TILE);
        tma_2d(sbase + SM_RING, &tm_wq, cta * 32, 0, bar_full);
        tma_2d(sbase + SM_RING + TILE, &tm_wq, cta * 32, 256, bar_full + 8);
        tma_3d_hint(sbase + SM_RING + 2 * TILE, &tm_k, 0, key0, 0, bar_full + 16, pol);
        tma_3d_hint(sbase + SM_RING + 3 * TILE, &tm_v, 0, key0, 0, bar_full + 24, pol);
    }

    if (warp == 8) {
        if (lane == 0) {
            for (int i = 0; i < NST; i++) { if (i >= 4) mbar_init(bar_full + 8 * i, 1); mbar_init(bar_empty + 8 * i, 4); }
            mbar_init(bar_clear, 1);
            for (int k = 0; k < 8; k++) mbar_init(bar_gu + 8 * k, 1);
            mbar_init(bar_bc, 8);
            ((volatile uint32_t*)(sgen + SM_PACE))[0] = 0;
            ((volatile uint32_t*)(sgen + SM_PACE))[1] = WINDOW;
            asm volatile("fence.mbarrier_init.release.cluster;" ::: "memory");
        }
        __syncwarp();
        asm volatile("bar.arrive 2, 288;" ::: "memory");
        asm volatile("bar.arrive 3, 64;" ::: "memory");
        if (lane == 0) {
            int slot = 4; uint32_t ph = 1;
            int landed = 0, wslot = 0; uint32_t wph = 0;
            int kv = 2;
            auto wait_window = [&](int idx, int window) {
                while (landed + window <= idx) {
                    mbar_wait(bar_full + 8 * wslot, wph);
                    if (++wslot == NST) { wslot = 0; wph ^= 1; }
                    landed++;
                }
            };
            volatile uint32_t* pace = (volatile uint32_t*)(sgen + SM_PACE);
            prefetch_tmap(&tm_wmod);
            pace[0] = 4;
            for (int idx = 4; idx < N_STREAM; idx++) {
                if (idx >= NST) mbar_wait(bar_empty + 8 * slot, ph);
                wait_window(idx, (int)pace[1]);
                if (idx == 12) { prefetch_tmap(&tm_wo); prefetch_tmap(&tm_wg); prefetch_tmap(&tm_wu); prefetch_tmap(&tm_wd); }
                const uint32_t fb = bar_full + 8 * slot, dst = sbase + SM_RING + slot * TILE;
                mbar_expect_tx(fb, TILE);
                if (idx == IDX_MOD) {
                    tma_2d(dst, &tm_wmod, 1024 + cta * 16, 0, fb);
                    tma_2d(dst + 8192, &tm_wmod, 1024 + cta * 16, 256, fb);
                } else {
                    tma_3d_hint(dst, (kv & 1) ? &tm_v : &tm_k, 0, key0 + (kv >> 1) * 512, 0, fb, pol);
                    kv++;
                }
                pace[0] = idx + 1;
                if (++slot == NST) { slot = 0; ph ^= 1; }
            }
            auto slot_free = [&](int idx) { mbar_wait(bar_empty + 8 * (idx % NST), ((idx / NST) & 1) ^ 1); };
#pragma unroll
            for (int s = 0; s < 2; s++) {
                const int idx = IDX_WO + s;
                slot_free(idx);
                wait_window(idx, WINDOW_TAIL);
                mbar_expect_tx(bar_full + 8 * (idx % NST), TILE);
                tma_3d(sbase + SM_RING + (idx % NST) * TILE, &tm_wo, 0, (cta >> 2) * 128 + s * 64, (cta & 3) * 2, bar_full + 8 * (idx % NST));
            }
            if (cta < NFFN) {
                slot_free(IDX_WG); slot_free(IDX_WU);
                mbar_wait(bar_full + 8 * (IDX_WO % NST), (IDX_WO / NST) & 1);
                mbar_wait(bar_full + 8 * ((IDX_WO + 1) % NST), ((IDX_WO + 1) / NST) & 1);
#pragma unroll
                for (int st = 0; st < 8; st++) {
                    if (st >= GU_WIN) mbar_wait(bar_gu + 8 * (st - GU_WIN), 0);
                    mbar_expect_tx(bar_gu + 8 * st, 4096);
                    tma_2d(sbase + SM_RING + (((st & 1) ? IDX_WU : IDX_WG) % NST) * TILE + (st >> 1) * 4096,
                           (st & 1) ? &tm_wu : &tm_wg, cta * 16, (st >> 1) * 128, bar_gu + 8 * st);
                }
                mbar_wait(bar_gu + 8 * 6, 0);
                slot_free(IDX_WD);
                mbar_expect_tx(bar_full + 8 * (IDX_WD % NST), TILE);
                tma_3d(sbase + SM_RING + (IDX_WD % NST) * TILE, &tm_wd, 0, cta * 16, 0, bar_full + 8 * (IDX_WD % NST));
            }
        }
    } else if (warp == 9) {
        Scratch* const sc = p.sc;
        const uint32_t tag = *(volatile unsigned*)&sc->epoch + 1;
        asm volatile("bar.sync 3, 64;" ::: "memory");
#pragma unroll 4
        for (int i = 0; i < NFFN * 2 / 32; i++) st_v4(&sc->inbox_dn[cta][0][0] + i * 32 + lane, 0u, 0u, 0u, 0u);
        if (cta >= NCTA - NOWN) {
#pragma unroll 4
            for (int i = 0; i < 8; i++) st_v4(&sc->inbox_wo[cta - (NCTA - NOWN)][0][0] + i * 32 + lane, 0u, 0u, 0u, 0u);
            if (lane < 8) st_v4((uint4*)&sc->x1[(cta - (NCTA - NOWN)) * 16] + lane, 0u, 0u, 0u, 0u);
        }
#pragma unroll 4
        for (int i = 0; i < 4; i++) st_v4((uint4*)&sc->part_o[cta][0][0] + i * 32 + lane, 0u, 0u, 0u, 0u);
        if (lane < 8) st_v4((uint4*)&sc->part_ml[cta][0][0] + lane, 0u, 0u, 0u, 0u);
        if (cta == 0 && lane == 0) asm volatile("st.relaxed.gpu.global.u32 [%0], %1;" ::"l"(&sc->progress), "r"(0u) : "memory");
        asm volatile("fence.acq_rel.gpu;" ::: "memory");
        __syncwarp();
        if (lane == 0) {
            asm volatile("fence.acq_rel.gpu;" ::: "memory");
            asm volatile("red.relaxed.gpu.global.add.u32 [%0], %1;" ::"l"(&sc->cleared), "r"(1u) : "memory");
            const uint32_t target = tag * NCTA;
            for (int it = 0; it < SPIN_LIMIT; it++) {
                uint32_t v;
                asm volatile("ld.relaxed.gpu.global.u32 %0, [%1];" : "=r"(v) : "l"(&sc->cleared) : "memory");
                if ((int32_t)(v - target) >= 0) break;
                __nanosleep(500);
            }
            asm volatile("fence.acq_rel.gpu;" ::: "memory");
            mbar_arrive(bar_clear);
            volatile uint32_t* pace = (volatile uint32_t*)(sgen + SM_PACE);
            uint32_t posted = 0;
            for (int it = 0; it < SPIN_LIMIT; it++) {
                const uint32_t own = pace[0];
                if (own >= N_STREAM) break;
                if (own > posted) {
                    asm volatile("red.relaxed.gpu.global.add.u32 [%0], %1;" ::"l"(&sc->progress), "r"(own - posted) : "memory");
                    posted = own;
                }
                uint32_t v;
                asm volatile("ld.relaxed.gpu.global.u32 %0, [%1];" : "=r"(v) : "l"(&sc->progress) : "memory");
                const int diff = (int)v - (int)own * NCTA;
                pace[1] = diff > PACE_THR ? WINDOW + 1 : diff < -PACE_THR ? WINDOW - 1 : WINDOW;
                __nanosleep(200);
            }
            if (cta == 0) asm volatile("st.relaxed.gpu.global.u32 [%0], %1;" ::"l"(&sc->epoch), "r"(tag) : "memory");
        }
    } else {
        const int g = lane >> 2, t = lane & 3;
        const int bb = g & 1;
        const int eb = lane >> 4;
        const int ec = 64 * warp + 4 * (lane & 15);
        if (warp == 0) TSTAMP(0);
        Scratch* const sc = p.sc;
        const float c00 = __bfloat162float(p.c[tid]), c01 = __bfloat162float(p.c[tid + 256]);
        const float c10 = __bfloat162float(p.c[D_MODEL + tid]), c11 = __bfloat162float(p.c[D_MODEL + tid + 256]);
        const uint2 xe = __ldg((const uint2*)(p.x + eb * D_MODEL + ec));
        const float xpivot = __bfloat162float(p.x[eb * D_MODEL]);
        const uint32_t tag = *(volatile unsigned*)&sc->epoch + 1;
        const int ocol = cta * 4 + (lane & 3);
        const int wcol = (cta >= NCTA - NOWN ? cta - (NCTA - NOWN) : 0) * 16 + (lane & 15);
        const float xo = __bfloat162float(p.x[eb * D_MODEL + wcol]);

        float* red = (float*)(sgen + SM_RED);
        float* red2 = (float*)(sgen + SM_RED2);
        float2* stat = (float2*)(sgen + SM_STAT);
        uint32_t* hs = (uint32_t*)(sgen + SM_HS) + warp * 64;
        float xn[4];
        {
            float xv[4] = {bf_lo(xe.x), bf_hi(xe.x), bf_lo(xe.y), bf_hi(xe.y)};
            const float2 ps = half_warp_sums(xv, xpivot);
            if ((lane & 15) == 0) stat[warp * 2 + eb] = ps;
            const float s00 = silu_bf(c00), s01 = silu_bf(c01), s10 = silu_bf(c10), s11 = silu_bf(c11);
            __nv_bfloat16* scs = (__nv_bfloat16*)(sgen + SM_SC);
            scs[tid] = __float2bfloat16_rn(s00); scs[tid + 256] = __float2bfloat16_rn(s01);
            scs[512 + tid] = __float2bfloat16_rn(s10); scs[512 + tid + 256] = __float2bfloat16_rn(s11);
            asm volatile("bar.sync 2, 288;" ::: "memory");
            if (warp == 0) TSTAMP(23);
            float cp[4] = {0.f, 0.f, 0.f, 0.f};
            const uint32_t* sc32 = (const uint32_t*)(sgen + SM_SC) + bb * 256 + 32 * warp + t;
            mbar_wait(bar_p0w, 0);
#pragma unroll
            for (int s = 0; s < 4; s++) {
                uint32_t r0, r1;
                asm volatile("ldmatrix.sync.aligned.m8n8.x2.trans.shared.b16 {%0,%1}, [%2];"
                             : "=r"(r0), "=r"(r1) : "r"(sbase + SM_MRG + (64 * warp + 16 * s + (lane & 15)) * 16) : "memory");
                const uint32_t a[4] = {r0, r0, r1, r1};
                mma16816(cp, a, sc32[8 * s], sc32[8 * s + 4]);
            }
            if (t == 0) { red[warp * 16 + g] = cp[0]; red[warp * 16 + 8 + g] = cp[1]; }
            if (warp == 0) TSTAMP(14);
            cons_sync();
            if (warp == 0) {
                float s = 0.f;
#pragma unroll
                for (int w = 0; w < 8; w++) s += red[w * 16 + (lane & 15)];
                const float nx = __shfl_down_sync(0xffffffffu, s, 1);
                if (lane < 16 && !(lane & 1))
                    st_ll2(&sc->mod[lane >> 3][cta * 4 + ((lane & 7) >> 1)], pack_bf16(s, nx), tag);
                TSTAMP(1);
            }
            float mean_bf, rstd;
            ln_stats(stat, eb, xpivot, mean_bf, rstd);
#pragma unroll
            for (int i = 0; i < 4; i++) xn[i] = ln_norm(xv[i], mean_bf, rstd);
        }
        {
            uint4 sa, ca;
            spin_cycles(DELAY_P1);
            for (int it = 0;; it++) {
                sa = ld_ll4((const uint4*)&sc->mod[eb][ec >> 1]);
                ca = ld_ll4((const uint4*)&sc->mod[eb][256 + (ec >> 1)]);
                const bool ok = sa.y == tag && sa.w == tag && ca.y == tag && ca.w == tag;
                if (__all_sync(0xffffffffu, ok) || it > SPIN_LIMIT) break;
            }
            *(uint2*)&hs[eb * 32 + 2 * (lane & 15)] =
                make_uint2(pack_bf16(ln_mod(xn[0], bf_lo(ca.x), bf_lo(sa.x)), ln_mod(xn[1], bf_hi(ca.x), bf_hi(sa.x))),
                           pack_bf16(ln_mod(xn[2], bf_lo(ca.z), bf_lo(sa.z)), ln_mod(xn[3], bf_hi(ca.z), bf_hi(sa.z))));
            __syncwarp();
            uint32_t hb[8];
#pragma unroll
            for (int i = 0; i < 8; i++) hb[i] = hs[bb * 32 + 8 * (i >> 1) + 4 * (i & 1) + t];
            if (warp == 0) TSTAMP(2);
            float cq[2][4] = {};
            const int ts = warp >> 2;
            mbar_wait(bar_full + 8 * ts, 0);
            const uint32_t tb = sbase + SM_RING + ts * TILE;
#pragma unroll
            for (int s = 0; s < 4; s++) {
                const int row = 64 * (warp & 3) + 16 * s + (lane & 7) + (lane >> 4) * 8;
#pragma unroll
                for (int mt = 0; mt < 2; mt++) {
                    const int ch = 2 * mt + ((lane >> 3) & 1);
                    uint32_t a[4];
                    ldsm4t(tb + row * 64 + ((ch ^ ((row >> 1) & 3)) << 4), a);
                    mma16816(cq[mt], a, hb[2 * s], hb[2 * s + 1]);
                }
            }
            if (t < 2) {
                const float v0 = t == 0 ? cq[0][0] : cq[1][0], v1 = t == 0 ? cq[0][1] : cq[1][1];
                const float v2 = t == 0 ? cq[0][2] : cq[1][2], v3 = t == 0 ? cq[0][3] : cq[1][3];
                *(float2*)&red2[warp * 64 + (16 * t + g) * 2] = make_float2(v0, v1);
                *(float2*)&red2[warp * 64 + (16 * t + g + 8) * 2] = make_float2(v2, v3);
            }
            cons_sync();
            if (warp < 4 && lane == 0) { mbar_arrive(bar_empty); mbar_arrive(bar_empty + 8); }
            if (warp == 0) {
                const int b = lane >> 4, cp = lane & 15;
                float q0 = 0.f, q1 = 0.f;
#pragma unroll
                for (int w = 0; w < 8; w++) {
                    const float4 v = *(const float4*)&red2[w * 64 + cp * 4];
                    q0 += b ? v.y : v.x; q1 += b ? v.w : v.z;
                }
                st_ll2(&sc->q[b][cta * 16 + cp], pack_bf16(q0, q1), tag);
                TSTAMP(3);
            }
        }
        const int pair = cta >> 3;
        uint32_t qf[16];
        {
            uint2* qs = (uint2*)(sgen + SM_QS);
            if (tid < 128) {
                const uint4* src = (const uint4*)&sc->q[pair >> 3][(pair & 7) * 256] + tid;
                uint4 v;
                spin_cycles(DELAY_Q);
                for (int it = 0;; it++) {
                    v = ld_ll4(src);
                    if ((v.y == tag && v.w == tag) || it > SPIN_LIMIT) break;
                }
                qs[tid] = make_uint2(v.x, v.z);
            }
            cons_sync();
            const uint32_t* q32 = (const uint32_t*)(sgen + SM_QS);
#pragma unroll
            for (int s = 0; s < 8; s++) {
                qf[2 * s] = q32[(g & 3) * 64 + 8 * s + t];
                qf[2 * s + 1] = q32[(g & 3) * 64 + 8 * s + 4 + t];
            }
        }
        if (warp == 0) TSTAMP(4);

        float o[8][4];
#pragma unroll
        for (int i = 0; i < 8; i++) { o[i][0] = o[i][1] = o[i][2] = o[i][3] = 0.f; }
        uint32_t mrun = 0xff80ff80u;
        float ls[4] = {0.f, 0.f, 0.f, 0.f};
        uint4 m_sb, m_cb; uint2 m_ga, m_gb0, m_gb1;
        {
            const int grp = warp >> 2, wi = warp & 3;
            const int krow = 16 * wi + (lane & 7) + ((lane >> 3) & 1) * 8;
            const uint32_t koff = krow * 128 + ((((lane >> 4) & 1) ^ (lane & 7)) << 4);
            const int vrow = 16 * wi + (lane & 7) + (lane >> 4) * 8;
            const uint32_t voff = vrow * 128 + ((((lane >> 3) & 1) ^ (lane & 7)) << 4);
            const uint32_t ones[4] = {0x3f803f80u, 0x3f803f80u, 0x3f803f80u, 0x3f803f80u};
            for (int i = grp; i < KV_TILES; i += 2) {
                if (i == MOD_AT + grp) {
                    float cm[4] = {};
                    const uint32_t* sc32 = (const uint32_t*)(sgen + SM_SC) + bb * 256 + 32 * warp + t;
                    mbar_wait(bar_full + 8 * (IDX_MOD % NST), (IDX_MOD / NST) & 1);
                    const uint32_t tb = sbase + SM_RING + (IDX_MOD % NST) * TILE;
#pragma unroll
                    for (int s = 0; s < 4; s++) {
                        const int row = 64 * warp + 16 * s + (lane & 7) + (lane >> 4) * 8;
                        const int ch = (lane >> 3) & 1;
                        uint32_t a[4];
                        ldsm4t(tb + row * 32 + ((ch ^ ((row >> 2) & 1)) << 4), a);
                        mma16816(cm, a, sc32[8 * s], sc32[8 * s + 4]);
                    }
                    if (t == 0) {
                        *(float2*)&red[warp * 64 + g * 2] = make_float2(cm[0], cm[1]);
                        *(float2*)&red[warp * 64 + (g + 8) * 2] = make_float2(cm[2], cm[3]);
                    }
                    cons_sync();
                    if (warp < 4 && lane == 0) mbar_arrive(bar_empty + 8 * (IDX_MOD % NST));
                    if (warp == 1 && lane < 16) {
                        const int b = lane >> 3, cp = lane & 7;
                        float q0 = 0.f, q1 = 0.f;
#pragma unroll
                        for (int w = 0; w < 8; w++) {
                            const float4 v = *(const float4*)&red[w * 64 + cp * 4];
                            q0 += b ? v.y : v.x; q1 += b ? v.w : v.z;
                        }
                        st_ll2(&sc->mod[b][512 + cta * 8 + cp], pack_bf16(q0, q1), tag);
                    }
                }
                if (i == 56 + grp) {
                    m_sb = ld_ll4((const uint4*)&sc->mod[eb][768 + (ec >> 1)]);
                    m_cb = ld_ll4((const uint4*)&sc->mod[eb][1024 + (ec >> 1)]);
                    m_ga = ld_ll2(&sc->mod[eb][512 + (wcol >> 1)]);
                    m_gb0 = ld_ll2(&sc->mod[0][1280 + (ocol >> 1)]); m_gb1 = ld_ll2(&sc->mod[1][1280 + (ocol >> 1)]);
                }
                if (i == 60 + grp) {
                    for (int it = 0;; it++) {
                        const bool ok = m_sb.y == tag && m_sb.w == tag && m_cb.y == tag && m_cb.w == tag &&
                                        m_ga.y == tag && m_gb0.y == tag && m_gb1.y == tag;
                        if (__all_sync(0xffffffffu, ok) || it > SPIN_LIMIT) break;
                        m_sb = ld_ll4((const uint4*)&sc->mod[eb][768 + (ec >> 1)]);
                        m_cb = ld_ll4((const uint4*)&sc->mod[eb][1024 + (ec >> 1)]);
                        m_ga = ld_ll2(&sc->mod[eb][512 + (wcol >> 1)]);
                        m_gb0 = ld_ll2(&sc->mod[0][1280 + (ocol >> 1)]); m_gb1 = ld_ll2(&sc->mod[1][1280 + (ocol >> 1)]);
                    }
                    mbar_wait(bar_clear, 0);
                }
                const int ki = kv_idx(i), ks = ki % NST, vs = (ki + 1) % NST;
                const uint32_t kph = (ki / NST) & 1, vph = ((ki + 1) / NST) & 1;
                mbar_wait(bar_full + 8 * ks, kph);
                const uint32_t kb = sbase + SM_RING + ks * TILE + koff;
                float sa[4] = {0.f, 0.f, 0.f, 0.f}, sb[4] = {0.f, 0.f, 0.f, 0.f};
#pragma unroll
                for (int s = 0; s < 8; s += 2) {
                    uint32_t a0[4], a1[4];
                    ldsm4((kb ^ ((s & 3) << 5)) + (s >> 2) * 8192, a0);
                    ldsm4((kb ^ (((s + 1) & 3) << 5)) + (s >> 2) * 8192, a1);
                    mma16816(sa, a0, qf[2 * s], qf[2 * s + 1]);
                    mma16816(sb, a1, qf[2 * s + 2], qf[2 * s + 3]);
                }
                __syncwarp();
                if (lane == 0) mbar_arrive(bar_empty + 8 * ks);
                uint32_t r01 = pack_bf16(sa[0] + sb[0], sa[1] + sb[1]);
                uint32_t r23 = pack_bf16(sa[2] + sb[2], sa[3] + sb[3]);
                r01 = pack_bf16(bf_lo(r01) * QK_SCALE, bf_hi(r01) * QK_SCALE);
                r23 = pack_bf16(bf_lo(r23) * QK_SCALE, bf_hi(r23) * QK_SCALE);
                uint32_t mx = max_bf16x2(r01, r23);
                mx = max_bf16x2(mx, __shfl_xor_sync(0xffffffffu, mx, 4));
                mx = max_bf16x2(mx, __shfl_xor_sync(0xffffffffu, mx, 8));
                mx = max_bf16x2(mx, __shfl_xor_sync(0xffffffffu, mx, 16));
                const uint32_t mnew = max_bf16x2(mrun, mx);
                const float m0 = bf_lo(mnew), m1 = bf_hi(mnew);
                if (__any_sync(0xffffffffu, mnew != mrun)) {
                    const float al0 = ex2((bf_lo(mrun) - m0) * LOG2E), al1 = ex2((bf_hi(mrun) - m1) * LOG2E);
                    ls[0] *= al0; ls[1] *= al1;
#pragma unroll
                    for (int d = 0; d < 8; d++) { o[d][0] *= al0; o[d][1] *= al1; o[d][2] *= al0; o[d][3] *= al1; }
                    mrun = mnew;
                }
                const float p0 = ex2((bf_lo(r01) - m0) * LOG2E), p1 = ex2((bf_hi(r01) - m1) * LOG2E);
                const float p2 = ex2((bf_lo(r23) - m0) * LOG2E), p3 = ex2((bf_hi(r23) - m1) * LOG2E);
                const uint32_t pb0 = movmatrix_t(pack_bf16(p0, p1)), pb1 = movmatrix_t(pack_bf16(p2, p3));
                mma16816(ls, ones, pb0, pb1);
                mbar_wait(bar_full + 8 * vs, vph);
                const uint32_t vb = sbase + SM_RING + vs * TILE + voff;
#pragma unroll
                for (int d = 0; d < 8; d++) {
                    uint32_t a[4];
                    ldsm4t((vb ^ ((d & 3) << 5)) + (d >> 2) * 8192, a);
                    mma16816(o[d], a, pb0, pb1);
                }
                __syncwarp();
                if (lane == 0) mbar_arrive(bar_empty + 8 * vs);
            }
        }
        if (warp == 7) TSTAMP(5);
        {
            float* mrg = (float*)(sgen + SM_MRG);
            float2* ml = (float2*)(sgen + SM_ML);
            {
                const int hp = (t & 1) * 2, up = t >> 1;
                if (g == 0 && up == 0) { ml[warp * 4 + hp] = make_float2(bf_lo(mrun), ls[0]); ml[warp * 4 + hp + 1] = make_float2(bf_hi(mrun), ls[1]); }
                float* m0p = mrg + (warp * 4 + hp) * 136 + up * 72 + g;
#pragma unroll
                for (int d = 0; d < 4; d++) {
                    m0p[16 * d] = up ? o[d + 4][0] : o[d][0]; m0p[136 + 16 * d] = up ? o[d + 4][1] : o[d][1];
                    m0p[16 * d + 8] = up ? o[d + 4][2] : o[d][2]; m0p[136 + 16 * d + 8] = up ? o[d + 4][3] : o[d][3];
                }
            }
            cons_sync();
            const int hh = tid >> 6, dp = tid & 63;
            float2 mw[8];
            float M = -INFINITY;
#pragma unroll
            for (int w = 0; w < 8; w++) { mw[w] = ml[w * 4 + hh]; M = fmaxf(M, mw[w].x); }
            float L = 0.f, o0 = 0.f, o1 = 0.f;
#pragma unroll
            for (int w = 0; w < 8; w++) {
                const float wt = ex2((mw[w].x - M) * LOG2E);
                const float2 v = *(const float2*)&mrg[(w * 4 + hh) * 136 + 2 * dp + (dp >= 32 ? 8 : 0)];
                L += wt * mw[w].y; o0 += wt * v.x; o1 += wt * v.y;
            }
            st_ll2(&sc->part_o[cta][hh][dp], tagf(o0, F_PART), tagf(o1, F_PART));
            if (dp < 4) st_ll2(&sc->part_ml[cta][hh][dp], tagf(M, F_PART), tagf(L, F_PART));
        }
        if (warp == 0) TSTAMP(6);
        {
            const int hq = cta >> 2, kvh = hq >> 2, hh = hq & 3;
            const int b = tid >> 7, dc = (tid >> 3) & 15, j = tid & 7;
            const int pc = (b * 8 + kvh) * 8 + j;
            const uint4* po = (const uint4*)&sc->part_o[pc][hh][0] + dc * 2;
            const uint2* pm = &sc->part_ml[pc - j][hh][0];
            uint4 vo0, vo1; uint2 vm[8];
            bool oko = false, okm = false;
            for (int it = 0;; it++) {
                if (!oko) { vo0 = ld_ll4(po); vo1 = ld_ll4(po + 1); }
                if (!okm) {
#pragma unroll
                    for (int jj = 0; jj < 8; jj++) vm[jj] = ld_ll2(pm + jj * 16);
                }
                oko = (vo0.x & vo0.y & vo0.z & vo0.w & vo1.x & vo1.y & vo1.z & vo1.w & 3u) == F_PART;
                uint32_t all = vm[0].x & vm[0].y;
#pragma unroll
                for (int jj = 1; jj < 8; jj++) all &= vm[jj].x & vm[jj].y;
                okm = (all & 3u) == F_PART;
                if (__all_sync(0xffffffffu, oko && okm) || it > SPIN_LIMIT) break;
            }
            float M = untag(vm[0].x);
#pragma unroll
            for (int jj = 1; jj < 8; jj++) M = fmaxf(M, untag(vm[jj].x));
            float wt = 0.f, L = 0.f;
#pragma unroll
            for (int jj = 0; jj < 8; jj++) {
                const float w_ = ex2((untag(vm[jj].x) - M) * LOG2E);
                L += w_ * untag(vm[jj].y);
                wt = jj == j ? w_ : wt;
            }
            wt *= rcp_approx(L);
            float v[8] = {wt * untag(vo0.x), wt * untag(vo0.y), wt * untag(vo0.z), wt * untag(vo0.w),
                          wt * untag(vo1.x), wt * untag(vo1.y), wt * untag(vo1.z), wt * untag(vo1.w)};
#define XRED(N, O)                                                                       \
            {                                                                            \
                const bool up = lane & (O);                                              \
                _Pragma("unroll") for (int i = 0; i < (N); i++) {                        \
                    const float send = up ? v[i] : v[i + (N)], keep = up ? v[i + (N)] : v[i]; \
                    v[i] = keep + __shfl_xor_sync(0xffffffffu, send, (O));               \
                }                                                                        \
            }
            XRED(4, 1) XRED(2, 2) XRED(1, 4)
#undef XRED
            __nv_bfloat16* os = (__nv_bfloat16*)(sgen + SM_OS);
            os[b * 128 + dc * 8 + 4 * (j & 1) + 2 * ((j >> 1) & 1) + (j >> 2)] = __float2bfloat16_rn(v[0]);
            if (warp == 0) TSTAMP(15);
            uint32_t wf[8][4];
            const uint32_t aoff_o = (warp >> 2) * 8192 + ((lane & 7) + (lane >> 4) * 8) * 128 +
                                    (((((warp & 3) * 2 + ((lane >> 3) & 1)) ^ (lane & 7))) << 4);
#pragma unroll
            for (int s = 0; s < 2; s++) {
                const int idx = IDX_WO + s;
                mbar_wait(bar_full + 8 * (idx % NST), (idx / NST) & 1);
                const uint32_t tb = sbase + SM_RING + (idx % NST) * TILE + aoff_o;
#pragma unroll
                for (int k4 = 0; k4 < 4; k4++) ldsm4t(tb + k4 * 2048, wf[s * 4 + k4]);
            }
            cons_sync();
            if (warp == 0) TSTAMP(7);
            const uint32_t* os32 = (const uint32_t*)(sgen + SM_OS) + bb * 64 + t;
            float y0[4] = {}, y1[4] = {};
#pragma unroll
            for (int ks = 0; ks < 8; ks += 2) {
                mma16816(y0, wf[ks], os32[8 * ks], os32[8 * ks + 4]);
                mma16816(y1, wf[ks + 1], os32[8 * ks + 8], os32[8 * ks + 12]);
            }
            if (t == 0)
                st_v4(&sc->inbox_wo[(cta & 3) * 8 + warp][hq][g], tagf(y0[0] + y1[0], F_WO), tagf(y0[1] + y1[1], F_WO),
                      tagf(y0[2] + y1[2], F_WO), tagf(y0[3] + y1[3], F_WO));
        }
        const uint32_t t_wo = clock32();
        if (warp == 0) TSTAMP(8);
        if (cta >= NCTA - NOWN) {
            const uint4* pin = &sc->inbox_wo[cta - (NCTA - NOWN)][0][0] + tid;
            uint4 v;
            spin_cycles(DELAY_B1);
            bool ok = false;
            for (int it = 0;; it++) {
                if (!ok) {
                    v = ld_ll4(pin);
                    ok = (v.x & v.y & v.z & v.w & 3u) == F_WO;
                }
                if (__all_sync(0xffffffffu, ok) || it > SPIN_LIMIT) break;
            }
            const bool u1 = lane & 8, u2 = lane & 16;
            const float a0 = untag(v.x), a1 = untag(v.y), a2 = untag(v.z), a3 = untag(v.w);
            const float k0 = (u1 ? a2 : a0) + __shfl_xor_sync(0xffffffffu, u1 ? a0 : a2, 8);
            const float k1 = (u1 ? a3 : a1) + __shfl_xor_sync(0xffffffffu, u1 ? a1 : a3, 8);
            red2[warp * 32 + lane] = (u2 ? k1 : k0) + __shfl_xor_sync(0xffffffffu, u2 ? k0 : k1, 16);
            cons_sync();
            if (warp == 0) {
                float a = 0.f;
#pragma unroll
                for (int w = 0; w < 8; w++) a += red2[w * 32 + lane];
                const float ga = (wcol & 1) ? bf_hi(m_ga.x) : bf_lo(m_ga.x);
                const float xm = bf16r(xo + bf16r(ga * bf16r(a)));
                const float xm_b1 = __shfl_down_sync(0xffffffffu, xm, 16);
                if (lane < 16) st_ll2(&sc->x1[wcol], pack_bf16(xm, xm_b1), F_X1);
                TSTAMP(10);
            }
        }
        const uint32_t aoff = warp * 2048 + ((lane & 7) + (lane >> 4) * 8) * 128 + ((((lane >> 3) & 1) ^ (lane & 7)) << 4);
        if (cta < NFFN) {
            const uint4* px = (const uint4*)&sc->x1[ec];
            const uint4* pp = (const uint4*)&sc->x1[0];
            uint4 va, vb, pa, pb;
            uint32_t gf[4][4], uf[4][4];
            mbar_wait(bar_gu + 8 * (2 * (warp >> 1)), 0);
            mbar_wait(bar_gu + 8 * (2 * (warp >> 1) + 1), 0);
            {
                const uint32_t tg = sbase + SM_RING + (IDX_WG % NST) * TILE, tu = sbase + SM_RING + (IDX_WU % NST) * TILE;
#pragma unroll
                for (int s = 0; s < 4; s++) {
                    const int row = 64 * warp + 16 * s + (lane & 7) + (lane >> 4) * 8;
                    const uint32_t off = row * 32 + ((((lane >> 3) & 1) ^ ((row >> 2) & 1)) << 4);
                    ldsm4t(tg + off, gf[s]);
                    ldsm4t(tu + off, uf[s]);
                }
            }
            const float c1v[4] = {bf16r(1.0f + bf_lo(m_cb.x)), bf16r(1.0f + bf_hi(m_cb.x)), bf16r(1.0f + bf_lo(m_cb.z)), bf16r(1.0f + bf_hi(m_cb.z))};
            float bg = 0.f, cgc = 0.f, bu = 0.f, cuc = 0.f;
            {
                uint32_t* pre = (uint32_t*)(sgen + SM_MRG) + warp * 128;
                float* bc = (float*)(sgen + SM_MRG + 4096);
                *(uint2*)&pre[eb * 32 + 2 * (lane & 15)] = make_uint2(pack_bf16(c1v[0], c1v[1]), pack_bf16(c1v[2], c1v[3]));
                *(uint2*)&pre[64 + eb * 32 + 2 * (lane & 15)] = make_uint2(m_sb.x, m_sb.z);
                __syncwarp();
                float yg[4] = {}, yu[4] = {};
                const uint32_t* pb = pre + ((g >> 1) & 1) * 64 + bb * 32 + t;
#pragma unroll
                for (int s = 0; s < 4; s++) {
                    const uint32_t b0 = pb[8 * s], b1 = pb[8 * s + 4];
                    mma16816(yg, gf[s], b0, b1);
                    mma16816(yu, uf[s], b0, b1);
                }
                const float y0 = t < 2 ? yg[0] : yu[0], y1 = t < 2 ? yg[1] : yu[1], y2 = t < 2 ? yg[2] : yu[2], y3 = t < 2 ? yg[3] : yu[3];
                float* dstp = bc + warp * 128 + (t >> 1) * 64 + (t & 1) * 32;
                *(float2*)&dstp[g * 2] = make_float2(y0, y1);
                *(float2*)&dstp[(g + 8) * 2] = make_float2(y2, y3);
                __syncwarp();
                if (lane == 0) mbar_arrive(bar_bc);
            }
            if (warp == 0) TSTAMP(11);
            float pivot2;
            {
                while (clock32() - t_wo < DELAY_X1) {}
                bool okx = false, okp = false;
                for (int it = 0;; it++) {
                    if (!okx) { va = ld_ll4(px); vb = ld_ll4(px + 1); }
                    if (!okp) { pa = ld_ll4(pp); pb = ld_ll4(pp + 1); }
                    okx = va.y == F_X1 && va.w == F_X1 && vb.y == F_X1 && vb.w == F_X1;
                    okp = pa.y == F_X1 && pa.w == F_X1 && pb.y == F_X1 && pb.w == F_X1;
                    if (__all_sync(0xffffffffu, okx && okp) || it > SPIN_LIMIT) break;
                }
                if (warp == 0) TSTAMP(9);
                const float xv[4] = {eb ? bf_hi(va.x) : bf_lo(va.x), eb ? bf_hi(va.z) : bf_lo(va.z),
                                     eb ? bf_hi(vb.x) : bf_lo(vb.x), eb ? bf_hi(vb.z) : bf_lo(vb.z)};
                const float p0 = 0.25f * ((bf_lo(pa.x) + bf_lo(pa.z)) + (bf_lo(pb.x) + bf_lo(pb.z)));
                const float p1 = 0.25f * ((bf_hi(pa.x) + bf_hi(pa.z)) + (bf_hi(pb.x) + bf_hi(pb.z)));
                const float pivot = eb ? p1 : p0;
                pivot2 = (lane & 1) ? p1 : p0;
                *(uint2*)&hs[eb * 32 + 2 * (lane & 15)] =
                    make_uint2(pack_bf16((xv[0] - pivot) * c1v[0], (xv[1] - pivot) * c1v[1]),
                               pack_bf16((xv[2] - pivot) * c1v[2], (xv[3] - pivot) * c1v[3]));
                __syncwarp();
                float cg[2][4] = {}, cu[2][4] = {};
#pragma unroll
                for (int s = 0; s < 4; s++) {
                    const uint32_t b0 = hs[bb * 32 + 8 * s + t], b1 = hs[bb * 32 + 8 * s + 4 + t];
                    mma16816(cg[s & 1], gf[s], b0, b1);
                    mma16816(cu[s & 1], uf[s], b0, b1);
                }
                const float2 ps = half_warp_sums(xv, pivot);
                if ((lane & 15) == 0) stat[warp * 2 + eb] = ps;
                {
                    const float* bc = (const float*)(sgen + SM_MRG + 4096);
                    mbar_wait(bar_bc, 0);
#pragma unroll
                    for (int w = 0; w < 8; w++) {
                        bg += bc[w * 128 + lane]; cgc += bc[w * 128 + 32 + lane];
                        bu += bc[w * 128 + 64 + lane]; cuc += bc[w * 128 + 96 + lane];
                    }
                }
                if (t < 2) {
                    float v[4];
#pragma unroll
                    for (int i = 0; i < 4; i++) v[i] = t ? cu[0][i] + cu[1][i] : cg[0][i] + cg[1][i];
                    *(float2*)&red[warp * 64 + t * 32 + g * 2] = make_float2(v[0], v[1]);
                    *(float2*)&red[warp * 64 + t * 32 + (g + 8) * 2] = make_float2(v[2], v[3]);
                }
            }
            uint32_t df[4][4];
            mbar_wait(bar_full + 8 * (IDX_WD % NST), (IDX_WD / NST) & 1);
#pragma unroll
            for (int mt = 0; mt < 4; mt++) ldsm4t((sbase + SM_RING + (IDX_WD % NST) * TILE + aoff) ^ (mt << 5), df[mt]);
            cons_sync();
            {
                float gs = 0.f, us = 0.f;
#pragma unroll
                for (int w = 0; w < 8; w++) { gs += red[w * 64 + lane]; us += red[w * 64 + 32 + lane]; }
                float mean_bf, rstd;
                ln_stats(stat, lane & 1, pivot2, mean_bf, rstd);
                const float dm = mean_bf - pivot2;
                gs = bf16r(rstd * (gs - dm * bg) + cgc);
                us = rstd * (us - dm * bu) + cuc;
                const float u2 = gs * (1.0f + 0.044715f * gs * gs) * (2.0f * 0.7978845608028654f * LOG2E);
                const float ge = bf16r(__fdividef(gs, 1.0f + ex2(-u2)));
                const float act = bf16r(ge * bf16r(us));
                const float a0 = __shfl_sync(0xffffffffu, act, 4 * t + bb), a1 = __shfl_sync(0xffffffffu, act, 4 * t + 2 + bb);
                const float a2 = __shfl_sync(0xffffffffu, act, 4 * t + 16 + bb), a3 = __shfl_sync(0xffffffffu, act, 4 * t + 18 + bb);
                const uint32_t b0 = pack_bf16(a0, a1), b1 = pack_bf16(a2, a3);
                float y[4][4] = {};
#pragma unroll
                for (int mt = 0; mt < 4; mt++) mma16816(y[mt], df[mt], b0, b1);
                float v[4];
#pragma unroll
                for (int i = 0; i < 4; i++) v[i] = t == 0 ? y[0][i] : t == 1 ? y[1][i] : t == 2 ? y[2][i] : y[3][i];
            {
                const bool odd = g & 1;
                const float sx = odd ? v[0] : v[2], sy = odd ? v[1] : v[3];
                const float rx = __shfl_xor_sync(0xffffffffu, sx, 4), ry = __shfl_xor_sync(0xffffffffu, sy, 4);
                const int c0 = 64 * warp + 16 * t + (odd ? g + 7 : g);
                const float e0 = odd ? rx : v[0], e1 = odd ? ry : v[1], e2 = odd ? v[2] : rx, e3 = odd ? v[3] : ry;
                st_v4(&sc->inbox_dn[c0 >> 2][cta][(c0 >> 1) & 1], tagf(e0, F_DOWN), tagf(e1, F_DOWN), tagf(e2, F_DOWN), tagf(e3, F_DOWN));
            }
            }
            if (warp == 0) TSTAMP(12);
        }
        {
            uint2 xw;
            float r0;
            {
                const uint4* pin = &sc->inbox_dn[cta][0][0] + tid;
                uint4 v = make_uint4(F_DOWN, F_DOWN, F_DOWN, F_DOWN);
                if (cta < NFFN) spin_cycles(DELAY_C);
                else while (clock32() - t_wo < DELAY_X1 + DELAY_NOFFN) {}
                xw = ld_ll2(&sc->x1[ocol]);
                bool ok = tid >= NFFN * 2;
                for (int it = 0;; it++) {
                    if (!ok) {
                        v = ld_ll4(pin);
                        ok = (v.x & v.y & v.z & v.w & 3u) == F_DOWN;
                    }
                    if (__all_sync(0xffffffffu, ok) || it > SPIN_LIMIT) break;
                }
                const bool u1 = lane & 2, u2 = lane & 4;
                const float a0 = untag(v.x), a1 = untag(v.y), a2 = untag(v.z), a3 = untag(v.w);
                const float k0 = (u1 ? a1 : a0) + __shfl_xor_sync(0xffffffffu, u1 ? a0 : a1, 2);
                const float k1 = (u1 ? a3 : a2) + __shfl_xor_sync(0xffffffffu, u1 ? a2 : a3, 2);
                r0 = (u2 ? k1 : k0) + __shfl_xor_sync(0xffffffffu, u2 ? k0 : k1, 4);
                r0 += __shfl_xor_sync(0xffffffffu, r0, 8);
                r0 += __shfl_xor_sync(0xffffffffu, r0, 16);
                if (lane < 8) red2[256 + warp * 8 + (2 * (lane & 1) + ((lane >> 2) & 1)) * 2 + ((lane >> 1) & 1)] = r0;
            }
            cons_sync();
            if (warp == 0) {
                float a0 = 0.f, a1 = 0.f;
#pragma unroll
                for (int w = 0; w < 8; w++) { const float2 v = *(const float2*)&red2[256 + w * 8 + (lane & 3) * 2]; a0 += v.x; a1 += v.y; }
                const bool hi = ocol & 1;
                const float gb0 = hi ? bf_hi(m_gb0.x) : bf_lo(m_gb0.x), gb1 = hi ? bf_hi(m_gb1.x) : bf_lo(m_gb1.x);
                for (int it = 0; !__all_sync(0xffffffffu, xw.y == F_X1) && it < SPIN_LIMIT; it++) xw = ld_ll2(&sc->x1[ocol]);
                if (lane < 4) {
                    p.out[ocol] = __float2bfloat16_rn(bf_lo(xw.x) + bf16r(gb0 * bf16r(a0)));
                    p.out[D_MODEL + ocol] = __float2bfloat16_rn(bf_hi(xw.x) + bf16r(gb1 * bf16r(a1)));
                }
                TSTAMP(13);
            }
        }
    }
}

typedef CUresult (*EncodeFn)(CUtensorMap*, CUtensorMapDataType, cuuint32_t, void*, const cuuint64_t*, const cuuint64_t*,
                             const cuuint32_t*, const cuuint32_t*, CUtensorMapInterleave, CUtensorMapSwizzle,
                             CUtensorMapL2promotion, CUtensorMapFloatOOBfill);

struct Maps { CUtensorMap k, v, wq, wmod, wmod8, wo, wg, wu, wd; };

void encode(EncodeFn fn, CUtensorMap* m, const void* ptr, int rank, const cuuint64_t* dims, const cuuint64_t* strides,
            const cuuint32_t* box, CUtensorMapSwizzle sw) {
    const cuuint32_t es[3] = {1, 1, 1};
    fn(m, CU_TENSOR_MAP_DATA_TYPE_BFLOAT16, rank, const_cast<void*>(ptr), dims, strides, box, es,
       CU_TENSOR_MAP_INTERLEAVE_NONE, sw, CU_TENSOR_MAP_L2_PROMOTION_L2_256B, CU_TENSOR_MAP_FLOAT_OOB_FILL_NONE);
}

}

extern "C" void kernel_launch(void* const* d_in, const int* in_sizes, int n_in, void* d_out, int out_size) {
    (void)in_sizes; (void)n_in; (void)out_size;
    static EncodeFn enc = nullptr;
    static Scratch* scratch = nullptr;
    if (!enc) {
        cudaGetSymbolAddress((void**)&scratch, g_scratch);
        void* fn = nullptr;
        cudaDriverEntryPointQueryResult qr;
        cudaGetDriverEntryPoint("cuTensorMapEncodeTiled", &fn, cudaEnableDefault, &qr);
        enc = (EncodeFn)fn;
        cudaFuncSetAttribute(fused_block_kernel, cudaFuncAttributeMaxDynamicSharedMemorySize, SMEM_BYTES);
    }
    Maps m;
    {
        const cuuint64_t dims[3] = {64, (cuuint64_t)16 * SK, 2}, str[2] = {256, 128};
        const cuuint32_t box[3] = {64, 64, 2};
        encode(enc, &m.k, d_in[1], 3, dims, str, box, CU_TENSOR_MAP_SWIZZLE_128B);
        encode(enc, &m.v, d_in[2], 3, dims, str, box, CU_TENSOR_MAP_SWIZZLE_128B);
    }
    {
        const cuuint64_t dims[2] = {4096, 512}, str[1] = {8192};
        const cuuint32_t box[2] = {32, 256};
        encode(enc, &m.wq, d_in[3], 2, dims, str, box, CU_TENSOR_MAP_SWIZZLE_64B);
    }
    {
        const cuuint64_t dims[2] = {N_MOD, 512}, str[1] = {N_MOD * 2};
        const cuuint32_t box[2] = {16, 256};
        encode(enc, &m.wmod, d_in[10], 2, dims, str, box, CU_TENSOR_MAP_SWIZZLE_32B);
        const cuuint32_t box8[2] = {8, 256};
        encode(enc, &m.wmod8, d_in[10], 2, dims, str, box8, CU_TENSOR_MAP_SWIZZLE_NONE);
    }
    {
        const cuuint64_t dims_o[3] = {64, 4096, 8}, dims_d[3] = {64, D_FF, 8}, str[2] = {1024, 128};
        const cuuint32_t box[3] = {64, 16, 8}, box_o[3] = {64, 64, 2};
        encode(enc, &m.wo, d_in[4], 3, dims_o, str, box_o, CU_TENSOR_MAP_SWIZZLE_128B);
        encode(enc, &m.wd, d_in[8], 3, dims_d, str, box, CU_TENSOR_MAP_SWIZZLE_128B);
    }
    {
        const cuuint64_t dims[2] = {D_FF, 512}, str[1] = {D_FF * 2};
        const cuuint32_t box[2] = {16, 128};
        encode(enc, &m.wg, d_in[6], 2, dims, str, box, CU_TENSOR_MAP_SWIZZLE_32B);
        encode(enc, &m.wu, d_in[7], 2, dims, str, box, CU_TENSOR_MAP_SWIZZLE_32B);
    }
    Params p;
    p.x = (const __nv_bfloat16*)d_in[0];
    p.c = (const __nv_bfloat16*)d_in[9];
    p.out = (__nv_bfloat16*)d_out;
    p.sc = scratch;
    fused_block_kernel<<<NCTA, NTHREADS, SMEM_BYTES, cudaStreamPerThread>>>(p, m.k, m.v, m.wq, m.wmod, m.wmod8, m.wo, m.wg, m.wu, m.wd);
}
```

```cpp
#include <cuda_runtime.h>
#include <cuda.h>
#include <cuda_bf16.h>
#include <stdint.h>

namespace {

constexpr int D_MODEL = 512;
constexpr int N_HEADS = 32;
constexpr int SK = 32768;
constexpr int DH = 128;
constexpr int D_FF = 1792;
constexpr int N_MOD = 6 * D_MODEL;

constexpr int NCTA = 128;
constexpr int NFFN = D_FF / 16;
constexpr int NOWN = 32;
constexpr int NTHREADS = 320;
constexpr int NST = 12;
constexpr int TILE = 16384;
#define WINDOW 3
#define WINDOW_TAIL 1
#define GU_WIN 3
#define PACE_THR 96
constexpr int KV_TILES = 64;
#define MOD_AT 8
static_assert(MOD_AT % 2 == 0 && MOD_AT >= 2 && MOD_AT < 56, "schedule");
__host__ __device__ constexpr int kv_idx(int i) { return 2 + 2 * i + (i >= MOD_AT ? 1 : 0); }
constexpr int IDX_MOD = 2 + 2 * MOD_AT;
constexpr int N_STREAM = kv_idx(KV_TILES - 1) + 2;
constexpr int IDX_WO = N_STREAM;
constexpr int IDX_WG = IDX_WO + 2;
constexpr int IDX_WU = IDX_WG + 1;
constexpr int IDX_WD = IDX_WU + 1;
constexpr int SPIN_LIMIT = 1 << 20;

constexpr float LOG2E = 1.4426950408889634f;
constexpr float QK_SCALE = 0.08838834764831845f;

constexpr int SM_RING = 0;
constexpr int SM_MRG = SM_RING + NST * TILE;
constexpr int SM_ML = SM_MRG + 8 * 4 * 136 * 4;
constexpr int SM_RED = SM_ML + 8 * 4 * 8;
constexpr int SM_RED2 = SM_RED + 8 * 64 * 4;
constexpr int SM_QS = SM_RED2 + 8 * 64 * 4;
constexpr int SM_OS = SM_QS + 512 * 2;
constexpr int SM_SC = SM_OS + 2 * 128 * 2;
constexpr int SM_HS = SM_SC + 2 * 512 * 2;
constexpr int SM_STAT = SM_HS + 8 * 2 * 32 * 4;
constexpr int SM_PACE = SM_STAT + 8 * 2 * 8;
constexpr int SM_BAR = SM_PACE + 16;
constexpr int SM_END = SM_BAR + (2 * NST + 1 + 8 + 3) * 8;
constexpr int SMEM_BYTES = SM_END + 1024;

struct Scratch {
    uint4 inbox_wo[NOWN][N_HEADS][8];
    uint4 inbox_dn[NCTA][NFFN][2];
    uint2 x1[D_MODEL];
    uint2 part_o[NCTA][4][64];
    uint2 part_ml[NCTA][4][4];
    uint2 mod[2][N_MOD / 2];
    uint2 q[2][N_HEADS * DH / 2];
    unsigned epoch;
    unsigned pad_[31];
    unsigned cleared;
    unsigned pad2_[31];
    unsigned progress;
};
__device__ Scratch g_scratch;
constexpr uint32_t F_PART = 1, F_WO = 1, F_DOWN = 1, F_X1 = 1;
__device__ __forceinline__ uint32_t tagf(float v, uint32_t f) { return (__float_as_uint(v) & ~3u) | f; }
__device__ __forceinline__ float untag(uint32_t v) { return __uint_as_float(v & ~3u); }

struct Params {
    const __nv_bfloat16* x;
    const __nv_bfloat16* c;
    __nv_bfloat16* out;
    Scratch* sc;
};

#define TSTAMP(i) do { } while (0)

__device__ __forceinline__ uint32_t smem_u32(const void* p) { return (uint32_t)__cvta_generic_to_shared(p); }

__device__ __forceinline__ void mbar_init(uint32_t bar, uint32_t cnt) {
    asm volatile("mbarrier.init.shared::cta.b64 [%0], %1;" ::"r"(bar), "r"(cnt) : "memory");
}
__device__ __forceinline__ void mbar_expect_tx(uint32_t bar, uint32_t bytes) {
    asm volatile("mbarrier.arrive.expect_tx.shared::cta.b64 _, [%0], %1;" ::"r"(bar), "r"(bytes) : "memory");
}
__device__ __forceinline__ void mbar_arrive(uint32_t bar) {
    asm volatile("mbarrier.arrive.shared::cta.b64 _, [%0];" ::"r"(bar) : "memory");
}
__device__ __forceinline__ bool mbar_try(uint32_t bar, uint32_t parity) {
    uint32_t ok;
    asm volatile(
        "{\n\t.reg .pred p;\n\t"
        "mbarrier.try_wait.parity.shared::cta.b64 p, [%1], %2;\n\t"
        "selp.u32 %0, 1, 0, p;\n\t}"
        : "=r"(ok) : "r"(bar), "r"(parity) : "memory");
    return ok != 0;
}
__device__ __forceinline__ void mbar_wait(uint32_t bar, uint32_t parity) {
    if (mbar_try(bar, parity)) return;
    const long long t0 = clock64();
    while (!mbar_try(bar, parity))
        if (clock64() - t0 > (1ll << 31)) return;
}
__device__ __forceinline__ void cons_sync() { asm volatile("bar.sync 1, 256;" ::: "memory"); }

__device__ __forceinline__ void tma_2d(uint32_t dst, const CUtensorMap* m, int c0, int c1, uint32_t bar) {
    asm volatile("cp.async.bulk.tensor.2d.shared::cluster.global.mbarrier::complete_tx::bytes [%0], [%1, {%3, %4}], [%2];"
                 ::"r"(dst), "l"(m), "r"(bar), "r"(c0), "r"(c1) : "memory");
}
__device__ __forceinline__ void tma_3d(uint32_t dst, const CUtensorMap* m, int c0, int c1, int c2, uint32_t bar) {
    asm volatile("cp.async.bulk.tensor.3d.shared::cluster.global.mbarrier::complete_tx::bytes [%0], [%1, {%3, %4, %5}], [%2];"
                 ::"r"(dst), "l"(m), "r"(bar), "r"(c0), "r"(c1), "r"(c2) : "memory");
}
__device__ __forceinline__ void tma_3d_hint(uint32_t dst, const CUtensorMap* m, int c0, int c1, int c2, uint32_t bar, uint64_t pol) {
    asm volatile("cp.async.bulk.tensor.3d.shared::cluster.global.mbarrier::complete_tx::bytes.L2::cache_hint [%0], [%1, {%3, %4, %5}], [%2], %6;"
                 ::"r"(dst), "l"(m), "r"(bar), "r"(c0), "r"(c1), "r"(c2), "l"(pol) : "memory");
}
__device__ __forceinline__ void prefetch_tmap(const CUtensorMap* m) {
    asm volatile("prefetch.tensormap [%0];" ::"l"(m) : "memory");
}

__device__ __forceinline__ void ldsm4(uint32_t addr, uint32_t (&r)[4]) {
    asm volatile("ldmatrix.sync.aligned.m8n8.x4.shared.b16 {%0,%1,%2,%3}, [%4];"
                 : "=r"(r[0]), "=r"(r[1]), "=r"(r[2]), "=r"(r[3]) : "r"(addr) : "memory");
}
__device__ __forceinline__ void ldsm4t(uint32_t addr, uint32_t (&r)[4]) {
    asm volatile("ldmatrix.sync.aligned.m8n8.x4.trans.shared.b16 {%0,%1,%2,%3}, [%4];"
                 : "=r"(r[0]), "=r"(r[1]), "=r"(r[2]), "=r"(r[3]) : "r"(addr) : "memory");
}
__device__ __forceinline__ void mma16816(float (&c)[4], const uint32_t (&a)[4], uint32_t b0, uint32_t b1) {
    asm volatile("mma.sync.aligned.m16n8k16.row.col.f32.bf16.bf16.f32 {%0,%1,%2,%3}, {%4,%5,%6,%7}, {%8,%9}, {%0,%1,%2,%3};"
                 : "+f"(c[0]), "+f"(c[1]), "+f"(c[2]), "+f"(c[3])
                 : "r"(a[0]), "r"(a[1]), "r"(a[2]), "r"(a[3]), "r"(b0), "r"(b1));
}
__device__ __forceinline__ uint32_t movmatrix_t(uint32_t a) {
    uint32_t d;
    asm volatile("movmatrix.sync.aligned.m8n8.trans.b16 %0, %1;" : "=r"(d) : "r"(a));
    return d;
}
__device__ __forceinline__ uint32_t pack_bf16(float a, float b) {
    uint32_t r;
    asm("cvt.rn.bf16x2.f32 %0, %1, %2;" : "=r"(r) : "f"(b), "f"(a));
    return r;
}
__device__ __forceinline__ float bf_lo(uint32_t v) { return __uint_as_float(v << 16); }
__device__ __forceinline__ float bf_hi(uint32_t v) { return __uint_as_float(v & 0xffff0000u); }
__device__ __forceinline__ float bf16r(float a) { return bf_lo(pack_bf16(a, 0.f)); }
__device__ __forceinline__ uint32_t max_bf16x2(uint32_t a, uint32_t b) {
    uint32_t r;
    asm("max.bf16x2 %0, %1, %2;" : "=r"(r) : "r"(a), "r"(b));
    return r;
}
__device__ __forceinline__ float ex2(float x) {
    float r;
    asm("ex2.approx.ftz.f32 %0, %1;" : "=f"(r) : "f"(x));
    return r;
}

__device__ __forceinline__ void st_ll2(uint2* p, uint32_t v, uint32_t tag) {
    asm volatile("st.relaxed.gpu.global.v2.u32 [%0], {%1, %2};" ::"l"(p), "r"(v), "r"(tag) : "memory");
}
__device__ __forceinline__ void st_v4(uint4* p, uint32_t a, uint32_t b, uint32_t c, uint32_t d) {
    asm volatile("st.relaxed.gpu.global.v4.u32 [%0], {%1, %2, %3, %4};" ::"l"(p), "r"(a), "r"(b), "r"(c), "r"(d) : "memory");
}
__device__ __forceinline__ uint2 ld_ll2(const uint2* p) {
    uint2 v;
    asm volatile("ld.relaxed.gpu.global.v2.u32 {%0, %1}, [%2];" : "=r"(v.x), "=r"(v.y) : "l"(p) : "memory");
    return v;
}
__device__ __forceinline__ uint4 ld_ll4(const uint4* p) {
    uint4 v;
    asm volatile("ld.relaxed.gpu.global.v4.u32 {%0, %1, %2, %3}, [%4];"
                 : "=r"(v.x), "=r"(v.y), "=r"(v.z), "=r"(v.w) : "l"(p) : "memory");
    return v;
}

#define DELAY_P1 1800
#define DELAY_Q 1800
#define DELAY_A 1000
#define DELAY_B1 300
#define DELAY_X1 2000
#define DELAY_NOFFN 1500
#define DELAY_C 600
__device__ __forceinline__ uint32_t clock32() {
    uint32_t c;
    asm volatile("mov.u32 %0, %clock;" : "=r"(c));
    return c;
}
__device__ __forceinline__ void spin_cycles(uint32_t n) {
    if (n > 0) { const uint32_t c0 = clock32(); while (clock32() - c0 < n) {} }
}
__device__ __forceinline__ float rcp_approx(float x) {
    float r;
    asm("rcp.approx.ftz.f32 %0, %1;" : "=f"(r) : "f"(x));
    return r;
}
__device__ __forceinline__ float sqrt_approx(float x) {
    float r;
    asm("sqrt.approx.f32 %0, %1;" : "=f"(r) : "f"(x));
    return r;
}

__device__ __forceinline__ float silu_bf(float v) { return bf16r(v / (1.0f + expf(-v))); }

__device__ __forceinline__ float2 half_warp_sums(const float (&v)[4], float pivot) {
    float s1 = 0.f, s2 = 0.f;
#pragma unroll
    for (int i = 0; i < 4; i++) { const float d = v[i] - pivot; s1 += d; s2 += d * d; }
#pragma unroll
    for (int o = 1; o < 16; o <<= 1) { s1 += __shfl_xor_sync(0xffffffffu, s1, o); s2 += __shfl_xor_sync(0xffffffffu, s2, o); }
    return make_float2(s1, s2);
}
__device__ __forceinline__ void ln_stats(const float2* stat, int b, float pivot, float& mean_bf, float& rstd) {
    float s1 = 0.f, s2 = 0.f;
#pragma unroll
    for (int w = 0; w < 8; w++) { const float2 v = stat[w * 2 + b]; s1 += v.x; s2 += v.y; }
    const float dm = s1 * (1.0f / D_MODEL);
    const float var = fmaxf(s2 * (1.0f / D_MODEL) - dm * dm, 0.f);
    mean_bf = bf16r(pivot + dm);
    rstd = rcp_approx(bf16r(sqrt_approx(bf16r(bf16r(var) + 1e-5f))));
}
__device__ __forceinline__ float ln_norm(float xv, float mean_bf, float rstd) { return bf16r(bf16r(xv - mean_bf) * rstd); }
__device__ __forceinline__ float ln_mod(float n, float cmul, float sadd) { return bf16r(n * bf16r(1.0f + cmul)) + sadd; }

__global__ void __launch_bounds__(NTHREADS, 1)
fused_block_kernel(const Params p, const __grid_constant__ CUtensorMap tm_k, const __grid_constant__ CUtensorMap tm_v,
                   const __grid_constant__ CUtensorMap tm_wq, const __grid_constant__ CUtensorMap tm_wmod,
                   const __grid_constant__ CUtensorMap tm_wmod8,
                   const __grid_constant__ CUtensorMap tm_wo, const __grid_constant__ CUtensorMap tm_wg,
                   const __grid_constant__ CUtensorMap tm_wu, const __grid_constant__ CUtensorMap tm_wd) {
    extern __shared__ unsigned char smem_raw[];
    const uint32_t sbase = (smem_u32(smem_raw) + 1023u) & ~1023u;
    unsigned char* sgen = smem_raw + (sbase - smem_u32(smem_raw));
    const int tid = threadIdx.x, warp = tid >> 5, lane = tid & 31;
    const int cta = blockIdx.x;
    const uint32_t bar_full = sbase + SM_BAR, bar_empty = bar_full + NST * 8;
    const uint32_t bar_clear = bar_empty + NST * 8;
    const uint32_t bar_gu = bar_clear + 8;
    const uint32_t bar_bc = bar_gu + 8 * 8;
    const uint32_t bar_p0w = bar_bc + 8;
    const uint32_t bar_gate = bar_p0w + 8;

    const int key0 = (cta >> 3) * SK + (cta & 7) * 64;
    uint64_t pol = 0;
    if (tid == 256) {
        asm volatile("createpolicy.fractional.L2::evict_first.b64 %0, 1.0;" : "=l"(pol));
        mbar_init(bar_p0w, 1);
#pragma unroll
        for (int i = 0; i < 4; i++) mbar_init(bar_full + 8 * i, 1);
        asm volatile("fence.mbarrier_init.release.cluster;" ::: "memory");
        mbar_expect_tx(bar_p0w, 8192);
        tma_2d(sbase + SM_MRG, &tm_wmod8, cta * 8, 0, bar_p0w);
        tma_2d(sbase + SM_MRG + 4096, &tm_wmod8, cta * 8, 256, bar_p0w);
#pragma unroll
        for (int i = 0; i < 4; i++) mbar_expect_tx(bar_full + 8 * i, TILE);
        tma_2d(sbase + SM_RING, &tm_wq, cta * 32, 0, bar_full);
        tma_2d(sbase + SM_RING + TILE, &tm_wq, cta * 32, 256, bar_full + 8);
        tma_3d_hint(sbase + SM_RING + 2 * TILE, &tm_k, 0, key0, 0, bar_full + 16, pol);
        tma_3d_hint(sbase + SM_RING + 3 * TILE, &tm_v, 0, key0, 0, bar_full + 24, pol);
    }

    if (warp == 8) {
        if (lane == 0) {
            for (int i = 0; i < NST; i++) { if (i >= 4) mbar_init(bar_full + 8 * i, 1); mbar_init(bar_empty + 8 * i, 4); }
            mbar_init(bar_clear, 1);
            for (int k = 0; k < 8; k++) mbar_init(bar_gu + 8 * k, 1);
            mbar_init(bar_bc, 8);
            mbar_init(bar_gate, 1);
            ((volatile uint32_t*)(sgen + SM_PACE))[0] = 0;
            ((volatile uint32_t*)(sgen + SM_PACE))[1] = WINDOW;
            asm volatile("fence.mbarrier_init.release.cluster;" ::: "memory");
        }
        __syncwarp();
        asm volatile("bar.arrive 2, 288;" ::: "memory");
        asm volatile("bar.arrive 3, 64;" ::: "memory");
        if (lane == 0) {
            int slot = 4; uint32_t ph = 1;
            int landed = 0, wslot = 0; uint32_t wph = 0;
            int kv = 2;
            auto wait_window = [&](int idx, int window) {
                while (landed + window <= idx) {
                    mbar_wait(bar_full + 8 * wslot, wph);
                    if (++wslot == NST) { wslot = 0; wph ^= 1; }
                    landed++;
                }
            };
            volatile uint32_t* pace = (volatile uint32_t*)(sgen + SM_PACE);
            prefetch_tmap(&tm_wmod);
            pace[0] = 4;
            for (int idx = 4; idx < N_STREAM; idx++) {
                if (idx >= NST) mbar_wait(bar_empty + 8 * slot, ph);
                wait_window(idx, (int)pace[1]);
                if (idx == 12) { prefetch_tmap(&tm_wo); prefetch_tmap(&tm_wg); prefetch_tmap(&tm_wu); prefetch_tmap(&tm_wd); }
                const uint32_t fb = bar_full + 8 * slot, dst = sbase + SM_RING + slot * TILE;
                mbar_expect_tx(fb, TILE);
                if (idx == IDX_MOD) {
                    tma_2d(dst, &tm_wmod, 1024 + cta * 16, 0, fb);
                    tma_2d(dst + 8192, &tm_wmod, 1024 + cta * 16, 256, fb);
                } else {
                    tma_3d_hint(dst, (kv & 1) ? &tm_v : &tm_k, 0, key0 + (kv >> 1) * 512, 0, fb, pol);
                    kv++;
                }
                pace[0] = idx + 1;
                if (++slot == NST) { slot = 0; ph ^= 1; }
            }
            auto slot_free = [&](int idx) { mbar_wait(bar_empty + 8 * (idx % NST), ((idx / NST) & 1) ^ 1); };
#pragma unroll
            for (int s = 0; s < 2; s++) {
                const int idx = IDX_WO + s;
                slot_free(idx);
                wait_window(idx, WINDOW_TAIL);
                mbar_expect_tx(bar_full + 8 * (idx % NST), TILE);
                tma_3d(sbase + SM_RING + (idx % NST) * TILE, &tm_wo, 0, (cta >> 2) * 128 + s * 64, (cta & 3) * 2, bar_full + 8 * (idx % NST));
            }
            if (cta < NFFN) {
                slot_free(IDX_WG); slot_free(IDX_WU);
                mbar_wait(bar_full + 8 * (IDX_WO % NST), (IDX_WO / NST) & 1);
                mbar_wait(bar_full + 8 * ((IDX_WO + 1) % NST), ((IDX_WO + 1) / NST) & 1);
#pragma unroll
                for (int st = 0; st < 8; st++) {
                    if (st >= GU_WIN) mbar_wait(bar_gu + 8 * (st - GU_WIN), 0);
                    mbar_expect_tx(bar_gu + 8 * st, 4096);
                    tma_2d(sbase + SM_RING + (((st & 1) ? IDX_WU : IDX_WG) % NST) * TILE + (st >> 1) * 4096,
                           (st & 1) ? &tm_wu : &tm_wg, cta * 16, (st >> 1) * 128, bar_gu + 8 * st);
                }
                mbar_wait(bar_gu + 8 * 6, 0);
                slot_free(IDX_WD);
                mbar_expect_tx(bar_full + 8 * (IDX_WD % NST), TILE);
                tma_3d(sbase + SM_RING + (IDX_WD % NST) * TILE, &tm_wd, 0, cta * 16, 0, bar_full + 8 * (IDX_WD % NST));
            }
        }
    } else if (warp == 9) {
        Scratch* const sc = p.sc;
        const uint32_t tag = *(volatile unsigned*)&sc->epoch + 1;
        asm volatile("bar.sync 3, 64;" ::: "memory");
#pragma unroll 4
        for (int i = 0; i < NFFN * 2 / 32; i++) st_v4(&sc->inbox_dn[cta][0][0] + i * 32 + lane, 0u, 0u, 0u, 0u);
        if (cta >= NCTA - NOWN) {
#pragma unroll 4
            for (int i = 0; i < 8; i++) st_v4(&sc->inbox_wo[cta - (NCTA - NOWN)][0][0] + i * 32 + lane, 0u, 0u, 0u, 0u);
            if (lane < 8) st_v4((uint4*)&sc->x1[(cta - (NCTA - NOWN)) * 16] + lane, 0u, 0u, 0u, 0u);
        }
#pragma unroll 4
        for (int i = 0; i < 4; i++) st_v4((uint4*)&sc->part_o[cta][0][0] + i * 32 + lane, 0u, 0u, 0u, 0u);
        if (lane < 8) st_v4((uint4*)&sc->part_ml[cta][0][0] + lane, 0u, 0u, 0u, 0u);
        if (cta == 0 && lane == 0) asm volatile("st.relaxed.gpu.global.u32 [%0], %1;" ::"l"(&sc->progress), "r"(0u) : "memory");
        asm volatile("fence.acq_rel.gpu;" ::: "memory");
        __syncwarp();
        if (lane == 0) {
            asm volatile("fence.acq_rel.gpu;" ::: "memory");
            asm volatile("red.relaxed.gpu.global.add.u32 [%0], %1;" ::"l"(&sc->cleared), "r"(1u) : "memory");
            const uint32_t target = tag * NCTA;
            for (int it = 0; it < SPIN_LIMIT; it++) {
                uint32_t v;
                asm volatile("ld.relaxed.gpu.global.u32 %0, [%1];" : "=r"(v) : "l"(&sc->cleared) : "memory");
                if ((int32_t)(v - target) >= 0) break;
                __nanosleep(500);
            }
            asm volatile("fence.acq_rel.gpu;" ::: "memory");
            mbar_arrive(bar_clear);
            volatile uint32_t* pace = (volatile uint32_t*)(sgen + SM_PACE);
            uint32_t posted = 0;
            for (int it = 0; it < SPIN_LIMIT; it++) {
                const uint32_t own = pace[0];
                if (own > posted) {
                    asm volatile("red.relaxed.gpu.global.add.u32 [%0], %1;" ::"l"(&sc->progress), "r"(own - posted) : "memory");
                    posted = own;
                }
                uint32_t v;
                asm volatile("ld.relaxed.gpu.global.u32 %0, [%1];" : "=r"(v) : "l"(&sc->progress) : "memory");
                if (own >= N_STREAM) {
                    if (v >= NCTA * N_STREAM) break;
                } else {
                    const int diff = (int)v - (int)own * NCTA;
                    pace[1] = diff > PACE_THR ? WINDOW + 1 : diff < -PACE_THR ? WINDOW - 1 : WINDOW;
                }
                __nanosleep(200);
            }
            pace[2] = clock32();
            mbar_arrive(bar_gate);
            if (cta == 0) asm volatile("st.relaxed.gpu.global.u32 [%0], %1;" ::"l"(&sc->epoch), "r"(tag) : "memory");
        }
    } else {
        const int g = lane >> 2, t = lane & 3;
        const int bb = g & 1;
        const int eb = lane >> 4;
        const int ec = 64 * warp + 4 * (lane & 15);
        if (warp == 0) TSTAMP(0);
        Scratch* const sc = p.sc;
        const float c00 = __bfloat162float(p.c[tid]), c01 = __bfloat162float(p.c[tid + 256]);
        const float c10 = __bfloat162float(p.c[D_MODEL + tid]), c11 = __bfloat162float(p.c[D_MODEL + tid + 256]);
        const uint2 xe = __ldg((const uint2*)(p.x + eb * D_MODEL + ec));
        const float xpivot = __bfloat162float(p.x[eb * D_MODEL]);
        const uint32_t tag = *(volatile unsigned*)&sc->epoch + 1;
        const int ocol = cta * 4 + (lane & 3);
        const int wcol = (cta >= NCTA - NOWN ? cta - (NCTA - NOWN) : 0) * 16 + (lane & 15);
        const float xo = __bfloat162float(p.x[eb * D_MODEL + wcol]);

        float* red = (float*)(sgen + SM_RED);
        float* red2 = (float*)(sgen + SM_RED2);
        float2* stat = (float2*)(sgen + SM_STAT);
        uint32_t* hs = (uint32_t*)(sgen + SM_HS) + warp * 64;
        float xn[4];
        {
            float xv[4] = {bf_lo(xe.x), bf_hi(xe.x), bf_lo(xe.y), bf_hi(xe.y)};
            const float2 ps = half_warp_sums(xv, xpivot);
            if ((lane & 15) == 0) stat[warp * 2 + eb] = ps;
            const float s00 = silu_bf(c00), s01 = silu_bf(c01), s10 = silu_bf(c10), s11 = silu_bf(c11);
            __nv_bfloat16* scs = (__nv_bfloat16*)(sgen + SM_SC);
            scs[tid] = __float2bfloat16_rn(s00); scs[tid + 256] = __float2bfloat16_rn(s01);
            scs[512 + tid] = __float2bfloat16_rn(s10); scs[512 + tid + 256] = __float2bfloat16_rn(s11);
            asm volatile("bar.sync 2, 288;" ::: "memory");
            if (warp == 0) TSTAMP(23);
            float cp[4] = {0.f, 0.f, 0.f, 0.f};
            const uint32_t* sc32 = (const uint32_t*)(sgen + SM_SC) + bb * 256 + 32 * warp + t;
            mbar_wait(bar_p0w, 0);
#pragma unroll
            for (int s = 0; s < 4; s++) {
                uint32_t r0, r1;
                asm volatile("ldmatrix.sync.aligned.m8n8.x2.trans.shared.b16 {%0,%1}, [%2];"
                             : "=r"(r0), "=r"(r1) : "r"(sbase + SM_MRG + (64 * warp + 16 * s + (lane & 15)) * 16) : "memory");
                const uint32_t a[4] = {r0, r0, r1, r1};
                mma16816(cp, a, sc32[8 * s], sc32[8 * s + 4]);
            }
            if (t == 0) { red[warp * 16 + g] = cp[0]; red[warp * 16 + 8 + g] = cp[1]; }
            if (warp == 0) TSTAMP(14);
            cons_sync();
            if (warp == 0) {
                float s = 0.f;
#pragma unroll
                for (int w = 0; w < 8; w++) s += red[w * 16 + (lane & 15)];
                const float nx = __shfl_down_sync(0xffffffffu, s, 1);
                if (lane < 16 && !(lane & 1))
                    st_ll2(&sc->mod[lane >> 3][cta * 4 + ((lane & 7) >> 1)], pack_bf16(s, nx), tag);
                TSTAMP(1);
            }
            float mean_bf, rstd;
            ln_stats(stat, eb, xpivot, mean_bf, rstd);
#pragma unroll
            for (int i = 0; i < 4; i++) xn[i] = ln_norm(xv[i], mean_bf, rstd);
        }
        {
            uint4 sa, ca;
            spin_cycles(DELAY_P1);
            for (int it = 0;; it++) {
                sa = ld_ll4((const uint4*)&sc->mod[eb][ec >> 1]);
                ca = ld_ll4((const uint4*)&sc->mod[eb][256 + (ec >> 1)]);
                const bool ok = sa.y == tag && sa.w == tag && ca.y == tag && ca.w == tag;
                if (__all_sync(0xffffffffu, ok) || it > SPIN_LIMIT) break;
            }
            *(uint2*)&hs[eb * 32 + 2 * (lane & 15)] =
                make_uint2(pack_bf16(ln_mod(xn[0], bf_lo(ca.x), bf_lo(sa.x)), ln_mod(xn[1], bf_hi(ca.x), bf_hi(sa.x))),
                           pack_bf16(ln_mod(xn[2], bf_lo(ca.z), bf_lo(sa.z)), ln_mod(xn[3], bf_hi(ca.z), bf_hi(sa.z))));
            __syncwarp();
            uint32_t hb[8];
#pragma unroll
            for (int i = 0; i < 8; i++) hb[i] = hs[bb * 32 + 8 * (i >> 1) + 4 * (i & 1) + t];
            if (warp == 0) TSTAMP(2);
            float cq[2][4] = {};
            const int ts = warp >> 2;
            mbar_wait(bar_full + 8 * ts, 0);
            const uint32_t tb = sbase + SM_RING + ts * TILE;
#pragma unroll
            for (int s = 0; s < 4; s++) {
                const int row = 64 * (warp & 3) + 16 * s + (lane & 7) + (lane >> 4) * 8;
#pragma unroll
                for (int mt = 0; mt < 2; mt++) {
                    const int ch = 2 * mt + ((lane >> 3) & 1);
                    uint32_t a[4];
                    ldsm4t(tb + row * 64 + ((ch ^ ((row >> 1) & 3)) << 4), a);
                    mma16816(cq[mt], a, hb[2 * s], hb[2 * s + 1]);
                }
            }
            if (t < 2) {
                const float v0 = t == 0 ? cq[0][0] : cq[1][0], v1 = t == 0 ? cq[0][1] : cq[1][1];
                const float v2 = t == 0 ? cq[0][2] : cq[1][2], v3 = t == 0 ? cq[0][3] : cq[1][3];
                *(float2*)&red2[warp * 64 + (16 * t + g) * 2] = make_float2(v0, v1);
                *(float2*)&red2[warp * 64 + (16 * t + g + 8) * 2] = make_float2(v2, v3);
            }
            cons_sync();
            if (warp < 4 && lane == 0) { mbar_arrive(bar_empty); mbar_arrive(bar_empty + 8); }
            if (warp == 0) {
                const int b = lane >> 4, cp = lane & 15;
                float q0 = 0.f, q1 = 0.f;
#pragma unroll
                for (int w = 0; w < 8; w++) {
                    const float4 v = *(const float4*)&red2[w * 64 + cp * 4];
                    q0 += b ? v.y : v.x; q1 += b ? v.w : v.z;
                }
                st_ll2(&sc->q[b][cta * 16 + cp], pack_bf16(q0, q1), tag);
                TSTAMP(3);
            }
        }
        const int pair = cta >> 3;
        uint32_t qf[16];
        {
            uint2* qs = (uint2*)(sgen + SM_QS);
            if (tid < 128) {
                const uint4* src = (const uint4*)&sc->q[pair >> 3][(pair & 7) * 256] + tid;
                uint4 v;
                spin_cycles(DELAY_Q);
                for (int it = 0;; it++) {
                    v = ld_ll4(src);
                    if ((v.y == tag && v.w == tag) || it > SPIN_LIMIT) break;
                }
                qs[tid] = make_uint2(v.x, v.z);
            }
            cons_sync();
            const uint32_t* q32 = (const uint32_t*)(sgen + SM_QS);
#pragma unroll
            for (int s = 0; s < 8; s++) {
                qf[2 * s] = q32[(g & 3) * 64 + 8 * s + t];
                qf[2 * s + 1] = q32[(g & 3) * 64 + 8 * s + 4 + t];
            }
        }
        if (warp == 0) TSTAMP(4);

        float o[8][4];
#pragma unroll
        for (int i = 0; i < 8; i++) { o[i][0] = o[i][1] = o[i][2] = o[i][3] = 0.f; }
        uint32_t mrun = 0xff80ff80u;
        float ls[4] = {0.f, 0.f, 0.f, 0.f};
        uint4 m_sb, m_cb; uint2 m_ga, m_gb0, m_gb1;
        {
            const int grp = warp >> 2, wi = warp & 3;
            const int krow = 16 * wi + (lane & 7) + ((lane >> 3) & 1) * 8;
            const uint32_t koff = krow * 128 + ((((lane >> 4) & 1) ^ (lane & 7)) << 4);
            const int vrow = 16 * wi + (lane & 7) + (lane >> 4) * 8;
            const uint32_t voff = vrow * 128 + ((((lane >> 3) & 1) ^ (lane & 7)) << 4);
            const uint32_t ones[4] = {0x3f803f80u, 0x3f803f80u, 0x3f803f80u, 0x3f803f80u};
            for (int i = grp; i < KV_TILES; i += 2) {
                if (i == MOD_AT + grp) {
                    float cm[4] = {};
                    const uint32_t* sc32 = (const uint32_t*)(sgen + SM_SC) + bb * 256 + 32 * warp + t;
                    mbar_wait(bar_full + 8 * (IDX_MOD % NST), (IDX_MOD / NST) & 1);
                    const uint32_t tb = sbase + SM_RING + (IDX_MOD % NST) * TILE;
#pragma unroll
                    for (int s = 0; s < 4; s++) {
                        const int row = 64 * warp + 16 * s + (lane & 7) + (lane >> 4) * 8;
                        const int ch = (lane >> 3) & 1;
                        uint32_t a[4];
                        ldsm4t(tb + row * 32 + ((ch ^ ((row >> 2) & 1)) << 4), a);
                        mma16816(cm, a, sc32[8 * s], sc32[8 * s + 4]);
                    }
                    if (t == 0) {
                        *(float2*)&red[warp * 64 + g * 2] = make_float2(cm[0], cm[1]);
                        *(float2*)&red[warp * 64 + (g + 8) * 2] = make_float2(cm[2], cm[3]);
                    }
                    cons_sync();
                    if (warp < 4 && lane == 0) mbar_arrive(bar_empty + 8 * (IDX_MOD % NST));
                    if (warp == 1 && lane < 16) {
                        const int b = lane >> 3, cp = lane & 7;
                        float q0 = 0.f, q1 = 0.f;
#pragma unroll
                        for (int w = 0; w < 8; w++) {
                            const float4 v = *(const float4*)&red[w * 64 + cp * 4];
                            q0 += b ? v.y : v.x; q1 += b ? v.w : v.z;
                        }
                        st_ll2(&sc->mod[b][512 + cta * 8 + cp], pack_bf16(q0, q1), tag);
                    }
                }
                if (i == 56 + grp) {
                    m_sb = ld_ll4((const uint4*)&sc->mod[eb][768 + (ec >> 1)]);
                    m_cb = ld_ll4((const uint4*)&sc->mod[eb][1024 + (ec >> 1)]);
                    m_ga = ld_ll2(&sc->mod[eb][512 + (wcol >> 1)]);
                    m_gb0 = ld_ll2(&sc->mod[0][1280 + (ocol >> 1)]); m_gb1 = ld_ll2(&sc->mod[1][1280 + (ocol >> 1)]);
                }
                if (i == 60 + grp) {
                    for (int it = 0;; it++) {
                        const bool ok = m_sb.y == tag && m_sb.w == tag && m_cb.y == tag && m_cb.w == tag &&
                                        m_ga.y == tag && m_gb0.y == tag && m_gb1.y == tag;
                        if (__all_sync(0xffffffffu, ok) || it > SPIN_LIMIT) break;
                        m_sb = ld_ll4((const uint4*)&sc->mod[eb][768 + (ec >> 1)]);
                        m_cb = ld_ll4((const uint4*)&sc->mod[eb][1024 + (ec >> 1)]);
                        m_ga = ld_ll2(&sc->mod[eb][512 + (wcol >> 1)]);
                        m_gb0 = ld_ll2(&sc->mod[0][1280 + (ocol >> 1)]); m_gb1 = ld_ll2(&sc->mod[1][1280 + (ocol >> 1)]);
                    }
                    mbar_wait(bar_clear, 0);
                }
                const int ki = kv_idx(i), ks = ki % NST, vs = (ki + 1) % NST;
                const uint32_t kph = (ki / NST) & 1, vph = ((ki + 1) / NST) & 1;
                mbar_wait(bar_full + 8 * ks, kph);
                const uint32_t kb = sbase + SM_RING + ks * TILE + koff;
                float sa[4] = {0.f, 0.f, 0.f, 0.f}, sb[4] = {0.f, 0.f, 0.f, 0.f};
#pragma unroll
                for (int s = 0; s < 8; s += 2) {
                    uint32_t a0[4], a1[4];
                    ldsm4((kb ^ ((s & 3) << 5)) + (s >> 2) * 8192, a0);
                    ldsm4((kb ^ (((s + 1) & 3) << 5)) + (s >> 2) * 8192, a1);
                    mma16816(sa, a0, qf[2 * s], qf[2 * s + 1]);
                    mma16816(sb, a1, qf[2 * s + 2], qf[2 * s + 3]);
                }
                __syncwarp();
                if (lane == 0) mbar_arrive(bar_empty + 8 * ks);
                uint32_t r01 = pack_bf16(sa[0] + sb[0], sa[1] + sb[1]);
                uint32_t r23 = pack_bf16(sa[2] + sb[2], sa[3] + sb[3]);
                r01 = pack_bf16(bf_lo(r01) * QK_SCALE, bf_hi(r01) * QK_SCALE);
                r23 = pack_bf16(bf_lo(r23) * QK_SCALE, bf_hi(r23) * QK_SCALE);
                uint32_t mx = max_bf16x2(r01, r23);
                mx = max_bf16x2(mx, __shfl_xor_sync(0xffffffffu, mx, 4));
                mx = max_bf16x2(mx, __shfl_xor_sync(0xffffffffu, mx, 8));
                mx = max_bf16x2(mx, __shfl_xor_sync(0xffffffffu, mx, 16));
                const uint32_t mnew = max_bf16x2(mrun, mx);
                const float m0 = bf_lo(mnew), m1 = bf_hi(mnew);
                if (__any_sync(0xffffffffu, mnew != mrun)) {
                    const float al0 = ex2((bf_lo(mrun) - m0) * LOG2E), al1 = ex2((bf_hi(mrun) - m1) * LOG2E);
                    ls[0] *= al0; ls[1] *= al1;
#pragma unroll
                    for (int d = 0; d < 8; d++) { o[d][0] *= al0; o[d][1] *= al1; o[d][2] *= al0; o[d][3] *= al1; }
                    mrun = mnew;
                }
                const float p0 = ex2((bf_lo(r01) - m0) * LOG2E), p1 = ex2((bf_hi(r01) - m1) * LOG2E);
                const float p2 = ex2((bf_lo(r23) - m0) * LOG2E), p3 = ex2((bf_hi(r23) - m1) * LOG2E);
                const uint32_t pb0 = movmatrix_t(pack_bf16(p0, p1)), pb1 = movmatrix_t(pack_bf16(p2, p3));
                mma16816(ls, ones, pb0, pb1);
                mbar_wait(bar_full + 8 * vs, vph);
                const uint32_t vb = sbase + SM_RING + vs * TILE + voff;
#pragma unroll
                for (int d = 0; d < 8; d++) {
                    uint32_t a[4];
                    ldsm4t((vb ^ ((d & 3) << 5)) + (d >> 2) * 8192, a);
                    mma16816(o[d], a, pb0, pb1);
                }
                __syncwarp();
                if (lane == 0) mbar_arrive(bar_empty + 8 * vs);
            }
        }
        if (warp == 7) TSTAMP(5);
        {
            float* mrg = (float*)(sgen + SM_MRG);
            float2* ml = (float2*)(sgen + SM_ML);
            {
                const int hp = (t & 1) * 2, up = t >> 1;
                if (g == 0 && up == 0) { ml[warp * 4 + hp] = make_float2(bf_lo(mrun), ls[0]); ml[warp * 4 + hp + 1] = make_float2(bf_hi(mrun), ls[1]); }
                float* m0p = mrg + (warp * 4 + hp) * 136 + up * 72 + g;
#pragma unroll
                for (int d = 0; d < 4; d++) {
                    m0p[16 * d] = up ? o[d + 4][0] : o[d][0]; m0p[136 + 16 * d] = up ? o[d + 4][1] : o[d][1];
                    m0p[16 * d + 8] = up ? o[d + 4][2] : o[d][2]; m0p[136 + 16 * d + 8] = up ? o[d + 4][3] : o[d][3];
                }
            }
            cons_sync();
            const int hh = tid >> 6, dp = tid & 63;
            float2 mw[8];
            float M = -INFINITY;
#pragma unroll
            for (int w = 0; w < 8; w++) { mw[w] = ml[w * 4 + hh]; M = fmaxf(M, mw[w].x); }
            float L = 0.f, o0 = 0.f, o1 = 0.f;
#pragma unroll
            for (int w = 0; w < 8; w++) {
                const float wt = ex2((mw[w].x - M) * LOG2E);
                const float2 v = *(const float2*)&mrg[(w * 4 + hh) * 136 + 2 * dp + (dp >= 32 ? 8 : 0)];
                L += wt * mw[w].y; o0 += wt * v.x; o1 += wt * v.y;
            }
            st_ll2(&sc->part_o[cta][hh][dp], tagf(o0, F_PART), tagf(o1, F_PART));
            if (dp < 4) st_ll2(&sc->part_ml[cta][hh][dp], tagf(M, F_PART), tagf(L, F_PART));
        }
        if (warp == 0) TSTAMP(6);
        {
            const int hq = cta >> 2, kvh = hq >> 2, hh = hq & 3;
            const int b = tid >> 7, dc = (tid >> 3) & 15, j = tid & 7;
            const int pc = (b * 8 + kvh) * 8 + j;
            const uint4* po = (const uint4*)&sc->part_o[pc][hh][0] + dc * 2;
            const uint2* pm = &sc->part_ml[pc - j][hh][0];
            uint4 vo0, vo1; uint2 vm[8];
            mbar_wait(bar_gate, 0);
            { const uint32_t tg = ((volatile uint32_t*)(sgen + SM_PACE))[2]; while (clock32() - tg < DELAY_A) {} }
            bool oko = false, okm = false;
            for (int it = 0;; it++) {
                if (!oko) { vo0 = ld_ll4(po); vo1 = ld_ll4(po + 1); }
                if (!okm) {
#pragma unroll
                    for (int jj = 0; jj < 8; jj++) vm[jj] = ld_ll2(pm + jj * 16);
                }
                oko = (vo0.x & vo0.y & vo0.z & vo0.w & vo1.x & vo1.y & vo1.z & vo1.w & 3u) == F_PART;
                uint32_t all = vm[0].x & vm[0].y;
#pragma unroll
                for (int jj = 1; jj < 8; jj++) all &= vm[jj].x & vm[jj].y;
                okm = (all & 3u) == F_PART;
                if (__all_sync(0xffffffffu, oko && okm) || it > SPIN_LIMIT) break;
            }
            float M = untag(vm[0].x);
#pragma unroll
            for (int jj = 1; jj < 8; jj++) M = fmaxf(M, untag(vm[jj].x));
            float wt = 0.f, L = 0.f;
#pragma unroll
            for (int jj = 0; jj < 8; jj++) {
                const float w_ = ex2((untag(vm[jj].x) - M) * LOG2E);
                L += w_ * untag(vm[jj].y);
                wt = jj == j ? w_ : wt;
            }
            wt *= rcp_approx(L);
            float v[8] = {wt * untag(vo0.x), wt * untag(vo0.y), wt * untag(vo0.z), wt * untag(vo0.w),
                          wt * untag(vo1.x), wt * untag(vo1.y), wt * untag(vo1.z), wt * untag(vo1.w)};
#define XRED(N, O)                                                                       \
            {                                                                            \
                const bool up = lane & (O);                                              \
                _Pragma("unroll") for (int i = 0; i < (N); i++) {                        \
                    const float send = up ? v[i] : v[i + (N)], keep = up ? v[i + (N)] : v[i]; \
                    v[i] = keep + __shfl_xor_sync(0xffffffffu, send, (O));               \
                }                                                                        \
            }
            XRED(4, 1) XRED(2, 2) XRED(1, 4)
#undef XRED
            __nv_bfloat16* os = (__nv_bfloat16*)(sgen + SM_OS);
            os[b * 128 + dc * 8 + 4 * (j & 1) + 2 * ((j >> 1) & 1) + (j >> 2)] = __float2bfloat16_rn(v[0]);
            if (warp == 0) TSTAMP(15);
            uint32_t wf[8][4];
            const uint32_t aoff_o = (warp >> 2) * 8192 + ((lane & 7) + (lane >> 4) * 8) * 128 +
                                    (((((warp & 3) * 2 + ((lane >> 3) & 1)) ^ (lane & 7))) << 4);
#pragma unroll
            for (int s = 0; s < 2; s++) {
                const int idx = IDX_WO + s;
                mbar_wait(bar_full + 8 * (idx % NST), (idx / NST) & 1);
                const uint32_t tb = sbase + SM_RING + (idx % NST) * TILE + aoff_o;
#pragma unroll
                for (int k4 = 0; k4 < 4; k4++) ldsm4t(tb + k4 * 2048, wf[s * 4 + k4]);
            }
            cons_sync();
            if (warp == 0) TSTAMP(7);
            const uint32_t* os32 = (const uint32_t*)(sgen + SM_OS) + bb * 64 + t;
            float y0[4] = {}, y1[4] = {};
#pragma unroll
            for (int ks = 0; ks < 8; ks += 2) {
                mma16816(y0, wf[ks], os32[8 * ks], os32[8 * ks + 4]);
                mma16816(y1, wf[ks + 1], os32[8 * ks + 8], os32[8 * ks + 12]);
            }
            if (t == 0)
                st_v4(&sc->inbox_wo[(cta & 3) * 8 + warp][hq][g], tagf(y0[0] + y1[0], F_WO), tagf(y0[1] + y1[1], F_WO),
                      tagf(y0[2] + y1[2], F_WO), tagf(y0[3] + y1[3], F_WO));
        }
        const uint32_t t_wo = clock32();
        if (warp == 0) TSTAMP(8);
        if (cta >= NCTA - NOWN) {
            const uint4* pin = &sc->inbox_wo[cta - (NCTA - NOWN)][0][0] + tid;
            uint4 v;
            spin_cycles(DELAY_B1);
            bool ok = false;
            for (int it = 0;; it++) {
                if (!ok) {
                    v = ld_ll4(pin);
                    ok = (v.x & v.y & v.z & v.w & 3u) == F_WO;
                }
                if (__all_sync(0xffffffffu, ok) || it > SPIN_LIMIT) break;
            }
            const bool u1 = lane & 8, u2 = lane & 16;
            const float a0 = untag(v.x), a1 = untag(v.y), a2 = untag(v.z), a3 = untag(v.w);
            const float k0 = (u1 ? a2 : a0) + __shfl_xor_sync(0xffffffffu, u1 ? a0 : a2, 8);
            const float k1 = (u1 ? a3 : a1) + __shfl_xor_sync(0xffffffffu, u1 ? a1 : a3, 8);
            red2[warp * 32 + lane] = (u2 ? k1 : k0) + __shfl_xor_sync(0xffffffffu, u2 ? k0 : k1, 16);
            cons_sync();
            if (warp == 0) {
                float a = 0.f;
#pragma unroll
                for (int w = 0; w < 8; w++) a += red2[w * 32 + lane];
                const float ga = (wcol & 1) ? bf_hi(m_ga.x) : bf_lo(m_ga.x);
                const float xm = bf16r(xo + bf16r(ga * bf16r(a)));
                const float xm_b1 = __shfl_down_sync(0xffffffffu, xm, 16);
                if (lane < 16) st_ll2(&sc->x1[wcol], pack_bf16(xm, xm_b1), F_X1);
                TSTAMP(10);
            }
        }
        const uint32_t aoff = warp * 2048 + ((lane & 7) + (lane >> 4) * 8) * 128 + ((((lane >> 3) & 1) ^ (lane & 7)) << 4);
        if (cta < NFFN) {
            const uint4* px = (const uint4*)&sc->x1[ec];
            const uint4* pp = (const uint4*)&sc->x1[0];
            uint4 va, vb, pa, pb;
            uint32_t gf[4][4], uf[4][4];
            mbar_wait(bar_gu + 8 * (2 * (warp >> 1)), 0);
            mbar_wait(bar_gu + 8 * (2 * (warp >> 1) + 1), 0);
            {
                const uint32_t tg = sbase + SM_RING + (IDX_WG % NST) * TILE, tu = sbase + SM_RING + (IDX_WU % NST) * TILE;
#pragma unroll
                for (int s = 0; s < 4; s++) {
                    const int row = 64 * warp + 16 * s + (lane & 7) + (lane >> 4) * 8;
                    const uint32_t off = row * 32 + ((((lane >> 3) & 1) ^ ((row >> 2) & 1)) << 4);
                    ldsm4t(tg + off, gf[s]);
                    ldsm4t(tu + off, uf[s]);
                }
            }
            const float c1v[4] = {bf16r(1.0f + bf_lo(m_cb.x)), bf16r(1.0f + bf_hi(m_cb.x)), bf16r(1.0f + bf_lo(m_cb.z)), bf16r(1.0f + bf_hi(m_cb.z))};
            float bg = 0.f, cgc = 0.f, bu = 0.f, cuc = 0.f;
            {
                uint32_t* pre = (uint32_t*)(sgen + SM_MRG) + warp * 128;
                float* bc = (float*)(sgen + SM_MRG + 4096);
                *(uint2*)&pre[eb * 32 + 2 * (lane & 15)] = make_uint2(pack_bf16(c1v[0], c1v[1]), pack_bf16(c1v[2], c1v[3]));
                *(uint2*)&pre[64 + eb * 32 + 2 * (lane & 15)] = make_uint2(m_sb.x, m_sb.z);
                __syncwarp();
                float yg[4] = {}, yu[4] = {};
                const uint32_t* pb = pre + ((g >> 1) & 1) * 64 + bb * 32 + t;
#pragma unroll
                for (int s = 0; s < 4; s++) {
                    const uint32_t b0 = pb[8 * s], b1 = pb[8 * s + 4];
                    mma16816(yg, gf[s], b0, b1);
                    mma16816(yu, uf[s], b0, b1);
                }
                const float y0 = t < 2 ? yg[0] : yu[0], y1 = t < 2 ? yg[1] : yu[1], y2 = t < 2 ? yg[2] : yu[2], y3 = t < 2 ? yg[3] : yu[3];
                float* dstp = bc + warp * 128 + (t >> 1) * 64 + (t & 1) * 32;
                *(float2*)&dstp[g * 2] = make_float2(y0, y1);
                *(float2*)&dstp[(g + 8) * 2] = make_float2(y2, y3);
                __syncwarp();
                if (lane == 0) mbar_arrive(bar_bc);
            }
            if (warp == 0) TSTAMP(11);
            float pivot2;
            {
                while (clock32() - t_wo < DELAY_X1) {}
                bool okx = false, okp = false;
                for (int it = 0;; it++) {
                    if (!okx) { va = ld_ll4(px); vb = ld_ll4(px + 1); }
                    if (!okp) { pa = ld_ll4(pp); pb = ld_ll4(pp + 1); }
                    okx = va.y == F_X1 && va.w == F_X1 && vb.y == F_X1 && vb.w == F_X1;
                    okp = pa.y == F_X1 && pa.w == F_X1 && pb.y == F_X1 && pb.w == F_X1;
                    if (__all_sync(0xffffffffu, okx && okp) || it > SPIN_LIMIT) break;
                }
                if (warp == 0) TSTAMP(9);
                const float xv[4] = {eb ? bf_hi(va.x) : bf_lo(va.x), eb ? bf_hi(va.z) : bf_lo(va.z),
                                     eb ? bf_hi(vb.x) : bf_lo(vb.x), eb ? bf_hi(vb.z) : bf_lo(vb.z)};
                const float p0 = 0.25f * ((bf_lo(pa.x) + bf_lo(pa.z)) + (bf_lo(pb.x) + bf_lo(pb.z)));
                const float p1 = 0.25f * ((bf_hi(pa.x) + bf_hi(pa.z)) + (bf_hi(pb.x) + bf_hi(pb.z)));
                const float pivot = eb ? p1 : p0;
                pivot2 = (lane & 1) ? p1 : p0;
                *(uint2*)&hs[eb * 32 + 2 * (lane & 15)] =
                    make_uint2(pack_bf16((xv[0] - pivot) * c1v[0], (xv[1] - pivot) * c1v[1]),
                               pack_bf16((xv[2] - pivot) * c1v[2], (xv[3] - pivot) * c1v[3]));
                __syncwarp();
                float cg[2][4] = {}, cu[2][4] = {};
#pragma unroll
                for (int s = 0; s < 4; s++) {
                    const uint32_t b0 = hs[bb * 32 + 8 * s + t], b1 = hs[bb * 32 + 8 * s + 4 + t];
                    mma16816(cg[s & 1], gf[s], b0, b1);
                    mma16816(cu[s & 1], uf[s], b0, b1);
                }
                const float2 ps = half_warp_sums(xv, pivot);
                if ((lane & 15) == 0) stat[warp * 2 + eb] = ps;
                {
                    const float* bc = (const float*)(sgen + SM_MRG + 4096);
                    mbar_wait(bar_bc, 0);
#pragma unroll
                    for (int w = 0; w < 8; w++) {
                        bg += bc[w * 128 + lane]; cgc += bc[w * 128 + 32 + lane];
                        bu += bc[w * 128 + 64 + lane]; cuc += bc[w * 128 + 96 + lane];
                    }
                }
                if (t < 2) {
                    float v[4];
#pragma unroll
                    for (int i = 0; i < 4; i++) v[i] = t ? cu[0][i] + cu[1][i] : cg[0][i] + cg[1][i];
                    *(float2*)&red[warp * 64 + t * 32 + g * 2] = make_float2(v[0], v[1]);
                    *(float2*)&red[warp * 64 + t * 32 + (g + 8) * 2] = make_float2(v[2], v[3]);
                }
            }
            uint32_t df[4][4];
            mbar_wait(bar_full + 8 * (IDX_WD % NST), (IDX_WD / NST) & 1);
#pragma unroll
            for (int mt = 0; mt < 4; mt++) ldsm4t((sbase + SM_RING + (IDX_WD % NST) * TILE + aoff) ^ (mt << 5), df[mt]);
            cons_sync();
            {
                float gs = 0.f, us = 0.f;
#pragma unroll
                for (int w = 0; w < 8; w++) { gs += red[w * 64 + lane]; us += red[w * 64 + 32 + lane]; }
                float mean_bf, rstd;
                ln_stats(stat, lane & 1, pivot2, mean_bf, rstd);
                const float dm = mean_bf - pivot2;
                gs = bf16r(rstd * (gs - dm * bg) + cgc);
                us = rstd * (us - dm * bu) + cuc;
                const float u2 = gs * (1.0f + 0.044715f * gs * gs) * (2.0f * 0.7978845608028654f * LOG2E);
                const float ge = bf16r(__fdividef(gs, 1.0f + ex2(-u2)));
                const float act = bf16r(ge * bf16r(us));
                const float a0 = __shfl_sync(0xffffffffu, act, 4 * t + bb), a1 = __shfl_sync(0xffffffffu, act, 4 * t + 2 + bb);
                const float a2 = __shfl_sync(0xffffffffu, act, 4 * t + 16 + bb), a3 = __shfl_sync(0xffffffffu, act, 4 * t + 18 + bb);
                const uint32_t b0 = pack_bf16(a0, a1), b1 = pack_bf16(a2, a3);
                float y[4][4] = {};
#pragma unroll
                for (int mt = 0; mt < 4; mt++) mma16816(y[mt], df[mt], b0, b1);
                float v[4];
#pragma unroll
                for (int i = 0; i < 4; i++) v[i] = t == 0 ? y[0][i] : t == 1 ? y[1][i] : t == 2 ? y[2][i] : y[3][i];
            {
                const bool odd = g & 1;
                const float sx = odd ? v[0] : v[2], sy = odd ? v[1] : v[3];
                const float rx = __shfl_xor_sync(0xffffffffu, sx, 4), ry = __shfl_xor_sync(0xffffffffu, sy, 4);
                const int c0 = 64 * warp + 16 * t + (odd ? g + 7 : g);
                const float e0 = odd ? rx : v[0], e1 = odd ? ry : v[1], e2 = odd ? v[2] : rx, e3 = odd ? v[3] : ry;
                st_v4(&sc->inbox_dn[c0 >> 2][cta][(c0 >> 1) & 1], tagf(e0, F_DOWN), tagf(e1, F_DOWN), tagf(e2, F_DOWN), tagf(e3, F_DOWN));
            }
            }
            if (warp == 0) TSTAMP(12);
        }
        {
            uint2 xw;
            float r0;
            {
                const uint4* pin = &sc->inbox_dn[cta][0][0] + tid;
                uint4 v = make_uint4(F_DOWN, F_DOWN, F_DOWN, F_DOWN);
                if (cta < NFFN) spin_cycles(DELAY_C);
                else while (clock32() - t_wo < DELAY_X1 + DELAY_NOFFN) {}
                xw = ld_ll2(&sc->x1[ocol]);
                bool ok = tid >= NFFN * 2;
                for (int it = 0;; it++) {
                    if (!ok) {
                        v = ld_ll4(pin);
                        ok = (v.x & v.y & v.z & v.w & 3u) == F_DOWN;
                    }
                    if (__all_sync(0xffffffffu, ok) || it > SPIN_LIMIT) break;
                }
                const bool u1 = lane & 2, u2 = lane & 4;
                const float a0 = untag(v.x), a1 = untag(v.y), a2 = untag(v.z), a3 = untag(v.w);
                const float k0 = (u1 ? a1 : a0) + __shfl_xor_sync(0xffffffffu, u1 ? a0 : a1, 2);
                const float k1 = (u1 ? a3 : a2) + __shfl_xor_sync(0xffffffffu, u1 ? a2 : a3, 2);
                r0 = (u2 ? k1 : k0) + __shfl_xor_sync(0xffffffffu, u2 ? k0 : k1, 4);
                r0 += __shfl_xor_sync(0xffffffffu, r0, 8);
                r0 += __shfl_xor_sync(0xffffffffu, r0, 16);
                if (lane < 8) red2[256 + warp * 8 + (2 * (lane & 1) + ((lane >> 2) & 1)) * 2 + ((lane >> 1) & 1)] = r0;
            }
            cons_sync();
            if (warp == 0) {
                float a0 = 0.f, a1 = 0.f;
#pragma unroll
                for (int w = 0; w < 8; w++) { const float2 v = *(const float2*)&red2[256 + w * 8 + (lane & 3) * 2]; a0 += v.x; a1 += v.y; }
                const bool hi = ocol & 1;
                const float gb0 = hi ? bf_hi(m_gb0.x) : bf_lo(m_gb0.x), gb1 = hi ? bf_hi(m_gb1.x) : bf_lo(m_gb1.x);
                for (int it = 0; !__all_sync(0xffffffffu, xw.y == F_X1) && it < SPIN_LIMIT; it++) xw = ld_ll2(&sc->x1[ocol]);
                if (lane < 4) {
                    p.out[ocol] = __float2bfloat16_rn(bf_lo(xw.x) + bf16r(gb0 * bf16r(a0)));
                    p.out[D_MODEL + ocol] = __float2bfloat16_rn(bf_hi(xw.x) + bf16r(gb1 * bf16r(a1)));
                }
                TSTAMP(13);
            }
        }
    }
}

typedef CUresult (*EncodeFn)(CUtensorMap*, CUtensorMapDataType, cuuint32_t, void*, const cuuint64_t*, const cuuint64_t*,
                             const cuuint32_t*, const cuuint32_t*, CUtensorMapInterleave, CUtensorMapSwizzle,
                             CUtensorMapL2promotion, CUtensorMapFloatOOBfill);

struct Maps { CUtensorMap k, v, wq, wmod, wmod8, wo, wg, wu, wd; };

void encode(EncodeFn fn, CUtensorMap* m, const void* ptr, int rank, const cuuint64_t* dims, const cuuint64_t* strides,
            const cuuint32_t* box, CUtensorMapSwizzle sw) {
    const cuuint32_t es[3] = {1, 1, 1};
    fn(m, CU_TENSOR_MAP_DATA_TYPE_BFLOAT16, rank, const_cast<void*>(ptr), dims, strides, box, es,
       CU_TENSOR_MAP_INTERLEAVE_NONE, sw, CU_TENSOR_MAP_L2_PROMOTION_L2_256B, CU_TENSOR_MAP_FLOAT_OOB_FILL_NONE);
}

}

extern "C" void kernel_launch(void* const* d_in, const int* in_sizes, int n_in, void* d_out, int out_size) {
    (void)in_sizes; (void)n_in; (void)out_size;
    static EncodeFn enc = nullptr;
    static Scratch* scratch = nullptr;
    if (!enc) {
        cudaGetSymbolAddress((void**)&scratch, g_scratch);
        void* fn = nullptr;
        cudaDriverEntryPointQueryResult qr;
        cudaGetDriverEntryPoint("cuTensorMapEncodeTiled", &fn, cudaEnableDefault, &qr);
        enc = (EncodeFn)fn;
        cudaFuncSetAttribute(fused_block_kernel, cudaFuncAttributeMaxDynamicSharedMemorySize, SMEM_BYTES);
    }
    Maps m;
    {
        const cuuint64_t dims[3] = {64, (cuuint64_t)16 * SK, 2}, str[2] = {256, 128};
        const cuuint32_t box[3] = {64, 64, 2};
        encode(enc, &m.k, d_in[1], 3, dims, str, box, CU_TENSOR_MAP_SWIZZLE_128B);
        encode(enc, &m.v, d_in[2], 3, dims, str, box, CU_TENSOR_MAP_SWIZZLE_128B);
    }
    {
        const cuuint64_t dims[2] = {4096, 512}, str[1] = {8192};
        const cuuint32_t box[2] = {32, 256};
        encode(enc, &m.wq, d_in[3], 2, dims, str, box, CU_TENSOR_MAP_SWIZZLE_64B);
    }
    {
        const cuuint64_t dims[2] = {N_MOD, 512}, str[1] = {N_MOD * 2};
        const cuuint32_t box[2] = {16, 256};
        encode(enc, &m.wmod, d_in[10], 2, dims, str, box, CU_TENSOR_MAP_SWIZZLE_32B);
        const cuuint32_t box8[2] = {8, 256};
        encode(enc, &m.wmod8, d_in[10], 2, dims, str, box8, CU_TENSOR_MAP_SWIZZLE_NONE);
    }
    {
        const cuuint64_t dims_o[3] = {64, 4096, 8}, dims_d[3] = {64, D_FF, 8}, str[2] = {1024, 128};
        const cuuint32_t box[3] = {64, 16, 8}, box_o[3] = {64, 64, 2};
        encode(enc, &m.wo, d_in[4], 3, dims_o, str, box_o, CU_TENSOR_MAP_SWIZZLE_128B);
        encode(enc, &m.wd, d_in[8], 3, dims_d, str, box, CU_TENSOR_MAP_SWIZZLE_128B);
    }
    {
        const cuuint64_t dims[2] = {D_FF, 512}, str[1] = {D_FF * 2};
        const cuuint32_t box[2] = {16, 128};
        encode(enc, &m.wg, d_in[6], 2, dims, str, box, CU_TENSOR_MAP_SWIZZLE_32B);
        encode(enc, &m.wu, d_in[7], 2, dims, str, box, CU_TENSOR_MAP_SWIZZLE_32B);
    }
    Params p;
    p.x = (const __nv_bfloat16*)d_in[0];
    p.c = (const __nv_bfloat16*)d_in[9];
    p.out = (__nv_bfloat16*)d_out;
    p.sc = scratch;
    fused_block_kernel<<<NCTA, NTHREADS, SMEM_BYTES, cudaStreamPerThread>>>(p, m.k, m.v, m.wq, m.wmod, m.wmod8, m.wo, m.wg, m.wu, m.wd);
}
```

```cpp
#include <cuda_runtime.h>
#include <cuda.h>
#include <cuda_bf16.h>
#include <stdint.h>

namespace {

constexpr int D_MODEL = 512;
constexpr int N_HEADS = 32;
constexpr int SK = 32768;
constexpr int DH = 128;
constexpr int D_FF = 1792;
constexpr int N_MOD = 6 * D_MODEL;

constexpr int NCTA = 128;
constexpr int NFFN = D_FF / 16;
constexpr int NOWN = 32;
constexpr int NTHREADS = 320;
constexpr int NST = 12;
constexpr int TILE = 16384;
#define WINDOW 3
#define WINDOW_TAIL 1
#define GU_WIN 3
#define PACE_THR 96
constexpr int KV_TILES = 64;
#define MOD_AT 8
static_assert(MOD_AT % 2 == 0 && MOD_AT >= 2 && MOD_AT < 56, "schedule");
__host__ __device__ constexpr int kv_idx(int i) { return 2 + 2 * i + (i >= MOD_AT ? 1 : 0); }
constexpr int IDX_MOD = 2 + 2 * MOD_AT;
constexpr int N_STREAM = kv_idx(KV_TILES - 1) + 2;
constexpr int IDX_WO = N_STREAM;
constexpr int IDX_WG = IDX_WO + 2;
constexpr int IDX_WU = IDX_WG + 1;
constexpr int IDX_WD = IDX_WU + 1;
constexpr int SPIN_LIMIT = 1 << 20;

constexpr float LOG2E = 1.4426950408889634f;
constexpr float QK_SCALE = 0.08838834764831845f;

constexpr int SM_RING = 0;
constexpr int SM_MRG = SM_RING + NST * TILE;
constexpr int SM_ML = SM_MRG + 8 * 4 * 136 * 4;
constexpr int SM_RED = SM_ML + 8 * 4 * 8;
constexpr int SM_RED2 = SM_RED + 8 * 64 * 4;
constexpr int SM_QS = SM_RED2 + 8 * 64 * 4;
constexpr int SM_OS = SM_QS + 512 * 2;
constexpr int SM_SC = SM_OS + 2 * 128 * 2;
constexpr int SM_HS = SM_SC + 2 * 512 * 2;
constexpr int SM_STAT = SM_HS + 8 * 2 * 32 * 4;
constexpr int SM_PACE = SM_STAT + 8 * 2 * 8;
constexpr int SM_BAR = SM_PACE + 16;
constexpr int SM_END = SM_BAR + (2 * NST + 1 + 8 + 3) * 8;
constexpr int SMEM_BYTES = SM_END + 1024;

struct Scratch {
    uint4 inbox_wo[NOWN][N_HEADS][8];
    uint4 inbox_dn[NCTA][NFFN][2];
    uint2 x1[D_MODEL];
    uint2 part_o[NCTA][4][64];
    uint2 part_ml[NCTA][4][4];
    uint2 mod[2][N_MOD / 2];
    uint2 q[2][N_HEADS * DH / 2];
    unsigned epoch;
    unsigned pad_[31];
    unsigned cleared;
    unsigned pad2_[31];
    unsigned progress;
};
__device__ Scratch g_scratch;
constexpr uint32_t F_PART = 1, F_WO = 1, F_DOWN = 1, F_X1 = 1;
__device__ __forceinline__ uint32_t tagf(float v, uint32_t f) { return (__float_as_uint(v) & ~3u) | f; }
__device__ __forceinline__ float untag(uint32_t v) { return __uint_as_float(v & ~3u); }

struct Params {
    const __nv_bfloat16* x;
    const __nv_bfloat16* c;
    __nv_bfloat16* out;
    Scratch* sc;
};

#define TSTAMP(i) do { } while (0)

__device__ __forceinline__ uint32_t smem_u32(const void* p) { return (uint32_t)__cvta_generic_to_shared(p); }

__device__ __forceinline__ void mbar_init(uint32_t bar, uint32_t cnt) {
    asm volatile("mbarrier.init.shared::cta.b64 [%0], %1;" ::"r"(bar), "r"(cnt) : "memory");
}
__device__ __forceinline__ void mbar_expect_tx(uint32_t bar, uint32_t bytes) {
    asm volatile("mbarrier.arrive.expect_tx.shared::cta.b64 _, [%0], %1;" ::"r"(bar), "r"(bytes) : "memory");
}
__device__ __forceinline__ void mbar_arrive(uint32_t bar) {
    asm volatile("mbarrier.arrive.shared::cta.b64 _, [%0];" ::"r"(bar) : "memory");
}
__device__ __forceinline__ bool mbar_try(uint32_t bar, uint32_t parity) {
    uint32_t ok;
    asm volatile(
        "{\n\t.reg .pred p;\n\t"
        "mbarrier.try_wait.parity.shared::cta.b64 p, [%1], %2;\n\t"
        "selp.u32 %0, 1, 0, p;\n\t}"
        : "=r"(ok) : "r"(bar), "r"(parity) : "memory");
    return ok != 0;
}
__device__ __forceinline__ void mbar_wait(uint32_t bar, uint32_t parity) {
    if (mbar_try(bar, parity)) return;
    const long long t0 = clock64();
    while (!mbar_try(bar, parity))
        if (clock64() - t0 > (1ll << 31)) return;
}
__device__ __forceinline__ void cons_sync() { asm volatile("bar.sync 1, 256;" ::: "memory"); }

__device__ __forceinline__ void tma_2d(uint32_t dst, const CUtensorMap* m, int c0, int c1, uint32_t bar) {
    asm volatile("cp.async.bulk.tensor.2d.shared::cluster.global.mbarrier::complete_tx::bytes [%0], [%1, {%3, %4}], [%2];"
                 ::"r"(dst), "l"(m), "r"(bar), "r"(c0), "r"(c1) : "memory");
}
__device__ __forceinline__ void tma_3d(uint32_t dst, const CUtensorMap* m, int c0, int c1, int c2, uint32_t bar) {
    asm volatile("cp.async.bulk.tensor.3d.shared::cluster.global.mbarrier::complete_tx::bytes [%0], [%1, {%3, %4, %5}], [%2];"
                 ::"r"(dst), "l"(m), "r"(bar), "r"(c0), "r"(c1), "r"(c2) : "memory");
}
__device__ __forceinline__ void tma_3d_hint(uint32_t dst, const CUtensorMap* m, int c0, int c1, int c2, uint32_t bar, uint64_t pol) {
    asm volatile("cp.async.bulk.tensor.3d.shared::cluster.global.mbarrier::complete_tx::bytes.L2::cache_hint [%0], [%1, {%3, %4, %5}], [%2], %6;"
                 ::"r"(dst), "l"(m), "r"(bar), "r"(c0), "r"(c1), "r"(c2), "l"(pol) : "memory");
}
__device__ __forceinline__ void prefetch_tmap(const CUtensorMap* m) {
    asm volatile("prefetch.tensormap [%0];" ::"l"(m) : "memory");
}

__device__ __forceinline__ void ldsm4(uint32_t addr, uint32_t (&r)[4]) {
    asm volatile("ldmatrix.sync.aligned.m8n8.x4.shared.b16 {%0,%1,%2,%3}, [%4];"
                 : "=r"(r[0]), "=r"(r[1]), "=r"(r[2]), "=r"(r[3]) : "r"(addr) : "memory");
}
__device__ __forceinline__ void ldsm4t(uint32_t addr, uint32_t (&r)[4]) {
    asm volatile("ldmatrix.sync.aligned.m8n8.x4.trans.shared.b16 {%0,%1,%2,%3}, [%4];"
                 : "=r"(r[0]), "=r"(r[1]), "=r"(r[2]), "=r"(r[3]) : "r"(addr) : "memory");
}
__device__ __forceinline__ void mma16816(float (&c)[4], const uint32_t (&a)[4], uint32_t b0, uint32_t b1) {
    asm volatile("mma.sync.aligned.m16n8k16.row.col.f32.bf16.bf16.f32 {%0,%1,%2,%3}, {%4,%5,%6,%7}, {%8,%9}, {%0,%1,%2,%3};"
                 : "+f"(c[0]), "+f"(c[1]), "+f"(c[2]), "+f"(c[3])
                 : "r"(a[0]), "r"(a[1]), "r"(a[2]), "r"(a[3]), "r"(b0), "r"(b1));
}
__device__ __forceinline__ uint32_t movmatrix_t(uint32_t a) {
    uint32_t d;
    asm volatile("movmatrix.sync.aligned.m8n8.trans.b16 %0, %1;" : "=r"(d) : "r"(a));
    return d;
}
__device__ __forceinline__ uint32_t pack_bf16(float a, float b) {
    uint32_t r;
    asm("cvt.rn.bf16x2.f32 %0, %1, %2;" : "=r"(r) : "f"(b), "f"(a));
    return r;
}
__device__ __forceinline__ float bf_lo(uint32_t v) { return __uint_as_float(v << 16); }
__device__ __forceinline__ float bf_hi(uint32_t v) { return __uint_as_float(v & 0xffff0000u); }
__device__ __forceinline__ float bf16r(float a) { return bf_lo(pack_bf16(a, 0.f)); }
__device__ __forceinline__ uint32_t max_bf16x2(uint32_t a, uint32_t b) {
    uint32_t r;
    asm("max.bf16x2 %0, %1, %2;" : "=r"(r) : "r"(a), "r"(b));
    return r;
}
__device__ __forceinline__ float ex2(float x) {
    float r;
    asm("ex2.approx.ftz.f32 %0, %1;" : "=f"(r) : "f"(x));
    return r;
}

__device__ __forceinline__ void st_ll2(uint2* p, uint32_t v, uint32_t tag) {
    asm volatile("st.relaxed.gpu.global.v2.u32 [%0], {%1, %2};" ::"l"(p), "r"(v), "r"(tag) : "memory");
}
__device__ __forceinline__ void st_v4(uint4* p, uint32_t a, uint32_t b, uint32_t c, uint32_t d) {
    asm volatile("st.relaxed.gpu.global.v4.u32 [%0], {%1, %2, %3, %4};" ::"l"(p), "r"(a), "r"(b), "r"(c), "r"(d) : "memory");
}
__device__ __forceinline__ uint2 ld_ll2(const uint2* p) {
    uint2 v;
    asm volatile("ld.relaxed.gpu.global.v2.u32 {%0, %1}, [%2];" : "=r"(v.x), "=r"(v.y) : "l"(p) : "memory");
    return v;
}
__device__ __forceinline__ uint4 ld_ll4(const uint4* p) {
    uint4 v;
    asm volatile("ld.relaxed.gpu.global.v4.u32 {%0, %1, %2, %3}, [%4];"
                 : "=r"(v.x), "=r"(v.y), "=r"(v.z), "=r"(v.w) : "l"(p) : "memory");
    return v;
}

#define DELAY_P1 1800
#define DELAY_Q 1800
#define DELAY_A 1000
#define DELAY_B1 300
#define DELAY_X1 2000
#define DELAY_NOFFN 1500
#define DELAY_C 600
__device__ __forceinline__ uint32_t clock32() {
    uint32_t c;
    asm volatile("mov.u32 %0, %clock;" : "=r"(c));
    return c;
}
__device__ __forceinline__ void spin_cycles(uint32_t n) {
    if (n > 0) { const uint32_t c0 = clock32(); while (clock32() - c0 < n) {} }
}
__device__ __forceinline__ float rcp_approx(float x) {
    float r;
    asm("rcp.approx.ftz.f32 %0, %1;" : "=f"(r) : "f"(x));
    return r;
}
__device__ __forceinline__ float sqrt_approx(float x) {
    float r;
    asm("sqrt.approx.f32 %0, %1;" : "=f"(r) : "f"(x));
    return r;
}

__device__ __forceinline__ float silu_bf(float v) { return bf16r(v / (1.0f + expf(-v))); }

__device__ __forceinline__ float2 half_warp_sums(const float (&v)[4], float pivot) {
    float s1 = 0.f, s2 = 0.f;
#pragma unroll
    for (int i = 0; i < 4; i++) { const float d = v[i] - pivot; s1 += d; s2 += d * d; }
#pragma unroll
    for (int o = 1; o < 16; o <<= 1) { s1 += __shfl_xor_sync(0xffffffffu, s1, o); s2 += __shfl_xor_sync(0xffffffffu, s2, o); }
    return make_float2(s1, s2);
}
__device__ __forceinline__ void ln_stats(const float2* stat, int b, float pivot, float& mean_bf, float& rstd) {
    float s1 = 0.f, s2 = 0.f;
#pragma unroll
    for (int w = 0; w < 8; w++) { const float2 v = stat[w * 2 + b]; s1 += v.x; s2 += v.y; }
    const float dm = s1 * (1.0f / D_MODEL);
    const float var = fmaxf(s2 * (1.0f / D_MODEL) - dm * dm, 0.f);
    mean_bf = bf16r(pivot + dm);
    rstd = rcp_approx(bf16r(sqrt_approx(bf16r(bf16r(var) + 1e-5f))));
}
__device__ __forceinline__ float ln_norm(float xv, float mean_bf, float rstd) { return bf16r(bf16r(xv - mean_bf) * rstd); }
__device__ __forceinline__ float ln_mod(float n, float cmul, float sadd) { return bf16r(n * bf16r(1.0f + cmul)) + sadd; }

__global__ void __launch_bounds__(NTHREADS, 1)
fused_block_kernel(const Params p, const __grid_constant__ CUtensorMap tm_k, const __grid_constant__ CUtensorMap tm_v,
                   const __grid_constant__ CUtensorMap tm_wq, const __grid_constant__ CUtensorMap tm_wmod,
                   const __grid_constant__ CUtensorMap tm_wmod8,
                   const __grid_constant__ CUtensorMap tm_wo, const __grid_constant__ CUtensorMap tm_wg,
                   const __grid_constant__ CUtensorMap tm_wu, const __grid_constant__ CUtensorMap tm_wd) {
    extern __shared__ unsigned char smem_raw[];
    const uint32_t sbase = (smem_u32(smem_raw) + 1023u) & ~1023u;
    unsigned char* sgen = smem_raw + (sbase - smem_u32(smem_raw));
    const int tid = threadIdx.x, warp = tid >> 5, lane = tid & 31;
    const int cta = blockIdx.x;
    const uint32_t bar_full = sbase + SM_BAR, bar_empty = bar_full + NST * 8;
    const uint32_t bar_clear = bar_empty + NST * 8;
    const uint32_t bar_gu = bar_clear + 8;
    const uint32_t bar_bc = bar_gu + 8 * 8;
    const uint32_t bar_p0w = bar_bc + 8;
    const uint32_t bar_gate = bar_p0w + 8;

    const int key0 = (cta >> 3) * SK + (cta & 7) * 64;
    uint64_t pol = 0;
    if (tid == 256) {
        asm volatile("createpolicy.fractional.L2::evict_first.b64 %0, 1.0;" : "=l"(pol));
        mbar_init(bar_p0w, 1);
#pragma unroll
        for (int i = 0; i < 4; i++) mbar_init(bar_full + 8 * i, 1);
        asm volatile("fence.mbarrier_init.release.cluster;" ::: "memory");
        mbar_expect_tx(bar_p0w, 8192);
        tma_2d(sbase + SM_MRG, &tm_wmod8, cta * 8, 0, bar_p0w);
        tma_2d(sbase + SM_MRG + 4096, &tm_wmod8, cta * 8, 256, bar_p0w);
#pragma unroll
        for (int i = 0; i < 4; i++) mbar_expect_tx(bar_full + 8 * i, TILE);
        tma_2d(sbase + SM_RING, &tm_wq, cta * 32, 0, bar_full);
        tma_2d(sbase + SM_RING + TILE, &tm_wq, cta * 32, 256, bar_full + 8);
        tma_3d_hint(sbase + SM_RING + 2 * TILE, &tm_k, 0, key0, 0, bar_full + 16, pol);
        tma_3d_hint(sbase + SM_RING + 3 * TILE, &tm_v, 0, key0, 0, bar_full + 24, pol);
    }

    if (warp == 8) {
        if (lane == 0) {
            for (int i = 0; i < NST; i++) { if (i >= 4) mbar_init(bar_full + 8 * i, 1); mbar_init(bar_empty + 8 * i, 4); }
            mbar_init(bar_clear, 1);
            for (int k = 0; k < 8; k++) mbar_init(bar_gu + 8 * k, 1);
            mbar_init(bar_bc, 8);
            mbar_init(bar_gate, 1);
            ((volatile uint32_t*)(sgen + SM_PACE))[0] = 0;
            ((volatile uint32_t*)(sgen + SM_PACE))[1] = WINDOW;
            asm volatile("fence.mbarrier_init.release.cluster;" ::: "memory");
        }
        __syncwarp();
        asm volatile("bar.arrive 2, 288;" ::: "memory");
        asm volatile("bar.arrive 3, 64;" ::: "memory");
        if (lane == 0) {
            int slot = 4; uint32_t ph = 1;
            int landed = 0, wslot = 0; uint32_t wph = 0;
            int kv = 2;
            auto wait_window = [&](int idx, int window) {
                while (landed + window <= idx) {
                    mbar_wait(bar_full + 8 * wslot, wph);
                    if (++wslot == NST) { wslot = 0; wph ^= 1; }
                    landed++;
                }
            };
            volatile uint32_t* pace = (volatile uint32_t*)(sgen + SM_PACE);
            prefetch_tmap(&tm_wmod);
            pace[0] = 4;
            for (int idx = 4; idx < N_STREAM; idx++) {
                if (idx >= NST) mbar_wait(bar_empty + 8 * slot, ph);
                wait_window(idx, (int)pace[1]);
                if (idx == 12) { prefetch_tmap(&tm_wo); prefetch_tmap(&tm_wg); prefetch_tmap(&tm_wu); prefetch_tmap(&tm_wd); }
                const uint32_t fb = bar_full + 8 * slot, dst = sbase + SM_RING + slot * TILE;
                mbar_expect_tx(fb, TILE);
                if (idx == IDX_MOD) {
                    tma_2d(dst, &tm_wmod, 1024 + cta * 16, 0, fb);
                    tma_2d(dst + 8192, &tm_wmod, 1024 + cta * 16, 256, fb);
                } else {
                    tma_3d_hint(dst, (kv & 1) ? &tm_v : &tm_k, 0, key0 + (kv >> 1) * 512, 0, fb, pol);
                    kv++;
                }
                pace[0] = idx + 1;
                if (++slot == NST) { slot = 0; ph ^= 1; }
            }
            auto slot_free = [&](int idx) { mbar_wait(bar_empty + 8 * (idx % NST), ((idx / NST) & 1) ^ 1); };
#pragma unroll
            for (int s = 0; s < 2; s++) {
                const int idx = IDX_WO + s;
                slot_free(idx);
                wait_window(idx, WINDOW_TAIL);
                mbar_expect_tx(bar_full + 8 * (idx % NST), TILE);
                tma_3d(sbase + SM_RING + (idx % NST) * TILE, &tm_wo, 0, (cta >> 2) * 128 + s * 64, (cta & 3) * 2, bar_full + 8 * (idx % NST));
            }
            if (cta < NFFN) {
                slot_free(IDX_WG); slot_free(IDX_WU);
                mbar_wait(bar_full + 8 * (IDX_WO % NST), (IDX_WO / NST) & 1);
                mbar_wait(bar_full + 8 * ((IDX_WO + 1) % NST), ((IDX_WO + 1) / NST) & 1);
#pragma unroll
                for (int st = 0; st < 8; st++) {
                    if (st >= GU_WIN) mbar_wait(bar_gu + 8 * (st - GU_WIN), 0);
                    mbar_expect_tx(bar_gu + 8 * st, 4096);
                    tma_2d(sbase + SM_RING + (((st & 1) ? IDX_WU : IDX_WG) % NST) * TILE + (st >> 1) * 4096,
                           (st & 1) ? &tm_wu : &tm_wg, cta * 16, (st >> 1) * 128, bar_gu + 8 * st);
                }
                mbar_wait(bar_gu + 8 * 6, 0);
                slot_free(IDX_WD);
                mbar_expect_tx(bar_full + 8 * (IDX_WD % NST), TILE);
                tma_3d(sbase + SM_RING + (IDX_WD % NST) * TILE, &tm_wd, 0, cta * 16, 0, bar_full + 8 * (IDX_WD % NST));
            }
        }
    } else if (warp == 9) {
        Scratch* const sc = p.sc;
        const uint32_t tag = *(volatile unsigned*)&sc->epoch + 1;
        asm volatile("bar.sync 3, 64;" ::: "memory");
#pragma unroll 4
        for (int i = 0; i < NFFN * 2 / 32; i++) st_v4(&sc->inbox_dn[cta][0][0] + i * 32 + lane, 0u, 0u, 0u, 0u);
        if (cta >= NCTA - NOWN) {
#pragma unroll 4
            for (int i = 0; i < 8; i++) st_v4(&sc->inbox_wo[cta - (NCTA - NOWN)][0][0] + i * 32 + lane, 0u, 0u, 0u, 0u);
            if (lane < 8) st_v4((uint4*)&sc->x1[(cta - (NCTA - NOWN)) * 16] + lane, 0u, 0u, 0u, 0u);
        }
#pragma unroll 4
        for (int i = 0; i < 4; i++) st_v4((uint4*)&sc->part_o[cta][0][0] + i * 32 + lane, 0u, 0u, 0u, 0u);
        if (lane < 8) st_v4((uint4*)&sc->part_ml[cta][0][0] + lane, 0u, 0u, 0u, 0u);
        if (cta == 0 && lane == 0) asm volatile("st.relaxed.gpu.global.u32 [%0], %1;" ::"l"(&sc->progress), "r"(0u) : "memory");
        asm volatile("fence.acq_rel.gpu;" ::: "memory");
        __syncwarp();
        if (lane == 0) {
            asm volatile("fence.acq_rel.gpu;" ::: "memory");
            asm volatile("red.relaxed.gpu.global.add.u32 [%0], %1;" ::"l"(&sc->cleared), "r"(1u) : "memory");
            const uint32_t target = tag * NCTA;
            for (int it = 0; it < SPIN_LIMIT; it++) {
                uint32_t v;
                asm volatile("ld.relaxed.gpu.global.u32 %0, [%1];" : "=r"(v) : "l"(&sc->cleared) : "memory");
                if ((int32_t)(v - target) >= 0) break;
                __nanosleep(500);
            }
            asm volatile("fence.acq_rel.gpu;" ::: "memory");
            mbar_arrive(bar_clear);
            volatile uint32_t* pace = (volatile uint32_t*)(sgen + SM_PACE);
            uint32_t posted = 0;
            for (int it = 0; it < SPIN_LIMIT; it++) {
                const uint32_t own = pace[0];
                if (own > posted) {
                    asm volatile("red.relaxed.gpu.global.add.u32 [%0], %1;" ::"l"(&sc->progress), "r"(own - posted) : "memory");
                    posted = own;
                }
                uint32_t v;
                asm volatile("ld.relaxed.gpu.global.u32 %0, [%1];" : "=r"(v) : "l"(&sc->progress) : "memory");
                if (own >= N_STREAM) {
                    if (v >= NCTA * N_STREAM) break;
                } else {
                    const int diff = (int)v - (int)own * NCTA;
                    pace[1] = diff > PACE_THR ? WINDOW + 1 : diff < -PACE_THR ? WINDOW - 1 : WINDOW;
                }
                __nanosleep(200);
            }
            pace[2] = clock32();
            mbar_arrive(bar_gate);
            if (cta == 0) asm volatile("st.relaxed.gpu.global.u32 [%0], %1;" ::"l"(&sc->epoch), "r"(tag) : "memory");
        }
    } else {
        const int g = lane >> 2, t = lane & 3;
        const int bb = g & 1;
        const int eb = lane >> 4;
        const int ec = 64 * warp + 4 * (lane & 15);
        if (warp == 0) TSTAMP(0);
        Scratch* const sc = p.sc;
        const float c00 = __bfloat162float(p.c[tid]), c01 = __bfloat162float(p.c[tid + 256]);
        const float c10 = __bfloat162float(p.c[D_MODEL + tid]), c11 = __bfloat162float(p.c[D_MODEL + tid + 256]);
        const uint2 xe = __ldg((const uint2*)(p.x + eb * D_MODEL + ec));
        const float xpivot = __bfloat162float(p.x[eb * D_MODEL]);
        const uint32_t tag = *(volatile unsigned*)&sc->epoch + 1;
        const int ocol = cta * 4 + (lane & 3);
        const int wcol = (cta >= NCTA - NOWN ? cta - (NCTA - NOWN) : 0) * 16 + (lane & 15);
        const float xo = __bfloat162float(p.x[eb * D_MODEL + wcol]);

        float* red = (float*)(sgen + SM_RED);
        float* red2 = (float*)(sgen + SM_RED2);
        float2* stat = (float2*)(sgen + SM_STAT);
        uint32_t* hs = (uint32_t*)(sgen + SM_HS) + warp * 64;
        float xn[4];
        {
            float xv[4] = {bf_lo(xe.x), bf_hi(xe.x), bf_lo(xe.y), bf_hi(xe.y)};
            const float2 ps = half_warp_sums(xv, xpivot);
            if ((lane & 15) == 0) stat[warp * 2 + eb] = ps;
            const float s00 = silu_bf(c00), s01 = silu_bf(c01), s10 = silu_bf(c10), s11 = silu_bf(c11);
            __nv_bfloat16* scs = (__nv_bfloat16*)(sgen + SM_SC);
            scs[tid] = __float2bfloat16_rn(s00); scs[tid + 256] = __float2bfloat16_rn(s01);
            scs[512 + tid] = __float2bfloat16_rn(s10); scs[512 + tid + 256] = __float2bfloat16_rn(s11);
            asm volatile("bar.sync 2, 288;" ::: "memory");
            if (warp == 0) TSTAMP(23);
            float cp[4] = {0.f, 0.f, 0.f, 0.f};
            const uint32_t* sc32 = (const uint32_t*)(sgen + SM_SC) + bb * 256 + 32 * warp + t;
            mbar_wait(bar_p0w, 0);
#pragma unroll
            for (int s = 0; s < 4; s++) {
                uint32_t r0, r1;
                asm volatile("ldmatrix.sync.aligned.m8n8.x2.trans.shared.b16 {%0,%1}, [%2];"
                             : "=r"(r0), "=r"(r1) : "r"(sbase + SM_MRG + (64 * warp + 16 * s + (lane & 15)) * 16) : "memory");
                const uint32_t a[4] = {r0, r0, r1, r1};
                mma16816(cp, a, sc32[8 * s], sc32[8 * s + 4]);
            }
            if (t == 0) { red[warp * 16 + g] = cp[0]; red[warp * 16 + 8 + g] = cp[1]; }
            if (warp == 0) TSTAMP(14);
            cons_sync();
            if (warp == 0) {
                float s = 0.f;
#pragma unroll
                for (int w = 0; w < 8; w++) s += red[w * 16 + (lane & 15)];
                const float nx = __shfl_down_sync(0xffffffffu, s, 1);
                if (lane < 16 && !(lane & 1))
                    st_ll2(&sc->mod[lane >> 3][cta * 4 + ((lane & 7) >> 1)], pack_bf16(s, nx), tag);
                TSTAMP(1);
            }
            float mean_bf, rstd;
            ln_stats(stat, eb, xpivot, mean_bf, rstd);
#pragma unroll
            for (int i = 0; i < 4; i++) xn[i] = ln_norm(xv[i], mean_bf, rstd);
        }
        {
            uint4 sa, ca;
            spin_cycles(DELAY_P1);
            for (int it = 0;; it++) {
                sa = ld_ll4((const uint4*)&sc->mod[eb][ec >> 1]);
                ca = ld_ll4((const uint4*)&sc->mod[eb][256 + (ec >> 1)]);
                const bool ok = sa.y == tag && sa.w == tag && ca.y == tag && ca.w == tag;
                if (__all_sync(0xffffffffu, ok) || it > SPIN_LIMIT) break;
            }
            *(uint2*)&hs[eb * 32 + 2 * (lane & 15)] =
                make_uint2(pack_bf16(ln_mod(xn[0], bf_lo(ca.x), bf_lo(sa.x)), ln_mod(xn[1], bf_hi(ca.x), bf_hi(sa.x))),
                           pack_bf16(ln_mod(xn[2], bf_lo(ca.z), bf_lo(sa.z)), ln_mod(xn[3], bf_hi(ca.z), bf_hi(sa.z))));
            __syncwarp();
            uint32_t hb[8];
#pragma unroll
            for (int i = 0; i < 8; i++) hb[i] = hs[bb * 32 + 8 * (i >> 1) + 4 * (i & 1) + t];
            if (warp == 0) TSTAMP(2);
            float cq[2][4] = {};
            const int ts = warp >> 2;
            mbar_wait(bar_full + 8 * ts, 0);
            const uint32_t tb = sbase + SM_RING + ts * TILE;
#pragma unroll
            for (int s = 0; s < 4; s++) {
                const int row = 64 * (warp & 3) + 16 * s + (lane & 7) + (lane >> 4) * 8;
#pragma unroll
                for (int mt = 0; mt < 2; mt++) {
                    const int ch = 2 * mt + ((lane >> 3) & 1);
                    uint32_t a[4];
                    ldsm4t(tb + row * 64 + ((ch ^ ((row >> 1) & 3)) << 4), a);
                    mma16816(cq[mt], a, hb[2 * s], hb[2 * s + 1]);
                }
            }
            if (t < 2) {
                const float v0 = t == 0 ? cq[0][0] : cq[1][0], v1 = t == 0 ? cq[0][1] : cq[1][1];
                const float v2 = t == 0 ? cq[0][2] : cq[1][2], v3 = t == 0 ? cq[0][3] : cq[1][3];
                *(float2*)&red2[warp * 64 + (16 * t + g) * 2] = make_float2(v0, v1);
                *(float2*)&red2[warp * 64 + (16 * t + g + 8) * 2] = make_float2(v2, v3);
            }
            cons_sync();
            if (warp < 4 && lane == 0) { mbar_arrive(bar_empty); mbar_arrive(bar_empty + 8); }
            if (warp == 0) {
                const int b = lane >> 4, cp = lane & 15;
                float q0 = 0.f, q1 = 0.f;
#pragma unroll
                for (int w = 0; w < 8; w++) {
                    const float4 v = *(const float4*)&red2[w * 64 + cp * 4];
                    q0 += b ? v.y : v.x; q1 += b ? v.w : v.z;
                }
                st_ll2(&sc->q[b][cta * 16 + cp], pack_bf16(q0, q1), tag);
                TSTAMP(3);
            }
        }
        const int pair = cta >> 3;
        uint32_t qf[16];
        {
            uint2* qs = (uint2*)(sgen + SM_QS);
            if (tid < 128) {
                const uint4* src = (const uint4*)&sc->q[pair >> 3][(pair & 7) * 256] + tid;
                uint4 v;
                spin_cycles(DELAY_Q);
                for (int it = 0;; it++) {
                    v = ld_ll4(src);
                    if ((v.y == tag && v.w == tag) || it > SPIN_LIMIT) break;
                }
                qs[tid] = make_uint2(v.x, v.z);
            }
            cons_sync();
            const uint32_t* q32 = (const uint32_t*)(sgen + SM_QS);
#pragma unroll
            for (int s = 0; s < 8; s++) {
                qf[2 * s] = q32[(g & 3) * 64 + 8 * s + t];
                qf[2 * s + 1] = q32[(g & 3) * 64 + 8 * s + 4 + t];
            }
        }
        if (warp == 0) TSTAMP(4);

        float o[8][4];
#pragma unroll
        for (int i = 0; i < 8; i++) { o[i][0] = o[i][1] = o[i][2] = o[i][3] = 0.f; }
        uint32_t mrun = 0xff80ff80u;
        float ls[4] = {0.f, 0.f, 0.f, 0.f};
        uint4 m_sb, m_cb; uint2 m_ga, m_gb0, m_gb1;
        {
            const int grp = warp >> 2, wi = warp & 3;
            const int krow = 16 * wi + (lane & 7) + ((lane >> 3) & 1) * 8;
            const uint32_t koff = krow * 128 + ((((lane >> 4) & 1) ^ (lane & 7)) << 4);
            const int vrow = 16 * wi + (lane & 7) + (lane >> 4) * 8;
            const uint32_t voff = vrow * 128 + ((((lane >> 3) & 1) ^ (lane & 7)) << 4);
            const uint32_t ones[4] = {0x3f803f80u, 0x3f803f80u, 0x3f803f80u, 0x3f803f80u};
            for (int i = grp; i < KV_TILES; i += 2) {
                if (i == MOD_AT + grp) {
                    float cm[4] = {};
                    const uint32_t* sc32 = (const uint32_t*)(sgen + SM_SC) + bb * 256 + 32 * warp + t;
                    mbar_wait(bar_full + 8 * (IDX_MOD % NST), (IDX_MOD / NST) & 1);
                    const uint32_t tb = sbase + SM_RING + (IDX_MOD % NST) * TILE;
#pragma unroll
                    for (int s = 0; s < 4; s++) {
                        const int row = 64 * warp + 16 * s + (lane & 7) + (lane >> 4) * 8;
                        const int ch = (lane >> 3) & 1;
                        uint32_t a[4];
                        ldsm4t(tb + row * 32 + ((ch ^ ((row >> 2) & 1)) << 4), a);
                        mma16816(cm, a, sc32[8 * s], sc32[8 * s + 4]);
                    }
                    if (t == 0) {
                        *(float2*)&red[warp * 64 + g * 2] = make_float2(cm[0], cm[1]);
                        *(float2*)&red[warp * 64 + (g + 8) * 2] = make_float2(cm[2], cm[3]);
                    }
                    cons_sync();
                    if (warp < 4 && lane == 0) mbar_arrive(bar_empty + 8 * (IDX_MOD % NST));
                    if (warp == 1 && lane < 16) {
                        const int b = lane >> 3, cp = lane & 7;
                        float q0 = 0.f, q1 = 0.f;
#pragma unroll
                        for (int w = 0; w < 8; w++) {
                            const float4 v = *(const float4*)&red[w * 64 + cp * 4];
                            q0 += b ? v.y : v.x; q1 += b ? v.w : v.z;
                        }
                        st_ll2(&sc->mod[b][512 + cta * 8 + cp], pack_bf16(q0, q1), tag);
                    }
                }
                if (i == 56 + grp) {
                    m_sb = ld_ll4((const uint4*)&sc->mod[eb][768 + (ec >> 1)]);
                    m_cb = ld_ll4((const uint4*)&sc->mod[eb][1024 + (ec >> 1)]);
                    m_ga = ld_ll2(&sc->mod[eb][512 + (wcol >> 1)]);
                    m_gb0 = ld_ll2(&sc->mod[0][1280 + (ocol >> 1)]); m_gb1 = ld_ll2(&sc->mod[1][1280 + (ocol >> 1)]);
                }
                if (i == 60 + grp) {
                    for (int it = 0;; it++) {
                        const bool ok = m_sb.y == tag && m_sb.w == tag && m_cb.y == tag && m_cb.w == tag &&
                                        m_ga.y == tag && m_gb0.y == tag && m_gb1.y == tag;
                        if (__all_sync(0xffffffffu, ok) || it > SPIN_LIMIT) break;
                        m_sb = ld_ll4((const uint4*)&sc->mod[eb][768 + (ec >> 1)]);
                        m_cb = ld_ll4((const uint4*)&sc->mod[eb][1024 + (ec >> 1)]);
                        m_ga = ld_ll2(&sc->mod[eb][512 + (wcol >> 1)]);
                        m_gb0 = ld_ll2(&sc->mod[0][1280 + (ocol >> 1)]); m_gb1 = ld_ll2(&sc->mod[1][1280 + (ocol >> 1)]);
                    }
                    mbar_wait(bar_clear, 0);
                }
                const int ki = kv_idx(i), ks = ki % NST, vs = (ki + 1) % NST;
                const uint32_t kph = (ki / NST) & 1, vph = ((ki + 1) / NST) & 1;
                mbar_wait(bar_full + 8 * ks, kph);
                const uint32_t kb = sbase + SM_RING + ks * TILE + koff;
                float sa[4] = {0.f, 0.f, 0.f, 0.f}, sb[4] = {0.f, 0.f, 0.f, 0.f};
#pragma unroll
                for (int s = 0; s < 8; s += 2) {
                    uint32_t a0[4], a1[4];
                    ldsm4((kb ^ ((s & 3) << 5)) + (s >> 2) * 8192, a0);
                    ldsm4((kb ^ (((s + 1) & 3) << 5)) + (s >> 2) * 8192, a1);
                    mma16816(sa, a0, qf[2 * s], qf[2 * s + 1]);
                    mma16816(sb, a1, qf[2 * s + 2], qf[2 * s + 3]);
                }
                __syncwarp();
                if (lane == 0) mbar_arrive(bar_empty + 8 * ks);
                uint32_t r01 = pack_bf16(sa[0] + sb[0], sa[1] + sb[1]);
                uint32_t r23 = pack_bf16(sa[2] + sb[2], sa[3] + sb[3]);
                r01 = pack_bf16(bf_lo(r01) * QK_SCALE, bf_hi(r01) * QK_SCALE);
                r23 = pack_bf16(bf_lo(r23) * QK_SCALE, bf_hi(r23) * QK_SCALE);
                uint32_t mx = max_bf16x2(r01, r23);
                mx = max_bf16x2(mx, __shfl_xor_sync(0xffffffffu, mx, 4));
                mx = max_bf16x2(mx, __shfl_xor_sync(0xffffffffu, mx, 8));
                mx = max_bf16x2(mx, __shfl_xor_sync(0xffffffffu, mx, 16));
                const uint32_t mnew = max_bf16x2(mrun, mx);
                const float m0 = bf_lo(mnew), m1 = bf_hi(mnew);
                if (__any_sync(0xffffffffu, mnew != mrun)) {
                    const float al0 = ex2((bf_lo(mrun) - m0) * LOG2E), al1 = ex2((bf_hi(mrun) - m1) * LOG2E);
                    ls[0] *= al0; ls[1] *= al1;
#pragma unroll
                    for (int d = 0; d < 8; d++) { o[d][0] *= al0; o[d][1] *= al1; o[d][2] *= al0; o[d][3] *= al1; }
                    mrun = mnew;
                }
                const float p0 = ex2((bf_lo(r01) - m0) * LOG2E), p1 = ex2((bf_hi(r01) - m1) * LOG2E);
                const float p2 = ex2((bf_lo(r23) - m0) * LOG2E), p3 = ex2((bf_hi(r23) - m1) * LOG2E);
                const uint32_t pb0 = movmatrix_t(pack_bf16(p0, p1)), pb1 = movmatrix_t(pack_bf16(p2, p3));
                mma16816(ls, ones, pb0, pb1);
                mbar_wait(bar_full + 8 * vs, vph);
                const uint32_t vb = sbase + SM_RING + vs * TILE + voff;
#pragma unroll
                for (int d = 0; d < 8; d++) {
                    uint32_t a[4];
                    ldsm4t((vb ^ ((d & 3) << 5)) + (d >> 2) * 8192, a);
                    mma16816(o[d], a, pb0, pb1);
                }
                __syncwarp();
                if (lane == 0) mbar_arrive(bar_empty + 8 * vs);
            }
        }
        if (warp == 7) TSTAMP(5);
        {
            float* mrg = (float*)(sgen + SM_MRG);
            float2* ml = (float2*)(sgen + SM_ML);
            {
                const int hp = (t & 1) * 2, up = t >> 1;
                if (g == 0 && up == 0) { ml[warp * 4 + hp] = make_float2(bf_lo(mrun), ls[0]); ml[warp * 4 + hp + 1] = make_float2(bf_hi(mrun), ls[1]); }
                float* m0p = mrg + (warp * 4 + hp) * 136 + up * 72 + g;
#pragma unroll
                for (int d = 0; d < 4; d++) {
                    m0p[16 * d] = up ? o[d + 4][0] : o[d][0]; m0p[136 + 16 * d] = up ? o[d + 4][1] : o[d][1];
                    m0p[16 * d + 8] = up ? o[d + 4][2] : o[d][2]; m0p[136 + 16 * d + 8] = up ? o[d + 4][3] : o[d][3];
                }
            }
            cons_sync();
            const int hh = tid >> 6, dp = tid & 63;
            float2 mw[8];
            float M = -INFINITY;
#pragma unroll
            for (int w = 0; w < 8; w++) { mw[w] = ml[w * 4 + hh]; M = fmaxf(M, mw[w].x); }
            float L = 0.f, o0 = 0.f, o1 = 0.f;
#pragma unroll
            for (int w = 0; w < 8; w++) {
                const float wt = ex2((mw[w].x - M) * LOG2E);
                const float2 v = *(const float2*)&mrg[(w * 4 + hh) * 136 + 2 * dp + (dp >= 32 ? 8 : 0)];
                L += wt * mw[w].y; o0 += wt * v.x; o1 += wt * v.y;
            }
            st_ll2(&sc->part_o[cta][hh][dp], tagf(o0, F_PART), tagf(o1, F_PART));
            if (dp < 4) st_ll2(&sc->part_ml[cta][hh][dp], tagf(M, F_PART), tagf(L, F_PART));
        }
        if (warp == 0) TSTAMP(6);
        {
            const int hq = cta >> 2, kvh = hq >> 2, hh = hq & 3;
            const int b = tid >> 7, dc = (tid >> 3) & 15, j = tid & 7;
            const int pc = (b * 8 + kvh) * 8 + j;
            const uint4* po = (const uint4*)&sc->part_o[pc][hh][0] + dc * 2;
            const uint2* pm = &sc->part_ml[pc - j][hh][0];
            uint4 vo0, vo1; uint2 vm[8];
            mbar_wait(bar_gate, 0);
            { const uint32_t tg = ((volatile uint32_t*)(sgen + SM_PACE))[2]; while (clock32() - tg < DELAY_A) {} }
            bool oko = false;
#pragma unroll
            for (int jj = 0; jj < 8; jj++) vm[jj] = make_uint2(0u, 0u);
            for (int it = 0;; it++) {
                if (!oko) { vo0 = ld_ll4(po); vo1 = ld_ll4(po + 1); }
#pragma unroll
                for (int jj = 0; jj < 8; jj++)
                    if ((vm[jj].x & vm[jj].y & 3u) != F_PART) vm[jj] = ld_ll2(pm + jj * 16);
                oko = (vo0.x & vo0.y & vo0.z & vo0.w & vo1.x & vo1.y & vo1.z & vo1.w & 3u) == F_PART;
                uint32_t all = vm[0].x & vm[0].y;
#pragma unroll
                for (int jj = 1; jj < 8; jj++) all &= vm[jj].x & vm[jj].y;
                if (__all_sync(0xffffffffu, oko && (all & 3u) == F_PART) || it > SPIN_LIMIT) break;
            }
            float M = untag(vm[0].x);
#pragma unroll
            for (int jj = 1; jj < 8; jj++) M = fmaxf(M, untag(vm[jj].x));
            float wt = 0.f, L = 0.f;
#pragma unroll
            for (int jj = 0; jj < 8; jj++) {
                const float w_ = ex2((untag(vm[jj].x) - M) * LOG2E);
                L += w_ * untag(vm[jj].y);
                wt = jj == j ? w_ : wt;
            }
            wt *= rcp_approx(L);
            float v[8] = {wt * untag(vo0.x), wt * untag(vo0.y), wt * untag(vo0.z), wt * untag(vo0.w),
                          wt * untag(vo1.x), wt * untag(vo1.y), wt * untag(vo1.z), wt * untag(vo1.w)};
#define XRED(N, O)                                                                       \
            {                                                                            \
                const bool up = lane & (O);                                              \
                _Pragma("unroll") for (int i = 0; i < (N); i++) {                        \
                    const float send = up ? v[i] : v[i + (N)], keep = up ? v[i + (N)] : v[i]; \
                    v[i] = keep + __shfl_xor_sync(0xffffffffu, send, (O));               \
                }                                                                        \
            }
            XRED(4, 1) XRED(2, 2) XRED(1, 4)
#undef XRED
            __nv_bfloat16* os = (__nv_bfloat16*)(sgen + SM_OS);
            os[b * 128 + dc * 8 + 4 * (j & 1) + 2 * ((j >> 1) & 1) + (j >> 2)] = __float2bfloat16_rn(v[0]);
            if (warp == 0) TSTAMP(15);
            uint32_t wf[8][4];
            const uint32_t aoff_o = (warp >> 2) * 8192 + ((lane & 7) + (lane >> 4) * 8) * 128 +
                                    (((((warp & 3) * 2 + ((lane >> 3) & 1)) ^ (lane & 7))) << 4);
#pragma unroll
            for (int s = 0; s < 2; s++) {
                const int idx = IDX_WO + s;
                mbar_wait(bar_full + 8 * (idx % NST), (idx / NST) & 1);
                const uint32_t tb = sbase + SM_RING + (idx % NST) * TILE + aoff_o;
#pragma unroll
                for (int k4 = 0; k4 < 4; k4++) ldsm4t(tb + k4 * 2048, wf[s * 4 + k4]);
            }
            cons_sync();
            if (warp == 0) TSTAMP(7);
            const uint32_t* os32 = (const uint32_t*)(sgen + SM_OS) + bb * 64 + t;
            float y0[4] = {}, y1[4] = {};
#pragma unroll
            for (int ks = 0; ks < 8; ks += 2) {
                mma16816(y0, wf[ks], os32[8 * ks], os32[8 * ks + 4]);
                mma16816(y1, wf[ks + 1], os32[8 * ks + 8], os32[8 * ks + 12]);
            }
            if (t == 0)
                st_v4(&sc->inbox_wo[(cta & 3) * 8 + warp][hq][g], tagf(y0[0] + y1[0], F_WO), tagf(y0[1] + y1[1], F_WO),
                      tagf(y0[2] + y1[2], F_WO), tagf(y0[3] + y1[3], F_WO));
        }
        const uint32_t t_wo = clock32();
        if (warp == 0) TSTAMP(8);
        if (cta >= NCTA - NOWN) {
            const uint4* pin = &sc->inbox_wo[cta - (NCTA - NOWN)][0][0] + tid;
            uint4 v;
            spin_cycles(DELAY_B1);
            bool ok = false;
            for (int it = 0;; it++) {
                if (!ok) {
                    v = ld_ll4(pin);
                    ok = (v.x & v.y & v.z & v.w & 3u) == F_WO;
                }
                if (__all_sync(0xffffffffu, ok) || it > SPIN_LIMIT) break;
            }
            const bool u1 = lane & 8, u2 = lane & 16;
            const float a0 = untag(v.x), a1 = untag(v.y), a2 = untag(v.z), a3 = untag(v.w);
            const float k0 = (u1 ? a2 : a0) + __shfl_xor_sync(0xffffffffu, u1 ? a0 : a2, 8);
            const float k1 = (u1 ? a3 : a1) + __shfl_xor_sync(0xffffffffu, u1 ? a1 : a3, 8);
            red2[warp * 32 + lane] = (u2 ? k1 : k0) + __shfl_xor_sync(0xffffffffu, u2 ? k0 : k1, 16);
            cons_sync();
            if (warp == 0) {
                float a = 0.f;
#pragma unroll
                for (int w = 0; w < 8; w++) a += red2[w * 32 + lane];
                const float ga = (wcol & 1) ? bf_hi(m_ga.x) : bf_lo(m_ga.x);
                const float xm = bf16r(xo + bf16r(ga * bf16r(a)));
                const float xm_b1 = __shfl_down_sync(0xffffffffu, xm, 16);
                if (lane < 16) st_ll2(&sc->x1[wcol], pack_bf16(xm, xm_b1), F_X1);
                TSTAMP(10);
            }
        }
        const uint32_t aoff = warp * 2048 + ((lane & 7) + (lane >> 4) * 8) * 128 + ((((lane >> 3) & 1) ^ (lane & 7)) << 4);
        if (cta < NFFN) {
            const uint4* px = (const uint4*)&sc->x1[ec];
            const uint4* pp = (const uint4*)&sc->x1[0];
            uint4 va, vb, pa, pb;
            uint32_t gf[4][4], uf[4][4];
            mbar_wait(bar_gu + 8 * (2 * (warp >> 1)), 0);
            mbar_wait(bar_gu + 8 * (2 * (warp >> 1) + 1), 0);
            {
                const uint32_t tg = sbase + SM_RING + (IDX_WG % NST) * TILE, tu = sbase + SM_RING + (IDX_WU % NST) * TILE;
#pragma unroll
                for (int s = 0; s < 4; s++) {
                    const int row = 64 * warp + 16 * s + (lane & 7) + (lane >> 4) * 8;
                    const uint32_t off = row * 32 + ((((lane >> 3) & 1) ^ ((row >> 2) & 1)) << 4);
                    ldsm4t(tg + off, gf[s]);
                    ldsm4t(tu + off, uf[s]);
                }
            }
            const float c1v[4] = {bf16r(1.0f + bf_lo(m_cb.x)), bf16r(1.0f + bf_hi(m_cb.x)), bf16r(1.0f + bf_lo(m_cb.z)), bf16r(1.0f + bf_hi(m_cb.z))};
            float bg = 0.f, cgc = 0.f, bu = 0.f, cuc = 0.f;
            {
                uint32_t* pre = (uint32_t*)(sgen + SM_MRG) + warp * 128;
                float* bc = (float*)(sgen + SM_MRG + 4096);
                *(uint2*)&pre[eb * 32 + 2 * (lane & 15)] = make_uint2(pack_bf16(c1v[0], c1v[1]), pack_bf16(c1v[2], c1v[3]));
                *(uint2*)&pre[64 + eb * 32 + 2 * (lane & 15)] = make_uint2(m_sb.x, m_sb.z);
                __syncwarp();
                float yg[4] = {}, yu[4] = {};
                const uint32_t* pb = pre + ((g >> 1) & 1) * 64 + bb * 32 + t;
#pragma unroll
                for (int s = 0; s < 4; s++) {
                    const uint32_t b0 = pb[8 * s], b1 = pb[8 * s + 4];
                    mma16816(yg, gf[s], b0, b1);
                    mma16816(yu, uf[s], b0, b1);
                }
                const float y0 = t < 2 ? yg[0] : yu[0], y1 = t < 2 ? yg[1] : yu[1], y2 = t < 2 ? yg[2] : yu[2], y3 = t < 2 ? yg[3] : yu[3];
                float* dstp = bc + warp * 128 + (t >> 1) * 64 + (t & 1) * 32;
                *(float2*)&dstp[g * 2] = make_float2(y0, y1);
                *(float2*)&dstp[(g + 8) * 2] = make_float2(y2, y3);
                __syncwarp();
                if (lane == 0) mbar_arrive(bar_bc);
            }
            if (warp == 0) TSTAMP(11);
            float pivot2;
            {
                while (clock32() - t_wo < DELAY_X1) {}
                bool okx = false, okp = false;
                for (int it = 0;; it++) {
                    if (!okx) { va = ld_ll4(px); vb = ld_ll4(px + 1); }
                    if (!okp) { pa = ld_ll4(pp); pb = ld_ll4(pp + 1); }
                    okx = va.y == F_X1 && va.w == F_X1 && vb.y == F_X1 && vb.w == F_X1;
                    okp = pa.y == F_X1 && pa.w == F_X1 && pb.y == F_X1 && pb.w == F_X1;
                    if (__all_sync(0xffffffffu, okx && okp) || it > SPIN_LIMIT) break;
                }
                if (warp == 0) TSTAMP(9);
                const float xv[4] = {eb ? bf_hi(va.x) : bf_lo(va.x), eb ? bf_hi(va.z) : bf_lo(va.z),
                                     eb ? bf_hi(vb.x) : bf_lo(vb.x), eb ? bf_hi(vb.z) : bf_lo(vb.z)};
                const float p0 = 0.25f * ((bf_lo(pa.x) + bf_lo(pa.z)) + (bf_lo(pb.x) + bf_lo(pb.z)));
                const float p1 = 0.25f * ((bf_hi(pa.x) + bf_hi(pa.z)) + (bf_hi(pb.x) + bf_hi(pb.z)));
                const float pivot = eb ? p1 : p0;
                pivot2 = (lane & 1) ? p1 : p0;
                *(uint2*)&hs[eb * 32 + 2 * (lane & 15)] =
                    make_uint2(pack_bf16((xv[0] - pivot) * c1v[0], (xv[1] - pivot) * c1v[1]),
                               pack_bf16((xv[2] - pivot) * c1v[2], (xv[3] - pivot) * c1v[3]));
                __syncwarp();
                float cg[2][4] = {}, cu[2][4] = {};
#pragma unroll
                for (int s = 0; s < 4; s++) {
                    const uint32_t b0 = hs[bb * 32 + 8 * s + t], b1 = hs[bb * 32 + 8 * s + 4 + t];
                    mma16816(cg[s & 1], gf[s], b0, b1);
                    mma16816(cu[s & 1], uf[s], b0, b1);
                }
                const float2 ps = half_warp_sums(xv, pivot);
                if ((lane & 15) == 0) stat[warp * 2 + eb] = ps;
                {
                    const float* bc = (const float*)(sgen + SM_MRG + 4096);
                    mbar_wait(bar_bc, 0);
#pragma unroll
                    for (int w = 0; w < 8; w++) {
                        bg += bc[w * 128 + lane]; cgc += bc[w * 128 + 32 + lane];
                        bu += bc[w * 128 + 64 + lane]; cuc += bc[w * 128 + 96 + lane];
                    }
                }
                if (t < 2) {
                    float v[4];
#pragma unroll
                    for (int i = 0; i < 4; i++) v[i] = t ? cu[0][i] + cu[1][i] : cg[0][i] + cg[1][i];
                    *(float2*)&red[warp * 64 + t * 32 + g * 2] = make_float2(v[0], v[1]);
                    *(float2*)&red[warp * 64 + t * 32 + (g + 8) * 2] = make_float2(v[2], v[3]);
                }
            }
            uint32_t df[4][4];
            mbar_wait(bar_full + 8 * (IDX_WD % NST), (IDX_WD / NST) & 1);
#pragma unroll
            for (int mt = 0; mt < 4; mt++) ldsm4t((sbase + SM_RING + (IDX_WD % NST) * TILE + aoff) ^ (mt << 5), df[mt]);
            cons_sync();
            {
                float gs = 0.f, us = 0.f;
#pragma unroll
                for (int w = 0; w < 8; w++) { gs += red[w * 64 + lane]; us += red[w * 64 + 32 + lane]; }
                float mean_bf, rstd;
                ln_stats(stat, lane & 1, pivot2, mean_bf, rstd);
                const float dm = mean_bf - pivot2;
                gs = bf16r(rstd * (gs - dm * bg) + cgc);
                us = rstd * (us - dm * bu) + cuc;
                const float u2 = gs * (1.0f + 0.044715f * gs * gs) * (2.0f * 0.7978845608028654f * LOG2E);
                const float ge = bf16r(__fdividef(gs, 1.0f + ex2(-u2)));
                const float act = bf16r(ge * bf16r(us));
                const float a0 = __shfl_sync(0xffffffffu, act, 4 * t + bb), a1 = __shfl_sync(0xffffffffu, act, 4 * t + 2 + bb);
                const float a2 = __shfl_sync(0xffffffffu, act, 4 * t + 16 + bb), a3 = __shfl_sync(0xffffffffu, act, 4 * t + 18 + bb);
                const uint32_t b0 = pack_bf16(a0, a1), b1 = pack_bf16(a2, a3);
                float y[4][4] = {};
#pragma unroll
                for (int mt = 0; mt < 4; mt++) mma16816(y[mt], df[mt], b0, b1);
                float v[4];
#pragma unroll
                for (int i = 0; i < 4; i++) v[i] = t == 0 ? y[0][i] : t == 1 ? y[1][i] : t == 2 ? y[2][i] : y[3][i];
            {
                const bool odd = g & 1;
                const float sx = odd ? v[0] : v[2], sy = odd ? v[1] : v[3];
                const float rx = __shfl_xor_sync(0xffffffffu, sx, 4), ry = __shfl_xor_sync(0xffffffffu, sy, 4);
                const int c0 = 64 * warp + 16 * t + (odd ? g + 7 : g);
                const float e0 = odd ? rx : v[0], e1 = odd ? ry : v[1], e2 = odd ? v[2] : rx, e3 = odd ? v[3] : ry;
                st_v4(&sc->inbox_dn[c0 >> 2][cta][(c0 >> 1) & 1], tagf(e0, F_DOWN), tagf(e1, F_DOWN), tagf(e2, F_DOWN), tagf(e3, F_DOWN));
            }
            }
            if (warp == 0) TSTAMP(12);
        }
        {
            uint2 xw;
            float r0;
            {
                const uint4* pin = &sc->inbox_dn[cta][0][0] + tid;
                uint4 v = make_uint4(F_DOWN, F_DOWN, F_DOWN, F_DOWN);
                if (cta < NFFN) spin_cycles(DELAY_C);
                else while (clock32() - t_wo < DELAY_X1 + DELAY_NOFFN) {}
                xw = ld_ll2(&sc->x1[ocol]);
                bool ok = tid >= NFFN * 2;
                for (int it = 0;; it++) {
                    if (!ok) {
                        v = ld_ll4(pin);
                        ok = (v.x & v.y & v.z & v.w & 3u) == F_DOWN;
                    }
                    if (__all_sync(0xffffffffu, ok) || it > SPIN_LIMIT) break;
                }
                const bool u1 = lane & 2, u2 = lane & 4;
                const float a0 = untag(v.x), a1 = untag(v.y), a2 = untag(v.z), a3 = untag(v.w);
                const float k0 = (u1 ? a1 : a0) + __shfl_xor_sync(0xffffffffu, u1 ? a0 : a1, 2);
                const float k1 = (u1 ? a3 : a2) + __shfl_xor_sync(0xffffffffu, u1 ? a2 : a3, 2);
                r0 = (u2 ? k1 : k0) + __shfl_xor_sync(0xffffffffu, u2 ? k0 : k1, 4);
                r0 += __shfl_xor_sync(0xffffffffu, r0, 8);
                r0 += __shfl_xor_sync(0xffffffffu, r0, 16);
                if (lane < 8) red2[256 + warp * 8 + (2 * (lane & 1) + ((lane >> 2) & 1)) * 2 + ((lane >> 1) & 1)] = r0;
            }
            cons_sync();
            if (warp == 0) {
                float a0 = 0.f, a1 = 0.f;
#pragma unroll
                for (int w = 0; w < 8; w++) { const float2 v = *(const float2*)&red2[256 + w * 8 + (lane & 3) * 2]; a0 += v.x; a1 += v.y; }
                const bool hi = ocol & 1;
                const float gb0 = hi ? bf_hi(m_gb0.x) : bf_lo(m_gb0.x), gb1 = hi ? bf_hi(m_gb1.x) : bf_lo(m_gb1.x);
                for (int it = 0; !__all_sync(0xffffffffu, xw.y == F_X1) && it < SPIN_LIMIT; it++) xw = ld_ll2(&sc->x1[ocol]);
                if (lane < 4) {
                    p.out[ocol] = __float2bfloat16_rn(bf_lo(xw.x) + bf16r(gb0 * bf16r(a0)));
                    p.out[D_MODEL + ocol] = __float2bfloat16_rn(bf_hi(xw.x) + bf16r(gb1 * bf16r(a1)));
                }
                TSTAMP(13);
            }
        }
    }
}

typedef CUresult (*EncodeFn)(CUtensorMap*, CUtensorMapDataType, cuuint32_t, void*, const cuuint64_t*, const cuuint64_t*,
                             const cuuint32_t*, const cuuint32_t*, CUtensorMapInterleave, CUtensorMapSwizzle,
                             CUtensorMapL2promotion, CUtensorMapFloatOOBfill);

struct Maps { CUtensorMap k, v, wq, wmod, wmod8, wo, wg, wu, wd; };

void encode(EncodeFn fn, CUtensorMap* m, const void* ptr, int rank, const cuuint64_t* dims, const cuuint64_t* strides,
            const cuuint32_t* box, CUtensorMapSwizzle sw) {
    const cuuint32_t es[3] = {1, 1, 1};
    fn(m, CU_TENSOR_MAP_DATA_TYPE_BFLOAT16, rank, const_cast<void*>(ptr), dims, strides, box, es,
       CU_TENSOR_MAP_INTERLEAVE_NONE, sw, CU_TENSOR_MAP_L2_PROMOTION_L2_256B, CU_TENSOR_MAP_FLOAT_OOB_FILL_NONE);
}

}

extern "C" void kernel_launch(void* const* d_in, const int* in_sizes, int n_in, void* d_out, int out_size) {
    (void)in_sizes; (void)n_in; (void)out_size;
    static EncodeFn enc = nullptr;
    static Scratch* scratch = nullptr;
    if (!enc) {
        cudaGetSymbolAddress((void**)&scratch, g_scratch);
        void* fn = nullptr;
        cudaDriverEntryPointQueryResult qr;
        cudaGetDriverEntryPoint("cuTensorMapEncodeTiled", &fn, cudaEnableDefault, &qr);
        enc = (EncodeFn)fn;
        cudaFuncSetAttribute(fused_block_kernel, cudaFuncAttributeMaxDynamicSharedMemorySize, SMEM_BYTES);
    }
    Maps m;
    {
        const cuuint64_t dims[3] = {64, (cuuint64_t)16 * SK, 2}, str[2] = {256, 128};
        const cuuint32_t box[3] = {64, 64, 2};
        encode(enc, &m.k, d_in[1], 3, dims, str, box, CU_TENSOR_MAP_SWIZZLE_128B);
        encode(enc, &m.v, d_in[2], 3, dims, str, box, CU_TENSOR_MAP_SWIZZLE_128B);
    }
    {
        const cuuint64_t dims[2] = {4096, 512}, str[1] = {8192};
        const cuuint32_t box[2] = {32, 256};
        encode(enc, &m.wq, d_in[3], 2, dims, str, box, CU_TENSOR_MAP_SWIZZLE_64B);
    }
    {
        const cuuint64_t dims[2] = {N_MOD, 512}, str[1] = {N_MOD * 2};
        const cuuint32_t box[2] = {16, 256};
        encode(enc, &m.wmod, d_in[10], 2, dims, str, box, CU_TENSOR_MAP_SWIZZLE_32B);
        const cuuint32_t box8[2] = {8, 256};
        encode(enc, &m.wmod8, d_in[10], 2, dims, str, box8, CU_TENSOR_MAP_SWIZZLE_NONE);
    }
    {
        const cuuint64_t dims_o[3] = {64, 4096, 8}, dims_d[3] = {64, D_FF, 8}, str[2] = {1024, 128};
        const cuuint32_t box[3] = {64, 16, 8}, box_o[3] = {64, 64, 2};
        encode(enc, &m.wo, d_in[4], 3, dims_o, str, box_o, CU_TENSOR_MAP_SWIZZLE_128B);
        encode(enc, &m.wd, d_in[8], 3, dims_d, str, box, CU_TENSOR_MAP_SWIZZLE_128B);
    }
    {
        const cuuint64_t dims[2] = {D_FF, 512}, str[1] = {D_FF * 2};
        const cuuint32_t box[2] = {16, 128};
        encode(enc, &m.wg, d_in[6], 2, dims, str, box, CU_TENSOR_MAP_SWIZZLE_32B);
        encode(enc, &m.wu, d_in[7], 2, dims, str, box, CU_TENSOR_MAP_SWIZZLE_32B);
    }
    Params p;
    p.x = (const __nv_bfloat16*)d_in[0];
    p.c = (const __nv_bfloat16*)d_in[9];
    p.out = (__nv_bfloat16*)d_out;
    p.sc = scratch;
    fused_block_kernel<<<NCTA, NTHREADS, SMEM_BYTES, cudaStreamPerThread>>>(p, m.k, m.v, m.wq, m.wmod, m.wmod8, m.wo, m.wg, m.wu, m.wd);
}
```

```cpp
#include <cuda_runtime.h>
#include <cuda.h>
#include <cuda_bf16.h>
#include <stdint.h>

namespace {

constexpr int D_MODEL = 512;
constexpr int N_HEADS = 32;
constexpr int SK = 32768;
constexpr int DH = 128;
constexpr int D_FF = 1792;
constexpr int N_MOD = 6 * D_MODEL;

constexpr int NCTA = 128;
constexpr int NFFN = D_FF / 16;
constexpr int NOWN = 32;
constexpr int NTHREADS = 320;
constexpr int NST = 12;
constexpr int TILE = 16384;
#define WINDOW 3
#define WINDOW_TAIL 1
#define GU_WIN 3
#define GU_RUSH 1
#define PACE_THR 96
constexpr int KV_TILES = 64;
#define MOD_AT 8
static_assert(MOD_AT % 2 == 0 && MOD_AT >= 2 && MOD_AT < 56, "schedule");
__host__ __device__ constexpr int kv_idx(int i) { return 2 + 2 * i + (i >= MOD_AT ? 1 : 0); }
constexpr int IDX_MOD = 2 + 2 * MOD_AT;
constexpr int N_STREAM = kv_idx(KV_TILES - 1) + 2;
constexpr int IDX_WO = N_STREAM;
constexpr int IDX_WG = IDX_WO + 2;
constexpr int IDX_WU = IDX_WG + 1;
constexpr int IDX_WD = IDX_WU + 1;
constexpr int SPIN_LIMIT = 1 << 20;

constexpr float LOG2E = 1.4426950408889634f;
constexpr float QK_SCALE = 0.08838834764831845f;

constexpr int SM_RING = 0;
constexpr int SM_MRG = SM_RING + NST * TILE;
constexpr int SM_ML = SM_MRG + 8 * 4 * 136 * 4;
constexpr int SM_RED = SM_ML + 8 * 4 * 8;
constexpr int SM_RED2 = SM_RED + 8 * 64 * 4;
constexpr int SM_QS = SM_RED2 + 8 * 64 * 4;
constexpr int SM_OS = SM_QS + 512 * 2;
constexpr int SM_SC = SM_OS + 2 * 128 * 2;
constexpr int SM_HS = SM_SC + 2 * 512 * 2;
constexpr int SM_STAT = SM_HS + 8 * 2 * 32 * 4;
constexpr int SM_PACE = SM_STAT + 8 * 2 * 8;
constexpr int SM_BAR = SM_PACE + 16;
constexpr int SM_END = SM_BAR + (2 * NST + 1 + 8 + 4) * 8;
constexpr int SMEM_BYTES = SM_END + 1024;

struct Scratch {
    uint4 inbox_wo[NOWN][N_HEADS][8];
    uint4 inbox_dn[NCTA][NFFN][2];
    uint2 x1[D_MODEL];
    uint2 part_o[NCTA][4][64];
    uint2 part_ml[NCTA][4][4];
    uint2 mod[2][N_MOD / 2];
    uint2 q[2][N_HEADS * DH / 2];
    unsigned epoch;
    unsigned pad_[31];
    unsigned cleared;
    unsigned pad2_[31];
    unsigned progress;
};
__device__ Scratch g_scratch;
constexpr uint32_t F_PART = 1, F_WO = 1, F_DOWN = 1, F_X1 = 1;
__device__ __forceinline__ uint32_t tagf(float v, uint32_t f) { return (__float_as_uint(v) & ~3u) | f; }
__device__ __forceinline__ float untag(uint32_t v) { return __uint_as_float(v & ~3u); }

struct Params {
    const __nv_bfloat16* x;
    const __nv_bfloat16* c;
    __nv_bfloat16* out;
    Scratch* sc;
};

#define TSTAMP(i) do { } while (0)

__device__ __forceinline__ uint32_t smem_u32(const void* p) { return (uint32_t)__cvta_generic_to_shared(p); }

__device__ __forceinline__ void mbar_init(uint32_t bar, uint32_t cnt) {
    asm volatile("mbarrier.init.shared::cta.b64 [%0], %1;" ::"r"(bar), "r"(cnt) : "memory");
}
__device__ __forceinline__ void mbar_expect_tx(uint32_t bar, uint32_t bytes) {
    asm volatile("mbarrier.arrive.expect_tx.shared::cta.b64 _, [%0], %1;" ::"r"(bar), "r"(bytes) : "memory");
}
__device__ __forceinline__ void mbar_arrive(uint32_t bar) {
    asm volatile("mbarrier.arrive.shared::cta.b64 _, [%0];" ::"r"(bar) : "memory");
}
__device__ __forceinline__ bool mbar_try(uint32_t bar, uint32_t parity) {
    uint32_t ok;
    asm volatile(
        "{\n\t.reg .pred p;\n\t"
        "mbarrier.try_wait.parity.shared::cta.b64 p, [%1], %2;\n\t"
        "selp.u32 %0, 1, 0, p;\n\t}"
        : "=r"(ok) : "r"(bar), "r"(parity) : "memory");
    return ok != 0;
}
__device__ __forceinline__ bool mbar_test(uint32_t bar, uint32_t parity) {
    uint32_t ok;
    asm volatile(
        "{\n\t.reg .pred p;\n\t"
        "mbarrier.test_wait.parity.shared::cta.b64 p, [%1], %2;\n\t"
        "selp.u32 %0, 1, 0, p;\n\t}"
        : "=r"(ok) : "r"(bar), "r"(parity) : "memory");
    return ok != 0;
}
__device__ __forceinline__ void mbar_wait(uint32_t bar, uint32_t parity) {
    if (mbar_try(bar, parity)) return;
    const long long t0 = clock64();
    while (!mbar_try(bar, parity))
        if (clock64() - t0 > (1ll << 31)) return;
}
__device__ __forceinline__ void cons_sync() { asm volatile("bar.sync 1, 256;" ::: "memory"); }

__device__ __forceinline__ void tma_2d(uint32_t dst, const CUtensorMap* m, int c0, int c1, uint32_t bar) {
    asm volatile("cp.async.bulk.tensor.2d.shared::cluster.global.mbarrier::complete_tx::bytes [%0], [%1, {%3, %4}], [%2];"
                 ::"r"(dst), "l"(m), "r"(bar), "r"(c0), "r"(c1) : "memory");
}
__device__ __forceinline__ void tma_3d(uint32_t dst, const CUtensorMap* m, int c0, int c1, int c2, uint32_t bar) {
    asm volatile("cp.async.bulk.tensor.3d.shared::cluster.global.mbarrier::complete_tx::bytes [%0], [%1, {%3, %4, %5}], [%2];"
                 ::"r"(dst), "l"(m), "r"(bar), "r"(c0), "r"(c1), "r"(c2) : "memory");
}
__device__ __forceinline__ void tma_3d_hint(uint32_t dst, const CUtensorMap* m, int c0, int c1, int c2, uint32_t bar, uint64_t pol) {
    asm volatile("cp.async.bulk.tensor.3d.shared::cluster.global.mbarrier::complete_tx::bytes.L2::cache_hint [%0], [%1, {%3, %4, %5}], [%2], %6;"
                 ::"r"(dst), "l"(m), "r"(bar), "r"(c0), "r"(c1), "r"(c2), "l"(pol) : "memory");
}
__device__ __forceinline__ void prefetch_tmap(const CUtensorMap* m) {
    asm volatile("prefetch.tensormap [%0];" ::"l"(m) : "memory");
}

__device__ __forceinline__ void ldsm4(uint32_t addr, uint32_t (&r)[4]) {
    asm volatile("ldmatrix.sync.aligned.m8n8.x4.shared.b16 {%0,%1,%2,%3}, [%4];"
                 : "=r"(r[0]), "=r"(r[1]), "=r"(r[2]), "=r"(r[3]) : "r"(addr) : "memory");
}
__device__ __forceinline__ void ldsm4t(uint32_t addr, uint32_t (&r)[4]) {
    asm volatile("ldmatrix.sync.aligned.m8n8.x4.trans.shared.b16 {%0,%1,%2,%3}, [%4];"
                 : "=r"(r[0]), "=r"(r[1]), "=r"(r[2]), "=r"(r[3]) : "r"(addr) : "memory");
}
__device__ __forceinline__ void mma16816(float (&c)[4], const uint32_t (&a)[4], uint32_t b0, uint32_t b1) {
    asm volatile("mma.sync.aligned.m16n8k16.row.col.f32.bf16.bf16.f32 {%0,%1,%2,%3}, {%4,%5,%6,%7}, {%8,%9}, {%0,%1,%2,%3};"
                 : "+f"(c[0]), "+f"(c[1]), "+f"(c[2]), "+f"(c[3])
                 : "r"(a[0]), "r"(a[1]), "r"(a[2]), "r"(a[3]), "r"(b0), "r"(b1));
}
__device__ __forceinline__ uint32_t movmatrix_t(uint32_t a) {
    uint32_t d;
    asm volatile("movmatrix.sync.aligned.m8n8.trans.b16 %0, %1;" : "=r"(d) : "r"(a));
    return d;
}
__device__ __forceinline__ uint32_t pack_bf16(float a, float b) {
    uint32_t r;
    asm("cvt.rn.bf16x2.f32 %0, %1, %2;" : "=r"(r) : "f"(b), "f"(a));
    return r;
}
__device__ __forceinline__ float bf_lo(uint32_t v) { return __uint_as_float(v << 16); }
__device__ __forceinline__ float bf_hi(uint32_t v) { return __uint_as_float(v & 0xffff0000u); }
__device__ __forceinline__ float bf16r(float a) { return bf_lo(pack_bf16(a, 0.f)); }
__device__ __forceinline__ uint32_t max_bf16x2(uint32_t a, uint32_t b) {
    uint32_t r;
    asm("max.bf16x2 %0, %1, %2;" : "=r"(r) : "r"(a), "r"(b));
    return r;
}
__device__ __forceinline__ float ex2(float x) {
    float r;
    asm("ex2.approx.ftz.f32 %0, %1;" : "=f"(r) : "f"(x));
    return r;
}

__device__ __forceinline__ void st_ll2(uint2* p, uint32_t v, uint32_t tag) {
    asm volatile("st.relaxed.gpu.global.v2.u32 [%0], {%1, %2};" ::"l"(p), "r"(v), "r"(tag) : "memory");
}
__device__ __forceinline__ void st_v4(uint4* p, uint32_t a, uint32_t b, uint32_t c, uint32_t d) {
    asm volatile("st.relaxed.gpu.global.v4.u32 [%0], {%1, %2, %3, %4};" ::"l"(p), "r"(a), "r"(b), "r"(c), "r"(d) : "memory");
}
__device__ __forceinline__ uint2 ld_ll2(const uint2* p) {
    uint2 v;
    asm volatile("ld.relaxed.gpu.global.v2.u32 {%0, %1}, [%2];" : "=r"(v.x), "=r"(v.y) : "l"(p) : "memory");
    return v;
}
__device__ __forceinline__ uint4 ld_ll4(const uint4* p) {
    uint4 v;
    asm volatile("ld.relaxed.gpu.global.v4.u32 {%0, %1, %2, %3}, [%4];"
                 : "=r"(v.x), "=r"(v.y), "=r"(v.z), "=r"(v.w) : "l"(p) : "memory");
    return v;
}

#define DELAY_P1 1800
#define DELAY_Q 1800
#define DELAY_A 1000
#define DELAY_B1 300
#define DELAY_X1 2000
#define DELAY_NOFFN 1500
#define DELAY_C 600
__device__ __forceinline__ uint32_t clock32() {
    uint32_t c;
    asm volatile("mov.u32 %0, %clock;" : "=r"(c));
    return c;
}
__device__ __forceinline__ void spin_cycles(uint32_t n) {
    if (n > 0) { const uint32_t c0 = clock32(); while (clock32() - c0 < n) {} }
}
__device__ __forceinline__ float rcp_approx(float x) {
    float r;
    asm("rcp.approx.ftz.f32 %0, %1;" : "=f"(r) : "f"(x));
    return r;
}
__device__ __forceinline__ float sqrt_approx(float x) {
    float r;
    asm("sqrt.approx.f32 %0, %1;" : "=f"(r) : "f"(x));
    return r;
}

__device__ __forceinline__ float silu_bf(float v) { return bf16r(v / (1.0f + expf(-v))); }

__device__ __forceinline__ float2 half_warp_sums(const float (&v)[4], float pivot) {
    float s1 = 0.f, s2 = 0.f;
#pragma unroll
    for (int i = 0; i < 4; i++) { const float d = v[i] - pivot; s1 += d; s2 += d * d; }
#pragma unroll
    for (int o = 1; o < 16; o <<= 1) { s1 += __shfl_xor_sync(0xffffffffu, s1, o); s2 += __shfl_xor_sync(0xffffffffu, s2, o); }
    return make_float2(s1, s2);
}
__device__ __forceinline__ void ln_stats(const float2* stat, int b, float pivot, float& mean_bf, float& rstd) {
    float s1 = 0.f, s2 = 0.f;
#pragma unroll
    for (int w = 0; w < 8; w++) { const float2 v = stat[w * 2 + b]; s1 += v.x; s2 += v.y; }
    const float dm = s1 * (1.0f / D_MODEL);
    const float var = fmaxf(s2 * (1.0f / D_MODEL) - dm * dm, 0.f);
    mean_bf = bf16r(pivot + dm);
    rstd = rcp_approx(bf16r(sqrt_approx(bf16r(bf16r(var) + 1e-5f))));
}
__device__ __forceinline__ float ln_norm(float xv, float mean_bf, float rstd) { return bf16r(bf16r(xv - mean_bf) * rstd); }
__device__ __forceinline__ float ln_mod(float n, float cmul, float sadd) { return bf16r(n * bf16r(1.0f + cmul)) + sadd; }

__global__ void __launch_bounds__(NTHREADS, 1)
fused_block_kernel(const Params p, const __grid_constant__ CUtensorMap tm_k, const __grid_constant__ CUtensorMap tm_v,
                   const __grid_constant__ CUtensorMap tm_wq, const __grid_constant__ CUtensorMap tm_wmod,
                   const __grid_constant__ CUtensorMap tm_wmod8,
                   const __grid_constant__ CUtensorMap tm_wo, const __grid_constant__ CUtensorMap tm_wg,
                   const __grid_constant__ CUtensorMap tm_wu, const __grid_constant__ CUtensorMap tm_wd) {
    extern __shared__ unsigned char smem_raw[];
    const uint32_t sbase = (smem_u32(smem_raw) + 1023u) & ~1023u;
    unsigned char* sgen = smem_raw + (sbase - smem_u32(smem_raw));
    const int tid = threadIdx.x, warp = tid >> 5, lane = tid & 31;
    const int cta = blockIdx.x;
    const uint32_t bar_full = sbase + SM_BAR, bar_empty = bar_full + NST * 8;
    const uint32_t bar_clear = bar_empty + NST * 8;
    const uint32_t bar_gu = bar_clear + 8;
    const uint32_t bar_bc = bar_gu + 8 * 8;
    const uint32_t bar_p0w = bar_bc + 8;
    const uint32_t bar_gate = bar_p0w + 8;
    const uint32_t bar_wopub = bar_gate + 8;

    const int key0 = (cta >> 3) * SK + (cta & 7) * 64;
    uint64_t pol = 0;
    if (tid == 256) {
        asm volatile("createpolicy.fractional.L2::evict_first.b64 %0, 1.0;" : "=l"(pol));
        mbar_init(bar_p0w, 1);
#pragma unroll
        for (int i = 0; i < 4; i++) mbar_init(bar_full + 8 * i, 1);
        asm volatile("fence.mbarrier_init.release.cluster;" ::: "memory");
        mbar_expect_tx(bar_p0w, 8192);
        tma_2d(sbase + SM_MRG, &tm_wmod8, cta * 8, 0, bar_p0w);
        tma_2d(sbase + SM_MRG + 4096, &tm_wmod8, cta * 8, 256, bar_p0w);
#pragma unroll
        for (int i = 0; i < 4; i++) mbar_expect_tx(bar_full + 8 * i, TILE);
        tma_2d(sbase + SM_RING, &tm_wq, cta * 32, 0, bar_full);
        tma_2d(sbase + SM_RING + TILE, &tm_wq, cta * 32, 256, bar_full + 8);
        tma_3d_hint(sbase + SM_RING + 2 * TILE, &tm_k, 0, key0, 0, bar_full + 16, pol);
        tma_3d_hint(sbase + SM_RING + 3 * TILE, &tm_v, 0, key0, 0, bar_full + 24, pol);
    }

    if (warp == 8) {
        if (lane == 0) {
            for (int i = 0; i < NST; i++) { if (i >= 4) mbar_init(bar_full + 8 * i, 1); mbar_init(bar_empty + 8 * i, 4); }
            mbar_init(bar_clear, 1);
            for (int k = 0; k < 8; k++) mbar_init(bar_gu + 8 * k, 1);
            mbar_init(bar_bc, 8);
            mbar_init(bar_gate, 1);
            mbar_init(bar_wopub, 1);
            ((volatile uint32_t*)(sgen + SM_PACE))[0] = 0;
            ((volatile uint32_t*)(sgen + SM_PACE))[1] = WINDOW;
            asm volatile("fence.mbarrier_init.release.cluster;" ::: "memory");
        }
        __syncwarp();
        asm volatile("bar.arrive 2, 288;" ::: "memory");
        asm volatile("bar.arrive 3, 64;" ::: "memory");
        if (lane == 0) {
            int slot = 4; uint32_t ph = 1;
            int landed = 0, wslot = 0; uint32_t wph = 0;
            int kv = 2;
            auto wait_window = [&](int idx, int window) {
                while (landed + window <= idx) {
                    mbar_wait(bar_full + 8 * wslot, wph);
                    if (++wslot == NST) { wslot = 0; wph ^= 1; }
                    landed++;
                }
            };
            volatile uint32_t* pace = (volatile uint32_t*)(sgen + SM_PACE);
            prefetch_tmap(&tm_wmod);
            pace[0] = 4;
            for (int idx = 4; idx < N_STREAM; idx++) {
                if (idx >= NST) mbar_wait(bar_empty + 8 * slot, ph);
                wait_window(idx, (int)pace[1]);
                if (idx == 12) { prefetch_tmap(&tm_wo); prefetch_tmap(&tm_wg); prefetch_tmap(&tm_wu); prefetch_tmap(&tm_wd); }
                const uint32_t fb = bar_full + 8 * slot, dst = sbase + SM_RING + slot * TILE;
                mbar_expect_tx(fb, TILE);
                if (idx == IDX_MOD) {
                    tma_2d(dst, &tm_wmod, 1024 + cta * 16, 0, fb);
                    tma_2d(dst + 8192, &tm_wmod, 1024 + cta * 16, 256, fb);
                } else {
                    tma_3d_hint(dst, (kv & 1) ? &tm_v : &tm_k, 0, key0 + (kv >> 1) * 512, 0, fb, pol);
                    kv++;
                }
                pace[0] = idx + 1;
                if (++slot == NST) { slot = 0; ph ^= 1; }
            }
            auto slot_free = [&](int idx) { mbar_wait(bar_empty + 8 * (idx % NST), ((idx / NST) & 1) ^ 1); };
#pragma unroll
            for (int s = 0; s < 2; s++) {
                const int idx = IDX_WO + s;
                slot_free(idx);
                wait_window(idx, WINDOW_TAIL);
                mbar_expect_tx(bar_full + 8 * (idx % NST), TILE);
                tma_3d(sbase + SM_RING + (idx % NST) * TILE, &tm_wo, 0, (cta >> 2) * 128 + s * 64, (cta & 3) * 2, bar_full + 8 * (idx % NST));
            }
            if (cta < NFFN) {
                slot_free(IDX_WG); slot_free(IDX_WU);
                mbar_wait(bar_full + 8 * (IDX_WO % NST), (IDX_WO / NST) & 1);
                mbar_wait(bar_full + 8 * ((IDX_WO + 1) % NST), ((IDX_WO + 1) / NST) & 1);
#pragma unroll
                for (int st = 0; st < 8; st++) {
                    if (st >= GU_WIN) {
                        if (GU_RUSH && cta < NCTA - NOWN) {
                            for (int it = 0; it < SPIN_LIMIT * 16; it++)
                                if (mbar_test(bar_gu + 8 * (st - GU_WIN), 0) || mbar_test(bar_wopub, 0)) break;
                        } else {
                            mbar_wait(bar_gu + 8 * (st - GU_WIN), 0);
                        }
                    }
                    mbar_expect_tx(bar_gu + 8 * st, 4096);
                    tma_2d(sbase + SM_RING + (((st & 1) ? IDX_WU : IDX_WG) % NST) * TILE + (st >> 1) * 4096,
                           (st & 1) ? &tm_wu : &tm_wg, cta * 16, (st >> 1) * 128, bar_gu + 8 * st);
                }
                if (GU_RUSH && cta < NCTA - NOWN) {
                    for (int it = 0; it < SPIN_LIMIT * 16; it++)
                        if (mbar_test(bar_gu + 8 * 6, 0) || mbar_test(bar_wopub, 0)) break;
                } else {
                    mbar_wait(bar_gu + 8 * 6, 0);
                }
                slot_free(IDX_WD);
                mbar_expect_tx(bar_full + 8 * (IDX_WD % NST), TILE);
                tma_3d(sbase + SM_RING + (IDX_WD % NST) * TILE, &tm_wd, 0, cta * 16, 0, bar_full + 8 * (IDX_WD % NST));
            }
        }
    } else if (warp == 9) {
        Scratch* const sc = p.sc;
        const uint32_t tag = *(volatile unsigned*)&sc->epoch + 1;
        asm volatile("bar.sync 3, 64;" ::: "memory");
#pragma unroll 4
        for (int i = 0; i < NFFN * 2 / 32; i++) st_v4(&sc->inbox_dn[cta][0][0] + i * 32 + lane, 0u, 0u, 0u, 0u);
        if (cta >= NCTA - NOWN) {
#pragma unroll 4
            for (int i = 0; i < 8; i++) st_v4(&sc->inbox_wo[cta - (NCTA - NOWN)][0][0] + i * 32 + lane, 0u, 0u, 0u, 0u);
            if (lane < 8) st_v4((uint4*)&sc->x1[(cta - (NCTA - NOWN)) * 16] + lane, 0u, 0u, 0u, 0u);
        }
#pragma unroll 4
        for (int i = 0; i < 4; i++) st_v4((uint4*)&sc->part_o[cta][0][0] + i * 32 + lane, 0u, 0u, 0u, 0u);
        if (lane < 8) st_v4((uint4*)&sc->part_ml[cta][0][0] + lane, 0u, 0u, 0u, 0u);
        if (cta == 0 && lane == 0) asm volatile("st.relaxed.gpu.global.u32 [%0], %1;" ::"l"(&sc->progress), "r"(0u) : "memory");
        asm volatile("fence.acq_rel.gpu;" ::: "memory");
        __syncwarp();
        if (lane == 0) {
            asm volatile("fence.acq_rel.gpu;" ::: "memory");
            asm volatile("red.relaxed.gpu.global.add.u32 [%0], %1;" ::"l"(&sc->cleared), "r"(1u) : "memory");
            const uint32_t target = tag * NCTA;
            for (int it = 0; it < SPIN_LIMIT; it++) {
                uint32_t v;
                asm volatile("ld.relaxed.gpu.global.u32 %0, [%1];" : "=r"(v) : "l"(&sc->cleared) : "memory");
                if ((int32_t)(v - target) >= 0) break;
                __nanosleep(500);
            }
            asm volatile("fence.acq_rel.gpu;" ::: "memory");
            mbar_arrive(bar_clear);
            volatile uint32_t* pace = (volatile uint32_t*)(sgen + SM_PACE);
            uint32_t posted = 0;
            for (int it = 0; it < SPIN_LIMIT; it++) {
                const uint32_t own = pace[0];
                if (own > posted) {
                    asm volatile("red.relaxed.gpu.global.add.u32 [%0], %1;" ::"l"(&sc->progress), "r"(own - posted) : "memory");
                    posted = own;
                }
                uint32_t v;
                asm volatile("ld.relaxed.gpu.global.u32 %0, [%1];" : "=r"(v) : "l"(&sc->progress) : "memory");
                if (own >= N_STREAM) {
                    if (v >= NCTA * N_STREAM) break;
                } else {
                    const int diff = (int)v - (int)own * NCTA;
                    pace[1] = diff > PACE_THR ? WINDOW + 1 : diff < -PACE_THR ? WINDOW - 1 : WINDOW;
                }
                __nanosleep(200);
            }
            pace[2] = clock32();
            mbar_arrive(bar_gate);
            if (cta == 0) asm volatile("st.relaxed.gpu.global.u32 [%0], %1;" ::"l"(&sc->epoch), "r"(tag) : "memory");
        }
    } else {
        const int g = lane >> 2, t = lane & 3;
        const int bb = g & 1;
        const int eb = lane >> 4;
        const int ec = 64 * warp + 4 * (lane & 15);
        if (warp == 0) TSTAMP(0);
        Scratch* const sc = p.sc;
        const float c00 = __bfloat162float(p.c[tid]), c01 = __bfloat162float(p.c[tid + 256]);
        const float c10 = __bfloat162float(p.c[D_MODEL + tid]), c11 = __bfloat162float(p.c[D_MODEL + tid + 256]);
        const uint2 xe = __ldg((const uint2*)(p.x + eb * D_MODEL + ec));
        const float xpivot = __bfloat162float(p.x[eb * D_MODEL]);
        const uint32_t tag = *(volatile unsigned*)&sc->epoch + 1;
        const int ocol = cta * 4 + (lane & 3);
        const int wcol = (cta >= NCTA - NOWN ? cta - (NCTA - NOWN) : 0) * 16 + (lane & 15);
        const float xo = __bfloat162float(p.x[eb * D_MODEL + wcol]);

        float* red = (float*)(sgen + SM_RED);
        float* red2 = (float*)(sgen + SM_RED2);
        float2* stat = (float2*)(sgen + SM_STAT);
        uint32_t* hs = (uint32_t*)(sgen + SM_HS) + warp * 64;
        float xn[4];
        {
            float xv[4] = {bf_lo(xe.x), bf_hi(xe.x), bf_lo(xe.y), bf_hi(xe.y)};
            const float2 ps = half_warp_sums(xv, xpivot);
            if ((lane & 15) == 0) stat[warp * 2 + eb] = ps;
            const float s00 = silu_bf(c00), s01 = silu_bf(c01), s10 = silu_bf(c10), s11 = silu_bf(c11);
            __nv_bfloat16* scs = (__nv_bfloat16*)(sgen + SM_SC);
            scs[tid] = __float2bfloat16_rn(s00); scs[tid + 256] = __float2bfloat16_rn(s01);
            scs[512 + tid] = __float2bfloat16_rn(s10); scs[512 + tid + 256] = __float2bfloat16_rn(s11);
            asm volatile("bar.sync 2, 288;" ::: "memory");
            if (warp == 0) TSTAMP(23);
            float cp[4] = {0.f, 0.f, 0.f, 0.f};
            const uint32_t* sc32 = (const uint32_t*)(sgen + SM_SC) + bb * 256 + 32 * warp + t;
            mbar_wait(bar_p0w, 0);
#pragma unroll
            for (int s = 0; s < 4; s++) {
                uint32_t r0, r1;
                asm volatile("ldmatrix.sync.aligned.m8n8.x2.trans.shared.b16 {%0,%1}, [%2];"
                             : "=r"(r0), "=r"(r1) : "r"(sbase + SM_MRG + (64 * warp + 16 * s + (lane & 15)) * 16) : "memory");
                const uint32_t a[4] = {r0, r0, r1, r1};
                mma16816(cp, a, sc32[8 * s], sc32[8 * s + 4]);
            }
            if (t == 0) { red[warp * 16 + g] = cp[0]; red[warp * 16 + 8 + g] = cp[1]; }
            if (warp == 0) TSTAMP(14);
            cons_sync();
            if (warp == 0) {
                float s = 0.f;
#pragma unroll
                for (int w = 0; w < 8; w++) s += red[w * 16 + (lane & 15)];
                const float nx = __shfl_down_sync(0xffffffffu, s, 1);
                if (lane < 16 && !(lane & 1))
                    st_ll2(&sc->mod[lane >> 3][cta * 4 + ((lane & 7) >> 1)], pack_bf16(s, nx), tag);
                TSTAMP(1);
            }
            float mean_bf, rstd;
            ln_stats(stat, eb, xpivot, mean_bf, rstd);
#pragma unroll
            for (int i = 0; i < 4; i++) xn[i] = ln_norm(xv[i], mean_bf, rstd);
        }
        {
            uint4 sa, ca;
            spin_cycles(DELAY_P1);
            for (int it = 0;; it++) {
                sa = ld_ll4((const uint4*)&sc->mod[eb][ec >> 1]);
                ca = ld_ll4((const uint4*)&sc->mod[eb][256 + (ec >> 1)]);
                const bool ok = sa.y == tag && sa.w == tag && ca.y == tag && ca.w == tag;
                if (__all_sync(0xffffffffu, ok) || it > SPIN_LIMIT) break;
            }
            *(uint2*)&hs[eb * 32 + 2 * (lane & 15)] =
                make_uint2(pack_bf16(ln_mod(xn[0], bf_lo(ca.x), bf_lo(sa.x)), ln_mod(xn[1], bf_hi(ca.x), bf_hi(sa.x))),
                           pack_bf16(ln_mod(xn[2], bf_lo(ca.z), bf_lo(sa.z)), ln_mod(xn[3], bf_hi(ca.z), bf_hi(sa.z))));
            __syncwarp();
            uint32_t hb[8];
#pragma unroll
            for (int i = 0; i < 8; i++) hb[i] = hs[bb * 32 + 8 * (i >> 1) + 4 * (i & 1) + t];
            if (warp == 0) TSTAMP(2);
            float cq[2][4] = {};
            const int ts = warp >> 2;
            mbar_wait(bar_full + 8 * ts, 0);
            const uint32_t tb = sbase + SM_RING + ts * TILE;
#pragma unroll
            for (int s = 0; s < 4; s++) {
                const int row = 64 * (warp & 3) + 16 * s + (lane & 7) + (lane >> 4) * 8;
#pragma unroll
                for (int mt = 0; mt < 2; mt++) {
                    const int ch = 2 * mt + ((lane >> 3) & 1);
                    uint32_t a[4];
                    ldsm4t(tb + row * 64 + ((ch ^ ((row >> 1) & 3)) << 4), a);
                    mma16816(cq[mt], a, hb[2 * s], hb[2 * s + 1]);
                }
            }
            if (t < 2) {
                const float v0 = t == 0 ? cq[0][0] : cq[1][0], v1 = t == 0 ? cq[0][1] : cq[1][1];
                const float v2 = t == 0 ? cq[0][2] : cq[1][2], v3 = t == 0 ? cq[0][3] : cq[1][3];
                *(float2*)&red2[warp * 64 + (16 * t + g) * 2] = make_float2(v0, v1);
                *(float2*)&red2[warp * 64 + (16 * t + g + 8) * 2] = make_float2(v2, v3);
            }
            cons_sync();
            if (warp < 4 && lane == 0) { mbar_arrive(bar_empty); mbar_arrive(bar_empty + 8); }
            if (warp == 0) {
                const int b = lane >> 4, cp = lane & 15;
                float q0 = 0.f, q1 = 0.f;
#pragma unroll
                for (int w = 0; w < 8; w++) {
                    const float4 v = *(const float4*)&red2[w * 64 + cp * 4];
                    q0 += b ? v.y : v.x; q1 += b ? v.w : v.z;
                }
                st_ll2(&sc->q[b][cta * 16 + cp], pack_bf16(q0, q1), tag);
                TSTAMP(3);
            }
        }
        const int pair = cta >> 3;
        uint32_t qf[16];
        {
            uint2* qs = (uint2*)(sgen + SM_QS);
            if (tid < 128) {
                const uint4* src = (const uint4*)&sc->q[pair >> 3][(pair & 7) * 256] + tid;
                uint4 v;
                spin_cycles(DELAY_Q);
                for (int it = 0;; it++) {
                    v = ld_ll4(src);
                    if ((v.y == tag && v.w == tag) || it > SPIN_LIMIT) break;
                }
                qs[tid] = make_uint2(v.x, v.z);
            }
            cons_sync();
            const uint32_t* q32 = (const uint32_t*)(sgen + SM_QS);
#pragma unroll
            for (int s = 0; s < 8; s++) {
                qf[2 * s] = q32[(g & 3) * 64 + 8 * s + t];
                qf[2 * s + 1] = q32[(g & 3) * 64 + 8 * s + 4 + t];
            }
        }
        if (warp == 0) TSTAMP(4);

        float o[8][4];
#pragma unroll
        for (int i = 0; i < 8; i++) { o[i][0] = o[i][1] = o[i][2] = o[i][3] = 0.f; }
        uint32_t mrun = 0xff80ff80u;
        float ls[4] = {0.f, 0.f, 0.f, 0.f};
        uint4 m_sb, m_cb; uint2 m_ga, m_gb0, m_gb1;
        {
            const int grp = warp >> 2, wi = warp & 3;
            const int krow = 16 * wi + (lane & 7) + ((lane >> 3) & 1) * 8;
            const uint32_t koff = krow * 128 + ((((lane >> 4) & 1) ^ (lane & 7)) << 4);
            const int vrow = 16 * wi + (lane & 7) + (lane >> 4) * 8;
            const uint32_t voff = vrow * 128 + ((((lane >> 3) & 1) ^ (lane & 7)) << 4);
            const uint32_t ones[4] = {0x3f803f80u, 0x3f803f80u, 0x3f803f80u, 0x3f803f80u};
            for (int i = grp; i < KV_TILES; i += 2) {
                if (i == MOD_AT + grp) {
                    float cm[4] = {};
                    const uint32_t* sc32 = (const uint32_t*)(sgen + SM_SC) + bb * 256 + 32 * warp + t;
                    mbar_wait(bar_full + 8 * (IDX_MOD % NST), (IDX_MOD / NST) & 1);
                    const uint32_t tb = sbase + SM_RING + (IDX_MOD % NST) * TILE;
#pragma unroll
                    for (int s = 0; s < 4; s++) {
                        const int row = 64 * warp + 16 * s + (lane & 7) + (lane >> 4) * 8;
                        const int ch = (lane >> 3) & 1;
                        uint32_t a[4];
                        ldsm4t(tb + row * 32 + ((ch ^ ((row >> 2) & 1)) << 4), a);
                        mma16816(cm, a, sc32[8 * s], sc32[8 * s + 4]);
                    }
                    if (t == 0) {
                        *(float2*)&red[warp * 64 + g * 2] = make_float2(cm[0], cm[1]);
                        *(float2*)&red[warp * 64 + (g + 8) * 2] = make_float2(cm[2], cm[3]);
                    }
                    cons_sync();
                    if (warp < 4 && lane == 0) mbar_arrive(bar_empty + 8 * (IDX_MOD % NST));
                    if (warp == 1 && lane < 16) {
                        const int b = lane >> 3, cp = lane & 7;
                        float q0 = 0.f, q1 = 0.f;
#pragma unroll
                        for (int w = 0; w < 8; w++) {
                            const float4 v = *(const float4*)&red[w * 64 + cp * 4];
                            q0 += b ? v.y : v.x; q1 += b ? v.w : v.z;
                        }
                        st_ll2(&sc->mod[b][512 + cta * 8 + cp], pack_bf16(q0, q1), tag);
                    }
                }
                if (i == 56 + grp) {
                    m_sb = ld_ll4((const uint4*)&sc->mod[eb][768 + (ec >> 1)]);
                    m_cb = ld_ll4((const uint4*)&sc->mod[eb][1024 + (ec >> 1)]);
                    m_ga = ld_ll2(&sc->mod[eb][512 + (wcol >> 1)]);
                    m_gb0 = ld_ll2(&sc->mod[0][1280 + (ocol >> 1)]); m_gb1 = ld_ll2(&sc->mod[1][1280 + (ocol >> 1)]);
                }
                if (i == 60 + grp) {
                    for (int it = 0;; it++) {
                        const bool ok = m_sb.y == tag && m_sb.w == tag && m_cb.y == tag && m_cb.w == tag &&
                                        m_ga.y == tag && m_gb0.y == tag && m_gb1.y == tag;
                        if (__all_sync(0xffffffffu, ok) || it > SPIN_LIMIT) break;
                        m_sb = ld_ll4((const uint4*)&sc->mod[eb][768 + (ec >> 1)]);
                        m_cb = ld_ll4((const uint4*)&sc->mod[eb][1024 + (ec >> 1)]);
                        m_ga = ld_ll2(&sc->mod[eb][512 + (wcol >> 1)]);
                        m_gb0 = ld_ll2(&sc->mod[0][1280 + (ocol >> 1)]); m_gb1 = ld_ll2(&sc->mod[1][1280 + (ocol >> 1)]);
                    }
                    mbar_wait(bar_clear, 0);
                }
                const int ki = kv_idx(i), ks = ki % NST, vs = (ki + 1) % NST;
                const uint32_t kph = (ki / NST) & 1, vph = ((ki + 1) / NST) & 1;
                mbar_wait(bar_full + 8 * ks, kph);
                const uint32_t kb = sbase + SM_RING + ks * TILE + koff;
                float sa[4] = {0.f, 0.f, 0.f, 0.f}, sb[4] = {0.f, 0.f, 0.f, 0.f};
#pragma unroll
                for (int s = 0; s < 8; s += 2) {
                    uint32_t a0[4], a1[4];
                    ldsm4((kb ^ ((s & 3) << 5)) + (s >> 2) * 8192, a0);
                    ldsm4((kb ^ (((s + 1) & 3) << 5)) + (s >> 2) * 8192, a1);
                    mma16816(sa, a0, qf[2 * s], qf[2 * s + 1]);
                    mma16816(sb, a1, qf[2 * s + 2], qf[2 * s + 3]);
                }
                __syncwarp();
                if (lane == 0) mbar_arrive(bar_empty + 8 * ks);
                uint32_t r01 = pack_bf16(sa[0] + sb[0], sa[1] + sb[1]);
                uint32_t r23 = pack_bf16(sa[2] + sb[2], sa[3] + sb[3]);
                r01 = pack_bf16(bf_lo(r01) * QK_SCALE, bf_hi(r01) * QK_SCALE);
                r23 = pack_bf16(bf_lo(r23) * QK_SCALE, bf_hi(r23) * QK_SCALE);
                uint32_t mx = max_bf16x2(r01, r23);
                mx = max_bf16x2(mx, __shfl_xor_sync(0xffffffffu, mx, 4));
                mx = max_bf16x2(mx, __shfl_xor_sync(0xffffffffu, mx, 8));
                mx = max_bf16x2(mx, __shfl_xor_sync(0xffffffffu, mx, 16));
                const uint32_t mnew = max_bf16x2(mrun, mx);
                const float m0 = bf_lo(mnew), m1 = bf_hi(mnew);
                if (__any_sync(0xffffffffu, mnew != mrun)) {
                    const float al0 = ex2((bf_lo(mrun) - m0) * LOG2E), al1 = ex2((bf_hi(mrun) - m1) * LOG2E);
                    ls[0] *= al0; ls[1] *= al1;
#pragma unroll
                    for (int d = 0; d < 8; d++) { o[d][0] *= al0; o[d][1] *= al1; o[d][2] *= al0; o[d][3] *= al1; }
                    mrun = mnew;
                }
                const float p0 = ex2((bf_lo(r01) - m0) * LOG2E), p1 = ex2((bf_hi(r01) - m1) * LOG2E);
                const float p2 = ex2((bf_lo(r23) - m0) * LOG2E), p3 = ex2((bf_hi(r23) - m1) * LOG2E);
                const uint32_t pb0 = movmatrix_t(pack_bf16(p0, p1)), pb1 = movmatrix_t(pack_bf16(p2, p3));
                mma16816(ls, ones, pb0, pb1);
                mbar_wait(bar_full + 8 * vs, vph);
                const uint32_t vb = sbase + SM_RING + vs * TILE + voff;
#pragma unroll
                for (int d = 0; d < 8; d++) {
                    uint32_t a[4];
                    ldsm4t((vb ^ ((d & 3) << 5)) + (d >> 2) * 8192, a);
                    mma16816(o[d], a, pb0, pb1);
                }
                __syncwarp();
                if (lane == 0) mbar_arrive(bar_empty + 8 * vs);
            }
        }
        if (warp == 7) TSTAMP(5);
        {
            float* mrg = (float*)(sgen + SM_MRG);
            float2* ml = (float2*)(sgen + SM_ML);
            {
                const int hp = (t & 1) * 2, up = t >> 1;
                if (g == 0 && up == 0) { ml[warp * 4 + hp] = make_float2(bf_lo(mrun), ls[0]); ml[warp * 4 + hp + 1] = make_float2(bf_hi(mrun), ls[1]); }
                float* m0p = mrg + (warp * 4 + hp) * 136 + up * 72 + g;
#pragma unroll
                for (int d = 0; d < 4; d++) {
                    m0p[16 * d] = up ? o[d + 4][0] : o[d][0]; m0p[136 + 16 * d] = up ? o[d + 4][1] : o[d][1];
                    m0p[16 * d + 8] = up ? o[d + 4][2] : o[d][2]; m0p[136 + 16 * d + 8] = up ? o[d + 4][3] : o[d][3];
                }
            }
            cons_sync();
            const int hh = tid >> 6, dp = tid & 63;
            float2 mw[8];
            float M = -INFINITY;
#pragma unroll
            for (int w = 0; w < 8; w++) { mw[w] = ml[w * 4 + hh]; M = fmaxf(M, mw[w].x); }
            float L = 0.f, o0 = 0.f, o1 = 0.f;
#pragma unroll
            for (int w = 0; w < 8; w++) {
                const float wt = ex2((mw[w].x - M) * LOG2E);
                const float2 v = *(const float2*)&mrg[(w * 4 + hh) * 136 + 2 * dp + (dp >= 32 ? 8 : 0)];
                L += wt * mw[w].y; o0 += wt * v.x; o1 += wt * v.y;
            }
            st_ll2(&sc->part_o[cta][hh][dp], tagf(o0, F_PART), tagf(o1, F_PART));
            if (dp < 4) st_ll2(&sc->part_ml[cta][hh][dp], tagf(M, F_PART), tagf(L, F_PART));
        }
        if (warp == 0) TSTAMP(6);
        {
            const int hq = cta >> 2, kvh = hq >> 2, hh = hq & 3;
            const int b = tid >> 7, dc = (tid >> 3) & 15, j = tid & 7;
            const int pc = (b * 8 + kvh) * 8 + j;
            const uint4* po = (const uint4*)&sc->part_o[pc][hh][0] + dc * 2;
            const uint2* pm = &sc->part_ml[pc - j][hh][0];
            uint4 vo0, vo1; uint2 vm[8];
            mbar_wait(bar_gate, 0);
            { const uint32_t tg = ((volatile uint32_t*)(sgen + SM_PACE))[2]; while (clock32() - tg < DELAY_A) {} }
            bool oko = false;
#pragma unroll
            for (int jj = 0; jj < 8; jj++) vm[jj] = make_uint2(0u, 0u);
            for (int it = 0;; it++) {
                if (!oko) { vo0 = ld_ll4(po); vo1 = ld_ll4(po + 1); }
#pragma unroll
                for (int jj = 0; jj < 8; jj++)
                    if ((vm[jj].x & vm[jj].y & 3u) != F_PART) vm[jj] = ld_ll2(pm + jj * 16);
                oko = (vo0.x & vo0.y & vo0.z & vo0.w & vo1.x & vo1.y & vo1.z & vo1.w & 3u) == F_PART;
                uint32_t all = vm[0].x & vm[0].y;
#pragma unroll
                for (int jj = 1; jj < 8; jj++) all &= vm[jj].x & vm[jj].y;
                if (__all_sync(0xffffffffu, oko && (all & 3u) == F_PART) || it > SPIN_LIMIT) break;
            }
            float M = untag(vm[0].x);
#pragma unroll
            for (int jj = 1; jj < 8; jj++) M = fmaxf(M, untag(vm[jj].x));
            float wt = 0.f, L = 0.f;
#pragma unroll
            for (int jj = 0; jj < 8; jj++) {
                const float w_ = ex2((untag(vm[jj].x) - M) * LOG2E);
                L += w_ * untag(vm[jj].y);
                wt = jj == j ? w_ : wt;
            }
            wt *= rcp_approx(L);
            float v[8] = {wt * untag(vo0.x), wt * untag(vo0.y), wt * untag(vo0.z), wt * untag(vo0.w),
                          wt * untag(vo1.x), wt * untag(vo1.y), wt * untag(vo1.z), wt * untag(vo1.w)};
#define XRED(N, O)                                                                       \
            {                                                                            \
                const bool up = lane & (O);                                              \
                _Pragma("unroll") for (int i = 0; i < (N); i++) {                        \
                    const float send = up ? v[i] : v[i + (N)], keep = up ? v[i + (N)] : v[i]; \
                    v[i] = keep + __shfl_xor_sync(0xffffffffu, send, (O));               \
                }                                                                        \
            }
            XRED(4, 1) XRED(2, 2) XRED(1, 4)
#undef XRED
            __nv_bfloat16* os = (__nv_bfloat16*)(sgen + SM_OS);
            os[b * 128 + dc * 8 + 4 * (j & 1) + 2 * ((j >> 1) & 1) + (j >> 2)] = __float2bfloat16_rn(v[0]);
            if (warp == 0) TSTAMP(15);
            uint32_t wf[8][4];
            const uint32_t aoff_o = (warp >> 2) * 8192 + ((lane & 7) + (lane >> 4) * 8) * 128 +
                                    (((((warp & 3) * 2 + ((lane >> 3) & 1)) ^ (lane & 7))) << 4);
#pragma unroll
            for (int s = 0; s < 2; s++) {
                const int idx = IDX_WO + s;
                mbar_wait(bar_full + 8 * (idx % NST), (idx / NST) & 1);
                const uint32_t tb = sbase + SM_RING + (idx % NST) * TILE + aoff_o;
#pragma unroll
                for (int k4 = 0; k4 < 4; k4++) ldsm4t(tb + k4 * 2048, wf[s * 4 + k4]);
            }
            cons_sync();
            if (warp == 0) TSTAMP(7);
            const uint32_t* os32 = (const uint32_t*)(sgen + SM_OS) + bb * 64 + t;
            float y0[4] = {}, y1[4] = {};
#pragma unroll
            for (int ks = 0; ks < 8; ks += 2) {
                mma16816(y0, wf[ks], os32[8 * ks], os32[8 * ks + 4]);
                mma16816(y1, wf[ks + 1], os32[8 * ks + 8], os32[8 * ks + 12]);
            }
            if (t == 0)
                st_v4(&sc->inbox_wo[(cta & 3) * 8 + warp][hq][g], tagf(y0[0] + y1[0], F_WO), tagf(y0[1] + y1[1], F_WO),
                      tagf(y0[2] + y1[2], F_WO), tagf(y0[3] + y1[3], F_WO));
        }
        if (tid == 0) mbar_arrive(bar_wopub);
        const uint32_t t_wo = clock32();
        if (warp == 0) TSTAMP(8);
        if (cta >= NCTA - NOWN) {
            const uint4* pin = &sc->inbox_wo[cta - (NCTA - NOWN)][0][0] + tid;
            uint4 v;
            spin_cycles(DELAY_B1);
            bool ok = false;
            for (int it = 0;; it++) {
                if (!ok) {
                    v = ld_ll4(pin);
                    ok = (v.x & v.y & v.z & v.w & 3u) == F_WO;
                }
                if (__all_sync(0xffffffffu, ok) || it > SPIN_LIMIT) break;
            }
            const bool u1 = lane & 8, u2 = lane & 16;
            const float a0 = untag(v.x), a1 = untag(v.y), a2 = untag(v.z), a3 = untag(v.w);
            const float k0 = (u1 ? a2 : a0) + __shfl_xor_sync(0xffffffffu, u1 ? a0 : a2, 8);
            const float k1 = (u1 ? a3 : a1) + __shfl_xor_sync(0xffffffffu, u1 ? a1 : a3, 8);
            red2[warp * 32 + lane] = (u2 ? k1 : k0) + __shfl_xor_sync(0xffffffffu, u2 ? k0 : k1, 16);
            cons_sync();
            if (warp == 0) {
                float a = 0.f;
#pragma unroll
                for (int w = 0; w < 8; w++) a += red2[w * 32 + lane];
                const float ga = (wcol & 1) ? bf_hi(m_ga.x) : bf_lo(m_ga.x);
                const float xm = bf16r(xo + bf16r(ga * bf16r(a)));
                const float xm_b1 = __shfl_down_sync(0xffffffffu, xm, 16);
                if (lane < 16) st_ll2(&sc->x1[wcol], pack_bf16(xm, xm_b1), F_X1);
                TSTAMP(10);
            }
        }
        const uint32_t aoff = warp * 2048 + ((lane & 7) + (lane >> 4) * 8) * 128 + ((((lane >> 3) & 1) ^ (lane & 7)) << 4);
        if (cta < NFFN) {
            const uint4* px = (const uint4*)&sc->x1[ec];
            const uint4* pp = (const uint4*)&sc->x1[0];
            uint4 va, vb, pa, pb;
            uint32_t gf[4][4], uf[4][4];
            mbar_wait(bar_gu + 8 * (2 * (warp >> 1)), 0);
            mbar_wait(bar_gu + 8 * (2 * (warp >> 1) + 1), 0);
            {
                const uint32_t tg = sbase + SM_RING + (IDX_WG % NST) * TILE, tu = sbase + SM_RING + (IDX_WU % NST) * TILE;
#pragma unroll
                for (int s = 0; s < 4; s++) {
                    const int row = 64 * warp + 16 * s + (lane & 7) + (lane >> 4) * 8;
                    const uint32_t off = row * 32 + ((((lane >> 3) & 1) ^ ((row >> 2) & 1)) << 4);
                    ldsm4t(tg + off, gf[s]);
                    ldsm4t(tu + off, uf[s]);
                }
            }
            const float c1v[4] = {bf16r(1.0f + bf_lo(m_cb.x)), bf16r(1.0f + bf_hi(m_cb.x)), bf16r(1.0f + bf_lo(m_cb.z)), bf16r(1.0f + bf_hi(m_cb.z))};
            float bg = 0.f, cgc = 0.f, bu = 0.f, cuc = 0.f;
            {
                uint32_t* pre = (uint32_t*)(sgen + SM_MRG) + warp * 128;
                float* bc = (float*)(sgen + SM_MRG + 4096);
                *(uint2*)&pre[eb * 32 + 2 * (lane & 15)] = make_uint2(pack_bf16(c1v[0], c1v[1]), pack_bf16(c1v[2], c1v[3]));
                *(uint2*)&pre[64 + eb * 32 + 2 * (lane & 15)] = make_uint2(m_sb.x, m_sb.z);
                __syncwarp();
                float yg[4] = {}, yu[4] = {};
                const uint32_t* pb = pre + ((g >> 1) & 1) * 64 + bb * 32 + t;
#pragma unroll
                for (int s = 0; s < 4; s++) {
                    const uint32_t b0 = pb[8 * s], b1 = pb[8 * s + 4];
                    mma16816(yg, gf[s], b0, b1);
                    mma16816(yu, uf[s], b0, b1);
                }
                const float y0 = t < 2 ? yg[0] : yu[0], y1 = t < 2 ? yg[1] : yu[1], y2 = t < 2 ? yg[2] : yu[2], y3 = t < 2 ? yg[3] : yu[3];
                float* dstp = bc + warp * 128 + (t >> 1) * 64 + (t & 1) * 32;
                *(float2*)&dstp[g * 2] = make_float2(y0, y1);
                *(float2*)&dstp[(g + 8) * 2] = make_float2(y2, y3);
                __syncwarp();
                if (lane == 0) mbar_arrive(bar_bc);
            }
            if (warp == 0) TSTAMP(11);
            float pivot2;
            {
                while (clock32() - t_wo < DELAY_X1) {}
                bool okx = false, okp = false;
                for (int it = 0;; it++) {
                    if (!okx) { va = ld_ll4(px); vb = ld_ll4(px + 1); }
                    if (!okp) { pa = ld_ll4(pp); pb = ld_ll4(pp + 1); }
                    okx = va.y == F_X1 && va.w == F_X1 && vb.y == F_X1 && vb.w == F_X1;
                    okp = pa.y == F_X1 && pa.w == F_X1 && pb.y == F_X1 && pb.w == F_X1;
                    if (__all_sync(0xffffffffu, okx && okp) || it > SPIN_LIMIT) break;
                }
                if (warp == 0) TSTAMP(9);
                const float xv[4] = {eb ? bf_hi(va.x) : bf_lo(va.x), eb ? bf_hi(va.z) : bf_lo(va.z),
                                     eb ? bf_hi(vb.x) : bf_lo(vb.x), eb ? bf_hi(vb.z) : bf_lo(vb.z)};
                const float p0 = 0.25f * ((bf_lo(pa.x) + bf_lo(pa.z)) + (bf_lo(pb.x) + bf_lo(pb.z)));
                const float p1 = 0.25f * ((bf_hi(pa.x) + bf_hi(pa.z)) + (bf_hi(pb.x) + bf_hi(pb.z)));
                const float pivot = eb ? p1 : p0;
                pivot2 = (lane & 1) ? p1 : p0;
                *(uint2*)&hs[eb * 32 + 2 * (lane & 15)] =
                    make_uint2(pack_bf16((xv[0] - pivot) * c1v[0], (xv[1] - pivot) * c1v[1]),
                               pack_bf16((xv[2] - pivot) * c1v[2], (xv[3] - pivot) * c1v[3]));
                __syncwarp();
                float cg[2][4] = {}, cu[2][4] = {};
#pragma unroll
                for (int s = 0; s < 4; s++) {
                    const uint32_t b0 = hs[bb * 32 + 8 * s + t], b1 = hs[bb * 32 + 8 * s + 4 + t];
                    mma16816(cg[s & 1], gf[s], b0, b1);
                    mma16816(cu[s & 1], uf[s], b0, b1);
                }
                const float2 ps = half_warp_sums(xv, pivot);
                if ((lane & 15) == 0) stat[warp * 2 + eb] = ps;
                {
                    const float* bc = (const float*)(sgen + SM_MRG + 4096);
                    mbar_wait(bar_bc, 0);
#pragma unroll
                    for (int w = 0; w < 8; w++) {
                        bg += bc[w * 128 + lane]; cgc += bc[w * 128 + 32 + lane];
                        bu += bc[w * 128 + 64 + lane]; cuc += bc[w * 128 + 96 + lane];
                    }
                }
                if (t < 2) {
                    float v[4];
#pragma unroll
                    for (int i = 0; i < 4; i++) v[i] = t ? cu[0][i] + cu[1][i] : cg[0][i] + cg[1][i];
                    *(float2*)&red[warp * 64 + t * 32 + g * 2] = make_float2(v[0], v[1]);
                    *(float2*)&red[warp * 64 + t * 32 + (g + 8) * 2] = make_float2(v[2], v[3]);
                }
            }
            uint32_t df[4][4];
            mbar_wait(bar_full + 8 * (IDX_WD % NST), (IDX_WD / NST) & 1);
#pragma unroll
            for (int mt = 0; mt < 4; mt++) ldsm4t((sbase + SM_RING + (IDX_WD % NST) * TILE + aoff) ^ (mt << 5), df[mt]);
            cons_sync();
            {
                float gs = 0.f, us = 0.f;
#pragma unroll
                for (int w = 0; w < 8; w++) { gs += red[w * 64 + lane]; us += red[w * 64 + 32 + lane]; }
                float mean_bf, rstd;
                ln_stats(stat, lane & 1, pivot2, mean_bf, rstd);
                const float dm = mean_bf - pivot2;
                gs = bf16r(rstd * (gs - dm * bg) + cgc);
                us = rstd * (us - dm * bu) + cuc;
                const float u2 = gs * (1.0f + 0.044715f * gs * gs) * (2.0f * 0.7978845608028654f * LOG2E);
                const float ge = bf16r(__fdividef(gs, 1.0f + ex2(-u2)));
                const float act = bf16r(ge * bf16r(us));
                const float a0 = __shfl_sync(0xffffffffu, act, 4 * t + bb), a1 = __shfl_sync(0xffffffffu, act, 4 * t + 2 + bb);
                const float a2 = __shfl_sync(0xffffffffu, act, 4 * t + 16 + bb), a3 = __shfl_sync(0xffffffffu, act, 4 * t + 18 + bb);
                const uint32_t b0 = pack_bf16(a0, a1), b1 = pack_bf16(a2, a3);
                float y[4][4] = {};
#pragma unroll
                for (int mt = 0; mt < 4; mt++) mma16816(y[mt], df[mt], b0, b1);
                float v[4];
#pragma unroll
                for (int i = 0; i < 4; i++) v[i] = t == 0 ? y[0][i] : t == 1 ? y[1][i] : t == 2 ? y[2][i] : y[3][i];
            {
                const bool odd = g & 1;
                const float sx = odd ? v[0] : v[2], sy = odd ? v[1] : v[3];
                const float rx = __shfl_xor_sync(0xffffffffu, sx, 4), ry = __shfl_xor_sync(0xffffffffu, sy, 4);
                const int c0 = 64 * warp + 16 * t + (odd ? g + 7 : g);
                const float e0 = odd ? rx : v[0], e1 = odd ? ry : v[1], e2 = odd ? v[2] : rx, e3 = odd ? v[3] : ry;
                st_v4(&sc->inbox_dn[c0 >> 2][cta][(c0 >> 1) & 1], tagf(e0, F_DOWN), tagf(e1, F_DOWN), tagf(e2, F_DOWN), tagf(e3, F_DOWN));
            }
            }
            if (warp == 0) TSTAMP(12);
        }
        {
            uint2 xw;
            float r0;
            {
                const uint4* pin = &sc->inbox_dn[cta][0][0] + tid;
                uint4 v = make_uint4(F_DOWN, F_DOWN, F_DOWN, F_DOWN);
                if (cta < NFFN) spin_cycles(DELAY_C);
                else while (clock32() - t_wo < DELAY_X1 + DELAY_NOFFN) {}
                xw = ld_ll2(&sc->x1[ocol]);
                bool ok = tid >= NFFN * 2;
                for (int it = 0;; it++) {
                    if (!ok) {
                        v = ld_ll4(pin);
                        ok = (v.x & v.y & v.z & v.w & 3u) == F_DOWN;
                    }
                    if (__all_sync(0xffffffffu, ok) || it > SPIN_LIMIT) break;
                }
                const bool u1 = lane & 2, u2 = lane & 4;
                const float a0 = untag(v.x), a1 = untag(v.y), a2 = untag(v.z), a3 = untag(v.w);
                const float k0 = (u1 ? a1 : a0) + __shfl_xor_sync(0xffffffffu, u1 ? a0 : a1, 2);
                const float k1 = (u1 ? a3 : a2) + __shfl_xor_sync(0xffffffffu, u1 ? a2 : a3, 2);
                r0 = (u2 ? k1 : k0) + __shfl_xor_sync(0xffffffffu, u2 ? k0 : k1, 4);
                r0 += __shfl_xor_sync(0xffffffffu, r0, 8);
                r0 += __shfl_xor_sync(0xffffffffu, r0, 16);
                if (lane < 8) red2[256 + warp * 8 + (2 * (lane & 1) + ((lane >> 2) & 1)) * 2 + ((lane >> 1) & 1)] = r0;
            }
            cons_sync();
            if (warp == 0) {
                float a0 = 0.f, a1 = 0.f;
#pragma unroll
                for (int w = 0; w < 8; w++) { const float2 v = *(const float2*)&red2[256 + w * 8 + (lane & 3) * 2]; a0 += v.x; a1 += v.y; }
                const bool hi = ocol & 1;
                const float gb0 = hi ? bf_hi(m_gb0.x) : bf_lo(m_gb0.x), gb1 = hi ? bf_hi(m_gb1.x) : bf_lo(m_gb1.x);
                for (int it = 0; !__all_sync(0xffffffffu, xw.y == F_X1) && it < SPIN_LIMIT; it++) xw = ld_ll2(&sc->x1[ocol]);
                if (lane < 4) {
                    p.out[ocol] = __float2bfloat16_rn(bf_lo(xw.x) + bf16r(gb0 * bf16r(a0)));
                    p.out[D_MODEL + ocol] = __float2bfloat16_rn(bf_hi(xw.x) + bf16r(gb1 * bf16r(a1)));
                }
                TSTAMP(13);
            }
        }
    }
}

typedef CUresult (*EncodeFn)(CUtensorMap*, CUtensorMapDataType, cuuint32_t, void*, const cuuint64_t*, const cuuint64_t*,
                             const cuuint32_t*, const cuuint32_t*, CUtensorMapInterleave, CUtensorMapSwizzle,
                             CUtensorMapL2promotion, CUtensorMapFloatOOBfill);

struct Maps { CUtensorMap k, v, wq, wmod, wmod8, wo, wg, wu, wd; };

void encode(EncodeFn fn, CUtensorMap* m, const void* ptr, int rank, const cuuint64_t* dims, const cuuint64_t* strides,
            const cuuint32_t* box, CUtensorMapSwizzle sw) {
    const cuuint32_t es[3] = {1, 1, 1};
    fn(m, CU_TENSOR_MAP_DATA_TYPE_BFLOAT16, rank, const_cast<void*>(ptr), dims, strides, box, es,
       CU_TENSOR_MAP_INTERLEAVE_NONE, sw, CU_TENSOR_MAP_L2_PROMOTION_L2_256B, CU_TENSOR_MAP_FLOAT_OOB_FILL_NONE);
}

}

extern "C" void kernel_launch(void* const* d_in, const int* in_sizes, int n_in, void* d_out, int out_size) {
    (void)in_sizes; (void)n_in; (void)out_size;
    static EncodeFn enc = nullptr;
    static Scratch* scratch = nullptr;
    if (!enc) {
        cudaGetSymbolAddress((void**)&scratch, g_scratch);
        void* fn = nullptr;
        cudaDriverEntryPointQueryResult qr;
        cudaGetDriverEntryPoint("cuTensorMapEncodeTiled", &fn, cudaEnableDefault, &qr);
        enc = (EncodeFn)fn;
        cudaFuncSetAttribute(fused_block_kernel, cudaFuncAttributeMaxDynamicSharedMemorySize, SMEM_BYTES);
    }
    Maps m;
    {
        const cuuint64_t dims[3] = {64, (cuuint64_t)16 * SK, 2}, str[2] = {256, 128};
        const cuuint32_t box[3] = {64, 64, 2};
        encode(enc, &m.k, d_in[1], 3, dims, str, box, CU_TENSOR_MAP_SWIZZLE_128B);
        encode(enc, &m.v, d_in[2], 3, dims, str, box, CU_TENSOR_MAP_SWIZZLE_128B);
    }
    {
        const cuuint64_t dims[2] = {4096, 512}, str[1] = {8192};
        const cuuint32_t box[2] = {32, 256};
        encode(enc, &m.wq, d_in[3], 2, dims, str, box, CU_TENSOR_MAP_SWIZZLE_64B);
    }
    {
        const cuuint64_t dims[2] = {N_MOD, 512}, str[1] = {N_MOD * 2};
        const cuuint32_t box[2] = {16, 256};
        encode(enc, &m.wmod, d_in[10], 2, dims, str, box, CU_TENSOR_MAP_SWIZZLE_32B);
        const cuuint32_t box8[2] = {8, 256};
        encode(enc, &m.wmod8, d_in[10], 2, dims, str, box8, CU_TENSOR_MAP_SWIZZLE_NONE);
    }
    {
        const cuuint64_t dims_o[3] = {64, 4096, 8}, dims_d[3] = {64, D_FF, 8}, str[2] = {1024, 128};
        const cuuint32_t box[3] = {64, 16, 8}, box_o[3] = {64, 64, 2};
        encode(enc, &m.wo, d_in[4], 3, dims_o, str, box_o, CU_TENSOR_MAP_SWIZZLE_128B);
        encode(enc, &m.wd, d_in[8], 3, dims_d, str, box, CU_TENSOR_MAP_SWIZZLE_128B);
    }
    {
        const cuuint64_t dims[2] = {D_FF, 512}, str[1] = {D_FF * 2};
        const cuuint32_t box[2] = {16, 128};
        encode(enc, &m.wg, d_in[6], 2, dims, str, box, CU_TENSOR_MAP_SWIZZLE_32B);
        encode(enc, &m.wu, d_in[7], 2, dims, str, box, CU_TENSOR_MAP_SWIZZLE_32B);
    }
    Params p;
    p.x = (const __nv_bfloat16*)d_in[0];
    p.c = (const __nv_bfloat16*)d_in[9];
    p.out = (__nv_bfloat16*)d_out;
    p.sc = scratch;
    fused_block_kernel<<<NCTA, NTHREADS, SMEM_BYTES, cudaStreamPerThread>>>(p, m.k, m.v, m.wq, m.wmod, m.wmod8, m.wo, m.wg, m.wu, m.wd);
}
```

```cpp
#include <cuda_runtime.h>
#include <cuda.h>
#include <cuda_bf16.h>
#include <stdint.h>

namespace {

constexpr int D_MODEL = 512;
constexpr int N_HEADS = 32;
constexpr int SK = 32768;
constexpr int DH = 128;
constexpr int D_FF = 1792;
constexpr int N_MOD = 6 * D_MODEL;

constexpr int NCTA = 128;
constexpr int NFFN = D_FF / 16;
constexpr int NOWN = 32;
constexpr int NTHREADS = 320;
constexpr int NST = 12;
constexpr int TILE = 16384;
#define WINDOW 3
#define WINDOW_TAIL 1
#define GU_WIN 3
#define CLEAR_AT 16
#define PACE_THR 96
constexpr int KV_TILES = 64;
#define MOD_AT 8
static_assert(MOD_AT % 2 == 0 && MOD_AT >= 2 && MOD_AT < 56, "schedule");
__host__ __device__ constexpr int kv_idx(int i) { return 2 + 2 * i + (i >= MOD_AT ? 1 : 0); }
constexpr int IDX_MOD = 2 + 2 * MOD_AT;
constexpr int N_STREAM = kv_idx(KV_TILES - 1) + 2;
constexpr int IDX_WO = N_STREAM;
constexpr int IDX_WG = IDX_WO + 2;
constexpr int IDX_WU = IDX_WG + 1;
constexpr int IDX_WD = IDX_WU + 1;
constexpr int SPIN_LIMIT = 1 << 20;

constexpr float LOG2E = 1.4426950408889634f;
constexpr float QK_SCALE = 0.08838834764831845f;

constexpr int SM_RING = 0;
constexpr int SM_MRG = SM_RING + NST * TILE;
constexpr int SM_ML = SM_MRG + 8 * 4 * 136 * 4;
constexpr int SM_RED = SM_ML + 8 * 4 * 8;
constexpr int SM_RED2 = SM_RED + 8 * 64 * 4;
constexpr int SM_QS = SM_RED2 + 8 * 64 * 4;
constexpr int SM_OS = SM_QS + 512 * 2;
constexpr int SM_SC = SM_OS + 2 * 128 * 2;
constexpr int SM_HS = SM_SC + 2 * 512 * 2;
constexpr int SM_STAT = SM_HS + 8 * 2 * 32 * 4;
constexpr int SM_PACE = SM_STAT + 8 * 2 * 8;
constexpr int SM_BAR = SM_PACE + 16;
constexpr int SM_END = SM_BAR + (2 * NST + 1 + 8 + 3) * 8;
constexpr int SMEM_BYTES = SM_END + 1024;

struct Scratch {
    uint4 inbox_wo[NOWN][N_HEADS][8];
    uint4 inbox_dn[NCTA][NFFN][2];
    uint2 x1[D_MODEL];
    uint2 part_o[NCTA][4][64];
    uint2 part_ml[NCTA][4][4];
    uint2 mod[2][N_MOD / 2];
    uint2 q[2][N_HEADS * DH / 2];
    unsigned epoch;
    unsigned pad_[31];
    unsigned cleared;
    unsigned pad2_[31];
    unsigned progress;
};
__device__ Scratch g_scratch;
constexpr uint32_t F_PART = 1, F_WO = 1, F_DOWN = 1, F_X1 = 1;
__device__ __forceinline__ uint32_t tagf(float v, uint32_t f) { return (__float_as_uint(v) & ~3u) | f; }
__device__ __forceinline__ float untag(uint32_t v) { return __uint_as_float(v & ~3u); }

struct Params {
    const __nv_bfloat16* x;
    const __nv_bfloat16* c;
    __nv_bfloat16* out;
    Scratch* sc;
};

#define TSTAMP(i) do { } while (0)

__device__ __forceinline__ uint32_t smem_u32(const void* p) { return (uint32_t)__cvta_generic_to_shared(p); }

__device__ __forceinline__ void mbar_init(uint32_t bar, uint32_t cnt) {
    asm volatile("mbarrier.init.shared::cta.b64 [%0], %1;" ::"r"(bar), "r"(cnt) : "memory");
}
__device__ __forceinline__ void mbar_expect_tx(uint32_t bar, uint32_t bytes) {
    asm volatile("mbarrier.arrive.expect_tx.shared::cta.b64 _, [%0], %1;" ::"r"(bar), "r"(bytes) : "memory");
}
__device__ __forceinline__ void mbar_arrive(uint32_t bar) {
    asm volatile("mbarrier.arrive.shared::cta.b64 _, [%0];" ::"r"(bar) : "memory");
}
__device__ __forceinline__ bool mbar_try(uint32_t bar, uint32_t parity) {
    uint32_t ok;
    asm volatile(
        "{\n\t.reg .pred p;\n\t"
        "mbarrier.try_wait.parity.shared::cta.b64 p, [%1], %2;\n\t"
        "selp.u32 %0, 1, 0, p;\n\t}"
        : "=r"(ok) : "r"(bar), "r"(parity) : "memory");
    return ok != 0;
}
__device__ __forceinline__ void mbar_wait(uint32_t bar, uint32_t parity) {
    if (mbar_try(bar, parity)) return;
    const long long t0 = clock64();
    while (!mbar_try(bar, parity))
        if (clock64() - t0 > (1ll << 31)) return;
}
__device__ __forceinline__ void cons_sync() { asm volatile("bar.sync 1, 256;" ::: "memory"); }

__device__ __forceinline__ void tma_2d(uint32_t dst, const CUtensorMap* m, int c0, int c1, uint32_t bar) {
    asm volatile("cp.async.bulk.tensor.2d.shared::cluster.global.mbarrier::complete_tx::bytes [%0], [%1, {%3, %4}], [%2];"
                 ::"r"(dst), "l"(m), "r"(bar), "r"(c0), "r"(c1) : "memory");
}
__device__ __forceinline__ void tma_3d(uint32_t dst, const CUtensorMap* m, int c0, int c1, int c2, uint32_t bar) {
    asm volatile("cp.async.bulk.tensor.3d.shared::cluster.global.mbarrier::complete_tx::bytes [%0], [%1, {%3, %4, %5}], [%2];"
                 ::"r"(dst), "l"(m), "r"(bar), "r"(c0), "r"(c1), "r"(c2) : "memory");
}
__device__ __forceinline__ void tma_3d_hint(uint32_t dst, const CUtensorMap* m, int c0, int c1, int c2, uint32_t bar, uint64_t pol) {
    asm volatile("cp.async.bulk.tensor.3d.shared::cluster.global.mbarrier::complete_tx::bytes.L2::cache_hint [%0], [%1, {%3, %4, %5}], [%2], %6;"
                 ::"r"(dst), "l"(m), "r"(bar), "r"(c0), "r"(c1), "r"(c2), "l"(pol) : "memory");
}
__device__ __forceinline__ void prefetch_tmap(const CUtensorMap* m) {
    asm volatile("prefetch.tensormap [%0];" ::"l"(m) : "memory");
}

__device__ __forceinline__ void ldsm4(uint32_t addr, uint32_t (&r)[4]) {
    asm volatile("ldmatrix.sync.aligned.m8n8.x4.shared.b16 {%0,%1,%2,%3}, [%4];"
                 : "=r"(r[0]), "=r"(r[1]), "=r"(r[2]), "=r"(r[3]) : "r"(addr) : "memory");
}
__device__ __forceinline__ void ldsm4t(uint32_t addr, uint32_t (&r)[4]) {
    asm volatile("ldmatrix.sync.aligned.m8n8.x4.trans.shared.b16 {%0,%1,%2,%3}, [%4];"
                 : "=r"(r[0]), "=r"(r[1]), "=r"(r[2]), "=r"(r[3]) : "r"(addr) : "memory");
}
__device__ __forceinline__ void mma16816(float (&c)[4], const uint32_t (&a)[4], uint32_t b0, uint32_t b1) {
    asm volatile("mma.sync.aligned.m16n8k16.row.col.f32.bf16.bf16.f32 {%0,%1,%2,%3}, {%4,%5,%6,%7}, {%8,%9}, {%0,%1,%2,%3};"
                 : "+f"(c[0]), "+f"(c[1]), "+f"(c[2]), "+f"(c[3])
                 : "r"(a[0]), "r"(a[1]), "r"(a[2]), "r"(a[3]), "r"(b0), "r"(b1));
}
__device__ __forceinline__ uint32_t movmatrix_t(uint32_t a) {
    uint32_t d;
    asm volatile("movmatrix.sync.aligned.m8n8.trans.b16 %0, %1;" : "=r"(d) : "r"(a));
    return d;
}
__device__ __forceinline__ uint32_t pack_bf16(float a, float b) {
    uint32_t r;
    asm("cvt.rn.bf16x2.f32 %0, %1, %2;" : "=r"(r) : "f"(b), "f"(a));
    return r;
}
__device__ __forceinline__ float bf_lo(uint32_t v) { return __uint_as_float(v << 16); }
__device__ __forceinline__ float bf_hi(uint32_t v) { return __uint_as_float(v & 0xffff0000u); }
__device__ __forceinline__ float bf16r(float a) { return bf_lo(pack_bf16(a, 0.f)); }
__device__ __forceinline__ uint32_t max_bf16x2(uint32_t a, uint32_t b) {
    uint32_t r;
    asm("max.bf16x2 %0, %1, %2;" : "=r"(r) : "r"(a), "r"(b));
    return r;
}
__device__ __forceinline__ float ex2(float x) {
    float r;
    asm("ex2.approx.ftz.f32 %0, %1;" : "=f"(r) : "f"(x));
    return r;
}

__device__ __forceinline__ void st_ll2(uint2* p, uint32_t v, uint32_t tag) {
    asm volatile("st.relaxed.gpu.global.v2.u32 [%0], {%1, %2};" ::"l"(p), "r"(v), "r"(tag) : "memory");
}
__device__ __forceinline__ void st_v4(uint4* p, uint32_t a, uint32_t b, uint32_t c, uint32_t d) {
    asm volatile("st.relaxed.gpu.global.v4.u32 [%0], {%1, %2, %3, %4};" ::"l"(p), "r"(a), "r"(b), "r"(c), "r"(d) : "memory");
}
__device__ __forceinline__ uint2 ld_ll2(const uint2* p) {
    uint2 v;
    asm volatile("ld.relaxed.gpu.global.v2.u32 {%0, %1}, [%2];" : "=r"(v.x), "=r"(v.y) : "l"(p) : "memory");
    return v;
}
__device__ __forceinline__ uint4 ld_ll4(const uint4* p) {
    uint4 v;
    asm volatile("ld.relaxed.gpu.global.v4.u32 {%0, %1, %2, %3}, [%4];"
                 : "=r"(v.x), "=r"(v.y), "=r"(v.z), "=r"(v.w) : "l"(p) : "memory");
    return v;
}

#define DELAY_P1 1800
#define DELAY_Q 1800
#define DELAY_A 1000
#define DELAY_B1 300
#define DELAY_X1 2000
#define DELAY_NOFFN 1500
#define DELAY_C 600
__device__ __forceinline__ uint32_t clock32() {
    uint32_t c;
    asm volatile("mov.u32 %0, %clock;" : "=r"(c));
    return c;
}
__device__ __forceinline__ void spin_cycles(uint32_t n) {
    if (n > 0) { const uint32_t c0 = clock32(); while (clock32() - c0 < n) {} }
}
__device__ __forceinline__ float rcp_approx(float x) {
    float r;
    asm("rcp.approx.ftz.f32 %0, %1;" : "=f"(r) : "f"(x));
    return r;
}
__device__ __forceinline__ float sqrt_approx(float x) {
    float r;
    asm("sqrt.approx.f32 %0, %1;" : "=f"(r) : "f"(x));
    return r;
}

__device__ __forceinline__ float silu_bf(float v) { return bf16r(v / (1.0f + expf(-v))); }

__device__ __forceinline__ float2 half_warp_sums(const float (&v)[4], float pivot) {
    float s1 = 0.f, s2 = 0.f;
#pragma unroll
    for (int i = 0; i < 4; i++) { const float d = v[i] - pivot; s1 += d; s2 += d * d; }
#pragma unroll
    for (int o = 1; o < 16; o <<= 1) { s1 += __shfl_xor_sync(0xffffffffu, s1, o); s2 += __shfl_xor_sync(0xffffffffu, s2, o); }
    return make_float2(s1, s2);
}
__device__ __forceinline__ void ln_stats(const float2* stat, int b, float pivot, float& mean_bf, float& rstd) {
    float s1 = 0.f, s2 = 0.f;
#pragma unroll
    for (int w = 0; w < 8; w++) { const float2 v = stat[w * 2 + b]; s1 += v.x; s2 += v.y; }
    const float dm = s1 * (1.0f / D_MODEL);
    const float var = fmaxf(s2 * (1.0f / D_MODEL) - dm * dm, 0.f);
    mean_bf = bf16r(pivot + dm);
    rstd = rcp_approx(bf16r(sqrt_approx(bf16r(bf16r(var) + 1e-5f))));
}
__device__ __forceinline__ float ln_norm(float xv, float mean_bf, float rstd) { return bf16r(bf16r(xv - mean_bf) * rstd); }
__device__ __forceinline__ float ln_mod(float n, float cmul, float sadd) { return bf16r(n * bf16r(1.0f + cmul)) + sadd; }

__global__ void __launch_bounds__(NTHREADS, 1)
fused_block_kernel(const Params p, const __grid_constant__ CUtensorMap tm_k, const __grid_constant__ CUtensorMap tm_v,
                   const __grid_constant__ CUtensorMap tm_wq, const __grid_constant__ CUtensorMap tm_wmod,
                   const __grid_constant__ CUtensorMap tm_wmod8,
                   const __grid_constant__ CUtensorMap tm_wo, const __grid_constant__ CUtensorMap tm_wg,
                   const __grid_constant__ CUtensorMap tm_wu, const __grid_constant__ CUtensorMap tm_wd) {
    extern __shared__ unsigned char smem_raw[];
    const uint32_t sbase = (smem_u32(smem_raw) + 1023u) & ~1023u;
    unsigned char* sgen = smem_raw + (sbase - smem_u32(smem_raw));
    const int tid = threadIdx.x, warp = tid >> 5, lane = tid & 31;
    const int cta = blockIdx.x;
    const uint32_t bar_full = sbase + SM_BAR, bar_empty = bar_full + NST * 8;
    const uint32_t bar_clear = bar_empty + NST * 8;
    const uint32_t bar_gu = bar_clear + 8;
    const uint32_t bar_bc = bar_gu + 8 * 8;
    const uint32_t bar_p0w = bar_bc + 8;
    const uint32_t bar_gate = bar_p0w + 8;

    const int key0 = (cta >> 3) * SK + (cta & 7) * 64;
    uint64_t pol = 0;
    if (tid == 256) {
        asm volatile("createpolicy.fractional.L2::evict_first.b64 %0, 1.0;" : "=l"(pol));
        mbar_init(bar_p0w, 1);
#pragma unroll
        for (int i = 0; i < 4; i++) mbar_init(bar_full + 8 * i, 1);
        asm volatile("fence.mbarrier_init.release.cluster;" ::: "memory");
        mbar_expect_tx(bar_p0w, 8192);
        tma_2d(sbase + SM_MRG, &tm_wmod8, cta * 8, 0, bar_p0w);
        tma_2d(sbase + SM_MRG + 4096, &tm_wmod8, cta * 8, 256, bar_p0w);
#pragma unroll
        for (int i = 0; i < 4; i++) mbar_expect_tx(bar_full + 8 * i, TILE);
        tma_2d(sbase + SM_RING, &tm_wq, cta * 32, 0, bar_full);
        tma_2d(sbase + SM_RING + TILE, &tm_wq, cta * 32, 256, bar_full + 8);
        tma_3d_hint(sbase + SM_RING + 2 * TILE, &tm_k, 0, key0, 0, bar_full + 16, pol);
        tma_3d_hint(sbase + SM_RING + 3 * TILE, &tm_v, 0, key0, 0, bar_full + 24, pol);
    }

    if (warp == 8) {
        if (lane == 0) {
            for (int i = 0; i < NST; i++) { if (i >= 4) mbar_init(bar_full + 8 * i, 1); mbar_init(bar_empty + 8 * i, 4); }
            mbar_init(bar_clear, 1);
            for (int k = 0; k < 8; k++) mbar_init(bar_gu + 8 * k, 1);
            mbar_init(bar_bc, 8);
            mbar_init(bar_gate, 1);
            ((volatile uint32_t*)(sgen + SM_PACE))[0] = 0;
            ((volatile uint32_t*)(sgen + SM_PACE))[1] = WINDOW;
            asm volatile("fence.mbarrier_init.release.cluster;" ::: "memory");
        }
        __syncwarp();
        asm volatile("bar.arrive 2, 288;" ::: "memory");
        asm volatile("bar.arrive 3, 64;" ::: "memory");
        if (lane == 0) {
            int slot = 4; uint32_t ph = 1;
            int landed = 0, wslot = 0; uint32_t wph = 0;
            int kv = 2;
            auto wait_window = [&](int idx, int window) {
                while (landed + window <= idx) {
                    mbar_wait(bar_full + 8 * wslot, wph);
                    if (++wslot == NST) { wslot = 0; wph ^= 1; }
                    landed++;
                }
            };
            volatile uint32_t* pace = (volatile uint32_t*)(sgen + SM_PACE);
            prefetch_tmap(&tm_wmod);
            pace[0] = 4;
            for (int idx = 4; idx < N_STREAM; idx++) {
                if (idx >= NST) mbar_wait(bar_empty + 8 * slot, ph);
                wait_window(idx, (int)pace[1]);
                if (idx == 12) { prefetch_tmap(&tm_wo); prefetch_tmap(&tm_wg); prefetch_tmap(&tm_wu); prefetch_tmap(&tm_wd); }
                const uint32_t fb = bar_full + 8 * slot, dst = sbase + SM_RING + slot * TILE;
                mbar_expect_tx(fb, TILE);
                if (idx == IDX_MOD) {
                    tma_2d(dst, &tm_wmod, 1024 + cta * 16, 0, fb);
                    tma_2d(dst + 8192, &tm_wmod, 1024 + cta * 16, 256, fb);
                } else {
                    tma_3d_hint(dst, (kv & 1) ? &tm_v : &tm_k, 0, key0 + (kv >> 1) * 512, 0, fb, pol);
                    kv++;
                }
                pace[0] = idx + 1;
                if (++slot == NST) { slot = 0; ph ^= 1; }
            }
            auto slot_free = [&](int idx) { mbar_wait(bar_empty + 8 * (idx % NST), ((idx / NST) & 1) ^ 1); };
#pragma unroll
            for (int s = 0; s < 2; s++) {
                const int idx = IDX_WO + s;
                slot_free(idx);
                wait_window(idx, WINDOW_TAIL);
                mbar_expect_tx(bar_full + 8 * (idx % NST), TILE);
                tma_3d(sbase + SM_RING + (idx % NST) * TILE, &tm_wo, 0, (cta >> 2) * 128 + s * 64, (cta & 3) * 2, bar_full + 8 * (idx % NST));
            }
            if (cta < NFFN) {
                slot_free(IDX_WG); slot_free(IDX_WU);
                mbar_wait(bar_full + 8 * (IDX_WO % NST), (IDX_WO / NST) & 1);
                mbar_wait(bar_full + 8 * ((IDX_WO + 1) % NST), ((IDX_WO + 1) / NST) & 1);
#pragma unroll
                for (int st = 0; st < 8; st++) {
                    if (st >= GU_WIN) mbar_wait(bar_gu + 8 * (st - GU_WIN), 0);
                    mbar_expect_tx(bar_gu + 8 * st, 4096);
                    tma_2d(sbase + SM_RING + (((st & 1) ? IDX_WU : IDX_WG) % NST) * TILE + (st >> 1) * 4096,
                           (st & 1) ? &tm_wu : &tm_wg, cta * 16, (st >> 1) * 128, bar_gu + 8 * st);
                }
                mbar_wait(bar_gu + 8 * 6, 0);
                slot_free(IDX_WD);
                mbar_expect_tx(bar_full + 8 * (IDX_WD % NST), TILE);
                tma_3d(sbase + SM_RING + (IDX_WD % NST) * TILE, &tm_wd, 0, cta * 16, 0, bar_full + 8 * (IDX_WD % NST));
            }
        }
    } else if (warp == 9) {
        Scratch* const sc = p.sc;
        const uint32_t tag = *(volatile unsigned*)&sc->epoch + 1;
        asm volatile("bar.sync 3, 64;" ::: "memory");
        volatile uint32_t* pace = (volatile uint32_t*)(sgen + SM_PACE);
        const uint32_t base = (tag - 1) * (uint32_t)(NCTA * N_STREAM);
        uint32_t posted = 0;
        int stage = 0;
        for (int it = 0; it < SPIN_LIMIT; it++) {
            const uint32_t own = __shfl_sync(0xffffffffu, pace[0], 0);
            if (stage == 0 && own >= CLEAR_AT) {
#pragma unroll 4
                for (int i = 0; i < NFFN * 2 / 32; i++) st_v4(&sc->inbox_dn[cta][0][0] + i * 32 + lane, 0u, 0u, 0u, 0u);
                if (cta >= NCTA - NOWN) {
#pragma unroll 4
                    for (int i = 0; i < 8; i++) st_v4(&sc->inbox_wo[cta - (NCTA - NOWN)][0][0] + i * 32 + lane, 0u, 0u, 0u, 0u);
                    if (lane < 8) st_v4((uint4*)&sc->x1[(cta - (NCTA - NOWN)) * 16] + lane, 0u, 0u, 0u, 0u);
                }
#pragma unroll 4
                for (int i = 0; i < 4; i++) st_v4((uint4*)&sc->part_o[cta][0][0] + i * 32 + lane, 0u, 0u, 0u, 0u);
                if (lane < 8) st_v4((uint4*)&sc->part_ml[cta][0][0] + lane, 0u, 0u, 0u, 0u);
                asm volatile("fence.acq_rel.gpu;" ::: "memory");
                __syncwarp();
                if (lane == 0) {
                    asm volatile("fence.acq_rel.gpu;" ::: "memory");
                    asm volatile("red.relaxed.gpu.global.add.u32 [%0], %1;" ::"l"(&sc->cleared), "r"(1u) : "memory");
                }
                stage = 1;
            }
            int done = 0;
            if (lane == 0) {
                if (own > posted) {
                    asm volatile("red.relaxed.gpu.global.add.u32 [%0], %1;" ::"l"(&sc->progress), "r"(own - posted) : "memory");
                    posted = own;
                }
                uint32_t v;
                asm volatile("ld.relaxed.gpu.global.u32 %0, [%1];" : "=r"(v) : "l"(&sc->progress) : "memory");
                v -= base;
                if (stage == 1 && own >= 2 * CLEAR_AT) {
                    uint32_t c;
                    asm volatile("ld.relaxed.gpu.global.u32 %0, [%1];" : "=r"(c) : "l"(&sc->cleared) : "memory");
                    if ((int32_t)(c - tag * NCTA) >= 0) {
                        asm volatile("fence.acq_rel.gpu;" ::: "memory");
                        mbar_arrive(bar_clear);
                        done = 2;
                    }
                }
                if (own >= N_STREAM) {
                    if (v >= NCTA * N_STREAM && (stage == 2 || done == 2)) done |= 1;
                } else {
                    const int diff = (int)v - (int)own * NCTA;
                    pace[1] = diff > PACE_THR ? WINDOW + 1 : diff < -PACE_THR ? WINDOW - 1 : WINDOW;
                }
                __nanosleep(200);
            }
            done = __shfl_sync(0xffffffffu, done, 0);
            if (done & 2) stage = 2;
            if (done & 1) break;
        }
        if (lane == 0) {
            pace[2] = clock32();
            mbar_arrive(bar_gate);
            if (cta == 0) asm volatile("st.relaxed.gpu.global.u32 [%0], %1;" ::"l"(&sc->epoch), "r"(tag) : "memory");
        }
    } else {
        const int g = lane >> 2, t = lane & 3;
        const int bb = g & 1;
        const int eb = lane >> 4;
        const int ec = 64 * warp + 4 * (lane & 15);
        if (warp == 0) TSTAMP(0);
        Scratch* const sc = p.sc;
        const float c00 = __bfloat162float(p.c[tid]), c01 = __bfloat162float(p.c[tid + 256]);
        const float c10 = __bfloat162float(p.c[D_MODEL + tid]), c11 = __bfloat162float(p.c[D_MODEL + tid + 256]);
        const uint2 xe = __ldg((const uint2*)(p.x + eb * D_MODEL + ec));
        const float xpivot = __bfloat162float(p.x[eb * D_MODEL]);
        const uint32_t tag = *(volatile unsigned*)&sc->epoch + 1;
        const int ocol = cta * 4 + (lane & 3);
        const int wcol = (cta >= NCTA - NOWN ? cta - (NCTA - NOWN) : 0) * 16 + (lane & 15);
        const float xo = __bfloat162float(p.x[eb * D_MODEL + wcol]);

        float* red = (float*)(sgen + SM_RED);
        float* red2 = (float*)(sgen + SM_RED2);
        float2* stat = (float2*)(sgen + SM_STAT);
        uint32_t* hs = (uint32_t*)(sgen + SM_HS) + warp * 64;
        float xn[4];
        {
            float xv[4] = {bf_lo(xe.x), bf_hi(xe.x), bf_lo(xe.y), bf_hi(xe.y)};
            const float2 ps = half_warp_sums(xv, xpivot);
            if ((lane & 15) == 0) stat[warp * 2 + eb] = ps;
            const float s00 = silu_bf(c00), s01 = silu_bf(c01), s10 = silu_bf(c10), s11 = silu_bf(c11);
            __nv_bfloat16* scs = (__nv_bfloat16*)(sgen + SM_SC);
            scs[tid] = __float2bfloat16_rn(s00); scs[tid + 256] = __float2bfloat16_rn(s01);
            scs[512 + tid] = __float2bfloat16_rn(s10); scs[512 + tid + 256] = __float2bfloat16_rn(s11);
            asm volatile("bar.sync 2, 288;" ::: "memory");
            if (warp == 0) TSTAMP(23);
            float cp[4] = {0.f, 0.f, 0.f, 0.f};
            const uint32_t* sc32 = (const uint32_t*)(sgen + SM_SC) + bb * 256 + 32 * warp + t;
            mbar_wait(bar_p0w, 0);
#pragma unroll
            for (int s = 0; s < 4; s++) {
                uint32_t r0, r1;
                asm volatile("ldmatrix.sync.aligned.m8n8.x2.trans.shared.b16 {%0,%1}, [%2];"
                             : "=r"(r0), "=r"(r1) : "r"(sbase + SM_MRG + (64 * warp + 16 * s + (lane & 15)) * 16) : "memory");
                const uint32_t a[4] = {r0, r0, r1, r1};
                mma16816(cp, a, sc32[8 * s], sc32[8 * s + 4]);
            }
            if (t == 0) { red[warp * 16 + g] = cp[0]; red[warp * 16 + 8 + g] = cp[1]; }
            if (warp == 0) TSTAMP(14);
            cons_sync();
            if (warp == 0) {
                float s = 0.f;
#pragma unroll
                for (int w = 0; w < 8; w++) s += red[w * 16 + (lane & 15)];
                const float nx = __shfl_down_sync(0xffffffffu, s, 1);
                if (lane < 16 && !(lane & 1))
                    st_ll2(&sc->mod[lane >> 3][cta * 4 + ((lane & 7) >> 1)], pack_bf16(s, nx), tag);
                TSTAMP(1);
            }
            float mean_bf, rstd;
            ln_stats(stat, eb, xpivot, mean_bf, rstd);
#pragma unroll
            for (int i = 0; i < 4; i++) xn[i] = ln_norm(xv[i], mean_bf, rstd);
        }
        {
            uint4 sa, ca;
            spin_cycles(DELAY_P1);
            for (int it = 0;; it++) {
                sa = ld_ll4((const uint4*)&sc->mod[eb][ec >> 1]);
                ca = ld_ll4((const uint4*)&sc->mod[eb][256 + (ec >> 1)]);
                const bool ok = sa.y == tag && sa.w == tag && ca.y == tag && ca.w == tag;
                if (__all_sync(0xffffffffu, ok) || it > SPIN_LIMIT) break;
            }
            *(uint2*)&hs[eb * 32 + 2 * (lane & 15)] =
                make_uint2(pack_bf16(ln_mod(xn[0], bf_lo(ca.x), bf_lo(sa.x)), ln_mod(xn[1], bf_hi(ca.x), bf_hi(sa.x))),
                           pack_bf16(ln_mod(xn[2], bf_lo(ca.z), bf_lo(sa.z)), ln_mod(xn[3], bf_hi(ca.z), bf_hi(sa.z))));
            __syncwarp();
            uint32_t hb[8];
#pragma unroll
            for (int i = 0; i < 8; i++) hb[i] = hs[bb * 32 + 8 * (i >> 1) + 4 * (i & 1) + t];
            if (warp == 0) TSTAMP(2);
            float cq[2][4] = {};
            const int ts = warp >> 2;
            mbar_wait(bar_full + 8 * ts, 0);
            const uint32_t tb = sbase + SM_RING + ts * TILE;
#pragma unroll
            for (int s = 0; s < 4; s++) {
                const int row = 64 * (warp & 3) + 16 * s + (lane & 7) + (lane >> 4) * 8;
#pragma unroll
                for (int mt = 0; mt < 2; mt++) {
                    const int ch = 2 * mt + ((lane >> 3) & 1);
                    uint32_t a[4];
                    ldsm4t(tb + row * 64 + ((ch ^ ((row >> 1) & 3)) << 4), a);
                    mma16816(cq[mt], a, hb[2 * s], hb[2 * s + 1]);
                }
            }
            if (t < 2) {
                const float v0 = t == 0 ? cq[0][0] : cq[1][0], v1 = t == 0 ? cq[0][1] : cq[1][1];
                const float v2 = t == 0 ? cq[0][2] : cq[1][2], v3 = t == 0 ? cq[0][3] : cq[1][3];
                *(float2*)&red2[warp * 64 + (16 * t + g) * 2] = make_float2(v0, v1);
                *(float2*)&red2[warp * 64 + (16 * t + g + 8) * 2] = make_float2(v2, v3);
            }
            cons_sync();
            if (warp < 4 && lane == 0) { mbar_arrive(bar_empty); mbar_arrive(bar_empty + 8); }
            if (warp == 0) {
                const int b = lane >> 4, cp = lane & 15;
                float q0 = 0.f, q1 = 0.f;
#pragma unroll
                for (int w = 0; w < 8; w++) {
                    const float4 v = *(const float4*)&red2[w * 64 + cp * 4];
                    q0 += b ? v.y : v.x; q1 += b ? v.w : v.z;
                }
                st_ll2(&sc->q[b][cta * 16 + cp], pack_bf16(q0, q1), tag);
                TSTAMP(3);
            }
        }
        const int pair = cta >> 3;
        uint32_t qf[16];
        {
            uint2* qs = (uint2*)(sgen + SM_QS);
            if (tid < 128) {
                const uint4* src = (const uint4*)&sc->q[pair >> 3][(pair & 7) * 256] + tid;
                uint4 v;
                spin_cycles(DELAY_Q);
                for (int it = 0;; it++) {
                    v = ld_ll4(src);
                    if ((v.y == tag && v.w == tag) || it > SPIN_LIMIT) break;
                }
                qs[tid] = make_uint2(v.x, v.z);
            }
            cons_sync();
            const uint32_t* q32 = (const uint32_t*)(sgen + SM_QS);
#pragma unroll
            for (int s = 0; s < 8; s++) {
                qf[2 * s] = q32[(g & 3) * 64 + 8 * s + t];
                qf[2 * s + 1] = q32[(g & 3) * 64 + 8 * s + 4 + t];
            }
        }
        if (warp == 0) TSTAMP(4);

        float o[8][4];
#pragma unroll
        for (int i = 0; i < 8; i++) { o[i][0] = o[i][1] = o[i][2] = o[i][3] = 0.f; }
        uint32_t mrun = 0xff80ff80u;
        float ls[4] = {0.f, 0.f, 0.f, 0.f};
        uint4 m_sb, m_cb; uint2 m_ga, m_gb0, m_gb1;
        {
            const int grp = warp >> 2, wi = warp & 3;
            const int krow = 16 * wi + (lane & 7) + ((lane >> 3) & 1) * 8;
            const uint32_t koff = krow * 128 + ((((lane >> 4) & 1) ^ (lane & 7)) << 4);
            const int vrow = 16 * wi + (lane & 7) + (lane >> 4) * 8;
            const uint32_t voff = vrow * 128 + ((((lane >> 3) & 1) ^ (lane & 7)) << 4);
            const uint32_t ones[4] = {0x3f803f80u, 0x3f803f80u, 0x3f803f80u, 0x3f803f80u};
            for (int i = grp; i < KV_TILES; i += 2) {
                if (i == MOD_AT + grp) {
                    float cm[4] = {};
                    const uint32_t* sc32 = (const uint32_t*)(sgen + SM_SC) + bb * 256 + 32 * warp + t;
                    mbar_wait(bar_full + 8 * (IDX_MOD % NST), (IDX_MOD / NST) & 1);
                    const uint32_t tb = sbase + SM_RING + (IDX_MOD % NST) * TILE;
#pragma unroll
                    for (int s = 0; s < 4; s++) {
                        const int row = 64 * warp + 16 * s + (lane & 7) + (lane >> 4) * 8;
                        const int ch = (lane >> 3) & 1;
                        uint32_t a[4];
                        ldsm4t(tb + row * 32 + ((ch ^ ((row >> 2) & 1)) << 4), a);
                        mma16816(cm, a, sc32[8 * s], sc32[8 * s + 4]);
                    }
                    if (t == 0) {
                        *(float2*)&red[warp * 64 + g * 2] = make_float2(cm[0], cm[1]);
                        *(float2*)&red[warp * 64 + (g + 8) * 2] = make_float2(cm[2], cm[3]);
                    }
                    cons_sync();
                    if (warp < 4 && lane == 0) mbar_arrive(bar_empty + 8 * (IDX_MOD % NST));
                    if (warp == 1 && lane < 16) {
                        const int b = lane >> 3, cp = lane & 7;
                        float q0 = 0.f, q1 = 0.f;
#pragma unroll
                        for (int w = 0; w < 8; w++) {
                            const float4 v = *(const float4*)&red[w * 64 + cp * 4];
                            q0 += b ? v.y : v.x; q1 += b ? v.w : v.z;
                        }
                        st_ll2(&sc->mod[b][512 + cta * 8 + cp], pack_bf16(q0, q1), tag);
                    }
                }
                if (i == 56 + grp) {
                    m_sb = ld_ll4((const uint4*)&sc->mod[eb][768 + (ec >> 1)]);
                    m_cb = ld_ll4((const uint4*)&sc->mod[eb][1024 + (ec >> 1)]);
                    m_ga = ld_ll2(&sc->mod[eb][512 + (wcol >> 1)]);
                    m_gb0 = ld_ll2(&sc->mod[0][1280 + (ocol >> 1)]); m_gb1 = ld_ll2(&sc->mod[1][1280 + (ocol >> 1)]);
                }
                if (i == 60 + grp) {
                    for (int it = 0;; it++) {
                        const bool ok = m_sb.y == tag && m_sb.w == tag && m_cb.y == tag && m_cb.w == tag &&
                                        m_ga.y == tag && m_gb0.y == tag && m_gb1.y == tag;
                        if (__all_sync(0xffffffffu, ok) || it > SPIN_LIMIT) break;
                        m_sb = ld_ll4((const uint4*)&sc->mod[eb][768 + (ec >> 1)]);
                        m_cb = ld_ll4((const uint4*)&sc->mod[eb][1024 + (ec >> 1)]);
                        m_ga = ld_ll2(&sc->mod[eb][512 + (wcol >> 1)]);
                        m_gb0 = ld_ll2(&sc->mod[0][1280 + (ocol >> 1)]); m_gb1 = ld_ll2(&sc->mod[1][1280 + (ocol >> 1)]);
                    }
                    mbar_wait(bar_clear, 0);
                }
                const int ki = kv_idx(i), ks = ki % NST, vs = (ki + 1) % NST;
                const uint32_t kph = (ki / NST) & 1, vph = ((ki + 1) / NST) & 1;
                mbar_wait(bar_full + 8 * ks, kph);
                const uint32_t kb = sbase + SM_RING + ks * TILE + koff;
                float sa[4] = {0.f, 0.f, 0.f, 0.f}, sb[4] = {0.f, 0.f, 0.f, 0.f};
#pragma unroll
                for (int s = 0; s < 8; s += 2) {
                    uint32_t a0[4], a1[4];
                    ldsm4((kb ^ ((s & 3) << 5)) + (s >> 2) * 8192, a0);
                    ldsm4((kb ^ (((s + 1) & 3) << 5)) + (s >> 2) * 8192, a1);
                    mma16816(sa, a0, qf[2 * s], qf[2 * s + 1]);
                    mma16816(sb, a1, qf[2 * s + 2], qf[2 * s + 3]);
                }
                __syncwarp();
                if (lane == 0) mbar_arrive(bar_empty + 8 * ks);
                uint32_t r01 = pack_bf16(sa[0] + sb[0], sa[1] + sb[1]);
                uint32_t r23 = pack_bf16(sa[2] + sb[2], sa[3] + sb[3]);
                r01 = pack_bf16(bf_lo(r01) * QK_SCALE, bf_hi(r01) * QK_SCALE);
                r23 = pack_bf16(bf_lo(r23) * QK_SCALE, bf_hi(r23) * QK_SCALE);
                uint32_t mx = max_bf16x2(r01, r23);
                mx = max_bf16x2(mx, __shfl_xor_sync(0xffffffffu, mx, 4));
                mx = max_bf16x2(mx, __shfl_xor_sync(0xffffffffu, mx, 8));
                mx = max_bf16x2(mx, __shfl_xor_sync(0xffffffffu, mx, 16));
                const uint32_t mnew = max_bf16x2(mrun, mx);
                const float m0 = bf_lo(mnew), m1 = bf_hi(mnew);
                if (__any_sync(0xffffffffu, mnew != mrun)) {
                    const float al0 = ex2((bf_lo(mrun) - m0) * LOG2E), al1 = ex2((bf_hi(mrun) - m1) * LOG2E);
                    ls[0] *= al0; ls[1] *= al1;
#pragma unroll
                    for (int d = 0; d < 8; d++) { o[d][0] *= al0; o[d][1] *= al1; o[d][2] *= al0; o[d][3] *= al1; }
                    mrun = mnew;
                }
                const float p0 = ex2((bf_lo(r01) - m0) * LOG2E), p1 = ex2((bf_hi(r01) - m1) * LOG2E);
                const float p2 = ex2((bf_lo(r23) - m0) * LOG2E), p3 = ex2((bf_hi(r23) - m1) * LOG2E);
                const uint32_t pb0 = movmatrix_t(pack_bf16(p0, p1)), pb1 = movmatrix_t(pack_bf16(p2, p3));
                mma16816(ls, ones, pb0, pb1);
                mbar_wait(bar_full + 8 * vs, vph);
                const uint32_t vb = sbase + SM_RING + vs * TILE + voff;
#pragma unroll
                for (int d = 0; d < 8; d++) {
                    uint32_t a[4];
                    ldsm4t((vb ^ ((d & 3) << 5)) + (d >> 2) * 8192, a);
                    mma16816(o[d], a, pb0, pb1);
                }
                __syncwarp();
                if (lane == 0) mbar_arrive(bar_empty + 8 * vs);
            }
        }
        if (warp == 7) TSTAMP(5);
        {
            float* mrg = (float*)(sgen + SM_MRG);
            float2* ml = (float2*)(sgen + SM_ML);
            {
                const int hp = (t & 1) * 2, up = t >> 1;
                if (g == 0 && up == 0) { ml[warp * 4 + hp] = make_float2(bf_lo(mrun), ls[0]); ml[warp * 4 + hp + 1] = make_float2(bf_hi(mrun), ls[1]); }
                float* m0p = mrg + (warp * 4 + hp) * 136 + up * 72 + g;
#pragma unroll
                for (int d = 0; d < 4; d++) {
                    m0p[16 * d] = up ? o[d + 4][0] : o[d][0]; m0p[136 + 16 * d] = up ? o[d + 4][1] : o[d][1];
                    m0p[16 * d + 8] = up ? o[d + 4][2] : o[d][2]; m0p[136 + 16 * d + 8] = up ? o[d + 4][3] : o[d][3];
                }
            }
            cons_sync();
            const int hh = tid >> 6, dp = tid & 63;
            float2 mw[8];
            float M = -INFINITY;
#pragma unroll
            for (int w = 0; w < 8; w++) { mw[w] = ml[w * 4 + hh]; M = fmaxf(M, mw[w].x); }
            float L = 0.f, o0 = 0.f, o1 = 0.f;
#pragma unroll
            for (int w = 0; w < 8; w++) {
                const float wt = ex2((mw[w].x - M) * LOG2E);
                const float2 v = *(const float2*)&mrg[(w * 4 + hh) * 136 + 2 * dp + (dp >= 32 ? 8 : 0)];
                L += wt * mw[w].y; o0 += wt * v.x; o1 += wt * v.y;
            }
            st_ll2(&sc->part_o[cta][hh][dp], tagf(o0, F_PART), tagf(o1, F_PART));
            if (dp < 4) st_ll2(&sc->part_ml[cta][hh][dp], tagf(M, F_PART), tagf(L, F_PART));
        }
        if (warp == 0) TSTAMP(6);
        {
            const int hq = cta >> 2, kvh = hq >> 2, hh = hq & 3;
            const int b = tid >> 7, dc = (tid >> 3) & 15, j = tid & 7;
            const int pc = (b * 8 + kvh) * 8 + j;
            const uint4* po = (const uint4*)&sc->part_o[pc][hh][0] + dc * 2;
            const uint2* pm = &sc->part_ml[pc - j][hh][0];
            uint4 vo0, vo1; uint2 vm[8];
            mbar_wait(bar_gate, 0);
            { const uint32_t tg = ((volatile uint32_t*)(sgen + SM_PACE))[2]; while (clock32() - tg < DELAY_A) {} }
            bool oko = false;
#pragma unroll
            for (int jj = 0; jj < 8; jj++) vm[jj] = make_uint2(0u, 0u);
            for (int it = 0;; it++) {
                if (!oko) { vo0 = ld_ll4(po); vo1 = ld_ll4(po + 1); }
#pragma unroll
                for (int jj = 0; jj < 8; jj++)
                    if ((vm[jj].x & vm[jj].y & 3u) != F_PART) vm[jj] = ld_ll2(pm + jj * 16);
                oko = (vo0.x & vo0.y & vo0.z & vo0.w & vo1.x & vo1.y & vo1.z & vo1.w & 3u) == F_PART;
                uint32_t all = vm[0].x & vm[0].y;
#pragma unroll
                for (int jj = 1; jj < 8; jj++) all &= vm[jj].x & vm[jj].y;
                if (__all_sync(0xffffffffu, oko && (all & 3u) == F_PART) || it > SPIN_LIMIT) break;
            }
            float M = untag(vm[0].x);
#pragma unroll
            for (int jj = 1; jj < 8; jj++) M = fmaxf(M, untag(vm[jj].x));
            float wt = 0.f, L = 0.f;
#pragma unroll
            for (int jj = 0; jj < 8; jj++) {
                const float w_ = ex2((untag(vm[jj].x) - M) * LOG2E);
                L += w_ * untag(vm[jj].y);
                wt = jj == j ? w_ : wt;
            }
            wt *= rcp_approx(L);
            float v[8] = {wt * untag(vo0.x), wt * untag(vo0.y), wt * untag(vo0.z), wt * untag(vo0.w),
                          wt * untag(vo1.x), wt * untag(vo1.y), wt * untag(vo1.z), wt * untag(vo1.w)};
#define XRED(N, O)                                                                       \
            {                                                                            \
                const bool up = lane & (O);                                              \
                _Pragma("unroll") for (int i = 0; i < (N); i++) {                        \
                    const float send = up ? v[i] : v[i + (N)], keep = up ? v[i + (N)] : v[i]; \
                    v[i] = keep + __shfl_xor_sync(0xffffffffu, send, (O));               \
                }                                                                        \
            }
            XRED(4, 1) XRED(2, 2) XRED(1, 4)
#undef XRED
            __nv_bfloat16* os = (__nv_bfloat16*)(sgen + SM_OS);
            os[b * 128 + dc * 8 + 4 * (j & 1) + 2 * ((j >> 1) & 1) + (j >> 2)] = __float2bfloat16_rn(v[0]);
            if (warp == 0) TSTAMP(15);
            uint32_t wf[8][4];
            const uint32_t aoff_o = (warp >> 2) * 8192 + ((lane & 7) + (lane >> 4) * 8) * 128 +
                                    (((((warp & 3) * 2 + ((lane >> 3) & 1)) ^ (lane & 7))) << 4);
#pragma unroll
            for (int s = 0; s < 2; s++) {
                const int idx = IDX_WO + s;
                mbar_wait(bar_full + 8 * (idx % NST), (idx / NST) & 1);
                const uint32_t tb = sbase + SM_RING + (idx % NST) * TILE + aoff_o;
#pragma unroll
                for (int k4 = 0; k4 < 4; k4++) ldsm4t(tb + k4 * 2048, wf[s * 4 + k4]);
            }
            cons_sync();
            if (warp == 0) TSTAMP(7);
            const uint32_t* os32 = (const uint32_t*)(sgen + SM_OS) + bb * 64 + t;
            float y0[4] = {}, y1[4] = {};
#pragma unroll
            for (int ks = 0; ks < 8; ks += 2) {
                mma16816(y0, wf[ks], os32[8 * ks], os32[8 * ks + 4]);
                mma16816(y1, wf[ks + 1], os32[8 * ks + 8], os32[8 * ks + 12]);
            }
            if (t == 0)
                st_v4(&sc->inbox_wo[(cta & 3) * 8 + warp][hq][g], tagf(y0[0] + y1[0], F_WO), tagf(y0[1] + y1[1], F_WO),
                      tagf(y0[2] + y1[2], F_WO), tagf(y0[3] + y1[3], F_WO));
        }
        const uint32_t t_wo = clock32();
        if (warp == 0) TSTAMP(8);
        if (cta >= NCTA - NOWN) {
            const uint4* pin = &sc->inbox_wo[cta - (NCTA - NOWN)][0][0] + tid;
            uint4 v;
            spin_cycles(DELAY_B1);
            bool ok = false;
            for (int it = 0;; it++) {
                if (!ok) {
                    v = ld_ll4(pin);
                    ok = (v.x & v.y & v.z & v.w & 3u) == F_WO;
                }
                if (__all_sync(0xffffffffu, ok) || it > SPIN_LIMIT) break;
            }
            const bool u1 = lane & 8, u2 = lane & 16;
            const float a0 = untag(v.x), a1 = untag(v.y), a2 = untag(v.z), a3 = untag(v.w);
            const float k0 = (u1 ? a2 : a0) + __shfl_xor_sync(0xffffffffu, u1 ? a0 : a2, 8);
            const float k1 = (u1 ? a3 : a1) + __shfl_xor_sync(0xffffffffu, u1 ? a1 : a3, 8);
            red2[warp * 32 + lane] = (u2 ? k1 : k0) + __shfl_xor_sync(0xffffffffu, u2 ? k0 : k1, 16);
            cons_sync();
            if (warp == 0) {
                float a = 0.f;
#pragma unroll
                for (int w = 0; w < 8; w++) a += red2[w * 32 + lane];
                const float ga = (wcol & 1) ? bf_hi(m_ga.x) : bf_lo(m_ga.x);
                const float xm = bf16r(xo + bf16r(ga * bf16r(a)));
                const float xm_b1 = __shfl_down_sync(0xffffffffu, xm, 16);
                if (lane < 16) st_ll2(&sc->x1[wcol], pack_bf16(xm, xm_b1), F_X1);
                TSTAMP(10);
            }
        }
        const uint32_t aoff = warp * 2048 + ((lane & 7) + (lane >> 4) * 8) * 128 + ((((lane >> 3) & 1) ^ (lane & 7)) << 4);
        if (cta < NFFN) {
            const uint4* px = (const uint4*)&sc->x1[ec];
            const uint4* pp = (const uint4*)&sc->x1[0];
            uint4 va, vb, pa, pb;
            uint32_t gf[4][4], uf[4][4];
            mbar_wait(bar_gu + 8 * (2 * (warp >> 1)), 0);
            mbar_wait(bar_gu + 8 * (2 * (warp >> 1) + 1), 0);
            {
                const uint32_t tg = sbase + SM_RING + (IDX_WG % NST) * TILE, tu = sbase + SM_RING + (IDX_WU % NST) * TILE;
#pragma unroll
                for (int s = 0; s < 4; s++) {
                    const int row = 64 * warp + 16 * s + (lane & 7) + (lane >> 4) * 8;
                    const uint32_t off = row * 32 + ((((lane >> 3) & 1) ^ ((row >> 2) & 1)) << 4);
                    ldsm4t(tg + off, gf[s]);
                    ldsm4t(tu + off, uf[s]);
                }
            }
            const float c1v[4] = {bf16r(1.0f + bf_lo(m_cb.x)), bf16r(1.0f + bf_hi(m_cb.x)), bf16r(1.0f + bf_lo(m_cb.z)), bf16r(1.0f + bf_hi(m_cb.z))};
            float bg = 0.f, cgc = 0.f, bu = 0.f, cuc = 0.f;
            {
                uint32_t* pre = (uint32_t*)(sgen + SM_MRG) + warp * 128;
                float* bc = (float*)(sgen + SM_MRG + 4096);
                *(uint2*)&pre[eb * 32 + 2 * (lane & 15)] = make_uint2(pack_bf16(c1v[0], c1v[1]), pack_bf16(c1v[2], c1v[3]));
                *(uint2*)&pre[64 + eb * 32 + 2 * (lane & 15)] = make_uint2(m_sb.x, m_sb.z);
                __syncwarp();
                float yg[4] = {}, yu[4] = {};
                const uint32_t* pb = pre + ((g >> 1) & 1) * 64 + bb * 32 + t;
#pragma unroll
                for (int s = 0; s < 4; s++) {
                    const uint32_t b0 = pb[8 * s], b1 = pb[8 * s + 4];
                    mma16816(yg, gf[s], b0, b1);
                    mma16816(yu, uf[s], b0, b1);
                }
                const float y0 = t < 2 ? yg[0] : yu[0], y1 = t < 2 ? yg[1] : yu[1], y2 = t < 2 ? yg[2] : yu[2], y3 = t < 2 ? yg[3] : yu[3];
                float* dstp = bc + warp * 128 + (t >> 1) * 64 + (t & 1) * 32;
                *(float2*)&dstp[g * 2] = make_float2(y0, y1);
                *(float2*)&dstp[(g + 8) * 2] = make_float2(y2, y3);
                __syncwarp();
                if (lane == 0) mbar_arrive(bar_bc);
            }
            if (warp == 0) TSTAMP(11);
            float pivot2;
            {
                while (clock32() - t_wo < DELAY_X1) {}
                bool okx = false, okp = false;
                for (int it = 0;; it++) {
                    if (!okx) { va = ld_ll4(px); vb = ld_ll4(px + 1); }
                    if (!okp) { pa = ld_ll4(pp); pb = ld_ll4(pp + 1); }
                    okx = va.y == F_X1 && va.w == F_X1 && vb.y == F_X1 && vb.w == F_X1;
                    okp = pa.y == F_X1 && pa.w == F_X1 && pb.y == F_X1 && pb.w == F_X1;
                    if (__all_sync(0xffffffffu, okx && okp) || it > SPIN_LIMIT) break;
                }
                if (warp == 0) TSTAMP(9);
                const float xv[4] = {eb ? bf_hi(va.x) : bf_lo(va.x), eb ? bf_hi(va.z) : bf_lo(va.z),
                                     eb ? bf_hi(vb.x) : bf_lo(vb.x), eb ? bf_hi(vb.z) : bf_lo(vb.z)};
                const float p0 = 0.25f * ((bf_lo(pa.x) + bf_lo(pa.z)) + (bf_lo(pb.x) + bf_lo(pb.z)));
                const float p1 = 0.25f * ((bf_hi(pa.x) + bf_hi(pa.z)) + (bf_hi(pb.x) + bf_hi(pb.z)));
                const float pivot = eb ? p1 : p0;
                pivot2 = (lane & 1) ? p1 : p0;
                *(uint2*)&hs[eb * 32 + 2 * (lane & 15)] =
                    make_uint2(pack_bf16((xv[0] - pivot) * c1v[0], (xv[1] - pivot) * c1v[1]),
                               pack_bf16((xv[2] - pivot) * c1v[2], (xv[3] - pivot) * c1v[3]));
                __syncwarp();
                float cg[2][4] = {}, cu[2][4] = {};
#pragma unroll
                for (int s = 0; s < 4; s++) {
                    const uint32_t b0 = hs[bb * 32 + 8 * s + t], b1 = hs[bb * 32 + 8 * s + 4 + t];
                    mma16816(cg[s & 1], gf[s], b0, b1);
                    mma16816(cu[s & 1], uf[s], b0, b1);
                }
                const float2 ps = half_warp_sums(xv, pivot);
                if ((lane & 15) == 0) stat[warp * 2 + eb] = ps;
                {
                    const float* bc = (const float*)(sgen + SM_MRG + 4096);
                    mbar_wait(bar_bc, 0);
#pragma unroll
                    for (int w = 0; w < 8; w++) {
                        bg += bc[w * 128 + lane]; cgc += bc[w * 128 + 32 + lane];
                        bu += bc[w * 128 + 64 + lane]; cuc += bc[w * 128 + 96 + lane];
                    }
                }
                if (t < 2) {
                    float v[4];
#pragma unroll
                    for (int i = 0; i < 4; i++) v[i] = t ? cu[0][i] + cu[1][i] : cg[0][i] + cg[1][i];
                    *(float2*)&red[warp * 64 + t * 32 + g * 2] = make_float2(v[0], v[1]);
                    *(float2*)&red[warp * 64 + t * 32 + (g + 8) * 2] = make_float2(v[2], v[3]);
                }
            }
            uint32_t df[4][4];
            mbar_wait(bar_full + 8 * (IDX_WD % NST), (IDX_WD / NST) & 1);
#pragma unroll
            for (int mt = 0; mt < 4; mt++) ldsm4t((sbase + SM_RING + (IDX_WD % NST) * TILE + aoff) ^ (mt << 5), df[mt]);
            cons_sync();
            {
                float gs = 0.f, us = 0.f;
#pragma unroll
                for (int w = 0; w < 8; w++) { gs += red[w * 64 + lane]; us += red[w * 64 + 32 + lane]; }
                float mean_bf, rstd;
                ln_stats(stat, lane & 1, pivot2, mean_bf, rstd);
                const float dm = mean_bf - pivot2;
                gs = bf16r(rstd * (gs - dm * bg) + cgc);
                us = rstd * (us - dm * bu) + cuc;
                const float u2 = gs * (1.0f + 0.044715f * gs * gs) * (2.0f * 0.7978845608028654f * LOG2E);
                const float ge = bf16r(__fdividef(gs, 1.0f + ex2(-u2)));
                const float act = bf16r(ge * bf16r(us));
                const float a0 = __shfl_sync(0xffffffffu, act, 4 * t + bb), a1 = __shfl_sync(0xffffffffu, act, 4 * t + 2 + bb);
                const float a2 = __shfl_sync(0xffffffffu, act, 4 * t + 16 + bb), a3 = __shfl_sync(0xffffffffu, act, 4 * t + 18 + bb);
                const uint32_t b0 = pack_bf16(a0, a1), b1 = pack_bf16(a2, a3);
                float y[4][4] = {};
#pragma unroll
                for (int mt = 0; mt < 4; mt++) mma16816(y[mt], df[mt], b0, b1);
                float v[4];
#pragma unroll
                for (int i = 0; i < 4; i++) v[i] = t == 0 ? y[0][i] : t == 1 ? y[1][i] : t == 2 ? y[2][i] : y[3][i];
            {
                const bool odd = g & 1;
                const float sx = odd ? v[0] : v[2], sy = odd ? v[1] : v[3];
                const float rx = __shfl_xor_sync(0xffffffffu, sx, 4), ry = __shfl_xor_sync(0xffffffffu, sy, 4);
                const int c0 = 64 * warp + 16 * t + (odd ? g + 7 : g);
                const float e0 = odd ? rx : v[0], e1 = odd ? ry : v[1], e2 = odd ? v[2] : rx, e3 = odd ? v[3] : ry;
                st_v4(&sc->inbox_dn[c0 >> 2][cta][(c0 >> 1) & 1], tagf(e0, F_DOWN), tagf(e1, F_DOWN), tagf(e2, F_DOWN), tagf(e3, F_DOWN));
            }
            }
            if (warp == 0) TSTAMP(12);
        }
        {
            uint2 xw;
            float r0;
            {
                const uint4* pin = &sc->inbox_dn[cta][0][0] + tid;
                uint4 v = make_uint4(F_DOWN, F_DOWN, F_DOWN, F_DOWN);
                if (cta < NFFN) spin_cycles(DELAY_C);
                else while (clock32() - t_wo < DELAY_X1 + DELAY_NOFFN) {}
                xw = ld_ll2(&sc->x1[ocol]);
                bool ok = tid >= NFFN * 2;
                for (int it = 0;; it++) {
                    if (!ok) {
                        v = ld_ll4(pin);
                        ok = (v.x & v.y & v.z & v.w & 3u) == F_DOWN;
                    }
                    if (__all_sync(0xffffffffu, ok) || it > SPIN_LIMIT) break;
                }
                const bool u1 = lane & 2, u2 = lane & 4;
                const float a0 = untag(v.x), a1 = untag(v.y), a2 = untag(v.z), a3 = untag(v.w);
                const float k0 = (u1 ? a1 : a0) + __shfl_xor_sync(0xffffffffu, u1 ? a0 : a1, 2);
                const float k1 = (u1 ? a3 : a2) + __shfl_xor_sync(0xffffffffu, u1 ? a2 : a3, 2);
                r0 = (u2 ? k1 : k0) + __shfl_xor_sync(0xffffffffu, u2 ? k0 : k1, 4);
                r0 += __shfl_xor_sync(0xffffffffu, r0, 8);
                r0 += __shfl_xor_sync(0xffffffffu, r0, 16);
                if (lane < 8) red2[256 + warp * 8 + (2 * (lane & 1) + ((lane >> 2) & 1)) * 2 + ((lane >> 1) & 1)] = r0;
            }
            cons_sync();
            if (warp == 0) {
                float a0 = 0.f, a1 = 0.f;
#pragma unroll
                for (int w = 0; w < 8; w++) { const float2 v = *(const float2*)&red2[256 + w * 8 + (lane & 3) * 2]; a0 += v.x; a1 += v.y; }
                const bool hi = ocol & 1;
                const float gb0 = hi ? bf_hi(m_gb0.x) : bf_lo(m_gb0.x), gb1 = hi ? bf_hi(m_gb1.x) : bf_lo(m_gb1.x);
                for (int it = 0; !__all_sync(0xffffffffu, xw.y == F_X1) && it < SPIN_LIMIT; it++) xw = ld_ll2(&sc->x1[ocol]);
                if (lane < 4) {
                    p.out[ocol] = __float2bfloat16_rn(bf_lo(xw.x) + bf16r(gb0 * bf16r(a0)));
                    p.out[D_MODEL + ocol] = __float2bfloat16_rn(bf_hi(xw.x) + bf16r(gb1 * bf16r(a1)));
                }
                TSTAMP(13);
            }
        }
    }
}

typedef CUresult (*EncodeFn)(CUtensorMap*, CUtensorMapDataType, cuuint32_t, void*, const cuuint64_t*, const cuuint64_t*,
                             const cuuint32_t*, const cuuint32_t*, CUtensorMapInterleave, CUtensorMapSwizzle,
                             CUtensorMapL2promotion, CUtensorMapFloatOOBfill);

struct Maps { CUtensorMap k, v, wq, wmod, wmod8, wo, wg, wu, wd; };

void encode(EncodeFn fn, CUtensorMap* m, const void* ptr, int rank, const cuuint64_t* dims, const cuuint64_t* strides,
            const cuuint32_t* box, CUtensorMapSwizzle sw) {
    const cuuint32_t es[3] = {1, 1, 1};
    fn(m, CU_TENSOR_MAP_DATA_TYPE_BFLOAT16, rank, const_cast<void*>(ptr), dims, strides, box, es,
       CU_TENSOR_MAP_INTERLEAVE_NONE, sw, CU_TENSOR_MAP_L2_PROMOTION_L2_256B, CU_TENSOR_MAP_FLOAT_OOB_FILL_NONE);
}

}

extern "C" void kernel_launch(void* const* d_in, const int* in_sizes, int n_in, void* d_out, int out_size) {
    (void)in_sizes; (void)n_in; (void)out_size;
    static EncodeFn enc = nullptr;
    static Scratch* scratch = nullptr;
    if (!enc) {
        cudaGetSymbolAddress((void**)&scratch, g_scratch);
        void* fn = nullptr;
        cudaDriverEntryPointQueryResult qr;
        cudaGetDriverEntryPoint("cuTensorMapEncodeTiled", &fn, cudaEnableDefault, &qr);
        enc = (EncodeFn)fn;
        cudaFuncSetAttribute(fused_block_kernel, cudaFuncAttributeMaxDynamicSharedMemorySize, SMEM_BYTES);
    }
    Maps m;
    {
        const cuuint64_t dims[3] = {64, (cuuint64_t)16 * SK, 2}, str[2] = {256, 128};
        const cuuint32_t box[3] = {64, 64, 2};
        encode(enc, &m.k, d_in[1], 3, dims, str, box, CU_TENSOR_MAP_SWIZZLE_128B);
        encode(enc, &m.v, d_in[2], 3, dims, str, box, CU_TENSOR_MAP_SWIZZLE_128B);
    }
    {
        const cuuint64_t dims[2] = {4096, 512}, str[1] = {8192};
        const cuuint32_t box[2] = {32, 256};
        encode(enc, &m.wq, d_in[3], 2, dims, str, box, CU_TENSOR_MAP_SWIZZLE_64B);
    }
    {
        const cuuint64_t dims[2] = {N_MOD, 512}, str[1] = {N_MOD * 2};
        const cuuint32_t box[2] = {16, 256};
        encode(enc, &m.wmod, d_in[10], 2, dims, str, box, CU_TENSOR_MAP_SWIZZLE_32B);
        const cuuint32_t box8[2] = {8, 256};
        encode(enc, &m.wmod8, d_in[10], 2, dims, str, box8, CU_TENSOR_MAP_SWIZZLE_NONE);
    }
    {
        const cuuint64_t dims_o[3] = {64, 4096, 8}, dims_d[3] = {64, D_FF, 8}, str[2] = {1024, 128};
        const cuuint32_t box[3] = {64, 16, 8}, box_o[3] = {64, 64, 2};
        encode(enc, &m.wo, d_in[4], 3, dims_o, str, box_o, CU_TENSOR_MAP_SWIZZLE_128B);
        encode(enc, &m.wd, d_in[8], 3, dims_d, str, box, CU_TENSOR_MAP_SWIZZLE_128B);
    }
    {
        const cuuint64_t dims[2] = {D_FF, 512}, str[1] = {D_FF * 2};
        const cuuint32_t box[2] = {16, 128};
        encode(enc, &m.wg, d_in[6], 2, dims, str, box, CU_TENSOR_MAP_SWIZZLE_32B);
        encode(enc, &m.wu, d_in[7], 2, dims, str, box, CU_TENSOR_MAP_SWIZZLE_32B);
    }
    Params p;
    p.x = (const __nv_bfloat16*)d_in[0];
    p.c = (const __nv_bfloat16*)d_in[9];
    p.out = (__nv_bfloat16*)d_out;
    p.sc = scratch;
    fused_block_kernel<<<NCTA, NTHREADS, SMEM_BYTES, cudaStreamPerThread>>>(p, m.k, m.v, m.wq, m.wmod, m.wmod8, m.wo, m.wg, m.wu, m.wd);
}
```

```cpp
#include <cuda_runtime.h>
#include <cuda.h>
#include <cuda_bf16.h>
#include <stdint.h>

namespace {

constexpr int D_MODEL = 512;
constexpr int N_HEADS = 32;
constexpr int SK = 32768;
constexpr int DH = 128;
constexpr int D_FF = 1792;
constexpr int N_MOD = 6 * D_MODEL;

constexpr int NCTA = 128;
constexpr int NFFN = D_FF / 16;
constexpr int NOWN = 32;
constexpr int NTHREADS = 320;
constexpr int NST = 12;
constexpr int TILE = 16384;
#define WINDOW 3
#define WINDOW_TAIL 1
#define GU_WIN 3
#define END_FAST 3
#define PACE_THR 96
constexpr int KV_TILES = 64;
#define MOD_AT 8
static_assert(MOD_AT % 2 == 0 && MOD_AT >= 2 && MOD_AT < 56, "schedule");
__host__ __device__ constexpr int kv_idx(int i) { return 2 + 2 * i + (i >= MOD_AT ? 1 : 0); }
constexpr int IDX_MOD = 2 + 2 * MOD_AT;
constexpr int N_STREAM = kv_idx(KV_TILES - 1) + 2;
constexpr int IDX_WO = N_STREAM;
constexpr int IDX_WG = IDX_WO + 2;
constexpr int IDX_WU = IDX_WG + 1;
constexpr int IDX_WD = IDX_WU + 1;
constexpr int SPIN_LIMIT = 1 << 20;

constexpr float LOG2E = 1.4426950408889634f;
constexpr float QK_SCALE = 0.08838834764831845f;

constexpr int SM_RING = 0;
constexpr int SM_MRG = SM_RING + NST * TILE;
constexpr int SM_ML = SM_MRG + 8 * 4 * 136 * 4;
constexpr int SM_RED = SM_ML + 8 * 4 * 8;
constexpr int SM_RED2 = SM_RED + 8 * 64 * 4;
constexpr int SM_QS = SM_RED2 + 8 * 64 * 4;
constexpr int SM_OS = SM_QS + 512 * 2;
constexpr int SM_SC = SM_OS + 2 * 128 * 2;
constexpr int SM_HS = SM_SC + 2 * 512 * 2;
constexpr int SM_STAT = SM_HS + 8 * 2 * 32 * 4;
constexpr int SM_PACE = SM_STAT + 8 * 2 * 8;
constexpr int SM_BAR = SM_PACE + 16;
constexpr int SM_END = SM_BAR + (2 * NST + 1 + 8 + 3) * 8;
constexpr int SMEM_BYTES = SM_END + 1024;

struct Scratch {
    uint4 inbox_wo[NOWN][N_HEADS][8];
    uint4 inbox_dn[NCTA][NFFN][2];
    uint2 x1[D_MODEL];
    uint2 part_o[NCTA][4][64];
    uint2 part_ml[NCTA][4][4];
    uint2 mod[2][N_MOD / 2];
    uint2 q[2][N_HEADS * DH / 2];
    unsigned epoch;
    unsigned pad_[31];
    unsigned cleared;
    unsigned pad2_[31];
    unsigned progress;
};
__device__ Scratch g_scratch;
constexpr uint32_t F_PART = 1, F_WO = 1, F_DOWN = 1, F_X1 = 1;
__device__ __forceinline__ uint32_t tagf(float v, uint32_t f) { return (__float_as_uint(v) & ~3u) | f; }
__device__ __forceinline__ float untag(uint32_t v) { return __uint_as_float(v & ~3u); }

struct Params {
    const __nv_bfloat16* x;
    const __nv_bfloat16* c;
    __nv_bfloat16* out;
    Scratch* sc;
};

#define TSTAMP(i) do { } while (0)

__device__ __forceinline__ uint32_t smem_u32(const void* p) { return (uint32_t)__cvta_generic_to_shared(p); }

__device__ __forceinline__ void mbar_init(uint32_t bar, uint32_t cnt) {
    asm volatile("mbarrier.init.shared::cta.b64 [%0], %1;" ::"r"(bar), "r"(cnt) : "memory");
}
__device__ __forceinline__ void mbar_expect_tx(uint32_t bar, uint32_t bytes) {
    asm volatile("mbarrier.arrive.expect_tx.shared::cta.b64 _, [%0], %1;" ::"r"(bar), "r"(bytes) : "memory");
}
__device__ __forceinline__ void mbar_arrive(uint32_t bar) {
    asm volatile("mbarrier.arrive.shared::cta.b64 _, [%0];" ::"r"(bar) : "memory");
}
__device__ __forceinline__ bool mbar_try(uint32_t bar, uint32_t parity) {
    uint32_t ok;
    asm volatile(
        "{\n\t.reg .pred p;\n\t"
        "mbarrier.try_wait.parity.shared::cta.b64 p, [%1], %2;\n\t"
        "selp.u32 %0, 1, 0, p;\n\t}"
        : "=r"(ok) : "r"(bar), "r"(parity) : "memory");
    return ok != 0;
}
__device__ __forceinline__ void mbar_wait(uint32_t bar, uint32_t parity) {
    if (mbar_try(bar, parity)) return;
    const long long t0 = clock64();
    while (!mbar_try(bar, parity))
        if (clock64() - t0 > (1ll << 31)) return;
}
__device__ __forceinline__ void cons_sync() { asm volatile("bar.sync 1, 256;" ::: "memory"); }

__device__ __forceinline__ void tma_2d(uint32_t dst, const CUtensorMap* m, int c0, int c1, uint32_t bar) {
    asm volatile("cp.async.bulk.tensor.2d.shared::cluster.global.mbarrier::complete_tx::bytes [%0], [%1, {%3, %4}], [%2];"
                 ::"r"(dst), "l"(m), "r"(bar), "r"(c0), "r"(c1) : "memory");
}
__device__ __forceinline__ void tma_3d(uint32_t dst, const CUtensorMap* m, int c0, int c1, int c2, uint32_t bar) {
    asm volatile("cp.async.bulk.tensor.3d.shared::cluster.global.mbarrier::complete_tx::bytes [%0], [%1, {%3, %4, %5}], [%2];"
                 ::"r"(dst), "l"(m), "r"(bar), "r"(c0), "r"(c1), "r"(c2) : "memory");
}
__device__ __forceinline__ void tma_3d_hint(uint32_t dst, const CUtensorMap* m, int c0, int c1, int c2, uint32_t bar, uint64_t pol) {
    asm volatile("cp.async.bulk.tensor.3d.shared::cluster.global.mbarrier::complete_tx::bytes.L2::cache_hint [%0], [%1, {%3, %4, %5}], [%2], %6;"
                 ::"r"(dst), "l"(m), "r"(bar), "r"(c0), "r"(c1), "r"(c2), "l"(pol) : "memory");
}
__device__ __forceinline__ void prefetch_tmap(const CUtensorMap* m) {
    asm volatile("prefetch.tensormap [%0];" ::"l"(m) : "memory");
}

__device__ __forceinline__ void ldsm4(uint32_t addr, uint32_t (&r)[4]) {
    asm volatile("ldmatrix.sync.aligned.m8n8.x4.shared.b16 {%0,%1,%2,%3}, [%4];"
                 : "=r"(r[0]), "=r"(r[1]), "=r"(r[2]), "=r"(r[3]) : "r"(addr) : "memory");
}
__device__ __forceinline__ void ldsm4t(uint32_t addr, uint32_t (&r)[4]) {
    asm volatile("ldmatrix.sync.aligned.m8n8.x4.trans.shared.b16 {%0,%1,%2,%3}, [%4];"
                 : "=r"(r[0]), "=r"(r[1]), "=r"(r[2]), "=r"(r[3]) : "r"(addr) : "memory");
}
__device__ __forceinline__ void mma16816(float (&c)[4], const uint32_t (&a)[4], uint32_t b0, uint32_t b1) {
    asm volatile("mma.sync.aligned.m16n8k16.row.col.f32.bf16.bf16.f32 {%0,%1,%2,%3}, {%4,%5,%6,%7}, {%8,%9}, {%0,%1,%2,%3};"
                 : "+f"(c[0]), "+f"(c[1]), "+f"(c[2]), "+f"(c[3])
                 : "r"(a[0]), "r"(a[1]), "r"(a[2]), "r"(a[3]), "r"(b0), "r"(b1));
}
__device__ __forceinline__ uint32_t movmatrix_t(uint32_t a) {
    uint32_t d;
    asm volatile("movmatrix.sync.aligned.m8n8.trans.b16 %0, %1;" : "=r"(d) : "r"(a));
    return d;
}
__device__ __forceinline__ uint32_t pack_bf16(float a, float b) {
    uint32_t r;
    asm("cvt.rn.bf16x2.f32 %0, %1, %2;" : "=r"(r) : "f"(b), "f"(a));
    return r;
}
__device__ __forceinline__ float bf_lo(uint32_t v) { return __uint_as_float(v << 16); }
__device__ __forceinline__ float bf_hi(uint32_t v) { return __uint_as_float(v & 0xffff0000u); }
__device__ __forceinline__ float bf16r(float a) { return bf_lo(pack_bf16(a, 0.f)); }
__device__ __forceinline__ uint32_t max_bf16x2(uint32_t a, uint32_t b) {
    uint32_t r;
    asm("max.bf16x2 %0, %1, %2;" : "=r"(r) : "r"(a), "r"(b));
    return r;
}
__device__ __forceinline__ float ex2(float x) {
    float r;
    asm("ex2.approx.ftz.f32 %0, %1;" : "=f"(r) : "f"(x));
    return r;
}

__device__ __forceinline__ void st_ll2(uint2* p, uint32_t v, uint32_t tag) {
    asm volatile("st.relaxed.gpu.global.v2.u32 [%0], {%1, %2};" ::"l"(p), "r"(v), "r"(tag) : "memory");
}
__device__ __forceinline__ void st_v4(uint4* p, uint32_t a, uint32_t b, uint32_t c, uint32_t d) {
    asm volatile("st.relaxed.gpu.global.v4.u32 [%0], {%1, %2, %3, %4};" ::"l"(p), "r"(a), "r"(b), "r"(c), "r"(d) : "memory");
}
__device__ __forceinline__ uint2 ld_ll2(const uint2* p) {
    uint2 v;
    asm volatile("ld.relaxed.gpu.global.v2.u32 {%0, %1}, [%2];" : "=r"(v.x), "=r"(v.y) : "l"(p) : "memory");
    return v;
}
__device__ __forceinline__ uint4 ld_ll4(const uint4* p) {
    uint4 v;
    asm volatile("ld.relaxed.gpu.global.v4.u32 {%0, %1, %2, %3}, [%4];"
                 : "=r"(v.x), "=r"(v.y), "=r"(v.z), "=r"(v.w) : "l"(p) : "memory");
    return v;
}

#define DELAY_P1 1800
#define DELAY_Q 1800
#define DELAY_A 1000
#define DELAY_B1 300
#define DELAY_X1 2000
#define DELAY_NOFFN 1500
#define DELAY_C 600
__device__ __forceinline__ uint32_t clock32() {
    uint32_t c;
    asm volatile("mov.u32 %0, %clock;" : "=r"(c));
    return c;
}
__device__ __forceinline__ void spin_cycles(uint32_t n) {
    if (n > 0) { const uint32_t c0 = clock32(); while (clock32() - c0 < n) {} }
}
__device__ __forceinline__ float rcp_approx(float x) {
    float r;
    asm("rcp.approx.ftz.f32 %0, %1;" : "=f"(r) : "f"(x));
    return r;
}
__device__ __forceinline__ float sqrt_approx(float x) {
    float r;
    asm("sqrt.approx.f32 %0, %1;" : "=f"(r) : "f"(x));
    return r;
}

__device__ __forceinline__ float silu_bf(float v) { return bf16r(v / (1.0f + expf(-v))); }

__device__ __forceinline__ float2 half_warp_sums(const float (&v)[4], float pivot) {
    float s1 = 0.f, s2 = 0.f;
#pragma unroll
    for (int i = 0; i < 4; i++) { const float d = v[i] - pivot; s1 += d; s2 += d * d; }
#pragma unroll
    for (int o = 1; o < 16; o <<= 1) { s1 += __shfl_xor_sync(0xffffffffu, s1, o); s2 += __shfl_xor_sync(0xffffffffu, s2, o); }
    return make_float2(s1, s2);
}
__device__ __forceinline__ void ln_stats(const float2* stat, int b, float pivot, float& mean_bf, float& rstd) {
    float s1 = 0.f, s2 = 0.f;
#pragma unroll
    for (int w = 0; w < 8; w++) { const float2 v = stat[w * 2 + b]; s1 += v.x; s2 += v.y; }
    const float dm = s1 * (1.0f / D_MODEL);
    const float var = fmaxf(s2 * (1.0f / D_MODEL) - dm * dm, 0.f);
    mean_bf = bf16r(pivot + dm);
    rstd = rcp_approx(bf16r(sqrt_approx(bf16r(bf16r(var) + 1e-5f))));
}
__device__ __forceinline__ float ln_norm(float xv, float mean_bf, float rstd) { return bf16r(bf16r(xv - mean_bf) * rstd); }
__device__ __forceinline__ float ln_mod(float n, float cmul, float sadd) { return bf16r(n * bf16r(1.0f + cmul)) + sadd; }

__global__ void __launch_bounds__(NTHREADS, 1)
fused_block_kernel(const Params p, const __grid_constant__ CUtensorMap tm_k, const __grid_constant__ CUtensorMap tm_v,
                   const __grid_constant__ CUtensorMap tm_wq, const __grid_constant__ CUtensorMap tm_wmod,
                   const __grid_constant__ CUtensorMap tm_wmod8,
                   const __grid_constant__ CUtensorMap tm_wo, const __grid_constant__ CUtensorMap tm_wg,
                   const __grid_constant__ CUtensorMap tm_wu, const __grid_constant__ CUtensorMap tm_wd) {
    extern __shared__ unsigned char smem_raw[];
    const uint32_t sbase = (smem_u32(smem_raw) + 1023u) & ~1023u;
    unsigned char* sgen = smem_raw + (sbase - smem_u32(smem_raw));
    const int tid = threadIdx.x, warp = tid >> 5, lane = tid & 31;
    const int cta = blockIdx.x;
    const uint32_t bar_full = sbase + SM_BAR, bar_empty = bar_full + NST * 8;
    const uint32_t bar_clear = bar_empty + NST * 8;
    const uint32_t bar_gu = bar_clear + 8;
    const uint32_t bar_bc = bar_gu + 8 * 8;
    const uint32_t bar_p0w = bar_bc + 8;
    const uint32_t bar_gate = bar_p0w + 8;

    const int key0 = (cta >> 3) * SK + (cta & 7) * 64;
    uint64_t pol = 0;
    if (tid == 256) {
        asm volatile("createpolicy.fractional.L2::evict_first.b64 %0, 1.0;" : "=l"(pol));
        mbar_init(bar_p0w, 1);
#pragma unroll
        for (int i = 0; i < 4; i++) mbar_init(bar_full + 8 * i, 1);
        asm volatile("fence.mbarrier_init.release.cluster;" ::: "memory");
        mbar_expect_tx(bar_p0w, 8192);
        tma_2d(sbase + SM_MRG, &tm_wmod8, cta * 8, 0, bar_p0w);
        tma_2d(sbase + SM_MRG + 4096, &tm_wmod8, cta * 8, 256, bar_p0w);
#pragma unroll
        for (int i = 0; i < 4; i++) mbar_expect_tx(bar_full + 8 * i, TILE);
        tma_2d(sbase + SM_RING, &tm_wq, cta * 32, 0, bar_full);
        tma_2d(sbase + SM_RING + TILE, &tm_wq, cta * 32, 256, bar_full + 8);
        tma_3d_hint(sbase + SM_RING + 2 * TILE, &tm_k, 0, key0, 0, bar_full + 16, pol);
        tma_3d_hint(sbase + SM_RING + 3 * TILE, &tm_v, 0, key0, 0, bar_full + 24, pol);
    }

    if (warp == 8) {
        if (lane == 0) {
            for (int i = 0; i < NST; i++) { if (i >= 4) mbar_init(bar_full + 8 * i, 1); mbar_init(bar_empty + 8 * i, 4); }
            mbar_init(bar_clear, 1);
            for (int k = 0; k < 8; k++) mbar_init(bar_gu + 8 * k, 1);
            mbar_init(bar_bc, 8);
            mbar_init(bar_gate, 1);
            ((volatile uint32_t*)(sgen + SM_PACE))[0] = 0;
            ((volatile uint32_t*)(sgen + SM_PACE))[1] = WINDOW;
            asm volatile("fence.mbarrier_init.release.cluster;" ::: "memory");
        }
        __syncwarp();
        asm volatile("bar.arrive 2, 288;" ::: "memory");
        asm volatile("bar.arrive 3, 64;" ::: "memory");
        if (lane == 0) {
            int slot = 4; uint32_t ph = 1;
            int landed = 0, wslot = 0; uint32_t wph = 0;
            int kv = 2;
            auto wait_window = [&](int idx, int window) {
                while (landed + window <= idx) {
                    mbar_wait(bar_full + 8 * wslot, wph);
                    if (++wslot == NST) { wslot = 0; wph ^= 1; }
                    landed++;
                }
            };
            volatile uint32_t* pace = (volatile uint32_t*)(sgen + SM_PACE);
            prefetch_tmap(&tm_wmod);
            pace[0] = 4;
            for (int idx = 4; idx < N_STREAM; idx++) {
                if (idx >= NST) mbar_wait(bar_empty + 8 * slot, ph);
                wait_window(idx, (int)pace[1]);
                if (idx == 12) { prefetch_tmap(&tm_wo); prefetch_tmap(&tm_wg); prefetch_tmap(&tm_wu); prefetch_tmap(&tm_wd); }
                const uint32_t fb = bar_full + 8 * slot, dst = sbase + SM_RING + slot * TILE;
                mbar_expect_tx(fb, TILE);
                if (idx == IDX_MOD) {
                    tma_2d(dst, &tm_wmod, 1024 + cta * 16, 0, fb);
                    tma_2d(dst + 8192, &tm_wmod, 1024 + cta * 16, 256, fb);
                } else {
                    tma_3d_hint(dst, (kv & 1) ? &tm_v : &tm_k, 0, key0 + (kv >> 1) * 512, 0, fb, pol);
                    kv++;
                }
                pace[0] = idx + 1;
                if (++slot == NST) { slot = 0; ph ^= 1; }
            }
            auto slot_free = [&](int idx) { mbar_wait(bar_empty + 8 * (idx % NST), ((idx / NST) & 1) ^ 1); };
#pragma unroll
            for (int s = 0; s < 2; s++) {
                const int idx = IDX_WO + s;
                slot_free(idx);
                wait_window(idx, WINDOW_TAIL);
                mbar_expect_tx(bar_full + 8 * (idx % NST), TILE);
                tma_3d(sbase + SM_RING + (idx % NST) * TILE, &tm_wo, 0, (cta >> 2) * 128 + s * 64, (cta & 3) * 2, bar_full + 8 * (idx % NST));
            }
            if (cta < NFFN) {
                slot_free(IDX_WG); slot_free(IDX_WU);
                mbar_wait(bar_full + 8 * (IDX_WO % NST), (IDX_WO / NST) & 1);
                mbar_wait(bar_full + 8 * ((IDX_WO + 1) % NST), ((IDX_WO + 1) / NST) & 1);
#pragma unroll
                for (int st = 0; st < 8; st++) {
                    if (st >= GU_WIN) mbar_wait(bar_gu + 8 * (st - GU_WIN), 0);
                    mbar_expect_tx(bar_gu + 8 * st, 4096);
                    tma_2d(sbase + SM_RING + (((st & 1) ? IDX_WU : IDX_WG) % NST) * TILE + (st >> 1) * 4096,
                           (st & 1) ? &tm_wu : &tm_wg, cta * 16, (st >> 1) * 128, bar_gu + 8 * st);
                }
                mbar_wait(bar_gu + 8 * 6, 0);
                slot_free(IDX_WD);
                mbar_expect_tx(bar_full + 8 * (IDX_WD % NST), TILE);
                tma_3d(sbase + SM_RING + (IDX_WD % NST) * TILE, &tm_wd, 0, cta * 16, 0, bar_full + 8 * (IDX_WD % NST));
            }
        }
    } else if (warp == 9) {
        Scratch* const sc = p.sc;
        const uint32_t tag = *(volatile unsigned*)&sc->epoch + 1;
        asm volatile("bar.sync 3, 64;" ::: "memory");
#pragma unroll 4
        for (int i = 0; i < NFFN * 2 / 32; i++) st_v4(&sc->inbox_dn[cta][0][0] + i * 32 + lane, 0u, 0u, 0u, 0u);
        if (cta >= NCTA - NOWN) {
#pragma unroll 4
            for (int i = 0; i < 8; i++) st_v4(&sc->inbox_wo[cta - (NCTA - NOWN)][0][0] + i * 32 + lane, 0u, 0u, 0u, 0u);
            if (lane < 8) st_v4((uint4*)&sc->x1[(cta - (NCTA - NOWN)) * 16] + lane, 0u, 0u, 0u, 0u);
        }
#pragma unroll 4
        for (int i = 0; i < 4; i++) st_v4((uint4*)&sc->part_o[cta][0][0] + i * 32 + lane, 0u, 0u, 0u, 0u);
        if (lane < 8) st_v4((uint4*)&sc->part_ml[cta][0][0] + lane, 0u, 0u, 0u, 0u);
        if (cta == 0 && lane == 0) asm volatile("st.relaxed.gpu.global.u32 [%0], %1;" ::"l"(&sc->progress), "r"(0u) : "memory");
        asm volatile("fence.acq_rel.gpu;" ::: "memory");
        __syncwarp();
        if (lane == 0) {
            asm volatile("fence.acq_rel.gpu;" ::: "memory");
            asm volatile("red.relaxed.gpu.global.add.u32 [%0], %1;" ::"l"(&sc->cleared), "r"(1u) : "memory");
            const uint32_t target = tag * NCTA;
            for (int it = 0; it < SPIN_LIMIT; it++) {
                uint32_t v;
                asm volatile("ld.relaxed.gpu.global.u32 %0, [%1];" : "=r"(v) : "l"(&sc->cleared) : "memory");
                if ((int32_t)(v - target) >= 0) break;
                __nanosleep(500);
            }
            asm volatile("fence.acq_rel.gpu;" ::: "memory");
            mbar_arrive(bar_clear);
            volatile uint32_t* pace = (volatile uint32_t*)(sgen + SM_PACE);
            uint32_t posted = 0;
            for (int it = 0; it < SPIN_LIMIT; it++) {
                const uint32_t own = pace[0];
                if (own > posted) {
                    asm volatile("red.relaxed.gpu.global.add.u32 [%0], %1;" ::"l"(&sc->progress), "r"(own - posted) : "memory");
                    posted = own;
                }
                uint32_t v;
                asm volatile("ld.relaxed.gpu.global.u32 %0, [%1];" : "=r"(v) : "l"(&sc->progress) : "memory");
                if (own >= N_STREAM) {
                    if (v >= NCTA * N_STREAM) break;
                } else {
                    const int diff = (int)v - (int)own * NCTA;
                    pace[1] = diff > PACE_THR ? WINDOW + 1 : diff < -PACE_THR ? WINDOW - 1 : WINDOW;
                }
                __nanosleep(own + END_FAST >= N_STREAM ? 30 : 200);
            }
            pace[2] = clock32();
            mbar_arrive(bar_gate);
            if (cta == 0) asm volatile("st.relaxed.gpu.global.u32 [%0], %1;" ::"l"(&sc->epoch), "r"(tag) : "memory");
        }
    } else {
        const int g = lane >> 2, t = lane & 3;
        const int bb = g & 1;
        const int eb = lane >> 4;
        const int ec = 64 * warp + 4 * (lane & 15);
        if (warp == 0) TSTAMP(0);
        Scratch* const sc = p.sc;
        const float c00 = __bfloat162float(p.c[tid]), c01 = __bfloat162float(p.c[tid + 256]);
        const float c10 = __bfloat162float(p.c[D_MODEL + tid]), c11 = __bfloat162float(p.c[D_MODEL + tid + 256]);
        const uint2 xe = __ldg((const uint2*)(p.x + eb * D_MODEL + ec));
        const float xpivot = __bfloat162float(p.x[eb * D_MODEL]);
        const uint32_t tag = *(volatile unsigned*)&sc->epoch + 1;
        const int ocol = cta * 4 + (lane & 3);
        const int wcol = (cta >= NCTA - NOWN ? cta - (NCTA - NOWN) : 0) * 16 + (lane & 15);
        const float xo = __bfloat162float(p.x[eb * D_MODEL + wcol]);

        float* red = (float*)(sgen + SM_RED);
        float* red2 = (float*)(sgen + SM_RED2);
        float2* stat = (float2*)(sgen + SM_STAT);
        uint32_t* hs = (uint32_t*)(sgen + SM_HS) + warp * 64;
        float xn[4];
        {
            float xv[4] = {bf_lo(xe.x), bf_hi(xe.x), bf_lo(xe.y), bf_hi(xe.y)};
            const float2 ps = half_warp_sums(xv, xpivot);
            if ((lane & 15) == 0) stat[warp * 2 + eb] = ps;
            const float s00 = silu_bf(c00), s01 = silu_bf(c01), s10 = silu_bf(c10), s11 = silu_bf(c11);
            __nv_bfloat16* scs = (__nv_bfloat16*)(sgen + SM_SC);
            scs[tid] = __float2bfloat16_rn(s00); scs[tid + 256] = __float2bfloat16_rn(s01);
            scs[512 + tid] = __float2bfloat16_rn(s10); scs[512 + tid + 256] = __float2bfloat16_rn(s11);
            asm volatile("bar.sync 2, 288;" ::: "memory");
            if (warp == 0) TSTAMP(23);
            float cp[4] = {0.f, 0.f, 0.f, 0.f};
            const uint32_t* sc32 = (const uint32_t*)(sgen + SM_SC) + bb * 256 + 32 * warp + t;
            mbar_wait(bar_p0w, 0);
#pragma unroll
            for (int s = 0; s < 4; s++) {
                uint32_t r0, r1;
                asm volatile("ldmatrix.sync.aligned.m8n8.x2.trans.shared.b16 {%0,%1}, [%2];"
                             : "=r"(r0), "=r"(r1) : "r"(sbase + SM_MRG + (64 * warp + 16 * s + (lane & 15)) * 16) : "memory");
                const uint32_t a[4] = {r0, r0, r1, r1};
                mma16816(cp, a, sc32[8 * s], sc32[8 * s + 4]);
            }
            if (t == 0) { red[warp * 16 + g] = cp[0]; red[warp * 16 + 8 + g] = cp[1]; }
            if (warp == 0) TSTAMP(14);
            cons_sync();
            if (warp == 0) {
                float s = 0.f;
#pragma unroll
                for (int w = 0; w < 8; w++) s += red[w * 16 + (lane & 15)];
                const float nx = __shfl_down_sync(0xffffffffu, s, 1);
                if (lane < 16 && !(lane & 1))
                    st_ll2(&sc->mod[lane >> 3][cta * 4 + ((lane & 7) >> 1)], pack_bf16(s, nx), tag);
                TSTAMP(1);
            }
            float mean_bf, rstd;
            ln_stats(stat, eb, xpivot, mean_bf, rstd);
#pragma unroll
            for (int i = 0; i < 4; i++) xn[i] = ln_norm(xv[i], mean_bf, rstd);
        }
        {
            uint4 sa, ca;
            spin_cycles(DELAY_P1);
            for (int it = 0;; it++) {
                sa = ld_ll4((const uint4*)&sc->mod[eb][ec >> 1]);
                ca = ld_ll4((const uint4*)&sc->mod[eb][256 + (ec >> 1)]);
                const bool ok = sa.y == tag && sa.w == tag && ca.y == tag && ca.w == tag;
                if (__all_sync(0xffffffffu, ok) || it > SPIN_LIMIT) break;
            }
            *(uint2*)&hs[eb * 32 + 2 * (lane & 15)] =
                make_uint2(pack_bf16(ln_mod(xn[0], bf_lo(ca.x), bf_lo(sa.x)), ln_mod(xn[1], bf_hi(ca.x), bf_hi(sa.x))),
                           pack_bf16(ln_mod(xn[2], bf_lo(ca.z), bf_lo(sa.z)), ln_mod(xn[3], bf_hi(ca.z), bf_hi(sa.z))));
            __syncwarp();
            uint32_t hb[8];
#pragma unroll
            for (int i = 0; i < 8; i++) hb[i] = hs[bb * 32 + 8 * (i >> 1) + 4 * (i & 1) + t];
            if (warp == 0) TSTAMP(2);
            float cq[2][4] = {};
            const int ts = warp >> 2;
            mbar_wait(bar_full + 8 * ts, 0);
            const uint32_t tb = sbase + SM_RING + ts * TILE;
#pragma unroll
            for (int s = 0; s < 4; s++) {
                const int row = 64 * (warp & 3) + 16 * s + (lane & 7) + (lane >> 4) * 8;
#pragma unroll
                for (int mt = 0; mt < 2; mt++) {
                    const int ch = 2 * mt + ((lane >> 3) & 1);
                    uint32_t a[4];
                    ldsm4t(tb + row * 64 + ((ch ^ ((row >> 1) & 3)) << 4), a);
                    mma16816(cq[mt], a, hb[2 * s], hb[2 * s + 1]);
                }
            }
            if (t < 2) {
                const float v0 = t == 0 ? cq[0][0] : cq[1][0], v1 = t == 0 ? cq[0][1] : cq[1][1];
                const float v2 = t == 0 ? cq[0][2] : cq[1][2], v3 = t == 0 ? cq[0][3] : cq[1][3];
                *(float2*)&red2[warp * 64 + (16 * t + g) * 2] = make_float2(v0, v1);
                *(float2*)&red2[warp * 64 + (16 * t + g + 8) * 2] = make_float2(v2, v3);
            }
            cons_sync();
            if (warp < 4 && lane == 0) { mbar_arrive(bar_empty); mbar_arrive(bar_empty + 8); }
            if (warp == 0) {
                const int b = lane >> 4, cp = lane & 15;
                float q0 = 0.f, q1 = 0.f;
#pragma unroll
                for (int w = 0; w < 8; w++) {
                    const float4 v = *(const float4*)&red2[w * 64 + cp * 4];
                    q0 += b ? v.y : v.x; q1 += b ? v.w : v.z;
                }
                st_ll2(&sc->q[b][cta * 16 + cp], pack_bf16(q0, q1), tag);
                TSTAMP(3);
            }
        }
        const int pair = cta >> 3;
        uint32_t qf[16];
        {
            uint2* qs = (uint2*)(sgen + SM_QS);
            if (tid < 128) {
                const uint4* src = (const uint4*)&sc->q[pair >> 3][(pair & 7) * 256] + tid;
                uint4 v;
                spin_cycles(DELAY_Q);
                for (int it = 0;; it++) {
                    v = ld_ll4(src);
                    if ((v.y == tag && v.w == tag) || it > SPIN_LIMIT) break;
                }
                qs[tid] = make_uint2(v.x, v.z);
            }
            cons_sync();
            const uint32_t* q32 = (const uint32_t*)(sgen + SM_QS);
#pragma unroll
            for (int s = 0; s < 8; s++) {
                qf[2 * s] = q32[(g & 3) * 64 + 8 * s + t];
                qf[2 * s + 1] = q32[(g & 3) * 64 + 8 * s + 4 + t];
            }
        }
        if (warp == 0) TSTAMP(4);

        float o[8][4];
#pragma unroll
        for (int i = 0; i < 8; i++) { o[i][0] = o[i][1] = o[i][2] = o[i][3] = 0.f; }
        uint32_t mrun = 0xff80ff80u;
        float ls[4] = {0.f, 0.f, 0.f, 0.f};
        uint4 m_sb, m_cb; uint2 m_ga, m_gb0, m_gb1;
        {
            const int grp = warp >> 2, wi = warp & 3;
            const int krow = 16 * wi + (lane & 7) + ((lane >> 3) & 1) * 8;
            const uint32_t koff = krow * 128 + ((((lane >> 4) & 1) ^ (lane & 7)) << 4);
            const int vrow = 16 * wi + (lane & 7) + (lane >> 4) * 8;
            const uint32_t voff = vrow * 128 + ((((lane >> 3) & 1) ^ (lane & 7)) << 4);
            const uint32_t ones[4] = {0x3f803f80u, 0x3f803f80u, 0x3f803f80u, 0x3f803f80u};
            for (int i = grp; i < KV_TILES; i += 2) {
                if (i == MOD_AT + grp) {
                    float cm[4] = {};
                    const uint32_t* sc32 = (const uint32_t*)(sgen + SM_SC) + bb * 256 + 32 * warp + t;
                    mbar_wait(bar_full + 8 * (IDX_MOD % NST), (IDX_MOD / NST) & 1);
                    const uint32_t tb = sbase + SM_RING + (IDX_MOD % NST) * TILE;
#pragma unroll
                    for (int s = 0; s < 4; s++) {
                        const int row = 64 * warp + 16 * s + (lane & 7) + (lane >> 4) * 8;
                        const int ch = (lane >> 3) & 1;
                        uint32_t a[4];
                        ldsm4t(tb + row * 32 + ((ch ^ ((row >> 2) & 1)) << 4), a);
                        mma16816(cm, a, sc32[8 * s], sc32[8 * s + 4]);
                    }
                    if (t == 0) {
                        *(float2*)&red[warp * 64 + g * 2] = make_float2(cm[0], cm[1]);
                        *(float2*)&red[warp * 64 + (g + 8) * 2] = make_float2(cm[2], cm[3]);
                    }
                    cons_sync();
                    if (warp < 4 && lane == 0) mbar_arrive(bar_empty + 8 * (IDX_MOD % NST));
                    if (warp == 1 && lane < 16) {
                        const int b = lane >> 3, cp = lane & 7;
                        float q0 = 0.f, q1 = 0.f;
#pragma unroll
                        for (int w = 0; w < 8; w++) {
                            const float4 v = *(const float4*)&red[w * 64 + cp * 4];
                            q0 += b ? v.y : v.x; q1 += b ? v.w : v.z;
                        }
                        st_ll2(&sc->mod[b][512 + cta * 8 + cp], pack_bf16(q0, q1), tag);
                    }
                }
                if (i == 56 + grp) {
                    m_sb = ld_ll4((const uint4*)&sc->mod[eb][768 + (ec >> 1)]);
                    m_cb = ld_ll4((const uint4*)&sc->mod[eb][1024 + (ec >> 1)]);
                    m_ga = ld_ll2(&sc->mod[eb][512 + (wcol >> 1)]);
                    m_gb0 = ld_ll2(&sc->mod[0][1280 + (ocol >> 1)]); m_gb1 = ld_ll2(&sc->mod[1][1280 + (ocol >> 1)]);
                }
                if (i == 60 + grp) {
                    for (int it = 0;; it++) {
                        const bool ok = m_sb.y == tag && m_sb.w == tag && m_cb.y == tag && m_cb.w == tag &&
                                        m_ga.y == tag && m_gb0.y == tag && m_gb1.y == tag;
                        if (__all_sync(0xffffffffu, ok) || it > SPIN_LIMIT) break;
                        m_sb = ld_ll4((const uint4*)&sc->mod[eb][768 + (ec >> 1)]);
                        m_cb = ld_ll4((const uint4*)&sc->mod[eb][1024 + (ec >> 1)]);
                        m_ga = ld_ll2(&sc->mod[eb][512 + (wcol >> 1)]);
                        m_gb0 = ld_ll2(&sc->mod[0][1280 + (ocol >> 1)]); m_gb1 = ld_ll2(&sc->mod[1][1280 + (ocol >> 1)]);
                    }
                    mbar_wait(bar_clear, 0);
                }
                const int ki = kv_idx(i), ks = ki % NST, vs = (ki + 1) % NST;
                const uint32_t kph = (ki / NST) & 1, vph = ((ki + 1) / NST) & 1;
                mbar_wait(bar_full + 8 * ks, kph);
                const uint32_t kb = sbase + SM_RING + ks * TILE + koff;
                float sa[4] = {0.f, 0.f, 0.f, 0.f}, sb[4] = {0.f, 0.f, 0.f, 0.f};
#pragma unroll
                for (int s = 0; s < 8; s += 2) {
                    uint32_t a0[4], a1[4];
                    ldsm4((kb ^ ((s & 3) << 5)) + (s >> 2) * 8192, a0);
                    ldsm4((kb ^ (((s + 1) & 3) << 5)) + (s >> 2) * 8192, a1);
                    mma16816(sa, a0, qf[2 * s], qf[2 * s + 1]);
                    mma16816(sb, a1, qf[2 * s + 2], qf[2 * s + 3]);
                }
                __syncwarp();
                if (lane == 0) mbar_arrive(bar_empty + 8 * ks);
                uint32_t r01 = pack_bf16(sa[0] + sb[0], sa[1] + sb[1]);
                uint32_t r23 = pack_bf16(sa[2] + sb[2], sa[3] + sb[3]);
                r01 = pack_bf16(bf_lo(r01) * QK_SCALE, bf_hi(r01) * QK_SCALE);
                r23 = pack_bf16(bf_lo(r23) * QK_SCALE, bf_hi(r23) * QK_SCALE);
                uint32_t mx = max_bf16x2(r01, r23);
                mx = max_bf16x2(mx, __shfl_xor_sync(0xffffffffu, mx, 4));
                mx = max_bf16x2(mx, __shfl_xor_sync(0xffffffffu, mx, 8));
                mx = max_bf16x2(mx, __shfl_xor_sync(0xffffffffu, mx, 16));
                const uint32_t mnew = max_bf16x2(mrun, mx);
                const float m0 = bf_lo(mnew), m1 = bf_hi(mnew);
                if (__any_sync(0xffffffffu, mnew != mrun)) {
                    const float al0 = ex2((bf_lo(mrun) - m0) * LOG2E), al1 = ex2((bf_hi(mrun) - m1) * LOG2E);
                    ls[0] *= al0; ls[1] *= al1;
#pragma unroll
                    for (int d = 0; d < 8; d++) { o[d][0] *= al0; o[d][1] *= al1; o[d][2] *= al0; o[d][3] *= al1; }
                    mrun = mnew;
                }
                const float p0 = ex2((bf_lo(r01) - m0) * LOG2E), p1 = ex2((bf_hi(r01) - m1) * LOG2E);
                const float p2 = ex2((bf_lo(r23) - m0) * LOG2E), p3 = ex2((bf_hi(r23) - m1) * LOG2E);
                const uint32_t pb0 = movmatrix_t(pack_bf16(p0, p1)), pb1 = movmatrix_t(pack_bf16(p2, p3));
                mma16816(ls, ones, pb0, pb1);
                mbar_wait(bar_full + 8 * vs, vph);
                const uint32_t vb = sbase + SM_RING + vs * TILE + voff;
#pragma unroll
                for (int d = 0; d < 8; d++) {
                    uint32_t a[4];
                    ldsm4t((vb ^ ((d & 3) << 5)) + (d >> 2) * 8192, a);
                    mma16816(o[d], a, pb0, pb1);
                }
                __syncwarp();
                if (lane == 0) mbar_arrive(bar_empty + 8 * vs);
            }
        }
        if (warp == 7) TSTAMP(5);
        {
            float* mrg = (float*)(sgen + SM_MRG);
            float2* ml = (float2*)(sgen + SM_ML);
            {
                const int hp = (t & 1) * 2, up = t >> 1;
                if (g == 0 && up == 0) { ml[warp * 4 + hp] = make_float2(bf_lo(mrun), ls[0]); ml[warp * 4 + hp + 1] = make_float2(bf_hi(mrun), ls[1]); }
                float* m0p = mrg + (warp * 4 + hp) * 136 + up * 72 + g;
#pragma unroll
                for (int d = 0; d < 4; d++) {
                    m0p[16 * d] = up ? o[d + 4][0] : o[d][0]; m0p[136 + 16 * d] = up ? o[d + 4][1] : o[d][1];
                    m0p[16 * d + 8] = up ? o[d + 4][2] : o[d][2]; m0p[136 + 16 * d + 8] = up ? o[d + 4][3] : o[d][3];
                }
            }
            cons_sync();
            const int hh = tid >> 6, dp = tid & 63;
            float2 mw[8];
            float M = -INFINITY;
#pragma unroll
            for (int w = 0; w < 8; w++) { mw[w] = ml[w * 4 + hh]; M = fmaxf(M, mw[w].x); }
            float L = 0.f, o0 = 0.f, o1 = 0.f;
#pragma unroll
            for (int w = 0; w < 8; w++) {
                const float wt = ex2((mw[w].x - M) * LOG2E);
                const float2 v = *(const float2*)&mrg[(w * 4 + hh) * 136 + 2 * dp + (dp >= 32 ? 8 : 0)];
                L += wt * mw[w].y; o0 += wt * v.x; o1 += wt * v.y;
            }
            st_ll2(&sc->part_o[cta][hh][dp], tagf(o0, F_PART), tagf(o1, F_PART));
            if (dp < 4) st_ll2(&sc->part_ml[cta][hh][dp], tagf(M, F_PART), tagf(L, F_PART));
        }
        if (warp == 0) TSTAMP(6);
        {
            const int hq = cta >> 2, kvh = hq >> 2, hh = hq & 3;
            const int b = tid >> 7, dc = (tid >> 3) & 15, j = tid & 7;
            const int pc = (b * 8 + kvh) * 8 + j;
            const uint4* po = (const uint4*)&sc->part_o[pc][hh][0] + dc * 2;
            const uint2* pm = &sc->part_ml[pc - j][hh][0];
            uint4 vo0, vo1; uint2 vm[8];
            mbar_wait(bar_gate, 0);
            { const uint32_t tg = ((volatile uint32_t*)(sgen + SM_PACE))[2]; while (clock32() - tg < DELAY_A) {} }
            bool oko = false;
#pragma unroll
            for (int jj = 0; jj < 8; jj++) vm[jj] = make_uint2(0u, 0u);
            for (int it = 0;; it++) {
                if (!oko) { vo0 = ld_ll4(po); vo1 = ld_ll4(po + 1); }
#pragma unroll
                for (int jj = 0; jj < 8; jj++)
                    if ((vm[jj].x & vm[jj].y & 3u) != F_PART) vm[jj] = ld_ll2(pm + jj * 16);
                oko = (vo0.x & vo0.y & vo0.z & vo0.w & vo1.x & vo1.y & vo1.z & vo1.w & 3u) == F_PART;
                uint32_t all = vm[0].x & vm[0].y;
#pragma unroll
                for (int jj = 1; jj < 8; jj++) all &= vm[jj].x & vm[jj].y;
                if (__all_sync(0xffffffffu, oko && (all & 3u) == F_PART) || it > SPIN_LIMIT) break;
            }
            float M = untag(vm[0].x);
#pragma unroll
            for (int jj = 1; jj < 8; jj++) M = fmaxf(M, untag(vm[jj].x));
            float wt = 0.f, L = 0.f;
#pragma unroll
            for (int jj = 0; jj < 8; jj++) {
                const float w_ = ex2((untag(vm[jj].x) - M) * LOG2E);
                L += w_ * untag(vm[jj].y);
                wt = jj == j ? w_ : wt;
            }
            wt *= rcp_approx(L);
            float v[8] = {wt * untag(vo0.x), wt * untag(vo0.y), wt * untag(vo0.z), wt * untag(vo0.w),
                          wt * untag(vo1.x), wt * untag(vo1.y), wt * untag(vo1.z), wt * untag(vo1.w)};
#define XRED(N, O)                                                                       \
            {                                                                            \
                const bool up = lane & (O);                                              \
                _Pragma("unroll") for (int i = 0; i < (N); i++) {                        \
                    const float send = up ? v[i] : v[i + (N)], keep = up ? v[i + (N)] : v[i]; \
                    v[i] = keep + __shfl_xor_sync(0xffffffffu, send, (O));               \
                }                                                                        \
            }
            XRED(4, 1) XRED(2, 2) XRED(1, 4)
#undef XRED
            __nv_bfloat16* os = (__nv_bfloat16*)(sgen + SM_OS);
            os[b * 128 + dc * 8 + 4 * (j & 1) + 2 * ((j >> 1) & 1) + (j >> 2)] = __float2bfloat16_rn(v[0]);
            if (warp == 0) TSTAMP(15);
            uint32_t wf[8][4];
            const uint32_t aoff_o = (warp >> 2) * 8192 + ((lane & 7) + (lane >> 4) * 8) * 128 +
                                    (((((warp & 3) * 2 + ((lane >> 3) & 1)) ^ (lane & 7))) << 4);
#pragma unroll
            for (int s = 0; s < 2; s++) {
                const int idx = IDX_WO + s;
                mbar_wait(bar_full + 8 * (idx % NST), (idx / NST) & 1);
                const uint32_t tb = sbase + SM_RING + (idx % NST) * TILE + aoff_o;
#pragma unroll
                for (int k4 = 0; k4 < 4; k4++) ldsm4t(tb + k4 * 2048, wf[s * 4 + k4]);
            }
            cons_sync();
            if (warp == 0) TSTAMP(7);
            const uint32_t* os32 = (const uint32_t*)(sgen + SM_OS) + bb * 64 + t;
            float y0[4] = {}, y1[4] = {};
#pragma unroll
            for (int ks = 0; ks < 8; ks += 2) {
                mma16816(y0, wf[ks], os32[8 * ks], os32[8 * ks + 4]);
                mma16816(y1, wf[ks + 1], os32[8 * ks + 8], os32[8 * ks + 12]);
            }
            if (t == 0)
                st_v4(&sc->inbox_wo[(cta & 3) * 8 + warp][hq][g], tagf(y0[0] + y1[0], F_WO), tagf(y0[1] + y1[1], F_WO),
                      tagf(y0[2] + y1[2], F_WO), tagf(y0[3] + y1[3], F_WO));
        }
        const uint32_t t_wo = clock32();
        if (warp == 0) TSTAMP(8);
        if (cta >= NCTA - NOWN) {
            const uint4* pin = &sc->inbox_wo[cta - (NCTA - NOWN)][0][0] + tid;
            uint4 v;
            spin_cycles(DELAY_B1);
            bool ok = false;
            for (int it = 0;; it++) {
                if (!ok) {
                    v = ld_ll4(pin);
                    ok = (v.x & v.y & v.z & v.w & 3u) == F_WO;
                }
                if (__all_sync(0xffffffffu, ok) || it > SPIN_LIMIT) break;
            }
            const bool u1 = lane & 8, u2 = lane & 16;
            const float a0 = untag(v.x), a1 = untag(v.y), a2 = untag(v.z), a3 = untag(v.w);
            const float k0 = (u1 ? a2 : a0) + __shfl_xor_sync(0xffffffffu, u1 ? a0 : a2, 8);
            const float k1 = (u1 ? a3 : a1) + __shfl_xor_sync(0xffffffffu, u1 ? a1 : a3, 8);
            red2[warp * 32 + lane] = (u2 ? k1 : k0) + __shfl_xor_sync(0xffffffffu, u2 ? k0 : k1, 16);
            cons_sync();
            if (warp == 0) {
                float a = 0.f;
#pragma unroll
                for (int w = 0; w < 8; w++) a += red2[w * 32 + lane];
                const float ga = (wcol & 1) ? bf_hi(m_ga.x) : bf_lo(m_ga.x);
                const float xm = bf16r(xo + bf16r(ga * bf16r(a)));
                const float xm_b1 = __shfl_down_sync(0xffffffffu, xm, 16);
                if (lane < 16) st_ll2(&sc->x1[wcol], pack_bf16(xm, xm_b1), F_X1);
                TSTAMP(10);
            }
        }
        const uint32_t aoff = warp * 2048 + ((lane & 7) + (lane >> 4) * 8) * 128 + ((((lane >> 3) & 1) ^ (lane & 7)) << 4);
        if (cta < NFFN) {
            const uint4* px = (const uint4*)&sc->x1[ec];
            const uint4* pp = (const uint4*)&sc->x1[0];
            uint4 va, vb, pa, pb;
            uint32_t gf[4][4], uf[4][4];
            mbar_wait(bar_gu + 8 * (2 * (warp >> 1)), 0);
            mbar_wait(bar_gu + 8 * (2 * (warp >> 1) + 1), 0);
            {
                const uint32_t tg = sbase + SM_RING + (IDX_WG % NST) * TILE, tu = sbase + SM_RING + (IDX_WU % NST) * TILE;
#pragma unroll
                for (int s = 0; s < 4; s++) {
                    const int row = 64 * warp + 16 * s + (lane & 7) + (lane >> 4) * 8;
                    const uint32_t off = row * 32 + ((((lane >> 3) & 1) ^ ((row >> 2) & 1)) << 4);
                    ldsm4t(tg + off, gf[s]);
                    ldsm4t(tu + off, uf[s]);
                }
            }
            const float c1v[4] = {bf16r(1.0f + bf_lo(m_cb.x)), bf16r(1.0f + bf_hi(m_cb.x)), bf16r(1.0f + bf_lo(m_cb.z)), bf16r(1.0f + bf_hi(m_cb.z))};
            float bg = 0.f, cgc = 0.f, bu = 0.f, cuc = 0.f;
            {
                uint32_t* pre = (uint32_t*)(sgen + SM_MRG) + warp * 128;
                float* bc = (float*)(sgen + SM_MRG + 4096);
                *(uint2*)&pre[eb * 32 + 2 * (lane & 15)] = make_uint2(pack_bf16(c1v[0], c1v[1]), pack_bf16(c1v[2], c1v[3]));
                *(uint2*)&pre[64 + eb * 32 + 2 * (lane & 15)] = make_uint2(m_sb.x, m_sb.z);
                __syncwarp();
                float yg[4] = {}, yu[4] = {};
                const uint32_t* pb = pre + ((g >> 1) & 1) * 64 + bb * 32 + t;
#pragma unroll
                for (int s = 0; s < 4; s++) {
                    const uint32_t b0 = pb[8 * s], b1 = pb[8 * s + 4];
                    mma16816(yg, gf[s], b0, b1);
                    mma16816(yu, uf[s], b0, b1);
                }
                const float y0 = t < 2 ? yg[0] : yu[0], y1 = t < 2 ? yg[1] : yu[1], y2 = t < 2 ? yg[2] : yu[2], y3 = t < 2 ? yg[3] : yu[3];
                float* dstp = bc + warp * 128 + (t >> 1) * 64 + (t & 1) * 32;
                *(float2*)&dstp[g * 2] = make_float2(y0, y1);
                *(float2*)&dstp[(g + 8) * 2] = make_float2(y2, y3);
                __syncwarp();
                if (lane == 0) mbar_arrive(bar_bc);
            }
            if (warp == 0) TSTAMP(11);
            float pivot2;
            {
                while (clock32() - t_wo < DELAY_X1) {}
                bool okx = false, okp = false;
                for (int it = 0;; it++) {
                    if (!okx) { va = ld_ll4(px); vb = ld_ll4(px + 1); }
                    if (!okp) { pa = ld_ll4(pp); pb = ld_ll4(pp + 1); }
                    okx = va.y == F_X1 && va.w == F_X1 && vb.y == F_X1 && vb.w == F_X1;
                    okp = pa.y == F_X1 && pa.w == F_X1 && pb.y == F_X1 && pb.w == F_X1;
                    if (__all_sync(0xffffffffu, okx && okp) || it > SPIN_LIMIT) break;
                }
                if (warp == 0) TSTAMP(9);
                const float xv[4] = {eb ? bf_hi(va.x) : bf_lo(va.x), eb ? bf_hi(va.z) : bf_lo(va.z),
                                     eb ? bf_hi(vb.x) : bf_lo(vb.x), eb ? bf_hi(vb.z) : bf_lo(vb.z)};
                const float p0 = 0.25f * ((bf_lo(pa.x) + bf_lo(pa.z)) + (bf_lo(pb.x) + bf_lo(pb.z)));
                const float p1 = 0.25f * ((bf_hi(pa.x) + bf_hi(pa.z)) + (bf_hi(pb.x) + bf_hi(pb.z)));
                const float pivot = eb ? p1 : p0;
                pivot2 = (lane & 1) ? p1 : p0;
                *(uint2*)&hs[eb * 32 + 2 * (lane & 15)] =
                    make_uint2(pack_bf16((xv[0] - pivot) * c1v[0], (xv[1] - pivot) * c1v[1]),
                               pack_bf16((xv[2] - pivot) * c1v[2], (xv[3] - pivot) * c1v[3]));
                __syncwarp();
                float cg[2][4] = {}, cu[2][4] = {};
#pragma unroll
                for (int s = 0; s < 4; s++) {
                    const uint32_t b0 = hs[bb * 32 + 8 * s + t], b1 = hs[bb * 32 + 8 * s + 4 + t];
                    mma16816(cg[s & 1], gf[s], b0, b1);
                    mma16816(cu[s & 1], uf[s], b0, b1);
                }
                const float2 ps = half_warp_sums(xv, pivot);
                if ((lane & 15) == 0) stat[warp * 2 + eb] = ps;
                {
                    const float* bc = (const float*)(sgen + SM_MRG + 4096);
                    mbar_wait(bar_bc, 0);
#pragma unroll
                    for (int w = 0; w < 8; w++) {
                        bg += bc[w * 128 + lane]; cgc += bc[w * 128 + 32 + lane];
                        bu += bc[w * 128 + 64 + lane]; cuc += bc[w * 128 + 96 + lane];
                    }
                }
                if (t < 2) {
                    float v[4];
#pragma unroll
                    for (int i = 0; i < 4; i++) v[i] = t ? cu[0][i] + cu[1][i] : cg[0][i] + cg[1][i];
                    *(float2*)&red[warp * 64 + t * 32 + g * 2] = make_float2(v[0], v[1]);
                    *(float2*)&red[warp * 64 + t * 32 + (g + 8) * 2] = make_float2(v[2], v[3]);
                }
            }
            uint32_t df[4][4];
            mbar_wait(bar_full + 8 * (IDX_WD % NST), (IDX_WD / NST) & 1);
#pragma unroll
            for (int mt = 0; mt < 4; mt++) ldsm4t((sbase + SM_RING + (IDX_WD % NST) * TILE + aoff) ^ (mt << 5), df[mt]);
            cons_sync();
            {
                float gs = 0.f, us = 0.f;
#pragma unroll
                for (int w = 0; w < 8; w++) { gs += red[w * 64 + lane]; us += red[w * 64 + 32 + lane]; }
                float mean_bf, rstd;
                ln_stats(stat, lane & 1, pivot2, mean_bf, rstd);
                const float dm = mean_bf - pivot2;
                gs = bf16r(rstd * (gs - dm * bg) + cgc);
                us = rstd * (us - dm * bu) + cuc;
                const float u2 = gs * (1.0f + 0.044715f * gs * gs) * (2.0f * 0.7978845608028654f * LOG2E);
                const float ge = bf16r(__fdividef(gs, 1.0f + ex2(-u2)));
                const float act = bf16r(ge * bf16r(us));
                const float a0 = __shfl_sync(0xffffffffu, act, 4 * t + bb), a1 = __shfl_sync(0xffffffffu, act, 4 * t + 2 + bb);
                const float a2 = __shfl_sync(0xffffffffu, act, 4 * t + 16 + bb), a3 = __shfl_sync(0xffffffffu, act, 4 * t + 18 + bb);
                const uint32_t b0 = pack_bf16(a0, a1), b1 = pack_bf16(a2, a3);
                float y[4][4] = {};
#pragma unroll
                for (int mt = 0; mt < 4; mt++) mma16816(y[mt], df[mt], b0, b1);
                float v[4];
#pragma unroll
                for (int i = 0; i < 4; i++) v[i] = t == 0 ? y[0][i] : t == 1 ? y[1][i] : t == 2 ? y[2][i] : y[3][i];
            {
                const bool odd = g & 1;
                const float sx = odd ? v[0] : v[2], sy = odd ? v[1] : v[3];
                const float rx = __shfl_xor_sync(0xffffffffu, sx, 4), ry = __shfl_xor_sync(0xffffffffu, sy, 4);
                const int c0 = 64 * warp + 16 * t + (odd ? g + 7 : g);
                const float e0 = odd ? rx : v[0], e1 = odd ? ry : v[1], e2 = odd ? v[2] : rx, e3 = odd ? v[3] : ry;
                st_v4(&sc->inbox_dn[c0 >> 2][cta][(c0 >> 1) & 1], tagf(e0, F_DOWN), tagf(e1, F_DOWN), tagf(e2, F_DOWN), tagf(e3, F_DOWN));
            }
            }
            if (warp == 0) TSTAMP(12);
        }
        {
            uint2 xw;
            float r0;
            {
                const uint4* pin = &sc->inbox_dn[cta][0][0] + tid;
                uint4 v = make_uint4(F_DOWN, F_DOWN, F_DOWN, F_DOWN);
                if (cta < NFFN) spin_cycles(DELAY_C);
                else while (clock32() - t_wo < DELAY_X1 + DELAY_NOFFN) {}
                xw = ld_ll2(&sc->x1[ocol]);
                bool ok = tid >= NFFN * 2;
                for (int it = 0;; it++) {
                    if (!ok) {
                        v = ld_ll4(pin);
                        ok = (v.x & v.y & v.z & v.w & 3u) == F_DOWN;
                    }
                    if (__all_sync(0xffffffffu, ok) || it > SPIN_LIMIT) break;
                }
                const bool u1 = lane & 2, u2 = lane & 4;
                const float a0 = untag(v.x), a1 = untag(v.y), a2 = untag(v.z), a3 = untag(v.w);
                const float k0 = (u1 ? a1 : a0) + __shfl_xor_sync(0xffffffffu, u1 ? a0 : a1, 2);
                const float k1 = (u1 ? a3 : a2) + __shfl_xor_sync(0xffffffffu, u1 ? a2 : a3, 2);
                r0 = (u2 ? k1 : k0) + __shfl_xor_sync(0xffffffffu, u2 ? k0 : k1, 4);
                r0 += __shfl_xor_sync(0xffffffffu, r0, 8);
                r0 += __shfl_xor_sync(0xffffffffu, r0, 16);
                if (lane < 8) red2[256 + warp * 8 + (2 * (lane & 1) + ((lane >> 2) & 1)) * 2 + ((lane >> 1) & 1)] = r0;
            }
            cons_sync();
            if (warp == 0) {
                float a0 = 0.f, a1 = 0.f;
#pragma unroll
                for (int w = 0; w < 8; w++) { const float2 v = *(const float2*)&red2[256 + w * 8 + (lane & 3) * 2]; a0 += v.x; a1 += v.y; }
                const bool hi = ocol & 1;
                const float gb0 = hi ? bf_hi(m_gb0.x) : bf_lo(m_gb0.x), gb1 = hi ? bf_hi(m_gb1.x) : bf_lo(m_gb1.x);
                for (int it = 0; !__all_sync(0xffffffffu, xw.y == F_X1) && it < SPIN_LIMIT; it++) xw = ld_ll2(&sc->x1[ocol]);
                if (lane < 4) {
                    p.out[ocol] = __float2bfloat16_rn(bf_lo(xw.x) + bf16r(gb0 * bf16r(a0)));
                    p.out[D_MODEL + ocol] = __float2bfloat16_rn(bf_hi(xw.x) + bf16r(gb1 * bf16r(a1)));
                }
                TSTAMP(13);
            }
        }
    }
}

typedef CUresult (*EncodeFn)(CUtensorMap*, CUtensorMapDataType, cuuint32_t, void*, const cuuint64_t*, const cuuint64_t*,
                             const cuuint32_t*, const cuuint32_t*, CUtensorMapInterleave, CUtensorMapSwizzle,
                             CUtensorMapL2promotion, CUtensorMapFloatOOBfill);

struct Maps { CUtensorMap k, v, wq, wmod, wmod8, wo, wg, wu, wd; };

void encode(EncodeFn fn, CUtensorMap* m, const void* ptr, int rank, const cuuint64_t* dims, const cuuint64_t* strides,
            const cuuint32_t* box, CUtensorMapSwizzle sw) {
    const cuuint32_t es[3] = {1, 1, 1};
    fn(m, CU_TENSOR_MAP_DATA_TYPE_BFLOAT16, rank, const_cast<void*>(ptr), dims, strides, box, es,
       CU_TENSOR_MAP_INTERLEAVE_NONE, sw, CU_TENSOR_MAP_L2_PROMOTION_L2_256B, CU_TENSOR_MAP_FLOAT_OOB_FILL_NONE);
}

}

extern "C" void kernel_launch(void* const* d_in, const int* in_sizes, int n_in, void* d_out, int out_size) {
    (void)in_sizes; (void)n_in; (void)out_size;
    static EncodeFn enc = nullptr;
    static Scratch* scratch = nullptr;
    if (!enc) {
        cudaGetSymbolAddress((void**)&scratch, g_scratch);
        void* fn = nullptr;
        cudaDriverEntryPointQueryResult qr;
        cudaGetDriverEntryPoint("cuTensorMapEncodeTiled", &fn, cudaEnableDefault, &qr);
        enc = (EncodeFn)fn;
        cudaFuncSetAttribute(fused_block_kernel, cudaFuncAttributeMaxDynamicSharedMemorySize, SMEM_BYTES);
    }
    Maps m;
    {
        const cuuint64_t dims[3] = {64, (cuuint64_t)16 * SK, 2}, str[2] = {256, 128};
        const cuuint32_t box[3] = {64, 64, 2};
        encode(enc, &m.k, d_in[1], 3, dims, str, box, CU_TENSOR_MAP_SWIZZLE_128B);
        encode(enc, &m.v, d_in[2], 3, dims, str, box, CU_TENSOR_MAP_SWIZZLE_128B);
    }
    {
        const cuuint64_t dims[2] = {4096, 512}, str[1] = {8192};
        const cuuint32_t box[2] = {32, 256};
        encode(enc, &m.wq, d_in[3], 2, dims, str, box, CU_TENSOR_MAP_SWIZZLE_64B);
    }
    {
        const cuuint64_t dims[2] = {N_MOD, 512}, str[1] = {N_MOD * 2};
        const cuuint32_t box[2] = {16, 256};
        encode(enc, &m.wmod, d_in[10], 2, dims, str, box, CU_TENSOR_MAP_SWIZZLE_32B);
        const cuuint32_t box8[2] = {8, 256};
        encode(enc, &m.wmod8, d_in[10], 2, dims, str, box8, CU_TENSOR_MAP_SWIZZLE_NONE);
    }
    {
        const cuuint64_t dims_o[3] = {64, 4096, 8}, dims_d[3] = {64, D_FF, 8}, str[2] = {1024, 128};
        const cuuint32_t box[3] = {64, 16, 8}, box_o[3] = {64, 64, 2};
        encode(enc, &m.wo, d_in[4], 3, dims_o, str, box_o, CU_TENSOR_MAP_SWIZZLE_128B);
        encode(enc, &m.wd, d_in[8], 3, dims_d, str, box, CU_TENSOR_MAP_SWIZZLE_128B);
    }
    {
        const cuuint64_t dims[2] = {D_FF, 512}, str[1] = {D_FF * 2};
        const cuuint32_t box[2] = {16, 128};
        encode(enc, &m.wg, d_in[6], 2, dims, str, box, CU_TENSOR_MAP_SWIZZLE_32B);
        encode(enc, &m.wu, d_in[7], 2, dims, str, box, CU_TENSOR_MAP_SWIZZLE_32B);
    }
    Params p;
    p.x = (const __nv_bfloat16*)d_in[0];
    p.c = (const __nv_bfloat16*)d_in[9];
    p.out = (__nv_bfloat16*)d_out;
    p.sc = scratch;
    fused_block_kernel<<<NCTA, NTHREADS, SMEM_BYTES, cudaStreamPerThread>>>(p, m.k, m.v, m.wq, m.wmod, m.wmod8, m.wo, m.wg, m.wu, m.wd);
}
```

```cpp
#include <cuda_runtime.h>
#include <cuda.h>
#include <cuda_bf16.h>
#include <stdint.h>

namespace {

constexpr int D_MODEL = 512;
constexpr int N_HEADS = 32;
constexpr int SK = 32768;
constexpr int DH = 128;
constexpr int D_FF = 1792;
constexpr int N_MOD = 6 * D_MODEL;

constexpr int NCTA = 128;
constexpr int NFFN = D_FF / 16;
constexpr int NOWN = 32;
constexpr int NTHREADS = 320;
constexpr int NST = 12;
constexpr int TILE = 16384;
#define WINDOW 3
#define WINDOW_TAIL 1
#define GU_WIN 3
#define PACE_THR 96
constexpr int KV_TILES = 64;
#define MOD_AT 8
static_assert(MOD_AT % 2 == 0 && MOD_AT >= 2 && MOD_AT < 56, "schedule");
__host__ __device__ constexpr int kv_idx(int i) { return 2 + 2 * i + (i >= MOD_AT ? 1 : 0); }
constexpr int IDX_MOD = 2 + 2 * MOD_AT;
constexpr int N_STREAM = kv_idx(KV_TILES - 1) + 2;
constexpr int IDX_WO = N_STREAM;
constexpr int IDX_WG = IDX_WO + 2;
constexpr int IDX_WU = IDX_WG + 1;
constexpr int IDX_WD = IDX_WU + 1;
constexpr int SPIN_LIMIT = 1 << 20;

constexpr float LOG2E = 1.4426950408889634f;
constexpr float QK_SCALE = 0.08838834764831845f;

constexpr int SM_RING = 0;
constexpr int SM_MRG = SM_RING + NST * TILE;
constexpr int SM_ML = SM_MRG + 8 * 4 * 136 * 4;
constexpr int SM_RED = SM_ML + 8 * 4 * 8;
constexpr int SM_RED2 = SM_RED + 8 * 64 * 4;
constexpr int SM_QS = SM_RED2 + 8 * 64 * 4;
constexpr int SM_OS = SM_QS + 512 * 2;
constexpr int SM_SC = SM_OS + 2 * 128 * 2;
constexpr int SM_HS = SM_SC + 2 * 512 * 2;
constexpr int SM_STAT = SM_HS + 8 * 2 * 32 * 4;
constexpr int SM_PACE = SM_STAT + 8 * 2 * 8;
constexpr int SM_BAR = SM_PACE + 16;
constexpr int SM_END = SM_BAR + (2 * NST + 1 + 8 + 3) * 8;
constexpr int SMEM_BYTES = SM_END + 1024;

struct Scratch {
    uint4 inbox_wo[NOWN][N_HEADS][8];
    uint4 inbox_dn[NCTA][NFFN][2];
    uint2 x1[D_MODEL];
    uint2 part_o[NCTA][4][64];
    uint2 part_ml[NCTA][4][4];
    uint2 mod[2][N_MOD / 2];
    uint2 q[2][N_HEADS * DH / 2];
    unsigned epoch;
    unsigned pad_[31];
    unsigned cleared;
    unsigned pad2_[31];
    unsigned progress;
};
__device__ Scratch g_scratch;
constexpr uint32_t F_PART = 1, F_WO = 1, F_DOWN = 1, F_X1 = 1;
__device__ __forceinline__ uint32_t tagf(float v, uint32_t f) { return (__float_as_uint(v) & ~3u) | f; }
__device__ __forceinline__ float untag(uint32_t v) { return __uint_as_float(v & ~3u); }

struct Params {
    const __nv_bfloat16* x;
    const __nv_bfloat16* c;
    __nv_bfloat16* out;
    Scratch* sc;
};

#define TSTAMP(i) do { } while (0)

__device__ __forceinline__ uint32_t smem_u32(const void* p) { return (uint32_t)__cvta_generic_to_shared(p); }

__device__ __forceinline__ void mbar_init(uint32_t bar, uint32_t cnt) {
    asm volatile("mbarrier.init.shared::cta.b64 [%0], %1;" ::"r"(bar), "r"(cnt) : "memory");
}
__device__ __forceinline__ void mbar_expect_tx(uint32_t bar, uint32_t bytes) {
    asm volatile("mbarrier.arrive.expect_tx.shared::cta.b64 _, [%0], %1;" ::"r"(bar), "r"(bytes) : "memory");
}
__device__ __forceinline__ void mbar_arrive(uint32_t bar) {
    asm volatile("mbarrier.arrive.shared::cta.b64 _, [%0];" ::"r"(bar) : "memory");
}
__device__ __forceinline__ bool mbar_try(uint32_t bar, uint32_t parity) {
    uint32_t ok;
    asm volatile(
        "{\n\t.reg .pred p;\n\t"
        "mbarrier.try_wait.parity.shared::cta.b64 p, [%1], %2;\n\t"
        "selp.u32 %0, 1, 0, p;\n\t}"
        : "=r"(ok) : "r"(bar), "r"(parity) : "memory");
    return ok != 0;
}
__device__ __forceinline__ void mbar_wait(uint32_t bar, uint32_t parity) {
    if (mbar_try(bar, parity)) return;
    const long long t0 = clock64();
    while (!mbar_try(bar, parity))
        if (clock64() - t0 > (1ll << 31)) return;
}
__device__ __forceinline__ void cons_sync() { asm volatile("bar.sync 1, 256;" ::: "memory"); }

__device__ __forceinline__ void tma_2d(uint32_t dst, const CUtensorMap* m, int c0, int c1, uint32_t bar) {
    asm volatile("cp.async.bulk.tensor.2d.shared::cluster.global.mbarrier::complete_tx::bytes [%0], [%1, {%3, %4}], [%2];"
                 ::"r"(dst), "l"(m), "r"(bar), "r"(c0), "r"(c1) : "memory");
}
__device__ __forceinline__ void tma_3d(uint32_t dst, const CUtensorMap* m, int c0, int c1, int c2, uint32_t bar) {
    asm volatile("cp.async.bulk.tensor.3d.shared::cluster.global.mbarrier::complete_tx::bytes [%0], [%1, {%3, %4, %5}], [%2];"
                 ::"r"(dst), "l"(m), "r"(bar), "r"(c0), "r"(c1), "r"(c2) : "memory");
}
__device__ __forceinline__ void tma_3d_hint(uint32_t dst, const CUtensorMap* m, int c0, int c1, int c2, uint32_t bar, uint64_t pol) {
    asm volatile("cp.async.bulk.tensor.3d.shared::cluster.global.mbarrier::complete_tx::bytes.L2::cache_hint [%0], [%1, {%3, %4, %5}], [%2], %6;"
                 ::"r"(dst), "l"(m), "r"(bar), "r"(c0), "r"(c1), "r"(c2), "l"(pol) : "memory");
}
__device__ __forceinline__ void prefetch_tmap(const CUtensorMap* m) {
    asm volatile("prefetch.tensormap [%0];" ::"l"(m) : "memory");
}

__device__ __forceinline__ void ldsm4(uint32_t addr, uint32_t (&r)[4]) {
    asm volatile("ldmatrix.sync.aligned.m8n8.x4.shared.b16 {%0,%1,%2,%3}, [%4];"
                 : "=r"(r[0]), "=r"(r[1]), "=r"(r[2]), "=r"(r[3]) : "r"(addr) : "memory");
}
__device__ __forceinline__ void ldsm4t(uint32_t addr, uint32_t (&r)[4]) {
    asm volatile("ldmatrix.sync.aligned.m8n8.x4.trans.shared.b16 {%0,%1,%2,%3}, [%4];"
                 : "=r"(r[0]), "=r"(r[1]), "=r"(r[2]), "=r"(r[3]) : "r"(addr) : "memory");
}
__device__ __forceinline__ void mma16816(float (&c)[4], const uint32_t (&a)[4], uint32_t b0, uint32_t b1) {
    asm volatile("mma.sync.aligned.m16n8k16.row.col.f32.bf16.bf16.f32 {%0,%1,%2,%3}, {%4,%5,%6,%7}, {%8,%9}, {%0,%1,%2,%3};"
                 : "+f"(c[0]), "+f"(c[1]), "+f"(c[2]), "+f"(c[3])
                 : "r"(a[0]), "r"(a[1]), "r"(a[2]), "r"(a[3]), "r"(b0), "r"(b1));
}
__device__ __forceinline__ uint32_t movmatrix_t(uint32_t a) {
    uint32_t d;
    asm volatile("movmatrix.sync.aligned.m8n8.trans.b16 %0, %1;" : "=r"(d) : "r"(a));
    return d;
}
__device__ __forceinline__ uint32_t pack_bf16(float a, float b) {
    uint32_t r;
    asm("cvt.rn.bf16x2.f32 %0, %1, %2;" : "=r"(r) : "f"(b), "f"(a));
    return r;
}
__device__ __forceinline__ float bf_lo(uint32_t v) { return __uint_as_float(v << 16); }
__device__ __forceinline__ float bf_hi(uint32_t v) { return __uint_as_float(v & 0xffff0000u); }
__device__ __forceinline__ float bf16r(float a) { return bf_lo(pack_bf16(a, 0.f)); }
__device__ __forceinline__ uint32_t max_bf16x2(uint32_t a, uint32_t b) {
    uint32_t r;
    asm("max.bf16x2 %0, %1, %2;" : "=r"(r) : "r"(a), "r"(b));
    return r;
}
__device__ __forceinline__ float ex2(float x) {
    float r;
    asm("ex2.approx.ftz.f32 %0, %1;" : "=f"(r) : "f"(x));
    return r;
}

__device__ __forceinline__ void st_ll2(uint2* p, uint32_t v, uint32_t tag) {
    asm volatile("st.relaxed.gpu.global.v2.u32 [%0], {%1, %2};" ::"l"(p), "r"(v), "r"(tag) : "memory");
}
__device__ __forceinline__ void st_v4(uint4* p, uint32_t a, uint32_t b, uint32_t c, uint32_t d) {
    asm volatile("st.relaxed.gpu.global.v4.u32 [%0], {%1, %2, %3, %4};" ::"l"(p), "r"(a), "r"(b), "r"(c), "r"(d) : "memory");
}
__device__ __forceinline__ uint2 ld_ll2(const uint2* p) {
    uint2 v;
    asm volatile("ld.relaxed.gpu.global.v2.u32 {%0, %1}, [%2];" : "=r"(v.x), "=r"(v.y) : "l"(p) : "memory");
    return v;
}
__device__ __forceinline__ uint4 ld_ll4(const uint4* p) {
    uint4 v;
    asm volatile("ld.relaxed.gpu.global.v4.u32 {%0, %1, %2, %3}, [%4];"
                 : "=r"(v.x), "=r"(v.y), "=r"(v.z), "=r"(v.w) : "l"(p) : "memory");
    return v;
}

#define DELAY_P1 1800
#define DELAY_Q 1800
#define DELAY_A 1000
#define DELAY_B1 300
#define DELAY_X1 2000
#define DELAY_NOFFN 1500
#define DELAY_C 600
__device__ __forceinline__ uint32_t clock32() {
    uint32_t c;
    asm volatile("mov.u32 %0, %clock;" : "=r"(c));
    return c;
}
__device__ __forceinline__ void spin_cycles(uint32_t n) {
    if (n > 0) { const uint32_t c0 = clock32(); while (clock32() - c0 < n) {} }
}
__device__ __forceinline__ float rcp_approx(float x) {
    float r;
    asm("rcp.approx.ftz.f32 %0, %1;" : "=f"(r) : "f"(x));
    return r;
}
__device__ __forceinline__ float sqrt_approx(float x) {
    float r;
    asm("sqrt.approx.f32 %0, %1;" : "=f"(r) : "f"(x));
    return r;
}

__device__ __forceinline__ float silu_bf(float v) { return bf16r(v / (1.0f + expf(-v))); }

__device__ __forceinline__ float2 half_warp_sums(const float (&v)[4], float pivot) {
    float s1 = 0.f, s2 = 0.f;
#pragma unroll
    for (int i = 0; i < 4; i++) { const float d = v[i] - pivot; s1 += d; s2 += d * d; }
#pragma unroll
    for (int o = 1; o < 16; o <<= 1) { s1 += __shfl_xor_sync(0xffffffffu, s1, o); s2 += __shfl_xor_sync(0xffffffffu, s2, o); }
    return make_float2(s1, s2);
}
template <bool PRECISE>
__device__ __forceinline__ void ln_stats(const float2* stat, int b, float pivot, float& mean_bf, float& std_bf) {
    float s1 = 0.f, s2 = 0.f;
#pragma unroll
    for (int w = 0; w < 8; w++) { const float2 v = stat[w * 2 + b]; s1 += v.x; s2 += v.y; }
    const float dm = s1 * (1.0f / D_MODEL);
    const float var = fmaxf(s2 * (1.0f / D_MODEL) - dm * dm, 0.f);
    mean_bf = bf16r(pivot + dm);
    const float ve = bf16r(bf16r(var) + 1e-5f);
    std_bf = bf16r(PRECISE ? sqrtf(ve) : sqrt_approx(ve));
}
__device__ __forceinline__ float ln_mod(float n, float cmul, float sadd) { return bf16r(n * bf16r(1.0f + cmul)) + sadd; }

__global__ void __launch_bounds__(NTHREADS, 1)
fused_block_kernel(const Params p, const __grid_constant__ CUtensorMap tm_k, const __grid_constant__ CUtensorMap tm_v,
                   const __grid_constant__ CUtensorMap tm_wq, const __grid_constant__ CUtensorMap tm_wmod,
                   const __grid_constant__ CUtensorMap tm_wmod8,
                   const __grid_constant__ CUtensorMap tm_wo, const __grid_constant__ CUtensorMap tm_wg,
                   const __grid_constant__ CUtensorMap tm_wu, const __grid_constant__ CUtensorMap tm_wd) {
    extern __shared__ unsigned char smem_raw[];
    const uint32_t sbase = (smem_u32(smem_raw) + 1023u) & ~1023u;
    unsigned char* sgen = smem_raw + (sbase - smem_u32(smem_raw));
    const int tid = threadIdx.x, warp = tid >> 5, lane = tid & 31;
    const int cta = blockIdx.x;
    const uint32_t bar_full = sbase + SM_BAR, bar_empty = bar_full + NST * 8;
    const uint32_t bar_clear = bar_empty + NST * 8;
    const uint32_t bar_gu = bar_clear + 8;
    const uint32_t bar_bc = bar_gu + 8 * 8;
    const uint32_t bar_p0w = bar_bc + 8;
    const uint32_t bar_gate = bar_p0w + 8;

    const int key0 = (cta >> 3) * SK + (cta & 7) * 64;
    uint64_t pol = 0;
    if (tid == 256) {
        asm volatile("createpolicy.fractional.L2::evict_first.b64 %0, 1.0;" : "=l"(pol));
        mbar_init(bar_p0w, 1);
#pragma unroll
        for (int i = 0; i < 4; i++) mbar_init(bar_full + 8 * i, 1);
        asm volatile("fence.mbarrier_init.release.cluster;" ::: "memory");
        mbar_expect_tx(bar_p0w, 8192);
#pragma unroll
        for (int i = 0; i < 4; i++) mbar_expect_tx(bar_full + 8 * i, TILE);
        tma_3d_hint(sbase + SM_RING + 2 * TILE, &tm_k, 0, key0, 0, bar_full + 16, pol);
        tma_2d(sbase + SM_MRG, &tm_wmod8, cta * 8, 0, bar_p0w);
        tma_2d(sbase + SM_MRG + 4096, &tm_wmod8, cta * 8, 256, bar_p0w);
        tma_2d(sbase + SM_RING, &tm_wq, cta * 32, 0, bar_full);
        tma_2d(sbase + SM_RING + TILE, &tm_wq, cta * 32, 256, bar_full + 8);
        tma_3d_hint(sbase + SM_RING + 3 * TILE, &tm_v, 0, key0, 0, bar_full + 24, pol);
    }

    if (warp == 8) {
        if (lane == 0) {
            for (int i = 0; i < NST; i++) { if (i >= 4) mbar_init(bar_full + 8 * i, 1); mbar_init(bar_empty + 8 * i, 4); }
            mbar_init(bar_clear, 1);
            for (int k = 0; k < 8; k++) mbar_init(bar_gu + 8 * k, 1);
            mbar_init(bar_bc, 8);
            mbar_init(bar_gate, 1);
            ((volatile uint32_t*)(sgen + SM_PACE))[0] = 0;
            ((volatile uint32_t*)(sgen + SM_PACE))[1] = WINDOW;
            asm volatile("fence.mbarrier_init.release.cluster;" ::: "memory");
        }
        __syncwarp();
        asm volatile("bar.arrive 2, 288;" ::: "memory");
        asm volatile("bar.arrive 3, 64;" ::: "memory");
        if (lane == 0) {
            int slot = 4; uint32_t ph = 1;
            int landed = 0, wslot = 0; uint32_t wph = 0;
            int kv = 2;
            auto wait_window = [&](int idx, int window) {
                while (landed + window <= idx) {
                    mbar_wait(bar_full + 8 * wslot, wph);
                    if (++wslot == NST) { wslot = 0; wph ^= 1; }
                    landed++;
                }
            };
            volatile uint32_t* pace = (volatile uint32_t*)(sgen + SM_PACE);
            prefetch_tmap(&tm_wmod);
            pace[0] = 4;
            for (int idx = 4; idx < N_STREAM; idx++) {
                if (idx >= NST) mbar_wait(bar_empty + 8 * slot, ph);
                wait_window(idx, (int)pace[1]);
                if (idx == 12) { prefetch_tmap(&tm_wo); prefetch_tmap(&tm_wg); prefetch_tmap(&tm_wu); prefetch_tmap(&tm_wd); }
                const uint32_t fb = bar_full + 8 * slot, dst = sbase + SM_RING + slot * TILE;
                mbar_expect_tx(fb, TILE);
                if (idx == IDX_MOD) {
                    tma_2d(dst, &tm_wmod, 1024 + cta * 16, 0, fb);
                    tma_2d(dst + 8192, &tm_wmod, 1024 + cta * 16, 256, fb);
                } else {
                    tma_3d_hint(dst, (kv & 1) ? &tm_v : &tm_k, 0, key0 + (kv >> 1) * 512, 0, fb, pol);
                    kv++;
                }
                pace[0] = idx + 1;
                if (++slot == NST) { slot = 0; ph ^= 1; }
            }
            auto slot_free = [&](int idx) { mbar_wait(bar_empty + 8 * (idx % NST), ((idx / NST) & 1) ^ 1); };
#pragma unroll
            for (int s = 0; s < 2; s++) {
                const int idx = IDX_WO + s;
                slot_free(idx);
                wait_window(idx, WINDOW_TAIL);
                mbar_expect_tx(bar_full + 8 * (idx % NST), TILE);
                tma_3d(sbase + SM_RING + (idx % NST) * TILE, &tm_wo, 0, (cta >> 2) * 128 + s * 64, (cta & 3) * 2, bar_full + 8 * (idx % NST));
            }
            if (cta < NFFN) {
                slot_free(IDX_WG); slot_free(IDX_WU);
                mbar_wait(bar_full + 8 * (IDX_WO % NST), (IDX_WO / NST) & 1);
                mbar_wait(bar_full + 8 * ((IDX_WO + 1) % NST), ((IDX_WO + 1) / NST) & 1);
#pragma unroll
                for (int st = 0; st < 8; st++) {
                    if (st >= GU_WIN) mbar_wait(bar_gu + 8 * (st - GU_WIN), 0);
                    mbar_expect_tx(bar_gu + 8 * st, 4096);
                    tma_2d(sbase + SM_RING + (((st & 1) ? IDX_WU : IDX_WG) % NST) * TILE + (st >> 1) * 4096,
                           (st & 1) ? &tm_wu : &tm_wg, cta * 16, (st >> 1) * 128, bar_gu + 8 * st);
                }
                mbar_wait(bar_gu + 8 * 6, 0);
                slot_free(IDX_WD);
                mbar_expect_tx(bar_full + 8 * (IDX_WD % NST), TILE);
                tma_3d(sbase + SM_RING + (IDX_WD % NST) * TILE, &tm_wd, 0, cta * 16, 0, bar_full + 8 * (IDX_WD % NST));
            }
        }
    } else if (warp == 9) {
        Scratch* const sc = p.sc;
        const uint32_t tag = *(volatile unsigned*)&sc->epoch + 1;
        asm volatile("bar.sync 3, 64;" ::: "memory");
#pragma unroll 4
        for (int i = 0; i < NFFN * 2 / 32; i++) st_v4(&sc->inbox_dn[cta][0][0] + i * 32 + lane, 0u, 0u, 0u, 0u);
        if (cta >= NCTA - NOWN) {
#pragma unroll 4
            for (int i = 0; i < 8; i++) st_v4(&sc->inbox_wo[cta - (NCTA - NOWN)][0][0] + i * 32 + lane, 0u, 0u, 0u, 0u);
            if (lane < 8) st_v4((uint4*)&sc->x1[(cta - (NCTA - NOWN)) * 16] + lane, 0u, 0u, 0u, 0u);
        }
#pragma unroll 4
        for (int i = 0; i < 4; i++) st_v4((uint4*)&sc->part_o[cta][0][0] + i * 32 + lane, 0u, 0u, 0u, 0u);
        if (lane < 8) st_v4((uint4*)&sc->part_ml[cta][0][0] + lane, 0u, 0u, 0u, 0u);
        if (cta == 0 && lane == 0) asm volatile("st.relaxed.gpu.global.u32 [%0], %1;" ::"l"(&sc->progress), "r"(0u) : "memory");
        asm volatile("fence.acq_rel.gpu;" ::: "memory");
        __syncwarp();
        if (lane == 0) {
            asm volatile("fence.acq_rel.gpu;" ::: "memory");
            asm volatile("red.relaxed.gpu.global.add.u32 [%0], %1;" ::"l"(&sc->cleared), "r"(1u) : "memory");
            const uint32_t target = tag * NCTA;
            for (int it = 0; it < SPIN_LIMIT; it++) {
                uint32_t v;
                asm volatile("ld.relaxed.gpu.global.u32 %0, [%1];" : "=r"(v) : "l"(&sc->cleared) : "memory");
                if ((int32_t)(v - target) >= 0) break;
                __nanosleep(500);
            }
            asm volatile("fence.acq_rel.gpu;" ::: "memory");
            mbar_arrive(bar_clear);
            volatile uint32_t* pace = (volatile uint32_t*)(sgen + SM_PACE);
            uint32_t posted = 0;
            for (int it = 0; it < SPIN_LIMIT; it++) {
                const uint32_t own = pace[0];
                if (own > posted) {
                    asm volatile("red.relaxed.gpu.global.add.u32 [%0], %1;" ::"l"(&sc->progress), "r"(own - posted) : "memory");
                    posted = own;
                }
                uint32_t v;
                asm volatile("ld.relaxed.gpu.global.u32 %0, [%1];" : "=r"(v) : "l"(&sc->progress) : "memory");
                if (own >= N_STREAM) {
                    if (v >= NCTA * N_STREAM) break;
                } else {
                    const int diff = (int)v - (int)own * NCTA;
                    pace[1] = diff > PACE_THR ? WINDOW + 1 : diff < -PACE_THR ? WINDOW - 1 : WINDOW;
                }
                __nanosleep(own + 3 >= N_STREAM ? 30 : 200);
            }
            pace[2] = clock32();
            mbar_arrive(bar_gate);
            if (cta == 0) asm volatile("st.relaxed.gpu.global.u32 [%0], %1;" ::"l"(&sc->epoch), "r"(tag) : "memory");
        }
    } else {
        const int g = lane >> 2, t = lane & 3;
        const int bb = g & 1;
        const int eb = lane >> 4;
        const int ec = 64 * warp + 4 * (lane & 15);
        if (warp == 0) TSTAMP(0);
        Scratch* const sc = p.sc;
        const float c00 = __bfloat162float(p.c[tid]), c01 = __bfloat162float(p.c[tid + 256]);
        const float c10 = __bfloat162float(p.c[D_MODEL + tid]), c11 = __bfloat162float(p.c[D_MODEL + tid + 256]);
        const uint2 xe = __ldg((const uint2*)(p.x + eb * D_MODEL + ec));
        const float xpivot = __bfloat162float(p.x[eb * D_MODEL]);
        const uint32_t tag = *(volatile unsigned*)&sc->epoch + 1;
        const int ocol = cta * 4 + (lane & 3);
        const int wcol = (cta >= NCTA - NOWN ? cta - (NCTA - NOWN) : 0) * 16 + (lane & 15);
        const float xo = __bfloat162float(p.x[eb * D_MODEL + wcol]);

        float* red = (float*)(sgen + SM_RED);
        float* red2 = (float*)(sgen + SM_RED2);
        float2* stat = (float2*)(sgen + SM_STAT);
        uint32_t* hs = (uint32_t*)(sgen + SM_HS) + warp * 64;
        float xn[4];
        {
            float xv[4] = {bf_lo(xe.x), bf_hi(xe.x), bf_lo(xe.y), bf_hi(xe.y)};
            const float2 ps = half_warp_sums(xv, xpivot);
            if ((lane & 15) == 0) stat[warp * 2 + eb] = ps;
            const float s00 = silu_bf(c00), s01 = silu_bf(c01), s10 = silu_bf(c10), s11 = silu_bf(c11);
            __nv_bfloat16* scs = (__nv_bfloat16*)(sgen + SM_SC);
            scs[tid] = __float2bfloat16_rn(s00); scs[tid + 256] = __float2bfloat16_rn(s01);
            scs[512 + tid] = __float2bfloat16_rn(s10); scs[512 + tid + 256] = __float2bfloat16_rn(s11);
            asm volatile("bar.sync 2, 288;" ::: "memory");
            if (warp == 0) TSTAMP(23);
            float cp[4] = {0.f, 0.f, 0.f, 0.f};
            const uint32_t* sc32 = (const uint32_t*)(sgen + SM_SC) + bb * 256 + 32 * warp + t;
            mbar_wait(bar_p0w, 0);
#pragma unroll
            for (int s = 0; s < 4; s++) {
                uint32_t r0, r1;
                asm volatile("ldmatrix.sync.aligned.m8n8.x2.trans.shared.b16 {%0,%1}, [%2];"
                             : "=r"(r0), "=r"(r1) : "r"(sbase + SM_MRG + (64 * warp + 16 * s + (lane & 15)) * 16) : "memory");
                const uint32_t a[4] = {r0, r0, r1, r1};
                mma16816(cp, a, sc32[8 * s], sc32[8 * s + 4]);
            }
            if (t == 0) { red[warp * 16 + g] = cp[0]; red[warp * 16 + 8 + g] = cp[1]; }
            if (warp == 0) TSTAMP(14);
            cons_sync();
            if (warp == 0) {
                float s = 0.f;
#pragma unroll
                for (int w = 0; w < 8; w++) s += red[w * 16 + (lane & 15)];
                const float nx = __shfl_down_sync(0xffffffffu, s, 1);
                if (lane < 16 && !(lane & 1))
                    st_ll2(&sc->mod[lane >> 3][cta * 4 + ((lane & 7) >> 1)], pack_bf16(s, nx), tag);
                TSTAMP(1);
            }
            float mean_bf, std_bf;
            ln_stats<true>(stat, eb, xpivot, mean_bf, std_bf);
#pragma unroll
            for (int i = 0; i < 4; i++) xn[i] = bf16r(bf16r(xv[i] - mean_bf) / std_bf);
        }
        {
            uint4 sa, ca;
            spin_cycles(DELAY_P1);
            for (int it = 0;; it++) {
                sa = ld_ll4((const uint4*)&sc->mod[eb][ec >> 1]);
                ca = ld_ll4((const uint4*)&sc->mod[eb][256 + (ec >> 1)]);
                const bool ok = sa.y == tag && sa.w == tag && ca.y == tag && ca.w == tag;
                if (__all_sync(0xffffffffu, ok) || it > SPIN_LIMIT) break;
            }
            *(uint2*)&hs[eb * 32 + 2 * (lane & 15)] =
                make_uint2(pack_bf16(ln_mod(xn[0], bf_lo(ca.x), bf_lo(sa.x)), ln_mod(xn[1], bf_hi(ca.x), bf_hi(sa.x))),
                           pack_bf16(ln_mod(xn[2], bf_lo(ca.z), bf_lo(sa.z)), ln_mod(xn[3], bf_hi(ca.z), bf_hi(sa.z))));
            __syncwarp();
            uint32_t hb[8];
#pragma unroll
            for (int i = 0; i < 8; i++) hb[i] = hs[bb * 32 + 8 * (i >> 1) + 4 * (i & 1) + t];
            if (warp == 0) TSTAMP(2);
            float cq[2][4] = {};
            const int ts = warp >> 2;
            mbar_wait(bar_full + 8 * ts, 0);
            const uint32_t tb = sbase + SM_RING + ts * TILE;
#pragma unroll
            for (int s = 0; s < 4; s++) {
                const int row = 64 * (warp & 3) + 16 * s + (lane & 7) + (lane >> 4) * 8;
#pragma unroll
                for (int mt = 0; mt < 2; mt++) {
                    const int ch = 2 * mt + ((lane >> 3) & 1);
                    uint32_t a[4];
                    ldsm4t(tb + row * 64 + ((ch ^ ((row >> 1) & 3)) << 4), a);
                    mma16816(cq[mt], a, hb[2 * s], hb[2 * s + 1]);
                }
            }
            if (t < 2) {
                const float v0 = t == 0 ? cq[0][0] : cq[1][0], v1 = t == 0 ? cq[0][1] : cq[1][1];
                const float v2 = t == 0 ? cq[0][2] : cq[1][2], v3 = t == 0 ? cq[0][3] : cq[1][3];
                *(float2*)&red2[warp * 64 + (16 * t + g) * 2] = make_float2(v0, v1);
                *(float2*)&red2[warp * 64 + (16 * t + g + 8) * 2] = make_float2(v2, v3);
            }
            cons_sync();
            if (warp < 4 && lane == 0) { mbar_arrive(bar_empty); mbar_arrive(bar_empty + 8); }
            if (warp == 0) {
                const int b = lane >> 4, cp = lane & 15;
                float q0 = 0.f, q1 = 0.f;
#pragma unroll
                for (int w = 0; w < 8; w++) {
                    const float4 v = *(const float4*)&red2[w * 64 + cp * 4];
                    q0 += b ? v.y : v.x; q1 += b ? v.w : v.z;
                }
                st_ll2(&sc->q[b][cta * 16 + cp], pack_bf16(q0, q1), tag);
                TSTAMP(3);
            }
        }
        const int pair = cta >> 3;
        uint32_t qf[16];
        {
            uint2* qs = (uint2*)(sgen + SM_QS);
            if (tid < 128) {
                const uint4* src = (const uint4*)&sc->q[pair >> 3][(pair & 7) * 256] + tid;
                uint4 v;
                spin_cycles(DELAY_Q);
                for (int it = 0;; it++) {
                    v = ld_ll4(src);
                    if ((v.y == tag && v.w == tag) || it > SPIN_LIMIT) break;
                }
                qs[tid] = make_uint2(v.x, v.z);
            }
            cons_sync();
            const uint32_t* q32 = (const uint32_t*)(sgen + SM_QS);
#pragma unroll
            for (int s = 0; s < 8; s++) {
                qf[2 * s] = q32[(g & 3) * 64 + 8 * s + t];
                qf[2 * s + 1] = q32[(g & 3) * 64 + 8 * s + 4 + t];
            }
        }
        if (warp == 0) TSTAMP(4);

        float o[8][4];
#pragma unroll
        for (int i = 0; i < 8; i++) { o[i][0] = o[i][1] = o[i][2] = o[i][3] = 0.f; }
        uint32_t mrun = 0xff80ff80u;
        float ls[4] = {0.f, 0.f, 0.f, 0.f};
        uint4 m_sb, m_cb; uint2 m_ga, m_gb0, m_gb1;
        {
            const int grp = warp >> 2, wi = warp & 3;
            const int krow = 16 * wi + (lane & 7) + ((lane >> 3) & 1) * 8;
            const uint32_t koff = krow * 128 + ((((lane >> 4) & 1) ^ (lane & 7)) << 4);
            const int vrow = 16 * wi + (lane & 7) + (lane >> 4) * 8;
            const uint32_t voff = vrow * 128 + ((((lane >> 3) & 1) ^ (lane & 7)) << 4);
            const uint32_t ones[4] = {0x3f803f80u, 0x3f803f80u, 0x3f803f80u, 0x3f803f80u};
            for (int i = grp; i < KV_TILES; i += 2) {
                if (i == MOD_AT + grp) {
                    float cm[4] = {};
                    const uint32_t* sc32 = (const uint32_t*)(sgen + SM_SC) + bb * 256 + 32 * warp + t;
                    mbar_wait(bar_full + 8 * (IDX_MOD % NST), (IDX_MOD / NST) & 1);
                    const uint32_t tb = sbase + SM_RING + (IDX_MOD % NST) * TILE;
#pragma unroll
                    for (int s = 0; s < 4; s++) {
                        const int row = 64 * warp + 16 * s + (lane & 7) + (lane >> 4) * 8;
                        const int ch = (lane >> 3) & 1;
                        uint32_t a[4];
                        ldsm4t(tb + row * 32 + ((ch ^ ((row >> 2) & 1)) << 4), a);
                        mma16816(cm, a, sc32[8 * s], sc32[8 * s + 4]);
                    }
                    if (t == 0) {
                        *(float2*)&red[warp * 64 + g * 2] = make_float2(cm[0], cm[1]);
                        *(float2*)&red[warp * 64 + (g + 8) * 2] = make_float2(cm[2], cm[3]);
                    }
                    cons_sync();
                    if (warp < 4 && lane == 0) mbar_arrive(bar_empty + 8 * (IDX_MOD % NST));
                    if (warp == 1 && lane < 16) {
                        const int b = lane >> 3, cp = lane & 7;
                        float q0 = 0.f, q1 = 0.f;
#pragma unroll
                        for (int w = 0; w < 8; w++) {
                            const float4 v = *(const float4*)&red[w * 64 + cp * 4];
                            q0 += b ? v.y : v.x; q1 += b ? v.w : v.z;
                        }
                        st_ll2(&sc->mod[b][512 + cta * 8 + cp], pack_bf16(q0, q1), tag);
                    }
                }
                if (i == 56 + grp) {
                    m_sb = ld_ll4((const uint4*)&sc->mod[eb][768 + (ec >> 1)]);
                    m_cb = ld_ll4((const uint4*)&sc->mod[eb][1024 + (ec >> 1)]);
                    m_ga = ld_ll2(&sc->mod[eb][512 + (wcol >> 1)]);
                    m_gb0 = ld_ll2(&sc->mod[0][1280 + (ocol >> 1)]); m_gb1 = ld_ll2(&sc->mod[1][1280 + (ocol >> 1)]);
                }
                if (i == 60 + grp) {
                    for (int it = 0;; it++) {
                        const bool ok = m_sb.y == tag && m_sb.w == tag && m_cb.y == tag && m_cb.w == tag &&
                                        m_ga.y == tag && m_gb0.y == tag && m_gb1.y == tag;
                        if (__all_sync(0xffffffffu, ok) || it > SPIN_LIMIT) break;
                        m_sb = ld_ll4((const uint4*)&sc->mod[eb][768 + (ec >> 1)]);
                        m_cb = ld_ll4((const uint4*)&sc->mod[eb][1024 + (ec >> 1)]);
                        m_ga = ld_ll2(&sc->mod[eb][512 + (wcol >> 1)]);
                        m_gb0 = ld_ll2(&sc->mod[0][1280 + (ocol >> 1)]); m_gb1 = ld_ll2(&sc->mod[1][1280 + (ocol >> 1)]);
                    }
                    mbar_wait(bar_clear, 0);
                }
                const int ki = kv_idx(i), ks = ki % NST, vs = (ki + 1) % NST;
                const uint32_t kph = (ki / NST) & 1, vph = ((ki + 1) / NST) & 1;
                mbar_wait(bar_full + 8 * ks, kph);
                const uint32_t kb = sbase + SM_RING + ks * TILE + koff;
                float sa[4] = {0.f, 0.f, 0.f, 0.f}, sb[4] = {0.f, 0.f, 0.f, 0.f};
#pragma unroll
                for (int s = 0; s < 8; s += 2) {
                    uint32_t a0[4], a1[4];
                    ldsm4((kb ^ ((s & 3) << 5)) + (s >> 2) * 8192, a0);
                    ldsm4((kb ^ (((s + 1) & 3) << 5)) + (s >> 2) * 8192, a1);
                    mma16816(sa, a0, qf[2 * s], qf[2 * s + 1]);
                    mma16816(sb, a1, qf[2 * s + 2], qf[2 * s + 3]);
                }
                __syncwarp();
                if (lane == 0) mbar_arrive(bar_empty + 8 * ks);
                uint32_t r01 = pack_bf16(sa[0] + sb[0], sa[1] + sb[1]);
                uint32_t r23 = pack_bf16(sa[2] + sb[2], sa[3] + sb[3]);
                r01 = pack_bf16(bf_lo(r01) * QK_SCALE, bf_hi(r01) * QK_SCALE);
                r23 = pack_bf16(bf_lo(r23) * QK_SCALE, bf_hi(r23) * QK_SCALE);
                uint32_t mx = max_bf16x2(r01, r23);
                mx = max_bf16x2(mx, __shfl_xor_sync(0xffffffffu, mx, 4));
                mx = max_bf16x2(mx, __shfl_xor_sync(0xffffffffu, mx, 8));
                mx = max_bf16x2(mx, __shfl_xor_sync(0xffffffffu, mx, 16));
                const uint32_t mnew = max_bf16x2(mrun, mx);
                const float m0 = bf_lo(mnew), m1 = bf_hi(mnew);
                if (__any_sync(0xffffffffu, mnew != mrun)) {
                    const float al0 = ex2((bf_lo(mrun) - m0) * LOG2E), al1 = ex2((bf_hi(mrun) - m1) * LOG2E);
                    ls[0] *= al0; ls[1] *= al1;
#pragma unroll
                    for (int d = 0; d < 8; d++) { o[d][0] *= al0; o[d][1] *= al1; o[d][2] *= al0; o[d][3] *= al1; }
                    mrun = mnew;
                }
                const float p0 = ex2((bf_lo(r01) - m0) * LOG2E), p1 = ex2((bf_hi(r01) - m1) * LOG2E);
                const float p2 = ex2((bf_lo(r23) - m0) * LOG2E), p3 = ex2((bf_hi(r23) - m1) * LOG2E);
                const uint32_t pb0 = movmatrix_t(pack_bf16(p0, p1)), pb1 = movmatrix_t(pack_bf16(p2, p3));
                mma16816(ls, ones, pb0, pb1);
                mbar_wait(bar_full + 8 * vs, vph);
                const uint32_t vb = sbase + SM_RING + vs * TILE + voff;
#pragma unroll
                for (int d = 0; d < 8; d++) {
                    uint32_t a[4];
                    ldsm4t((vb ^ ((d & 3) << 5)) + (d >> 2) * 8192, a);
                    mma16816(o[d], a, pb0, pb1);
                }
                __syncwarp();
                if (lane == 0) mbar_arrive(bar_empty + 8 * vs);
            }
        }
        if (warp == 7) TSTAMP(5);
        {
            float* mrg = (float*)(sgen + SM_MRG);
            float2* ml = (float2*)(sgen + SM_ML);
            {
                const int hp = (t & 1) * 2, up = t >> 1;
                if (g == 0 && up == 0) { ml[warp * 4 + hp] = make_float2(bf_lo(mrun), ls[0]); ml[warp * 4 + hp + 1] = make_float2(bf_hi(mrun), ls[1]); }
                float* m0p = mrg + (warp * 4 + hp) * 136 + up * 72 + g;
#pragma unroll
                for (int d = 0; d < 4; d++) {
                    m0p[16 * d] = up ? o[d + 4][0] : o[d][0]; m0p[136 + 16 * d] = up ? o[d + 4][1] : o[d][1];
                    m0p[16 * d + 8] = up ? o[d + 4][2] : o[d][2]; m0p[136 + 16 * d + 8] = up ? o[d + 4][3] : o[d][3];
                }
            }
            cons_sync();
            const int hh = tid >> 6, dp = tid & 63;
            float2 mw[8];
            float M = -INFINITY;
#pragma unroll
            for (int w = 0; w < 8; w++) { mw[w] = ml[w * 4 + hh]; M = fmaxf(M, mw[w].x); }
            float L = 0.f, o0 = 0.f, o1 = 0.f;
#pragma unroll
            for (int w = 0; w < 8; w++) {
                const float wt = ex2((mw[w].x - M) * LOG2E);
                const float2 v = *(const float2*)&mrg[(w * 4 + hh) * 136 + 2 * dp + (dp >= 32 ? 8 : 0)];
                L += wt * mw[w].y; o0 += wt * v.x; o1 += wt * v.y;
            }
            st_ll2(&sc->part_o[cta][hh][dp], tagf(o0, F_PART), tagf(o1, F_PART));
            if (dp < 4) st_ll2(&sc->part_ml[cta][hh][dp], tagf(M, F_PART), tagf(L, F_PART));
        }
        if (warp == 0) TSTAMP(6);
        {
            const int hq = cta >> 2, kvh = hq >> 2, hh = hq & 3;
            const int b = tid >> 7, dc = (tid >> 3) & 15, j = tid & 7;
            const int pc = (b * 8 + kvh) * 8 + j;
            const uint4* po = (const uint4*)&sc->part_o[pc][hh][0] + dc * 2;
            const uint2* pm = &sc->part_ml[pc - j][hh][0];
            uint4 vo0, vo1; uint2 vm[8];
            mbar_wait(bar_gate, 0);
            { const uint32_t tg = ((volatile uint32_t*)(sgen + SM_PACE))[2]; while (clock32() - tg < DELAY_A) {} }
            bool oko = false;
#pragma unroll
            for (int jj = 0; jj < 8; jj++) vm[jj] = make_uint2(0u, 0u);
            for (int it = 0;; it++) {
                if (!oko) { vo0 = ld_ll4(po); vo1 = ld_ll4(po + 1); }
#pragma unroll
                for (int jj = 0; jj < 8; jj++)
                    if ((vm[jj].x & vm[jj].y & 3u) != F_PART) vm[jj] = ld_ll2(pm + jj * 16);
                oko = (vo0.x & vo0.y & vo0.z & vo0.w & vo1.x & vo1.y & vo1.z & vo1.w & 3u) == F_PART;
                uint32_t all = vm[0].x & vm[0].y;
#pragma unroll
                for (int jj = 1; jj < 8; jj++) all &= vm[jj].x & vm[jj].y;
                if (__all_sync(0xffffffffu, oko && (all & 3u) == F_PART) || it > SPIN_LIMIT) break;
            }
            float M = untag(vm[0].x);
#pragma unroll
            for (int jj = 1; jj < 8; jj++) M = fmaxf(M, untag(vm[jj].x));
            float wt = 0.f, L = 0.f;
#pragma unroll
            for (int jj = 0; jj < 8; jj++) {
                const float w_ = ex2((untag(vm[jj].x) - M) * LOG2E);
                L += w_ * untag(vm[jj].y);
                wt = jj == j ? w_ : wt;
            }
            wt *= rcp_approx(L);
            float v[8] = {wt * untag(vo0.x), wt * untag(vo0.y), wt * untag(vo0.z), wt * untag(vo0.w),
                          wt * untag(vo1.x), wt * untag(vo1.y), wt * untag(vo1.z), wt * untag(vo1.w)};
#define XRED(N, O)                                                                       \
            {                                                                            \
                const bool up = lane & (O);                                              \
                _Pragma("unroll") for (int i = 0; i < (N); i++) {                        \
                    const float send = up ? v[i] : v[i + (N)], keep = up ? v[i + (N)] : v[i]; \
                    v[i] = keep + __shfl_xor_sync(0xffffffffu, send, (O));               \
                }                                                                        \
            }
            XRED(4, 1) XRED(2, 2) XRED(1, 4)
#undef XRED
            __nv_bfloat16* os = (__nv_bfloat16*)(sgen + SM_OS);
            os[b * 128 + dc * 8 + 4 * (j & 1) + 2 * ((j >> 1) & 1) + (j >> 2)] = __float2bfloat16_rn(v[0]);
            if (warp == 0) TSTAMP(15);
            uint32_t wf[8][4];
            const uint32_t aoff_o = (warp >> 2) * 8192 + ((lane & 7) + (lane >> 4) * 8) * 128 +
                                    (((((warp & 3) * 2 + ((lane >> 3) & 1)) ^ (lane & 7))) << 4);
#pragma unroll
            for (int s = 0; s < 2; s++) {
                const int idx = IDX_WO + s;
                mbar_wait(bar_full + 8 * (idx % NST), (idx / NST) & 1);
                const uint32_t tb = sbase + SM_RING + (idx % NST) * TILE + aoff_o;
#pragma unroll
                for (int k4 = 0; k4 < 4; k4++) ldsm4t(tb + k4 * 2048, wf[s * 4 + k4]);
            }
            cons_sync();
            if (warp == 0) TSTAMP(7);
            const uint32_t* os32 = (const uint32_t*)(sgen + SM_OS) + bb * 64 + t;
            float y0[4] = {}, y1[4] = {};
#pragma unroll
            for (int ks = 0; ks < 8; ks += 2) {
                mma16816(y0, wf[ks], os32[8 * ks], os32[8 * ks + 4]);
                mma16816(y1, wf[ks + 1], os32[8 * ks + 8], os32[8 * ks + 12]);
            }
            if (t == 0)
                st_v4(&sc->inbox_wo[(cta & 3) * 8 + warp][hq][g], tagf(y0[0] + y1[0], F_WO), tagf(y0[1] + y1[1], F_WO),
                      tagf(y0[2] + y1[2], F_WO), tagf(y0[3] + y1[3], F_WO));
        }
        const uint32_t t_wo = clock32();
        if (warp == 0) TSTAMP(8);
        if (cta >= NCTA - NOWN) {
            const uint4* pin = &sc->inbox_wo[cta - (NCTA - NOWN)][0][0] + tid;
            uint4 v;
            spin_cycles(DELAY_B1);
            bool ok = false;
            for (int it = 0;; it++) {
                if (!ok) {
                    v = ld_ll4(pin);
                    ok = (v.x & v.y & v.z & v.w & 3u) == F_WO;
                }
                if (__all_sync(0xffffffffu, ok) || it > SPIN_LIMIT) break;
            }
            const bool u1 = lane & 8, u2 = lane & 16;
            const float a0 = untag(v.x), a1 = untag(v.y), a2 = untag(v.z), a3 = untag(v.w);
            const float k0 = (u1 ? a2 : a0) + __shfl_xor_sync(0xffffffffu, u1 ? a0 : a2, 8);
            const float k1 = (u1 ? a3 : a1) + __shfl_xor_sync(0xffffffffu, u1 ? a1 : a3, 8);
            red2[warp * 32 + lane] = (u2 ? k1 : k0) + __shfl_xor_sync(0xffffffffu, u2 ? k0 : k1, 16);
            cons_sync();
            if (warp == 0) {
                float a = 0.f;
#pragma unroll
                for (int w = 0; w < 8; w++) a += red2[w * 32 + lane];
                const float ga = (wcol & 1) ? bf_hi(m_ga.x) : bf_lo(m_ga.x);
                const float xm = bf16r(xo + bf16r(ga * bf16r(a)));
                const float xm_b1 = __shfl_down_sync(0xffffffffu, xm, 16);
                if (lane < 16) st_ll2(&sc->x1[wcol], pack_bf16(xm, xm_b1), F_X1);
                TSTAMP(10);
            }
        }
        const uint32_t aoff = warp * 2048 + ((lane & 7) + (lane >> 4) * 8) * 128 + ((((lane >> 3) & 1) ^ (lane & 7)) << 4);
        if (cta < NFFN) {
            const uint4* px = (const uint4*)&sc->x1[ec];
            const uint4* pp = (const uint4*)&sc->x1[0];
            uint4 va, vb, pa, pb;
            uint32_t gf[4][4], uf[4][4];
            mbar_wait(bar_gu + 8 * (2 * (warp >> 1)), 0);
            mbar_wait(bar_gu + 8 * (2 * (warp >> 1) + 1), 0);
            {
                const uint32_t tg = sbase + SM_RING + (IDX_WG % NST) * TILE, tu = sbase + SM_RING + (IDX_WU % NST) * TILE;
#pragma unroll
                for (int s = 0; s < 4; s++) {
                    const int row = 64 * warp + 16 * s + (lane & 7) + (lane >> 4) * 8;
                    const uint32_t off = row * 32 + ((((lane >> 3) & 1) ^ ((row >> 2) & 1)) << 4);
                    ldsm4t(tg + off, gf[s]);
                    ldsm4t(tu + off, uf[s]);
                }
            }
            const float c1v[4] = {bf16r(1.0f + bf_lo(m_cb.x)), bf16r(1.0f + bf_hi(m_cb.x)), bf16r(1.0f + bf_lo(m_cb.z)), bf16r(1.0f + bf_hi(m_cb.z))};
            float bg = 0.f, cgc = 0.f, bu = 0.f, cuc = 0.f;
            {
                uint32_t* pre = (uint32_t*)(sgen + SM_MRG) + warp * 128;
                float* bc = (float*)(sgen + SM_MRG + 4096);
                *(uint2*)&pre[eb * 32 + 2 * (lane & 15)] = make_uint2(pack_bf16(c1v[0], c1v[1]), pack_bf16(c1v[2], c1v[3]));
                *(uint2*)&pre[64 + eb * 32 + 2 * (lane & 15)] = make_uint2(m_sb.x, m_sb.z);
                __syncwarp();
                float yg[4] = {}, yu[4] = {};
                const uint32_t* pb = pre + ((g >> 1) & 1) * 64 + bb * 32 + t;
#pragma unroll
                for (int s = 0; s < 4; s++) {
                    const uint32_t b0 = pb[8 * s], b1 = pb[8 * s + 4];
                    mma16816(yg, gf[s], b0, b1);
                    mma16816(yu, uf[s], b0, b1);
                }
                const float y0 = t < 2 ? yg[0] : yu[0], y1 = t < 2 ? yg[1] : yu[1], y2 = t < 2 ? yg[2] : yu[2], y3 = t < 2 ? yg[3] : yu[3];
                float* dstp = bc + warp * 128 + (t >> 1) * 64 + (t & 1) * 32;
                *(float2*)&dstp[g * 2] = make_float2(y0, y1);
                *(float2*)&dstp[(g + 8) * 2] = make_float2(y2, y3);
                __syncwarp();
                if (lane == 0) mbar_arrive(bar_bc);
            }
            if (warp == 0) TSTAMP(11);
            float pivot2;
            {
                while (clock32() - t_wo < DELAY_X1) {}
                bool okx = false, okp = false;
                for (int it = 0;; it++) {
                    if (!okx) { va = ld_ll4(px); vb = ld_ll4(px + 1); }
                    if (!okp) { pa = ld_ll4(pp); pb = ld_ll4(pp + 1); }
                    okx = va.y == F_X1 && va.w == F_X1 && vb.y == F_X1 && vb.w == F_X1;
                    okp = pa.y == F_X1 && pa.w == F_X1 && pb.y == F_X1 && pb.w == F_X1;
                    if (__all_sync(0xffffffffu, okx && okp) || it > SPIN_LIMIT) break;
                }
                if (warp == 0) TSTAMP(9);
                const float xv[4] = {eb ? bf_hi(va.x) : bf_lo(va.x), eb ? bf_hi(va.z) : bf_lo(va.z),
                                     eb ? bf_hi(vb.x) : bf_lo(vb.x), eb ? bf_hi(vb.z) : bf_lo(vb.z)};
                const float p0 = 0.25f * ((bf_lo(pa.x) + bf_lo(pa.z)) + (bf_lo(pb.x) + bf_lo(pb.z)));
                const float p1 = 0.25f * ((bf_hi(pa.x) + bf_hi(pa.z)) + (bf_hi(pb.x) + bf_hi(pb.z)));
                const float pivot = eb ? p1 : p0;
                pivot2 = (lane & 1) ? p1 : p0;
                *(uint2*)&hs[eb * 32 + 2 * (lane & 15)] =
                    make_uint2(pack_bf16((xv[0] - pivot) * c1v[0], (xv[1] - pivot) * c1v[1]),
                               pack_bf16((xv[2] - pivot) * c1v[2], (xv[3] - pivot) * c1v[3]));
                __syncwarp();
                float cg[2][4] = {}, cu[2][4] = {};
#pragma unroll
                for (int s = 0; s < 4; s++) {
                    const uint32_t b0 = hs[bb * 32 + 8 * s + t], b1 = hs[bb * 32 + 8 * s + 4 + t];
                    mma16816(cg[s & 1], gf[s], b0, b1);
                    mma16816(cu[s & 1], uf[s], b0, b1);
                }
                const float2 ps = half_warp_sums(xv, pivot);
                if ((lane & 15) == 0) stat[warp * 2 + eb] = ps;
                {
                    const float* bc = (const float*)(sgen + SM_MRG + 4096);
                    mbar_wait(bar_bc, 0);
#pragma unroll
                    for (int w = 0; w < 8; w++) {
                        bg += bc[w * 128 + lane]; cgc += bc[w * 128 + 32 + lane];
                        bu += bc[w * 128 + 64 + lane]; cuc += bc[w * 128 + 96 + lane];
                    }
                }
                if (t < 2) {
                    float v[4];
#pragma unroll
                    for (int i = 0; i < 4; i++) v[i] = t ? cu[0][i] + cu[1][i] : cg[0][i] + cg[1][i];
                    *(float2*)&red[warp * 64 + t * 32 + g * 2] = make_float2(v[0], v[1]);
                    *(float2*)&red[warp * 64 + t * 32 + (g + 8) * 2] = make_float2(v[2], v[3]);
                }
            }
            uint32_t df[4][4];
            mbar_wait(bar_full + 8 * (IDX_WD % NST), (IDX_WD / NST) & 1);
#pragma unroll
            for (int mt = 0; mt < 4; mt++) ldsm4t((sbase + SM_RING + (IDX_WD % NST) * TILE + aoff) ^ (mt << 5), df[mt]);
            cons_sync();
            {
                float gs = 0.f, us = 0.f;
#pragma unroll
                for (int w = 0; w < 8; w++) { gs += red[w * 64 + lane]; us += red[w * 64 + 32 + lane]; }
                float mean_bf, std_bf;
                ln_stats<false>(stat, lane & 1, pivot2, mean_bf, std_bf);
                const float rstd = rcp_approx(std_bf), dm = mean_bf - pivot2;
                gs = bf16r(rstd * (gs - dm * bg) + cgc);
                us = rstd * (us - dm * bu) + cuc;
                const float u2 = gs * (1.0f + 0.044715f * gs * gs) * (2.0f * 0.7978845608028654f * LOG2E);
                const float ge = bf16r(__fdividef(gs, 1.0f + ex2(-u2)));
                const float act = bf16r(ge * bf16r(us));
                const float a0 = __shfl_sync(0xffffffffu, act, 4 * t + bb), a1 = __shfl_sync(0xffffffffu, act, 4 * t + 2 + bb);
                const float a2 = __shfl_sync(0xffffffffu, act, 4 * t + 16 + bb), a3 = __shfl_sync(0xffffffffu, act, 4 * t + 18 + bb);
                const uint32_t b0 = pack_bf16(a0, a1), b1 = pack_bf16(a2, a3);
                float y[4][4] = {};
#pragma unroll
                for (int mt = 0; mt < 4; mt++) mma16816(y[mt], df[mt], b0, b1);
                float v[4];
#pragma unroll
                for (int i = 0; i < 4; i++) v[i] = t == 0 ? y[0][i] : t == 1 ? y[1][i] : t == 2 ? y[2][i] : y[3][i];
            {
                const bool odd = g & 1;
                const float sx = odd ? v[0] : v[2], sy = odd ? v[1] : v[3];
                const float rx = __shfl_xor_sync(0xffffffffu, sx, 4), ry = __shfl_xor_sync(0xffffffffu, sy, 4);
                const int c0 = 64 * warp + 16 * t + (odd ? g + 7 : g);
                const float e0 = odd ? rx : v[0], e1 = odd ? ry : v[1], e2 = odd ? v[2] : rx, e3 = odd ? v[3] : ry;
                st_v4(&sc->inbox_dn[c0 >> 2][cta][(c0 >> 1) & 1], tagf(e0, F_DOWN), tagf(e1, F_DOWN), tagf(e2, F_DOWN), tagf(e3, F_DOWN));
            }
            }
            if (warp == 0) TSTAMP(12);
        }
        {
            uint2 xw;
            float r0;
            {
                const uint4* pin = &sc->inbox_dn[cta][0][0] + tid;
                uint4 v = make_uint4(F_DOWN, F_DOWN, F_DOWN, F_DOWN);
                if (cta < NFFN) spin_cycles(DELAY_C);
                else while (clock32() - t_wo < DELAY_X1 + DELAY_NOFFN) {}
                xw = ld_ll2(&sc->x1[ocol]);
                bool ok = tid >= NFFN * 2;
                for (int it = 0;; it++) {
                    if (!ok) {
                        v = ld_ll4(pin);
                        ok = (v.x & v.y & v.z & v.w & 3u) == F_DOWN;
                    }
                    if (__all_sync(0xffffffffu, ok) || it > SPIN_LIMIT) break;
                }
                const bool u1 = lane & 2, u2 = lane & 4;
                const float a0 = untag(v.x), a1 = untag(v.y), a2 = untag(v.z), a3 = untag(v.w);
                const float k0 = (u1 ? a1 : a0) + __shfl_xor_sync(0xffffffffu, u1 ? a0 : a1, 2);
                const float k1 = (u1 ? a3 : a2) + __shfl_xor_sync(0xffffffffu, u1 ? a2 : a3, 2);
                r0 = (u2 ? k1 : k0) + __shfl_xor_sync(0xffffffffu, u2 ? k0 : k1, 4);
                r0 += __shfl_xor_sync(0xffffffffu, r0, 8);
                r0 += __shfl_xor_sync(0xffffffffu, r0, 16);
                if (lane < 8) red2[256 + warp * 8 + (2 * (lane & 1) + ((lane >> 2) & 1)) * 2 + ((lane >> 1) & 1)] = r0;
            }
            cons_sync();
            if (warp == 0) {
                float a0 = 0.f, a1 = 0.f;
#pragma unroll
                for (int w = 0; w < 8; w++) { const float2 v = *(const float2*)&red2[256 + w * 8 + (lane & 3) * 2]; a0 += v.x; a1 += v.y; }
                const bool hi = ocol & 1;
                const float gb0 = hi ? bf_hi(m_gb0.x) : bf_lo(m_gb0.x), gb1 = hi ? bf_hi(m_gb1.x) : bf_lo(m_gb1.x);
                for (int it = 0; !__all_sync(0xffffffffu, xw.y == F_X1) && it < SPIN_LIMIT; it++) xw = ld_ll2(&sc->x1[ocol]);
                if (lane < 4) {
                    p.out[ocol] = __float2bfloat16_rn(bf_lo(xw.x) + bf16r(gb0 * bf16r(a0)));
                    p.out[D_MODEL + ocol] = __float2bfloat16_rn(bf_hi(xw.x) + bf16r(gb1 * bf16r(a1)));
                }
                TSTAMP(13);
            }
        }
    }
}

typedef CUresult (*EncodeFn)(CUtensorMap*, CUtensorMapDataType, cuuint32_t, void*, const cuuint64_t*, const cuuint64_t*,
                             const cuuint32_t*, const cuuint32_t*, CUtensorMapInterleave, CUtensorMapSwizzle,
                             CUtensorMapL2promotion, CUtensorMapFloatOOBfill);

struct Maps { CUtensorMap k, v, wq, wmod, wmod8, wo, wg, wu, wd; };

void encode(EncodeFn fn, CUtensorMap* m, const void* ptr, int rank, const cuuint64_t* dims, const cuuint64_t* strides,
            const cuuint32_t* box, CUtensorMapSwizzle sw) {
    const cuuint32_t es[3] = {1, 1, 1};
    fn(m, CU_TENSOR_MAP_DATA_TYPE_BFLOAT16, rank, const_cast<void*>(ptr), dims, strides, box, es,
       CU_TENSOR_MAP_INTERLEAVE_NONE, sw, CU_TENSOR_MAP_L2_PROMOTION_L2_256B, CU_TENSOR_MAP_FLOAT_OOB_FILL_NONE);
}

}

extern "C" void kernel_launch(void* const* d_in, const int* in_sizes, int n_in, void* d_out, int out_size) {
    (void)in_sizes; (void)n_in; (void)out_size;
    static EncodeFn enc = nullptr;
    static Scratch* scratch = nullptr;
    if (!enc) {
        cudaGetSymbolAddress((void**)&scratch, g_scratch);
        void* fn = nullptr;
        cudaDriverEntryPointQueryResult qr;
        cudaGetDriverEntryPoint("cuTensorMapEncodeTiled", &fn, cudaEnableDefault, &qr);
        enc = (EncodeFn)fn;
        cudaFuncSetAttribute(fused_block_kernel, cudaFuncAttributeMaxDynamicSharedMemorySize, SMEM_BYTES);
    }
    Maps m;
    {
        const cuuint64_t dims[3] = {64, (cuuint64_t)16 * SK, 2}, str[2] = {256, 128};
        const cuuint32_t box[3] = {64, 64, 2};
        encode(enc, &m.k, d_in[1], 3, dims, str, box, CU_TENSOR_MAP_SWIZZLE_128B);
        encode(enc, &m.v, d_in[2], 3, dims, str, box, CU_TENSOR_MAP_SWIZZLE_128B);
    }
    {
        const cuuint64_t dims[2] = {4096, 512}, str[1] = {8192};
        const cuuint32_t box[2] = {32, 256};
        encode(enc, &m.wq, d_in[3], 2, dims, str, box, CU_TENSOR_MAP_SWIZZLE_64B);
    }
    {
        const cuuint64_t dims[2] = {N_MOD, 512}, str[1] = {N_MOD * 2};
        const cuuint32_t box[2] = {16, 256};
        encode(enc, &m.wmod, d_in[10], 2, dims, str, box, CU_TENSOR_MAP_SWIZZLE_32B);
        const cuuint32_t box8[2] = {8, 256};
        encode(enc, &m.wmod8, d_in[10], 2, dims, str, box8, CU_TENSOR_MAP_SWIZZLE_NONE);
    }
    {
        const cuuint64_t dims_o[3] = {64, 4096, 8}, dims_d[3] = {64, D_FF, 8}, str[2] = {1024, 128};
        const cuuint32_t box[3] = {64, 16, 8}, box_o[3] = {64, 64, 2};
        encode(enc, &m.wo, d_in[4], 3, dims_o, str, box_o, CU_TENSOR_MAP_SWIZZLE_128B);
        encode(enc, &m.wd, d_in[8], 3, dims_d, str, box, CU_TENSOR_MAP_SWIZZLE_128B);
    }
    {
        const cuuint64_t dims[2] = {D_FF, 512}, str[1] = {D_FF * 2};
        const cuuint32_t box[2] = {16, 128};
        encode(enc, &m.wg, d_in[6], 2, dims, str, box, CU_TENSOR_MAP_SWIZZLE_32B);
        encode(enc, &m.wu, d_in[7], 2, dims, str, box, CU_TENSOR_MAP_SWIZZLE_32B);
    }
    Params p;
    p.x = (const __nv_bfloat16*)d_in[0];
    p.c = (const __nv_bfloat16*)d_in[9];
    p.out = (__nv_bfloat16*)d_out;
    p.sc = scratch;
    fused_block_kernel<<<NCTA, NTHREADS, SMEM_BYTES, cudaStreamPerThread>>>(p, m.k, m.v, m.wq, m.wmod, m.wmod8, m.wo, m.wg, m.wu, m.wd);
}
```
